```python
import torch

def _softmax(x, axis=-1):
    return torch.softmax(x, dim=axis)
def _gelu(x):
    return torch.nn.functional.gelu(x, approximate="tanh")
def _silu(x):
    return torch.nn.functional.silu(x)
def _sigmoid(x):
    return torch.sigmoid(x)
def _layernorm(x, axis=-1, eps=1e-5):
    m = x.mean(dim=axis, keepdim=True)
    v = x.var(dim=axis, keepdim=True, unbiased=False)
    return (x - m) / torch.sqrt(v + eps)
def _scatter_add(tgt, idx, src, axis=0):
    return tgt.clone().index_add_(axis, idx, src)
def _segment_sum(src, seg, n):
    out = torch.zeros((n,) + src.shape[1:], dtype=src.dtype)
    return out.index_add_(0, seg, src)
def _pad(x, pw):
    flat = tuple(v for pair in reversed(pw) for v in pair)
    return torch.nn.functional.pad(x, flat)

kernel_name = 'parallel_sum__sliding_local_dilated__moe_arch_mod__prompt'

def setup_inputs():

    _w = (lambda a: (lambda t: t.to(torch.bfloat16) if t.is_floating_point() else t)(torch.as_tensor(a)))
    def _A_setup():
        B, S, D = 1, 2048, 1024
        return {
            "x": _w((lambda *s: torch.randn(*s, dtype=torch.bfloat16) * 0.05)(B, S, D)),
            "wqkv": _w((lambda *s: torch.randn(*s, dtype=torch.bfloat16) * 0.05)(D, 3 * D)),
            "wo": _w((lambda *s: torch.randn(*s, dtype=torch.bfloat16) * 0.05)(D, D)),
        }
    _A_in = _A_setup()

    def _B_setup():
        B, S, D, F, C = 1, 2048, 1024, 3584, 8
        return {
            "x": _w((lambda *s: torch.randn(*s, dtype=torch.bfloat16) * 0.05)(B, S, D)),
            "w_r": _w((lambda *s: torch.randn(*s, dtype=torch.bfloat16) * 0.05)(D)),
            "w_gate": _w((lambda *s: torch.randn(*s, dtype=torch.bfloat16) * 0.05)(D, F)),
            "w_up": _w((lambda *s: torch.randn(*s, dtype=torch.bfloat16) * 0.05)(D, F)),
            "w_down": _w((lambda *s: torch.randn(*s, dtype=torch.bfloat16) * 0.05)(F, D)),
        }
    _B_in = _B_setup()

    return {
        "A_x": _A_in["x"],
        "A_wqkv": _A_in["wqkv"],
        "A_wo": _A_in["wo"],
        "B_x": _B_in["x"],
        "B_w_r": _B_in["w_r"],
        "B_w_gate": _B_in["w_gate"],
        "B_w_up": _B_in["w_up"],
        "B_w_down": _B_in["w_down"],
    }

def reference(A_x, A_wqkv, A_wo, B_x, B_w_r, B_w_gate, B_w_up, B_w_down):
    def _A_ref(x, wqkv, wo):
        B, S, D = x.shape
        H = 32; Dh = D // H
        W, dil = 8, 2
        qkv = (lambda x, *d: x.permute(*d))((x @ wqkv).reshape(B, S, 3, H, Dh), 2, 0, 3, 1, 4)
        q, k, v = qkv[0], qkv[1], qkv[2]
        scale = Dh ** -0.5
        pos = torch.arange(S)
        off = torch.arange(W) * dil
        idx = pos[:, None] - off[None, :]
        mask = idx >= 0
        idx_c = torch.where(mask, idx, 0).reshape(-1)
        kg = k[:, :, idx_c, :].reshape(B, H, S, W, Dh)
        vg = v[:, :, idx_c, :].reshape(B, H, S, W, Dh)
        logits = torch.einsum("bhsd,bhswd->bhsw", q, kg) * scale
        logits = torch.where(mask[None, None, :, :], logits, -1e9)
        attn = _softmax(logits, axis=-1)
        o = torch.einsum("bhsw,bhswd->bhsd", attn, vg)
        return (lambda x, *d: x.permute(*d))(o, 0, 2, 1, 3).reshape(B, S, D) @ wo

    def _B_ref(x, w_r, w_gate, w_up, w_down):
        B, S, D = x.shape
        C = 8
        r = x @ w_r
        idx = torch.argsort(-r, axis=-1)[:, :C]
        idx_e = (lambda x, n, axis: torch.repeat_interleave(x, n, dim=axis))(idx.reshape(B, C, 1), D, axis=2)
        x_sel = (lambda x, i, axis: torch.take_along_dim(x, i, dim=axis))(x, idx_e, axis=1)
        g = _silu(x_sel @ w_gate)
        u = x_sel @ w_up
        y = (g * u) @ w_down
        r_sel = _sigmoid((lambda x, i, axis: torch.take_along_dim(x, i, dim=axis))(r, idx, axis=1))
        y = y * r_sel.reshape(B, C, 1)
        b_off = (torch.arange(B) * S).reshape(B, 1)
        flat_idx = (idx + b_off).reshape(B * C)
        zero = (x * 0.0).reshape(B * S, D)
        upd = _scatter_add(zero, flat_idx, y.reshape(B * C, D), axis=0)
        return x + upd.reshape(B, S, D)

    x = A_x
    xn = _layernorm(x, axis=-1)
    return x + _A_ref(xn, A_wqkv, A_wo) + _B_ref(xn, B_w_r, B_w_gate, B_w_up, B_w_down)
```

```cpp
#include <cuda_runtime.h>
#include <cuda.h>
#include <cuda_bf16.h>
#include <stdint.h>

namespace {

constexpr int BOX = 8192, W_BYTES = 3 * BOX;
constexpr int OFF_X0 = 0, OFF_W = 6 * BOX, OFF_X1 = 18 * BOX;
constexpr int OFF_O0 = 0, OFF_WO = 5 * BOX, OFF_O1 = 19 * BOX;
constexpr int OFF_H0 = 5 * BOX, OFF_H1 = 18 * BOX;
constexpr int NO = 5, NWO = 7, NF = 3, F_BYTES = 9216;
constexpr int OFF_FR = 24 * BOX;
constexpr int OFF_UPD = OFF_FR + NF * F_BYTES;
constexpr int OFF_HIN = OFF_UPD + 2048;
constexpr int OFF_CS = OFF_HIN + 2048;
constexpr int OFF_SEL = OFF_CS + 768;
constexpr int OFF_STAT = OFF_FR + 32768;
constexpr int OFF_EP = OFF_STAT + 2112;
constexpr int OFF_BAR = OFF_EP + 16;
constexpr int B_WFULL = 0, B_XFULL = 4, B_AUX = 16, B_XT = 17, B_WOFULL = 19, B_OFULL = 26, B_ROW = 36, B_FFULL = 37;
constexpr int B_WEMPTY = 42, B_XEMPTY = 46, B_WOEMPTY = 52, B_OEMPTY = 59;
constexpr int B_G1DONE = 66, B_FEMPTY = 67, B_UPD = 70, B_STAGED = 72, NBAR = 78;
constexpr int SMEM_BYTES = OFF_BAR + NBAR * 8;
static_assert(OFF_SEL + 32 <= OFF_STAT && SMEM_BYTES + 256 <= 232448 && OFF_BAR % 8 == 0 && OFF_UPD % 1024 == 0, "smem");
#define POLL_NS 100
#define HELP_AT 64
#define ROWS_AT 7
#define STATS_UNROLL 1
constexpr int kStatsUnroll = STATS_UNROLL;
constexpr int BUDGET = 1 << 18;

struct Scratch {
    uint8_t o[2048 * 1024 * 2];
    float ypart[8][8][1024];
    uint32_t halo[128][512];
    uint32_t h[14336];
    uint32_t xsel[4096];
    uint2 row[2048];
    float cs[16][192];
    uint32_t oflag[16][32];
    uint32_t hflag[128], yflag[128], sel[32], csflag[32], epoch[32];
};
__device__ __align__(1024) Scratch g_scr;

#define TS(i) do {} while (0)
#define TS_END() do {} while (0)
#define TSC(c, i) do {} while (0)
constexpr int SMEM_LAUNCH = SMEM_BYTES;
__device__ __forceinline__ uint32_t smem_u32(const void* p) { return (uint32_t)__cvta_generic_to_shared(p); }
__device__ __forceinline__ void mbar_init(uint32_t bar, uint32_t cnt) { asm volatile("mbarrier.init.shared::cta.b64 [%0], %1;" ::"r"(bar), "r"(cnt) : "memory"); }
__device__ __forceinline__ void mbar_expect_tx(uint32_t bar, uint32_t bytes) { asm volatile("mbarrier.arrive.expect_tx.shared::cta.b64 _, [%0], %1;" ::"r"(bar), "r"(bytes) : "memory"); }
__device__ __forceinline__ void mbar_arrive(uint32_t bar) { asm volatile("mbarrier.arrive.shared::cta.b64 _, [%0];" ::"r"(bar) : "memory"); }
__device__ __forceinline__ uint32_t mapa(uint32_t a, uint32_t cta) { uint32_t r; asm("mapa.shared::cluster.u32 %0, %1, %2;" : "=r"(r) : "r"(a), "r"(cta)); return r; }
__device__ __forceinline__ void mbar_arrive_at(uint32_t cbar) { asm volatile("mbarrier.arrive.shared::cluster.b64 _, [%0];" ::"r"(cbar) : "memory"); }
__device__ __forceinline__ void mbar_wait(uint32_t bar, uint32_t parity, int& budget) {
    asm volatile("{\n.reg .pred p;\nLAB_WAIT:\nmbarrier.try_wait.parity.shared::cta.b64 p, [%1], %2;\n"
                 "add.s32 %0, %0, -1;\nsetp.gt.and.s32 p, %0, 0, !p;\n@p bra LAB_WAIT;\n}" : "+r"(budget) : "r"(bar), "r"(parity) : "memory");
}
__device__ __forceinline__ void tma_2d_mc(uint32_t dst, const CUtensorMap* m, uint32_t bar, int c0, int c1) {
    asm volatile("cp.async.bulk.tensor.2d.shared::cluster.global.mbarrier::complete_tx::bytes.multicast::cluster [%0], [%1, {%3, %4}], [%2], %5;" ::"r"(dst), "l"(m), "r"(bar), "r"(c0), "r"(c1), "h"((uint16_t)3) : "memory");
}
__device__ __forceinline__ void tma_3d(uint32_t dst, const CUtensorMap* m, uint32_t bar, int c0, int c1, int c2) {
    asm volatile("cp.async.bulk.tensor.3d.shared::cluster.global.mbarrier::complete_tx::bytes [%0], [%1, {%3, %4, %5}], [%2];" ::"r"(dst), "l"(m), "r"(bar), "r"(c0), "r"(c1), "r"(c2) : "memory");
}
__device__ __forceinline__ void tma_4d(uint32_t dst, const CUtensorMap* m, uint32_t bar, int c0, int c1, int c2, int c3) {
    asm volatile("cp.async.bulk.tensor.4d.shared::cluster.global.mbarrier::complete_tx::bytes [%0], [%1, {%3, %4, %5, %6}], [%2];" ::"r"(dst), "l"(m), "r"(bar), "r"(c0), "r"(c1), "r"(c2), "r"(c3) : "memory");
}
__device__ __forceinline__ void tma_4d_mc(uint32_t dst, const CUtensorMap* m, uint32_t bar, int c0, int c1, int c2, int c3) {
    asm volatile("cp.async.bulk.tensor.4d.shared::cluster.global.mbarrier::complete_tx::bytes.multicast::cluster [%0], [%1, {%3, %4, %5, %6}], [%2], %7;" ::"r"(dst), "l"(m), "r"(bar), "r"(c0), "r"(c1), "r"(c2), "r"(c3), "h"((uint16_t)3) : "memory");
}
__device__ __forceinline__ void tma_pf_3d(const CUtensorMap* m, int c0, int c1, int c2) {
    asm volatile("cp.async.bulk.prefetch.tensor.3d.L2.global [%0, {%1, %2, %3}];" ::"l"(m), "r"(c0), "r"(c1), "r"(c2) : "memory");
}
__device__ __forceinline__ void bulk_g2s(uint32_t dst, const void* src, uint32_t bytes, uint32_t bar) {
    asm volatile("cp.async.bulk.shared::cluster.global.mbarrier::complete_tx::bytes [%0], [%1], %2, [%3];" ::"r"(dst), "l"(src), "r"(bytes), "r"(bar) : "memory");
}
__device__ __forceinline__ void bulk_s2g(void* dst, uint32_t src, uint32_t bytes) {
    asm volatile("cp.async.bulk.global.shared::cta.bulk_group [%0], [%1], %2;" ::"l"(dst), "r"(src), "r"(bytes) : "memory");
}
__device__ __forceinline__ void bulk_s2c(uint32_t cdst, uint32_t src, uint32_t bytes, uint32_t cbar) {
    asm volatile("cp.async.bulk.shared::cluster.shared::cta.mbarrier::complete_tx::bytes [%0], [%1], %2, [%3];" ::"r"(cdst), "r"(src), "r"(bytes), "r"(cbar) : "memory");
}
__device__ __forceinline__ void cluster_wait() { asm volatile("barrier.cluster.wait.aligned;" ::: "memory"); }
__device__ __forceinline__ void fence_gpu() { asm volatile("fence.acq_rel.gpu;" ::: "memory"); }
__device__ __forceinline__ void fence_async_smem() { asm volatile("fence.proxy.async.shared::cta;" ::: "memory"); }
__device__ __forceinline__ void fence_async_gmem() { asm volatile("fence.proxy.async.global;" ::: "memory"); }
__device__ __forceinline__ void wg_fence() { asm volatile("wgmma.fence.sync.aligned;" ::: "memory"); }
__device__ __forceinline__ void wg_commit() { asm volatile("wgmma.commit_group.sync.aligned;" ::: "memory"); }
template <int N> __device__ __forceinline__ void wg_wait() { asm volatile("wgmma.wait_group.sync.aligned %0;" ::"n"(N) : "memory"); }
__device__ __forceinline__ uint64_t mkdesc(uint32_t lo, uint32_t hi) { return ((uint64_t)hi << 32) | lo; }
__host__ __device__ constexpr uint32_t dhi(uint32_t sbo, uint32_t mode) { return (sbo >> 4) | (mode << 30); }
__host__ __device__ constexpr uint32_t dlo(uint32_t off, uint32_t lbo) { return (off >> 4) + ((lbo >> 4) << 16); }
__device__ __forceinline__ bool elect_one() {
    uint32_t e;
    asm volatile("{\n.reg .pred p;\nelect.sync _|p, 0xffffffff;\nselp.u32 %0, 1, 0, p;\n}" : "=r"(e));
    return e;
}
template <int R> __device__ __forceinline__ void reg_inc() { asm volatile("setmaxnreg.inc.sync.aligned.u32 %0;" ::"n"(R)); }
template <int R> __device__ __forceinline__ void reg_dec() { asm volatile("setmaxnreg.dec.sync.aligned.u32 %0;" ::"n"(R)); }
__device__ __forceinline__ void bar_sync(int id, int n) { asm volatile("bar.sync %0, %1;" ::"r"(id), "r"(n) : "memory"); }
__device__ __forceinline__ void bar_arrive(int id, int n) { asm volatile("bar.arrive %0, %1;" ::"r"(id), "r"(n) : "memory"); }
__device__ __forceinline__ uint32_t pack_bf16(float lo, float hi) { uint32_t r; asm("cvt.rn.bf16x2.f32 %0, %1, %2;" : "=r"(r) : "f"(hi), "f"(lo)); return r; }
__device__ __forceinline__ float bf_lo(uint32_t u) { return __uint_as_float(u << 16); }
__device__ __forceinline__ float bf_hi(uint32_t u) { return __uint_as_float(u & 0xffff0000u); }
__device__ __forceinline__ float bf16r(float v) { return bf_lo(pack_bf16(v, 0.f)); }
__device__ __forceinline__ float rcp(float x) { float r; asm("rcp.approx.ftz.f32 %0, %1;" : "=f"(r) : "f"(x)); return r; }
__device__ __forceinline__ float ex2(float x) { float r; asm("ex2.approx.ftz.f32 %0, %1;" : "=f"(r) : "f"(x)); return r; }
__device__ __forceinline__ float sigmoidf(float v) { return rcp(1.f + ex2(v * -1.4426950408889634f)); }
__device__ __forceinline__ uint32_t movm(uint32_t a) { uint32_t d; asm volatile("movmatrix.sync.aligned.m8n8.trans.b16 %0, %1;" : "=r"(d) : "r"(a)); return d; }
__device__ __forceinline__ void mma16816(float (&c)[4], uint32_t a0, uint32_t a1, uint32_t a2, uint32_t a3, uint32_t b0, uint32_t b1) {
    asm volatile("mma.sync.aligned.m16n8k16.row.col.f32.bf16.bf16.f32 {%0,%1,%2,%3}, {%4,%5,%6,%7}, {%8,%9}, {%0,%1,%2,%3};"
                 : "+f"(c[0]), "+f"(c[1]), "+f"(c[2]), "+f"(c[3]) : "r"(a0), "r"(a1), "r"(a2), "r"(a3), "r"(b0), "r"(b1));
}
__device__ __forceinline__ void mma1688(float (&c)[4], uint32_t a0, uint32_t a1, uint32_t b0) {
    asm volatile("mma.sync.aligned.m16n8k8.row.col.f32.bf16.bf16.f32 {%0,%1,%2,%3}, {%4,%5}, {%6}, {%0,%1,%2,%3};"
                 : "+f"(c[0]), "+f"(c[1]), "+f"(c[2]), "+f"(c[3]) : "r"(a0), "r"(a1), "r"(b0));
}
__device__ __forceinline__ void stsm4(uint32_t a, uint32_t r0, uint32_t r1, uint32_t r2, uint32_t r3) {
    asm volatile("stmatrix.sync.aligned.m8n8.x4.shared.b16 [%0], {%1,%2,%3,%4};" ::"r"(a), "r"(r0), "r"(r1), "r"(r2), "r"(r3) : "memory");
}
__device__ __forceinline__ uint32_t ld_rlx(const void* p) { uint32_t v; asm volatile("ld.relaxed.gpu.global.u32 %0, [%1];" : "=r"(v) : "l"(p) : "memory"); return v; }
__device__ __forceinline__ uint32_t ld_acq(const void* p) { uint32_t v; asm volatile("ld.acquire.gpu.global.u32 %0, [%1];" : "=r"(v) : "l"(p) : "memory"); return v; }
__device__ __forceinline__ uint2 ld_rlx2(const void* p) { uint2 v; asm volatile("ld.relaxed.gpu.global.v2.u32 {%0,%1}, [%2];" : "=r"(v.x), "=r"(v.y) : "l"(p) : "memory"); return v; }
__device__ __forceinline__ uint4 ld_rlx4(const void* p) { uint4 v; asm volatile("ld.relaxed.gpu.global.v4.u32 {%0,%1,%2,%3}, [%4];" : "=r"(v.x), "=r"(v.y), "=r"(v.z), "=r"(v.w) : "l"(p) : "memory"); return v; }
__device__ __forceinline__ void st_rlx(void* p, uint32_t v) { asm volatile("st.relaxed.gpu.global.u32 [%0], %1;" ::"l"(p), "r"(v) : "memory"); }
__device__ __forceinline__ void st_rlx2(void* p, uint32_t a, uint32_t b) { asm volatile("st.relaxed.gpu.global.v2.u32 [%0], {%1,%2};" ::"l"(p), "r"(a), "r"(b) : "memory"); }
__device__ __forceinline__ void st_rlx4(void* p, uint32_t a, uint32_t b, uint32_t c, uint32_t d) { asm volatile("st.relaxed.gpu.global.v4.u32 [%0], {%1,%2,%3,%4};" ::"l"(p), "r"(a), "r"(b), "r"(c), "r"(d) : "memory"); }
__device__ __forceinline__ uint4 ldg_nc(const void* p) { uint4 v; asm volatile("ld.global.nc.v4.u32 {%0,%1,%2,%3}, [%4];" : "=r"(v.x), "=r"(v.y), "=r"(v.z), "=r"(v.w) : "l"(p)); return v; }
__device__ __forceinline__ void sts4(uint32_t a, uint32_t x, uint32_t y, uint32_t z, uint32_t w) { asm volatile("st.shared.v4.u32 [%0], {%1,%2,%3,%4};" ::"r"(a), "r"(x), "r"(y), "r"(z), "r"(w) : "memory"); }
__device__ __forceinline__ void sts2(uint32_t a, uint32_t x, uint32_t y) { asm volatile("st.shared.v2.u32 [%0], {%1,%2};" ::"r"(a), "r"(x), "r"(y) : "memory"); }
__device__ __forceinline__ void sts1(uint32_t a, uint32_t v) { asm volatile("st.shared.u32 [%0], %1;" ::"r"(a), "r"(v) : "memory"); }
__device__ __forceinline__ uint4 lds4(uint32_t a) { uint4 v; asm volatile("ld.shared.v4.u32 {%0,%1,%2,%3}, [%4];" : "=r"(v.x), "=r"(v.y), "=r"(v.z), "=r"(v.w) : "r"(a) : "memory"); return v; }
__device__ __forceinline__ float4 lds4f(uint32_t a) { float4 v; asm volatile("ld.shared.v4.f32 {%0,%1,%2,%3}, [%4];" : "=f"(v.x), "=f"(v.y), "=f"(v.z), "=f"(v.w) : "r"(a) : "memory"); return v; }
__device__ __forceinline__ float2 lds2f(uint32_t a) { float2 v; asm volatile("ld.shared.v2.f32 {%0,%1}, [%2];" : "=f"(v.x), "=f"(v.y) : "r"(a) : "memory"); return v; }
__device__ __forceinline__ float lds1f(uint32_t a) { float v; asm volatile("ld.shared.f32 %0, [%1];" : "=f"(v) : "r"(a) : "memory"); return v; }
__device__ __forceinline__ uint32_t lds1(uint32_t a) { uint32_t v; asm volatile("ld.shared.u32 %0, [%1];" : "=r"(v) : "r"(a) : "memory"); return v; }
__device__ __forceinline__ uint32_t redux_max(uint32_t v) { uint32_t r; asm volatile("redux.sync.max.u32 %0, %1, 0xffffffff;" : "=r"(r) : "r"(v)); return r; }
__device__ __forceinline__ uint32_t poll_all(const uint32_t* p, uint32_t mask, uint32_t want, int& budget) {
    uint32_t v;
#pragma unroll 1
    while (v = ld_acq(p), !__all_sync(0xffffffffu, (v & mask) == want) && --budget > 0) __nanosleep(POLL_NS);
    return v;
}

template <int TA, int TB>
__device__ __forceinline__ void wgmma_n192(float (&d)[96], uint64_t da, uint64_t db, int keep) {
    asm volatile("{\n.reg .pred p;\nsetp.ne.b32 p, %98, 0;\n"
        "wgmma.mma_async.sync.aligned.m64n192k16.f32.bf16.bf16 "
        "{%0, %1, %2, %3, %4, %5, %6, %7, %8, %9, %10, %11, %12, %13, %14, %15, "
        "%16, %17, %18, %19, %20, %21, %22, %23, %24, %25, %26, %27, %28, %29, %30, %31, "
        "%32, %33, %34, %35, %36, %37, %38, %39, %40, %41, %42, %43, %44, %45, %46, %47, "
        "%48, %49, %50, %51, %52, %53, %54, %55, %56, %57, %58, %59, %60, %61, %62, %63, "
        "%64, %65, %66, %67, %68, %69, %70, %71, %72, %73, %74, %75, %76, %77, %78, %79, "
        "%80, %81, %82, %83, %84, %85, %86, %87, %88, %89, %90, %91, %92, %93, %94, %95}, "
        "%96, %97, p, 1, 1, %99, %100;\n}\n"
        : "+f"(d[0]), "+f"(d[1]), "+f"(d[2]), "+f"(d[3]), "+f"(d[4]), "+f"(d[5]), "+f"(d[6]), "+f"(d[7]),
          "+f"(d[8]), "+f"(d[9]), "+f"(d[10]), "+f"(d[11]), "+f"(d[12]), "+f"(d[13]), "+f"(d[14]), "+f"(d[15]),
          "+f"(d[16]), "+f"(d[17]), "+f"(d[18]), "+f"(d[19]), "+f"(d[20]), "+f"(d[21]), "+f"(d[22]), "+f"(d[23]),
          "+f"(d[24]), "+f"(d[25]), "+f"(d[26]), "+f"(d[27]), "+f"(d[28]), "+f"(d[29]), "+f"(d[30]), "+f"(d[31]),
          "+f"(d[32]), "+f"(d[33]), "+f"(d[34]), "+f"(d[35]), "+f"(d[36]), "+f"(d[37]), "+f"(d[38]), "+f"(d[39]),
          "+f"(d[40]), "+f"(d[41]), "+f"(d[42]), "+f"(d[43]), "+f"(d[44]), "+f"(d[45]), "+f"(d[46]), "+f"(d[47]),
          "+f"(d[48]), "+f"(d[49]), "+f"(d[50]), "+f"(d[51]), "+f"(d[52]), "+f"(d[53]), "+f"(d[54]), "+f"(d[55]),
          "+f"(d[56]), "+f"(d[57]), "+f"(d[58]), "+f"(d[59]), "+f"(d[60]), "+f"(d[61]), "+f"(d[62]), "+f"(d[63]),
          "+f"(d[64]), "+f"(d[65]), "+f"(d[66]), "+f"(d[67]), "+f"(d[68]), "+f"(d[69]), "+f"(d[70]), "+f"(d[71]),
          "+f"(d[72]), "+f"(d[73]), "+f"(d[74]), "+f"(d[75]), "+f"(d[76]), "+f"(d[77]), "+f"(d[78]), "+f"(d[79]),
          "+f"(d[80]), "+f"(d[81]), "+f"(d[82]), "+f"(d[83]), "+f"(d[84]), "+f"(d[85]), "+f"(d[86]), "+f"(d[87]),
          "+f"(d[88]), "+f"(d[89]), "+f"(d[90]), "+f"(d[91]), "+f"(d[92]), "+f"(d[93]), "+f"(d[94]), "+f"(d[95])
        : "l"(da), "l"(db), "r"(keep), "n"(TA), "n"(TB));
}
template <int TA, int TB>
__device__ __forceinline__ void wgmma_n128(float (&d)[64], uint64_t da, uint64_t db, int keep) {
    asm volatile("{\n.reg .pred p;\nsetp.ne.b32 p, %66, 0;\n"
        "wgmma.mma_async.sync.aligned.m64n128k16.f32.bf16.bf16 "
        "{%0, %1, %2, %3, %4, %5, %6, %7, %8, %9, %10, %11, %12, %13, %14, %15, "
        "%16, %17, %18, %19, %20, %21, %22, %23, %24, %25, %26, %27, %28, %29, %30, %31, "
        "%32, %33, %34, %35, %36, %37, %38, %39, %40, %41, %42, %43, %44, %45, %46, %47, "
        "%48, %49, %50, %51, %52, %53, %54, %55, %56, %57, %58, %59, %60, %61, %62, %63}, "
        "%64, %65, p, 1, 1, %67, %68;\n}\n"
        : "+f"(d[0]), "+f"(d[1]), "+f"(d[2]), "+f"(d[3]), "+f"(d[4]), "+f"(d[5]), "+f"(d[6]), "+f"(d[7]),
          "+f"(d[8]), "+f"(d[9]), "+f"(d[10]), "+f"(d[11]), "+f"(d[12]), "+f"(d[13]), "+f"(d[14]), "+f"(d[15]),
          "+f"(d[16]), "+f"(d[17]), "+f"(d[18]), "+f"(d[19]), "+f"(d[20]), "+f"(d[21]), "+f"(d[22]), "+f"(d[23]),
          "+f"(d[24]), "+f"(d[25]), "+f"(d[26]), "+f"(d[27]), "+f"(d[28]), "+f"(d[29]), "+f"(d[30]), "+f"(d[31]),
          "+f"(d[32]), "+f"(d[33]), "+f"(d[34]), "+f"(d[35]), "+f"(d[36]), "+f"(d[37]), "+f"(d[38]), "+f"(d[39]),
          "+f"(d[40]), "+f"(d[41]), "+f"(d[42]), "+f"(d[43]), "+f"(d[44]), "+f"(d[45]), "+f"(d[46]), "+f"(d[47]),
          "+f"(d[48]), "+f"(d[49]), "+f"(d[50]), "+f"(d[51]), "+f"(d[52]), "+f"(d[53]), "+f"(d[54]), "+f"(d[55]),
          "+f"(d[56]), "+f"(d[57]), "+f"(d[58]), "+f"(d[59]), "+f"(d[60]), "+f"(d[61]), "+f"(d[62]), "+f"(d[63])
        : "l"(da), "l"(db), "r"(keep), "n"(TA), "n"(TB));
}
template <int TA, int TB>
__device__ __forceinline__ void wgmma_n8(float (&d)[4], uint64_t da, uint64_t db, int keep) {
    asm volatile("{\n.reg .pred p;\nsetp.ne.b32 p, %6, 0;\n"
        "wgmma.mma_async.sync.aligned.m64n8k16.f32.bf16.bf16 "
        "{%0, %1, %2, %3}, "
        "%4, %5, p, 1, 1, %7, %8;\n}\n"
        : "+f"(d[0]), "+f"(d[1]), "+f"(d[2]), "+f"(d[3])
        : "l"(da), "l"(db), "r"(keep), "n"(TA), "n"(TB));
}
__device__ __forceinline__ void wgmma_rs_n128(float (&d)[64], uint32_t a0, uint32_t a1, uint32_t a2, uint32_t a3, uint64_t db) {
    asm volatile("{\n.reg .pred p;\nsetp.ne.b32 p, 1, 0;\n"
        "wgmma.mma_async.sync.aligned.m64n128k16.f32.bf16.bf16 "
        "{%0, %1, %2, %3, %4, %5, %6, %7, %8, %9, %10, %11, %12, %13, %14, %15, "
        "%16, %17, %18, %19, %20, %21, %22, %23, %24, %25, %26, %27, %28, %29, %30, %31, "
        "%32, %33, %34, %35, %36, %37, %38, %39, %40, %41, %42, %43, %44, %45, %46, %47, "
        "%48, %49, %50, %51, %52, %53, %54, %55, %56, %57, %58, %59, %60, %61, %62, %63}, "
        "{%64, %65, %66, %67}, %68, p, 1, 1, 1;\n}\n"
        : "+f"(d[0]), "+f"(d[1]), "+f"(d[2]), "+f"(d[3]), "+f"(d[4]), "+f"(d[5]), "+f"(d[6]), "+f"(d[7]),
          "+f"(d[8]), "+f"(d[9]), "+f"(d[10]), "+f"(d[11]), "+f"(d[12]), "+f"(d[13]), "+f"(d[14]), "+f"(d[15]),
          "+f"(d[16]), "+f"(d[17]), "+f"(d[18]), "+f"(d[19]), "+f"(d[20]), "+f"(d[21]), "+f"(d[22]), "+f"(d[23]),
          "+f"(d[24]), "+f"(d[25]), "+f"(d[26]), "+f"(d[27]), "+f"(d[28]), "+f"(d[29]), "+f"(d[30]), "+f"(d[31]),
          "+f"(d[32]), "+f"(d[33]), "+f"(d[34]), "+f"(d[35]), "+f"(d[36]), "+f"(d[37]), "+f"(d[38]), "+f"(d[39]),
          "+f"(d[40]), "+f"(d[41]), "+f"(d[42]), "+f"(d[43]), "+f"(d[44]), "+f"(d[45]), "+f"(d[46]), "+f"(d[47]),
          "+f"(d[48]), "+f"(d[49]), "+f"(d[50]), "+f"(d[51]), "+f"(d[52]), "+f"(d[53]), "+f"(d[54]), "+f"(d[55]),
          "+f"(d[56]), "+f"(d[57]), "+f"(d[58]), "+f"(d[59]), "+f"(d[60]), "+f"(d[61]), "+f"(d[62]), "+f"(d[63])
        : "r"(a0), "r"(a1), "r"(a2), "r"(a3), "l"(db));
}

template <int HS>
__device__ __forceinline__ void attn_unit(const uint32_t* q, const uint32_t* k, const uint32_t* v, const uint32_t* kh, const uint32_t* vh,
                                          const float* f, const float* rk, float bias0, float bias1, bool u0, bool u1, uint32_t mU, uint32_t dst) {
    float s0[4] = {0.f, 0.f, 0.f, 0.f}, s1[4] = {0.f, 0.f, 0.f, 0.f}, s2[4] = {0.f, 0.f, 0.f, 0.f};
#pragma unroll
    for (int ks = 0; ks < 2; ks++) {
        mma16816(s0, q[4 * ks], q[4 * ks + 1], q[4 * ks + 2], q[4 * ks + 3], kh[HS * 2 * ks], kh[HS * (2 * ks + 1)]);
        mma16816(s1, q[4 * ks], q[4 * ks + 1], q[4 * ks + 2], q[4 * ks + 3], k[4 * ks], k[4 * ks + 2]);
        mma16816(s2, q[4 * ks], q[4 * ks + 1], q[4 * ks + 2], q[4 * ks + 3], k[4 * ks + 1], k[4 * ks + 3]);
    }
    float a0 = fmaf(u0 ? s0[0] : s1[0], f[0], bias0), a1 = fmaf(u1 ? s0[1] : s1[1], f[1], bias1);
    float b0 = (u0 ? s1[2] : s2[2]) * f[2], b1 = (u1 ? s1[3] : s2[3]) * f[3];
    float ma = fmaxf(a0, a1), mb = fmaxf(b0, b1);
    ma = fmaxf(ma, __shfl_xor_sync(0xffffffffu, ma, 1)); mb = fmaxf(mb, __shfl_xor_sync(0xffffffffu, mb, 1));
    ma = fmaxf(ma, __shfl_xor_sync(0xffffffffu, ma, 2)); mb = fmaxf(mb, __shfl_xor_sync(0xffffffffu, mb, 2));
    a0 = ex2(a0 - ma); a1 = ex2(a1 - ma); b0 = ex2(b0 - mb); b1 = ex2(b1 - mb);
    float sa = a0 + a1, sb = b0 + b1;
    a0 *= rk[0]; a1 *= rk[1]; b0 *= rk[2]; b1 *= rk[3];
    sa += __shfl_xor_sync(0xffffffffu, sa, 1); sb += __shfl_xor_sync(0xffffffffu, sb, 1);
    sa += __shfl_xor_sync(0xffffffffu, sa, 2); sb += __shfl_xor_sync(0xffffffffu, sb, 2);
    const float ia = rcp(sa), ib = rcp(sb);
    const uint32_t plo = pack_bf16(a0 * ia, a1 * ia), phi = pack_bf16(b0 * ib, b1 * ib);
    const uint32_t pa0 = plo & mU, pa2 = plo & ~mU, pa3 = phi & mU, pb1 = phi & ~mU;
    uint32_t o[8];
#pragma unroll
    for (int jj = 0; jj < 4; jj++) {
        float c[4] = {0.f, 0.f, 0.f, 0.f};
        mma16816(c, pa0, 0u, pa2, pa3, vh[HS * jj], v[2 * jj]);
        mma1688(c, 0u, pb1, v[2 * jj + 1]);
        o[2 * jj] = pack_bf16(c[0], c[1]); o[2 * jj + 1] = pack_bf16(c[2], c[3]);
    }
    stsm4(dst, o[0], o[1], o[2], o[3]);
    stsm4(dst ^ 32, o[4], o[5], o[6], o[7]);
}

__device__ __forceinline__ uint32_t norm_pair(uint32_t u, float m, float rinv) {
    const uint32_t d = pack_bf16(bf_lo(u) - m, bf_hi(u) - m);
    return pack_bf16(bf_lo(d) * rinv, bf_hi(d) * rinv);
}

__global__ void __launch_bounds__(512, 1)
fused_kernel(const __grid_constant__ CUtensorMap mx, const __grid_constant__ CUtensorMap mw, const __grid_constant__ CUtensorMap mwo,
             const __grid_constant__ CUtensorMap mout, const __grid_constant__ CUtensorMap mgu, const __grid_constant__ CUtensorMap mwd,
             const __grid_constant__ CUtensorMap mo,
             const __nv_bfloat16* __restrict__ x, const __nv_bfloat16* __restrict__ wr, Scratch* __restrict__ scr, int swap_gu) {
    extern __shared__ __align__(1024) uint8_t smem[];
    const uint32_t sb = smem_u32(smem);
    const uint32_t bars = sb + OFF_BAR;
    const int tid = threadIdx.x, lane = tid & 31, warp = __shfl_sync(0xffffffffu, tid >> 5, 0);
    const uint32_t sd = (sb & 0x3FFFF) >> 4;
    const int hp = blockIdx.x & 1, cl = blockIdx.x >> 1;
    const int pr = cl < 4 ? 39 + 8 * cl : cl < 36 ? cl - 4 : cl < 64 ? cl - 4 + ((cl - 36) * 37 >> 8) : cl;
    const int b = pr * 2 + hp, mt = pr >> 3, p = pr & 7, nt = 2 * p + hp, rh = p & 1, cb = (p & 6) + hp;
    const int par = mt >> 2, j0 = (mt & 3) * 256;
    int budget = BUDGET;

    TSC(tid == 0, 0);
    auto load_w = [&](int k) {
        const uint32_t full = bars + 8 * (B_WFULL + (k & 3));
        mbar_expect_tx(full, W_BYTES);
        tma_3d(sb + OFF_W + (k & 3) * W_BYTES, &mw, full, nt * 64, k * 64, 0);
    };
    if (elect_one()) {
        const uint32_t cnt = warp < B_WEMPTY / 6 ? 1 : warp < B_G1DONE / 6 ? 2 : warp < B_STAGED / 6 ? 4 : 8;
        if (warp < NBAR / 6) {
#pragma unroll
            for (int i = 0; i < 6; i++) mbar_init(bars + 48 * warp + 8 * i, cnt);
        }
        asm volatile("fence.mbarrier_init.release.cluster;" ::: "memory");
    }
    __syncthreads();

    if (b >= 128) {
        const int hc = b - 128, g = lane >> 2, t = lane & 3;
        if (warp < 12) {
            const int n = warp / 3, part = warp - 3 * n;
            auto load = [&](int k) {
                const uint32_t full = bars + 8 * (2 * n + (k & 1));
                mbar_expect_tx(full, W_BYTES);
                tma_3d(sb + (2 * n + (k & 1)) * W_BYTES, &mw, full, (4 * hc + n) * 64, k * 64, 0);
            };
            if (part == 0 && elect_one()) { load(0); load(1); }
            __syncwarp();
            float c0[4] = {0.f, 0.f, 0.f, 0.f}, c1[4] = {0.f, 0.f, 0.f, 0.f};
            const uint32_t sel = g == 0 ? 0x3f80u : g == 1 ? 0x3f800000u : 0u;
            const uint32_t a = sb + 2 * n * W_BYTES + part * BOX + t * 256 + ((g ^ (2 * t)) << 4);
#pragma unroll 1
            for (int k = 0; k < 16; k++) {
                mbar_wait(bars + 8 * (2 * n + (k & 1)), (k >> 1) & 1, budget);
                uint4 v[8], u[8];
#pragma unroll
                for (int i = 0; i < 8; i++) { v[i] = lds4(a + (k & 1) * W_BYTES + i * 1024); u[i] = lds4(((a + 128) ^ 16) + (k & 1) * W_BYTES + i * 1024); }
#pragma unroll
                for (int i = 0; i < 8; i++) { mma16816(c0, v[i].x, v[i].y, u[i].x, u[i].y, sel, sel); mma16816(c1, v[i].z, v[i].w, u[i].z, u[i].w, sel, sel); }
                bar_sync(1 + n, 96);
                if (part == 0 && k < 14 && elect_one()) load(k + 2);
                __syncwarp();
            }
            if (t == 0) {
                float* d = &scr->cs[4 * hc + n][(part * 4 + (g >> 1)) * 16 + (g & 1) * 2];
                st_rlx2(d, __float_as_uint(c0[0]), __float_as_uint(c0[1])); st_rlx2(d + 4, __float_as_uint(c0[2]), __float_as_uint(c0[3]));
                st_rlx2(d + 8, __float_as_uint(c1[0]), __float_as_uint(c1[1])); st_rlx2(d + 12, __float_as_uint(c1[2]), __float_as_uint(c1[3]));
            }
            bar_sync(5, 416);
            if (tid == 0) { fence_gpu(); st_rlx(&scr->csflag[hc], lds1(sb + OFF_EP)); }
            TSC(tid == 0, 19);
        } else {
            const int ta = tid - 384, wq = warp - 12, jl = 2 * hc + 1;
            const uint32_t ep = ld_rlx(&scr->epoch[0]) + 1;
            if (wq == 0) { if (lane == 0) sts1(sb + OFF_EP, ep); bar_arrive(5, 416); }
            uint32_t kv[16];
#pragma unroll 1
            do {
                uint32_t bad = 0;
#pragma unroll
                for (int n = 0; n < 8; n++) { const uint4 q = ld_rlx4(&scr->row[(n * 128 + ta) * 2]); kv[2 * n] = q.y; kv[2 * n + 1] = q.w; bad |= (q.y ^ ep) | (q.w ^ ep); }
                if ((bad & 31) == 0) break;
            } while (--budget > 0);
            __syncwarp();
            TSC(ta == 0, 17);
            uint32_t m1 = 0, m2 = 0, mine = 0;
#pragma unroll
            for (int n = 0; n < 16; n++) { m2 = max(m2, min(m1, kv[n])); m1 = max(m1, kv[n]); }
            bool spare = true;
#pragma unroll 1
            for (int r = 0; r <= jl; r++) {
                const uint32_t top = redux_max(m1);
                if (lane == r) mine = top;
                if (m1 == top) {
                    m1 = m2;
                    if (!spare) {
                        m1 = 0;
#pragma unroll
                        for (int n = 0; n < 16; n++) m1 = max(m1, kv[n] < top ? kv[n] : 0u);
                    }
                    spare = false;
                }
                __syncwarp();
            }
            if (lane < 8) sts1(sb + OFF_STAT + (wq * 8 + lane) * 4, mine);
            bar_sync(6, 128);
            const uint32_t c = lds1(sb + OFF_STAT + lane * 4);
            int rank = 0;
#pragma unroll
            for (int i = 0; i < 8; i++) { const uint4 q = lds4(sb + OFF_STAT + i * 16); rank += (q.x > c) + (q.y > c) + (q.z > c) + (q.w > c); }
            const uint32_t k0 = redux_max(rank == jl - 1 ? c : 0u), k1 = redux_max(rank == jl ? c : 0u);
            const int r0 = 2047 - ((k0 >> 5) & 2047), r1 = 2047 - ((k1 >> 5) & 2047);
            TSC(ta == 0, 18);
            const uint4 v0 = ldg_nc(x + (size_t)r0 * 1024 + ta * 8), v1 = ldg_nc(x + (size_t)r1 * 1024 + ta * 8);
            const uint32_t s0 = ld_rlx(&scr->row[r0]), s1 = ld_rlx(&scr->row[r1]);
            const float m0 = bf_lo(s0), i0 = rcp(bf_hi(s0)), mm1 = bf_lo(s1), i1 = rcp(bf_hi(s1));
            st_rlx4(&scr->xsel[ta * 32 + hc * 8], norm_pair(v0.x, m0, i0), norm_pair(v0.y, m0, i0), norm_pair(v0.z, m0, i0), norm_pair(v0.w, m0, i0));
            st_rlx4(&scr->xsel[ta * 32 + hc * 8 + 4], norm_pair(v1.x, mm1, i1), norm_pair(v1.y, mm1, i1), norm_pair(v1.z, mm1, i1), norm_pair(v1.w, mm1, i1));
            bar_sync(6, 128);
            if (ta == 0) { fence_gpu(); st_rlx2(&scr->sel[2 * hc], k0, k1); }
            TSC(ta == 0, 20);
        }
        TS_END();
        return;
    }
    asm volatile("barrier.cluster.arrive.relaxed.aligned;" ::: "memory");

    const int kc = b >> 4, c2 = b & 15;
    if (warp >= 12) {
        reg_dec<24>();
        if (warp == 12) {
            if (elect_one()) {
#pragma unroll 1
                for (int n = 0; n < 12; n++) {
                    const int w = n & 1, j = n < 8 ? (n >> 1) + 2 : (n >> 1) - 4;
                    const uint32_t full = bars + 8 * (B_XFULL + w * 6 + j);
                    mbar_expect_tx(full, BOX);
                    tma_4d(sb + w * OFF_X1 + j * BOX, &mx, full, par * 1024 + (n >> 2) * 64, 0, (j0 + w * 128) >> 5, (~n >> 1) & 1);
                    if (n == ROWS_AT) { mbar_expect_tx(bars + 8 * B_ROW, 4 * BOX); bulk_g2s(sb + OFF_FR, x + (size_t)b * 16 * 1024, 4 * BOX, bars + 8 * B_ROW); }
                    if (n == 0 || (n & 3) == 3) load_w((n + 1) >> 2);
                }
#pragma unroll 1
                for (int k = 4; k < 16; k++) {
                    mbar_wait(bars + 8 * (B_WEMPTY + (k & 3)), ((k >> 2) & 1) ^ 1, budget);
                    load_w(k);
#pragma unroll 1
                    for (int q = 2 * k - 8; q < 2 * k - 6; q++) {
                        if (q < 16) { if (b < 112) tma_pf_3d(&mgu, b * 32, q * 64, 0); }
                        else if (q == 16) tma_pf_3d(&mwo, 0, (b >> 3) * 64, (b & 7) * 2);
                        else tma_pf_3d(&mwd, 0, kc * 448 + (q - 17) * 64, c2);
                    }
                }
                TS(27);
                int s = 1;
#pragma unroll 1
                for (int i = 0; i < 16; i++) {
                    mbar_wait(bars + 8 * (i < 4 ? B_WEMPTY + min(i, 2) : i == 4 ? B_G1DONE : B_WOEMPTY + s), i < 4 || i >= 12, budget);
                    if (i == 4) {
#pragma unroll 1
                        for (int n = 0; n < 4; n++) {
                            const uint32_t f2 = bars + 8 * (B_XT + (n >> 1));
                            if (!(n & 1)) mbar_expect_tx(f2, 2 * BOX);
                            tma_4d(sb + (n >> 1) * OFF_O1 + (3 + (n & 1)) * BOX, &mx, f2, par * 1024 + cb * 128 + (n & 1) * 64, 0, (j0 + rh * 128) >> 5, 1 - (n >> 1));
                        }
                    }
                    const uint32_t full = bars + 8 * (B_WOFULL + s);
                    mbar_expect_tx(full, 2 * BOX);
                    tma_3d(sb + OFF_WO + s * 2 * BOX, &mwo, full, 0, ((2 * p + (i < 2 ? i ^ hp : i)) & 15) * 64, cb * 2);
                    TSC(TIMING == 4, 48 + i);
                    if (++s == NWO) s = 0;
                }
                TS(25);
            }
        } else {
            bar_sync(8, 224);
            const uint32_t ep = lds1(sb + OFF_EP);
            if (warp == 13) {
                cluster_wait();
                if (elect_one()) {
                    int j = 2; uint32_t ph = 0;
#pragma unroll 1
                    for (int n = 6; n < 32; n++) {
                        mbar_wait(bars + 8 * (B_XEMPTY + j), ph, budget);
                        tma_4d_mc(sb + hp * OFF_X1 + j * BOX, &mx, bars + 8 * (B_XFULL + hp * 6 + j), par * 1024 + (n >> 1) * 64, 0, (j0 + hp * 128) >> 5, ~n & 1);
                        if (++j == 6) j = 0;
                        if (j == 2) ph ^= 1;
                    }
                }
                __syncwarp();
                uint32_t* hs = &scr->halo[b - 16][lane * 4];
#pragma unroll 1
                for (int c = 0; c < 4; c += 2) {
                    uint4 v0 = make_uint4(0, 0, 0, 0), v1 = v0;
                    if (j0) {
#pragma unroll 1
                        do { v0 = ld_rlx4(hs + c * 128); v1 = ld_rlx4(hs + c * 128 + 128); } while ((v0.x == 0 || v1.x == 0) && --budget > 0);
                        st_rlx(hs + c * 128, 0); st_rlx(hs + c * 128 + 128, 0);
                    }
                    sts4(sb + OFF_HIN + c * 512 + lane * 16, v0.x, v0.y, v0.z, v0.w);
                    sts4(sb + OFF_HIN + c * 512 + 512 + lane * 16, v1.x, v1.y, v1.z, v1.w);
                }
                __syncwarp();
                bar_arrive(11, 64);
                TSC(lane == 0, 31);
                const int src = ((mt * 2 + rh) * 2 + 1 - hp) * 1024;
                const uint32_t* fl = &scr->oflag[mt * 2 + 1 - hp][lane & 15];
                uint32_t ready = 0, ph = 0;
                int s = 2;
#pragma unroll 1
                for (int i = 2; i < 16; i++) {
                    const int kb = (2 * p + i) & 15;
#pragma unroll 1
                    while (!((ready >> kb) & 1) && --budget > 0) ready = __ballot_sync(0xffffffffu, ld_acq(fl) == ep);
                    TSC(lane == 0 && i == 2, 30);
                    if (elect_one()) {
                        mbar_wait(bars + 8 * (B_OEMPTY + s), ph, budget);
                        tma_2d_mc(sb + hp * OFF_O1 + s * BOX, &mo, bars + 8 * (B_OFULL + hp * NO + s), 0, src + kb * 64);
                        TSC(TIMING == 4 && hp == 0, 32 + i);
                    }
                    budget = __shfl_sync(0xffffffffu, budget, 0);
                    if (++s == NO) s = 0;
                    if (s == 2) ph ^= 1;
                }
            } else if (warp == 14) {
                int s = 0; uint32_t ph = 0;
#pragma unroll 1
                for (int q = b < 112 ? 0 : 16; q < 23; q++) {
                    if (!(q & 15)) {
                        poll_all(q ? &scr->hflag[kc * 14 + min(lane, 13)] : &scr->sel[lane & 7], q ? ~0u : 31u, q ? ep : ep & 31, budget);
                        TSC(lane == 0, q ? 29 : 26);
                        if (b == 0 && q == 0 && lane == 0) st_rlx(&scr->epoch[0], ep);
                        fence_async_gmem();
                    }
                    if (elect_one()) {
                        const uint32_t full = bars + 8 * (B_FFULL + s), dst = sb + OFF_FR + s * F_BYTES;
                        mbar_wait(bars + 8 * (B_FEMPTY + s), ph, budget);
                        mbar_expect_tx(full, F_BYTES);
                        tma_3d(dst, q < 16 ? &mgu : &mwd, full, q < 16 ? b * 32 : 0, q < 16 ? q * 64 : kc * 448 + (q - 16) * 64, q < 16 ? 0 : c2);
                        bulk_g2s(dst + BOX, q < 16 ? scr->xsel + q * 256 : scr->h + (kc * 7 + q - 16) * 256, 1024, full);
                    }
                    budget = __shfl_sync(0xffffffffu, budget, 0);
                    if (++s == NF) { s = 0; ph ^= 1; }
                }
            } else {
                mbar_wait(bars + 8 * B_FEMPTY, 0, budget);
#pragma unroll 1
                for (int i = lane; i < 264; i += 32) {
                    const int j = j0 - 8 + i;
                    uint2 v = make_uint2(0x7f800000u, 0);
                    if (j >= 0) {
#pragma unroll 1
                        do { v = ld_rlx2(&scr->row[2 * j + par]); } while (((v.y ^ ep) & 31) && --budget > 0);
                    }
                    sts2(sb + OFF_STAT + i * 8, __float_as_uint(-bf_lo(v.x)), __float_as_uint(rcp(bf_hi(v.x))));
                }
                budget = __shfl_sync(0xffffffffu, budget, 0);
                poll_all(&scr->csflag[nt >> 2], ~0u, ep, budget);
#pragma unroll
                for (int i = 0; i < 3; i++) { const uint2 v = ld_rlx2(&scr->cs[nt][i * 64 + lane * 2]); sts2(sb + OFF_CS + i * 256 + lane * 8, v.x, v.y); }
                __syncwarp();
                if (elect_one()) {
                    mbar_arrive(bars + 8 * B_AUX);
                    TS(21);
                    uint8_t* dst = scr->o + ((size_t)(mt * 4 + 1) * 16 + nt) * BOX;
#pragma unroll 1
                    for (int v = 0; v < 2; v++) {
                        const uint32_t ring = sb + v * OFF_O1, fb = bars + 8 * (B_OFULL + v * NO + 1);
                        mbar_expect_tx(fb, BOX);
                        mbar_wait(bars + 8 * (B_STAGED + v), 0, budget);
                        bulk_s2g(dst + (rh * 32 - v * 16) * BOX, ring, BOX);
                        bulk_s2g(dst + ((rh ^ 1) * 32 - v * 16) * BOX, ring + 2 * BOX, BOX);
                        asm volatile("cp.async.bulk.commit_group;" ::: "memory");
                        bulk_s2c(mapa(ring + BOX, hp ^ 1), ring, BOX, mapa(fb, hp ^ 1));
                    }
#pragma unroll
                    for (int v = 0; v < 2; v++) {
                        if (v == 0) asm volatile("cp.async.bulk.wait_group 1;" ::: "memory"); else asm volatile("cp.async.bulk.wait_group 0;" ::: "memory");
                        TS(12 + 2 * v);
                        mbar_arrive(bars + 8 * (B_OFULL + v * NO));
                        mbar_expect_tx(bars + 8 * (B_OFULL + v * NO + 2), BOX);
                        mbar_arrive_at(mapa(bars + 8 * (B_OEMPTY + 2), v));
                        fence_gpu();
                        st_rlx(&scr->oflag[mt * 2 + 1 - v][nt], ep);
                        TS(13 + 2 * v);
                    }
                }
            }
        }
        TS_END();
    } else if (warp >= 8) {
        reg_dec<40>();
        const int wq = warp - 8, ta = tid - 256, g = lane >> 2, t = lane & 3;
        const uint32_t rbuf = sb + OFF_FR + wq * BOX, rbar = bars + 8 * B_ROW;
        const uint4 wv = ldg_nc(wr + ta * 8);
        if (ta == 0) sts1(sb + OFF_EP, ld_rlx(&scr->epoch[0]) + 1);
        sts4(sb + OFF_STAT + ta * 16, wv.x, wv.y, wv.z, wv.w);
        bar_sync(8, 224);
        const uint32_t ep = lds1(sb + OFF_EP);
        {
            float sw = 0.f;
#pragma unroll 1
            for (int i = 0; i < 16; i++) { const uint32_t q = lds1(sb + OFF_STAT + i * 128 + lane * 4); sw += bf_lo(q) + bf_hi(q); }
#pragma unroll 1
            for (int o = 16; o > 0; o >>= 1) sw += __shfl_xor_sync(0xffffffffu, sw, o);
            float s1 = 0.f, s2 = 0.f, sr = 0.f;
            const uint32_t xa = rbuf + (lane >> 3) * 2048 + (lane & 7) * 16, wa = sb + OFF_STAT + (lane & 7) * 16;
            mbar_wait(rbar, 0, budget);
            TSC(ta == 0, 17);
            uint4 u = lds4(xa), w4 = lds4(wa);
#pragma unroll kStatsUnroll
            for (int i = 1; i <= 16; i++) {
                const uint32_t o = (i * 128) & 2047;
                const uint4 un = lds4(xa + o), wn = lds4(wa + o);
#pragma unroll
                for (int c = 0; c < 4; c++) {
                    const float a0 = bf_lo((&u.x)[c]), a1 = bf_hi((&u.x)[c]);
                    s1 += a0; s2 = fmaf(a0, a0, s2); sr = fmaf(a0, bf_lo((&w4.x)[c]), sr);
                    s1 += a1; s2 = fmaf(a1, a1, s2); sr = fmaf(a1, bf_hi((&w4.x)[c]), sr);
                }
                u = un; w4 = wn;
            }
#pragma unroll 1
            for (int o = 1; o < 8; o <<= 1) {
                s1 += __shfl_xor_sync(0xffffffffu, s1, o); s2 += __shfl_xor_sync(0xffffffffu, s2, o); sr += __shfl_xor_sync(0xffffffffu, sr, o);
            }
            const float mean = s1 * (1.f / 1024.f), mb = bf16r(mean);
            float var = fmaf(-mean, mean, s2 * (1.f / 1024.f));
            sr = fmaf(-mb, sw, sr);
            if (__builtin_expect(__any_sync(0xffffffffu, mean * mean > 256.f * var), 0)) {
                float a2 = 0.f, ar = 0.f;
#pragma unroll 1
                for (int i = 0; i < 64; i++) {
                    const uint32_t o = (i >> 2) * 128 + (i & 3) * 4, q1 = lds1(xa + o), q2 = lds1(wa + o);
                    a2 = fmaf(bf_lo(q1) - mean, bf_lo(q1) - mean, fmaf(bf_hi(q1) - mean, bf_hi(q1) - mean, a2));
                    ar = fmaf(bf_lo(q1) - mb, bf_lo(q2), fmaf(bf_hi(q1) - mb, bf_hi(q2), ar));
                }
#pragma unroll 1
                for (int o = 1; o < 8; o <<= 1) { a2 += __shfl_xor_sync(0xffffffffu, a2, o); ar += __shfl_xor_sync(0xffffffffu, ar, o); }
                var = a2 * (1.f / 1024.f); sr = ar;
            }
            const int s = b * 16 + wq * 4 + (lane >> 3);
            float den;
            asm("sqrt.approx.f32 %0, %1;" : "=f"(den) : "f"(bf16r(bf16r(var) + 1e-5f)));
            const uint32_t st = pack_bf16(mb, den);
            const uint32_t rb = pack_bf16(0.f, sr * rcp(bf_hi(st)) + 0.f);
            uint32_t ord = (int)rb < 0 ? ~rb & 0xffff0000u : rb | 0x80000000u;
            if ((rb & 0x7fffffffu) > 0x7f800000u) ord = 0;
            if ((lane & 7) == 0) st_rlx2(&scr->row[s], st, ord | ((2047 - s) << 5) | (ep & 31));
            __syncwarp();
            if (lane < NF) mbar_arrive(bars + 8 * (B_FEMPTY + lane));
        }
        TSC(ta == 0, 18);
        {
            int s = 0; uint32_t fph = 0;
#pragma unroll 1
            for (int ph = b < 112 ? 0 : 1; ph < 2; ph++) {
                float acc[4] = {0.f, 0.f, 0.f, 0.f};
                const uint32_t alo = sd + (ph ? dlo(OFF_FR, 8192) : dlo(OFF_FR, 4096)), ahi = ph ? dhi(1024, 1) : dhi(512, 2), astep = ph ? 128 : 64;
                if (ph) mbar_wait(bars + 8 * (B_STAGED + 1), 0, budget);
#pragma unroll 1
                for (int q = ph ? 7 : 16; q > 0; q--) {
                    mbar_wait(bars + 8 * (B_FFULL + s), fph, budget);
                    TSC(TIMING == 3 && ta == 0, 32 + (ph ? 23 : 16) - q);
                    const uint32_t da = alo + s * (F_BYTES >> 4), db = sd + dlo(OFF_FR + BOX, 128) + s * (F_BYTES >> 4);
                    wg_fence();
#pragma unroll
                    for (int j = 0; j < 4; j++) wgmma_n8<1, 0>(acc, mkdesc(da + j * astep, ahi), mkdesc(db + j * 16, dhi(128, 0)), 1);
                    wg_commit();
                    wg_wait<0>();
                    if (lane == 0) mbar_arrive(bars + 8 * (B_FEMPTY + s));
                    if (++s == NF) { s = 0; fph ^= 1; }
                }
                if (ph == 0) {
                    const bool second = (wq >= 2) != (swap_gu != 0);
                    const uint32_t xa = sb + OFF_UPD + ((wq & 1) * 32 + lane) * 16;
                    if (second) sts4(xa, __float_as_uint(acc[0]), __float_as_uint(acc[1]), __float_as_uint(acc[2]), __float_as_uint(acc[3]));
                    bar_sync(12, 128);
                    if (!second) {
                        const float4 up = lds4f(xa);
                        float hv[4];
#pragma unroll
                        for (int c = 0; c < 4; c++) { const float ga = bf16r(acc[c]); hv[c] = bf16r(ga * sigmoidf(ga)) * bf16r((&up.x)[c]); }
                        uint32_t* hd = &scr->h[(b * 4 + (wq & 1) * 2) * 32 + lane];
                        st_rlx(hd, movm(pack_bf16(hv[0], hv[1]))); st_rlx(hd + 32, movm(pack_bf16(hv[2], hv[3])));
                    }
                } else {
#pragma unroll
                    for (int c = 0; c < 4; c++) st_rlx(&scr->ypart[kc][2 * t + (c & 1)][c2 * 64 + wq * 16 + (c >> 1) * 8 + g], __float_as_uint(acc[c]));
                }
                bar_sync(12, 128);
                if (ta == 0) { fence_gpu(); st_rlx(&scr->hflag[ph * 128 + b], ep); }
                TSC(ta == 0, 22 + ph);
            }
        }
#pragma unroll 1
        for (int j = wq; j < 8; j += 4) {
            const uint32_t kj = ld_rlx(&scr->sel[j]);
            const int row = 2047 - ((kj >> 5) & 2047), jj = (row & 1) == par ? (row >> 1) - j0 : -1;
            float4 a = make_float4(0.f, 0.f, 0.f, 0.f);
            if ((jj >> 7) == rh) {
                poll_all(&scr->yflag[(lane & 7) * 16 + cb * 2 + (lane >> 4)], ~0u, ep, budget);
#pragma unroll 4
                for (int m = 0; m < 8; m++) {
                    const uint4 v = ld_rlx4(&scr->ypart[m][j][cb * 128 + lane * 4]);
                    a.x += __uint_as_float(v.x); a.y += __uint_as_float(v.y); a.z += __uint_as_float(v.z); a.w += __uint_as_float(v.w);
                }
            }
            const float sig = bf16r(sigmoidf(__uint_as_float(((int)kj < 0 ? kj & 0x7fffffffu : ~kj) & 0xffff0000u)));
            sts2(sb + OFF_UPD + (lane >> 4) * 1024 + j * 128 + ((((lane >> 1) & 7) ^ j) << 4) + (lane & 1) * 8,
                 pack_bf16(bf16r(a.x) * sig, bf16r(a.y) * sig), pack_bf16(bf16r(a.z) * sig, bf16r(a.w) * sig));
            sts1(sb + OFF_SEL + j * 4, jj);
        }
        fence_async_smem();
        __syncwarp();
        if (lane == 0) mbar_arrive(bars + 8 * B_UPD);
        TSC(ta == 0, 24);
        TS_END();
    } else {
        reg_inc<224>();
        const int w = warp >> 2, wi = warp & 3, g = lane >> 2, t = lane & 3;
        const bool elect = (tid & 127) == 0;
        const uint32_t mad = (lane & 15) * 128 + (((lane >> 4) ^ (lane & 7)) << 4);
        {
            float acc0[96], acc1[96];
            {
                const uint32_t xfull = bars + 8 * (B_XFULL + w * 6), xempty = mapa(bars + 8 * B_XEMPTY, w), dx0 = sd + dlo(w * OFF_X1, 16);
                int j = 2, pj = 0; uint32_t xph = 0;
                cluster_wait();
#pragma unroll 1
                for (int k = 0; k < 16; k++) {
                    const uint32_t dx = dx0 + j * (BOX >> 4), dw = sd + dlo(OFF_W, BOX) + (k & 3) * (W_BYTES >> 4);
                    mbar_wait(bars + 8 * (B_WFULL + (k & 3)), (k >> 2) & 1, budget);
                    mbar_wait(xfull + 8 * j, xph, budget);
                    TSC(elect && k == 0, 1 + 8 * w);
                    TSC(TIMING == 1 && tid == 0, 32 + k);
                    wg_fence();
#pragma unroll
                    for (int kk = 0; kk < 4; kk++) wgmma_n192<0, 1>(acc1, mkdesc(dx + kk * 2, dhi(1024, 1)), mkdesc(dw + kk * 128, dhi(1024, 1)), kk ? 1 : k);
                    wg_commit();
                    wg_wait<1>();
                    if (elect && k > 0) {
                        mbar_arrive(bars + 8 * (B_WEMPTY + ((k - 1) & 3)));
                        if (k <= 13) { mbar_expect_tx(xfull + 8 * pj, BOX); mbar_arrive_at(xempty + 8 * pj); }
                    }
                    mbar_wait(xfull + 8 * j + 8, xph, budget);
                    wg_fence();
#pragma unroll
                    for (int kk = 0; kk < 4; kk++) wgmma_n192<0, 1>(acc0, mkdesc(dx + 512 + kk * 2, dhi(1024, 1)), mkdesc(dw + kk * 128, dhi(1024, 1)), kk ? 1 : k);
                    wg_commit();
                    wg_wait<1>();
                    if (elect && k <= 12) { mbar_expect_tx(xfull + 8 * j, BOX); mbar_arrive_at(xempty + 8 * j); }
                    pj = j + 1;
                    j += 2;
                    if (j == 6) j = 0;
                    if (j == 2) xph ^= 1;
                }
            }
            mbar_wait(bars + 8 * B_AUX, 0, budget);
            const uint32_t sta = sb + OFF_STAT + (8 + w * 128 + wi * 32) * 8, csa = sb + OFF_CS + t * 16;
            uint32_t pk0[48], pk1[48];
            auto np = [&](const float* a, uint32_t* d, int jp, int e, float nm, const float4& c) {
                d[4 * jp + e] = pack_bf16(fmaf(nm, c.x, a[8 * jp + 2 * e]), fmaf(nm, c.y, a[8 * jp + 2 * e + 1]));
                d[4 * jp + 2 + e] = pack_bf16(fmaf(nm, c.z, a[8 * jp + 4 + 2 * e]), fmaf(nm, c.w, a[8 * jp + 5 + 2 * e]));
            };
            {
                const float n0 = lds1f(sta + (16 + g) * 8), n1 = lds1f(sta + (24 + g) * 8);
#pragma unroll
                for (int jp = 4; jp < 12; jp++) np(acc1, pk1, jp, 1, n1, lds4f(csa + jp * 64));
#pragma unroll
                for (int j = 16; j < 24; j++) pk1[2 * j + 1] = movm(pk1[2 * j + 1]);
                if (warp < 7) {
#pragma unroll
                    for (int c = 0; c < 4; c++) sts4(sb + (w ? OFF_H1 : OFF_H0) + wi * 2048 + c * 512 + lane * 16, pk1[17 + 8 * c], pk1[19 + 8 * c], pk1[21 + 8 * c], pk1[23 + 8 * c]);
                    bar_arrive(1 + warp, 64);
                } else if (j0 != 768) {
#pragma unroll
                    for (int c = 0; c < 4; c++) st_rlx4(&scr->halo[b][c * 128 + lane * 4], max(pk1[17 + 8 * c], 1u), pk1[19 + 8 * c], pk1[21 + 8 * c], pk1[23 + 8 * c]);
                }
                TSC(tid == 224, 28);
#pragma unroll
                for (int jp = 0; jp < 12; jp++) {
                    const float4 c = lds4f(csa + jp * 64);
                    np(acc1, pk1, jp, 0, n0, c);
                    if (jp < 4) np(acc1, pk1, jp, 1, n1, c);
                }
#pragma unroll
                for (int j = 16; j < 24; j++) pk1[2 * j] = movm(pk1[2 * j]);
            }
            const bool u0 = 2 * t > g, u1 = 2 * t + 1 > g;
            const uint32_t mU = (u0 ? 0xffffu : 0u) | (u1 ? 0xffff0000u : 0u);
            const uint32_t ka0 = sta + (2 * t - (u0 ? 8 : 0)) * 8 + 4, ka1 = sta + (2 * t + 1 - (u1 ? 8 : 0)) * 8 + 4;
            float rk[2][4], f[2][4], n0 = 0.f, n1 = 0.f;
#pragma unroll
            for (int e = 0; e < 4; e++) {
                const float2 q = lds2f(sta + (8 * e + g) * 8);
                if (e == 0) n0 = q.x;
                if (e == 1) n1 = q.x;
                const float rq = q.y * (0.17677669529663687f * 1.4426950408889634f);
                rk[e >> 1][(e & 1) * 2] = lds1f(ka0 + e * 64); rk[e >> 1][(e & 1) * 2 + 1] = lds1f(ka1 + e * 64);
                f[e >> 1][(e & 1) * 2] = rq * rk[e >> 1][(e & 1) * 2]; f[e >> 1][(e & 1) * 2 + 1] = rq * rk[e >> 1][(e & 1) * 2 + 1];
            }
            wg_wait<0>();
            if (elect) { mbar_arrive(bars + 8 * B_G1DONE); mbar_arrive_at(mapa(bars + 8 * B_G1DONE, hp ^ 1)); }
            TSC(elect, 2 + 8 * w);
#pragma unroll
            for (int jp = 4; jp < 12; jp++) { const float4 c = lds4f(csa + jp * 64); np(acc0, pk0, jp, 1, n1, c); np(acc0, pk0, jp, 0, n0, c); }
#pragma unroll
            for (int j = 16; j < 24; j++) { pk0[2 * j + 1] = movm(pk0[2 * j + 1]); pk0[2 * j] = movm(pk0[2 * j]); }
            const uint32_t od = sb + (w == rh ? 0 : 2 * BOX) + wi * 2048 + mad;
            mbar_wait(bars + 8 * B_G1DONE, 0, budget);
#pragma unroll
            for (int hd = 0; hd < 2; hd++)
                attn_unit<2>(&pk1[hd * 8], &pk1[16 + hd * 8], &pk1[32 + hd * 8], &pk0[17 + hd * 8], &pk0[33 + hd * 8], f[1], rk[1], 0.f, 0.f, u0, u1, mU, od ^ (hd * 64));
#pragma unroll
            for (int jp = 0; jp < 4; jp++) { const float4 c = lds4f(csa + jp * 64); np(acc0, pk0, jp, 0, n0, c); np(acc0, pk0, jp, 1, n1, c); }
            fence_async_smem();
            __syncwarp();
            if (lane == 0) mbar_arrive(bars + 8 * B_STAGED);
            TSC(elect, 3 + 8 * w);
            bar_sync(warp ? warp : 11, 64);
            uint4 hl[4];
#pragma unroll
            for (int c = 0; c < 4; c++) hl[c] = lds4(sb + (warp == 0 ? OFF_HIN : warp <= 4 ? OFF_H0 - 2048 : OFF_H1 - 5 * 2048) + warp * 2048 + c * 512 + lane * 16);
            const bool first = warp == 0 && j0 == 0;
            const float bias0 = first && u0 ? -INFINITY : 0.f, bias1 = first && u1 ? -INFINITY : 0.f;
#pragma unroll
            for (int hd = 0; hd < 2; hd++)
                attn_unit<1>(&pk0[hd * 8], &pk0[16 + hd * 8], &pk0[32 + hd * 8], &hl[hd].x, &hl[2 + hd].x, f[0], rk[0], bias0, bias1, u0, u1, mU, (od + OFF_O1) ^ (hd * 64));
            fence_async_smem();
            __syncwarp();
            if (lane == 0) mbar_arrive(bars + 8 * (B_STAGED + 1));
        }
        TSC(tid == 0, 4);
        float acc[64];
        const uint32_t ring = sb + w * OFF_O1, ofull = bars + 8 * (B_OFULL + w * NO), oempty = mapa(bars + 8 * B_OEMPTY, w);
        const int r0 = rh * 128 + wi * 32 + (1 - w) * 16 + g;
        {
            const float2 s0 = lds2f(sb + OFF_STAT + (8 + r0) * 8), s1 = lds2f(sb + OFF_STAT + (16 + r0) * 8);
            const float m0 = s0.x * s0.y, f0 = 1.f + s0.y, m1 = s1.x * s1.y, f1 = 1.f + s1.y;
            mbar_wait(bars + 8 * (B_XT + w), 0, budget);
#pragma unroll
            for (int j = 0; j < 8; j++) {
                uint32_t a0, a1, a2, a3;
                asm volatile("ldmatrix.sync.aligned.m8n8.x4.shared.b16 {%0,%1,%2,%3}, [%4];" : "=r"(a0), "=r"(a1), "=r"(a2), "=r"(a3)
                             : "r"(((ring + wi * 2048 + mad) ^ ((j & 3) * 32)) + (3 + (j >> 2)) * BOX) : "memory");
                acc[8 * j + 0] = fmaf(bf_lo(a0), f0, m0); acc[8 * j + 1] = fmaf(bf_hi(a0), f0, m0);
                acc[8 * j + 2] = fmaf(bf_lo(a1), f1, m1); acc[8 * j + 3] = fmaf(bf_hi(a1), f1, m1);
                acc[8 * j + 4] = fmaf(bf_lo(a2), f0, m0); acc[8 * j + 5] = fmaf(bf_hi(a2), f0, m0);
                acc[8 * j + 6] = fmaf(bf_lo(a3), f1, m1); acc[8 * j + 7] = fmaf(bf_hi(a3), f1, m1);
            }
        }
        bar_sync(9 + w, 128);
        if (elect) {
            mbar_arrive(bars + 8 * (B_WOEMPTY + 6)); mbar_arrive(bars + 8 * B_WOEMPTY);
            mbar_expect_tx(ofull + 24, BOX); mbar_expect_tx(ofull + 32, BOX);
            mbar_arrive_at(oempty + 24); mbar_arrive_at(oempty + 32);
        }
        TSC(tid == 0, 5);
        {
            const uint32_t da0 = sd + dlo(w * OFF_O1, 16);
            int os = 0, ws = 1, pos = 0, pws = 0; uint32_t oph = 0, wph = 0;
#pragma unroll 1
            for (int i = 0; i < 16; i++) {
                const uint32_t da = da0 + os * (BOX >> 4), db = sd + dlo(OFF_WO, BOX) + ws * (2 * BOX >> 4);
                mbar_wait(bars + 8 * (B_WOFULL + ws), wph, budget);
                mbar_wait(ofull + 8 * os, oph, budget);
                TSC(TIMING == 1 && tid == 0, 48 + i);
                TSC(TIMING == 2 && elect, 32 + w * 16 + i);
                wg_fence();
#pragma unroll
                for (int kk = 0; kk < 4; kk++) wgmma_n128<0, 1>(acc, mkdesc(da + kk * 2, dhi(1024, 1)), mkdesc(db + kk * 128, dhi(1024, 1)), 1);
                wg_commit();
                wg_wait<1>();
                if (elect && i > 0 && i <= 11) {
                    mbar_expect_tx(ofull + 8 * pos, BOX); mbar_arrive_at(oempty + 8 * pos);
                    if (i <= 9) mbar_arrive(bars + 8 * (B_WOEMPTY + pws));
                }
                pos = os; pws = ws;
                if (++os == NO) { os = 0; oph ^= 1; }
                if (++ws == NWO) ws = 0;
                if (ws == 1) wph ^= 1;
            }
            mbar_wait(bars + 8 * B_UPD, 0, budget);
            const float2 sl = lds2f(sb + OFF_SEL + t * 8);
            const int d0 = __float_as_int(sl.x) - r0, d1 = __float_as_int(sl.y) - r0;
            const uint32_t a0 = (d0 == 0 ? 0x3f80u : 0u) | (d1 == 0 ? 0x3f800000u : 0u), a1 = (d0 == 8 ? 0x3f80u : 0u) | (d1 == 8 ? 0x3f800000u : 0u);
            wg_fence();
            wgmma_rs_n128(acc, a0, a1, 0u, 0u, mkdesc(sd + dlo(OFF_UPD, 1024), dhi(0, 1)));
            wg_commit();
            wg_wait<0>();
            TSC(elect, 7 + 9 * w);
            const uint32_t os0 = ring + BOX + wi * 4096;
#pragma unroll
            for (int j = 0; j < 8; j++)
                stsm4(((os0 + mad) ^ ((j & 3) * 32)) + (j >> 2) * 2048, pack_bf16(acc[8 * j], acc[8 * j + 1]), pack_bf16(acc[8 * j + 2], acc[8 * j + 3]),
                      pack_bf16(acc[8 * j + 4], acc[8 * j + 5]), pack_bf16(acc[8 * j + 6], acc[8 * j + 7]));
            fence_async_smem();
            __syncwarp();
            if (elect_one()) {
                asm volatile("cp.async.bulk.tensor.5d.global.shared::cta.bulk_group [%0, {%2, %2, %3, %4, %5}], [%1];\ncp.async.bulk.commit_group;\ncp.async.bulk.wait_group.read 0;"
                             ::"l"(&mout), "r"(os0), "r"(0), "r"(((j0 + rh * 128) >> 5) + wi), "r"(1 - w), "r"(par * 16 + cb * 2) : "memory");
            }
            TSC(elect, 8 - 2 * w);
            TS_END();
        }
    }
}

typedef CUresult (*EncodeFn)(CUtensorMap*, CUtensorMapDataType, cuuint32_t, void*, const cuuint64_t*, const cuuint64_t*, const cuuint32_t*,
                             const cuuint32_t*, CUtensorMapInterleave, CUtensorMapSwizzle, CUtensorMapL2promotion, CUtensorMapFloatOOBfill);

CUtensorMap make_map(EncodeFn fn, const void* base, int rank, const cuuint64_t* dims, const cuuint64_t* strides, const cuuint32_t* box,
                     CUtensorMapSwizzle swz = CU_TENSOR_MAP_SWIZZLE_128B, CUtensorMapL2promotion pro = CU_TENSOR_MAP_L2_PROMOTION_L2_256B) {
    CUtensorMap m;
    cuuint32_t es[5] = {1, 1, 1, 1, 1};
    fn(&m, CU_TENSOR_MAP_DATA_TYPE_BFLOAT16, rank, (void*)base, dims, strides, box, es, CU_TENSOR_MAP_INTERLEAVE_NONE,
       swz, pro, CU_TENSOR_MAP_FLOAT_OOB_FILL_NONE);
    return m;
}

}

extern "C" void kernel_launch(void* const* d_in, const int* in_sizes, int n_in, void* d_out, int out_size) {
    (void)in_sizes; (void)n_in; (void)out_size;
    const __nv_bfloat16* x = (const __nv_bfloat16*)d_in[0];
    const __nv_bfloat16* wqkv = (const __nv_bfloat16*)d_in[1];
    const __nv_bfloat16* wo = (const __nv_bfloat16*)d_in[2];
    const __nv_bfloat16* wr = (const __nv_bfloat16*)d_in[4];
    const __nv_bfloat16* wg = (const __nv_bfloat16*)d_in[5];
    const __nv_bfloat16* wu = (const __nv_bfloat16*)d_in[6];
    const __nv_bfloat16* wd = (const __nv_bfloat16*)d_in[7];
    static EncodeFn fn = nullptr;
    static Scratch* scr = nullptr;
    if (!fn) {
        void* p = nullptr; cudaDriverEntryPointQueryResult q;
        cudaGetDriverEntryPoint("cuTensorMapEncodeTiled", &p, cudaEnableDefault, &q);
        fn = (EncodeFn)p;
        cudaFuncSetAttribute(fused_kernel, cudaFuncAttributeMaxDynamicSharedMemorySize, SMEM_LAUNCH);
        cudaGetSymbolAddress((void**)&scr, g_scr);
    }
    const cuuint64_t xd[4] = {2048, 16, 32, 2}, xs[4] = {4096, 131072, 65536, 128}, od[5] = {64, 16, 32, 2, 32};
    const cuuint32_t xb[4] = {64, 16, 4, 1}, ob[5] = {64, 16, 1, 1, 2};
    const cuuint64_t wdm[3] = {1024, 1024, 3}, wst[2] = {6144, 2048};
    const cuuint32_t wb[3] = {64, 64, 3};
    const cuuint64_t wod[3] = {64, 1024, 16}, wdd[3] = {64, 3584, 16}, wos[2] = {2048, 128};
    const cuuint32_t wob[3] = {64, 64, 2}, wdb[3] = {64, 64, 1};
    CUtensorMap mx = make_map(fn, x, 4, xd, xs, xb), mw = make_map(fn, wqkv, 3, wdm, wst, wb);
    CUtensorMap mwo = make_map(fn, wo, 3, wod, wos, wob), mout = make_map(fn, d_out, 5, od, xs, ob);
    const int swap_gu = wu < wg;
    const cuuint64_t gd[3] = {3584, 1024, 2}, gst[2] = {7168, (cuuint64_t)(swap_gu ? (const char*)wg - (const char*)wu : (const char*)wu - (const char*)wg)};
    const cuuint32_t gb[3] = {32, 64, 2};
    CUtensorMap mgu = make_map(fn, swap_gu ? wu : wg, 3, gd, gst, gb, CU_TENSOR_MAP_SWIZZLE_64B, CU_TENSOR_MAP_L2_PROMOTION_L2_128B);
    CUtensorMap mwd = make_map(fn, wd, 3, wdd, wos, wdb, CU_TENSOR_MAP_SWIZZLE_128B, CU_TENSOR_MAP_L2_PROMOTION_L2_128B);
    const cuuint64_t md[2] = {64, 32768}, ms[1] = {128};
    const cuuint32_t mb[2] = {64, 64};
    CUtensorMap mo = make_map(fn, scr, 2, md, ms, mb, CU_TENSOR_MAP_SWIZZLE_NONE, CU_TENSOR_MAP_L2_PROMOTION_NONE);
    cudaLaunchConfig_t cfg = {};
    cfg.gridDim = dim3(132); cfg.blockDim = dim3(512); cfg.dynamicSmemBytes = SMEM_LAUNCH; cfg.stream = cudaStreamPerThread;
    cudaLaunchAttribute at[1];
    at[0].id = cudaLaunchAttributeClusterDimension; at[0].val.clusterDim.x = 2; at[0].val.clusterDim.y = 1; at[0].val.clusterDim.z = 1;
    cfg.attrs = at; cfg.numAttrs = 1;
    cudaLaunchKernelEx(&cfg, fused_kernel, mx, mw, mwo, mout, mgu, mwd, mo, x, wr, scr, swap_gu);
}
```

```cpp
#include <cuda_runtime.h>
#include <cuda.h>
#include <cuda_bf16.h>
#include <stdint.h>

namespace {

constexpr int BOX = 8192, W_BYTES = 3 * BOX;
constexpr int OFF_X0 = 0, OFF_W = 6 * BOX, OFF_X1 = 18 * BOX;
constexpr int OFF_O0 = 0, OFF_WO = 5 * BOX, OFF_O1 = 19 * BOX;
constexpr int OFF_H0 = 5 * BOX, OFF_H1 = 18 * BOX;
constexpr int NO = 5, NWO = 7, NF = 3, F_BYTES = 9216;
constexpr int OFF_FR = 24 * BOX;
constexpr int CS_BYTES = 3136;
constexpr int OFF_CS = OFF_FR + NF * F_BYTES;
constexpr int OFF_UPD = OFF_CS;
constexpr int OFF_HIN = OFF_CS + CS_BYTES;
constexpr int OFF_STAT = OFF_HIN + 2048;
constexpr int OFF_SEL = OFF_STAT + 2112;
constexpr int OFF_EP = OFF_SEL + 32;
constexpr int OFF_BAR = OFF_EP + 16;
constexpr int B_WFULL = 0, B_XFULL = 4, B_AUX = 16, B_XT = 17, B_WOFULL = 19, B_OFULL = 26, B_ROW = 36, B_FFULL = 37;
constexpr int B_WEMPTY = 42, B_XEMPTY = 46, B_WOEMPTY = 52, B_OEMPTY = 59;
constexpr int B_G1DONE = 66, B_FEMPTY = 67, B_UPD = 70, B_STAGED = 72, NBAR = 74;
constexpr int SMEM_BYTES = OFF_BAR + NBAR * 8;
static_assert(OFF_FR + 32768 <= OFF_STAT && SMEM_BYTES + 256 <= 232448 && OFF_BAR % 8 == 0 && OFF_UPD % 1024 == 0, "smem");
#define POLL_NS 100
#define HELP_AT 64
#define ROWS_AT 7
#define STATS_UNROLL 1
constexpr int kStatsUnroll = STATS_UNROLL;
constexpr int BUDGET = 1 << 18;

struct Scratch {
    uint8_t o[2048 * 1024 * 2];
    float ypart[8][8][1024];
    uint32_t halo[128][512];
    uint32_t h[14336];
    uint32_t xsel[4096];
    uint2 row[2048];
    uint32_t cs[16][800];
    uint32_t oflag[16][32];
    uint32_t hflag[128], yflag[128], sel[32], csflag[32], epoch[32];
};
__device__ __align__(1024) Scratch g_scr;

#define TS(i) do {} while (0)
#define TS_END() do {} while (0)
#define TSC(c, i) do {} while (0)
constexpr int SMEM_LAUNCH = SMEM_BYTES;
__device__ __forceinline__ uint32_t smem_u32(const void* p) { return (uint32_t)__cvta_generic_to_shared(p); }
__device__ __forceinline__ void mbar_init(uint32_t bar, uint32_t cnt) { asm volatile("mbarrier.init.shared::cta.b64 [%0], %1;" ::"r"(bar), "r"(cnt) : "memory"); }
__device__ __forceinline__ void mbar_expect_tx(uint32_t bar, uint32_t bytes) { asm volatile("mbarrier.arrive.expect_tx.shared::cta.b64 _, [%0], %1;" ::"r"(bar), "r"(bytes) : "memory"); }
__device__ __forceinline__ void mbar_arrive(uint32_t bar) { asm volatile("mbarrier.arrive.shared::cta.b64 _, [%0];" ::"r"(bar) : "memory"); }
__device__ __forceinline__ uint32_t mapa(uint32_t a, uint32_t cta) { uint32_t r; asm("mapa.shared::cluster.u32 %0, %1, %2;" : "=r"(r) : "r"(a), "r"(cta)); return r; }
__device__ __forceinline__ void mbar_arrive_at(uint32_t cbar) { asm volatile("mbarrier.arrive.shared::cluster.b64 _, [%0];" ::"r"(cbar) : "memory"); }
__device__ __forceinline__ void mbar_wait(uint32_t bar, uint32_t parity, int& budget) {
    asm volatile("{\n.reg .pred p;\nLAB_WAIT:\nmbarrier.try_wait.parity.shared::cta.b64 p, [%1], %2;\n"
                 "add.s32 %0, %0, -1;\nsetp.gt.and.s32 p, %0, 0, !p;\n@p bra LAB_WAIT;\n}" : "+r"(budget) : "r"(bar), "r"(parity) : "memory");
}
__device__ __forceinline__ void tma_2d_mc(uint32_t dst, const CUtensorMap* m, uint32_t bar, int c0, int c1) {
    asm volatile("cp.async.bulk.tensor.2d.shared::cluster.global.mbarrier::complete_tx::bytes.multicast::cluster [%0], [%1, {%3, %4}], [%2], %5;" ::"r"(dst), "l"(m), "r"(bar), "r"(c0), "r"(c1), "h"((uint16_t)3) : "memory");
}
__device__ __forceinline__ void tma_3d(uint32_t dst, const CUtensorMap* m, uint32_t bar, int c0, int c1, int c2) {
    asm volatile("cp.async.bulk.tensor.3d.shared::cluster.global.mbarrier::complete_tx::bytes [%0], [%1, {%3, %4, %5}], [%2];" ::"r"(dst), "l"(m), "r"(bar), "r"(c0), "r"(c1), "r"(c2) : "memory");
}
__device__ __forceinline__ void tma_4d(uint32_t dst, const CUtensorMap* m, uint32_t bar, int c0, int c1, int c2, int c3) {
    asm volatile("cp.async.bulk.tensor.4d.shared::cluster.global.mbarrier::complete_tx::bytes [%0], [%1, {%3, %4, %5, %6}], [%2];" ::"r"(dst), "l"(m), "r"(bar), "r"(c0), "r"(c1), "r"(c2), "r"(c3) : "memory");
}
__device__ __forceinline__ void tma_4d_mc(uint32_t dst, const CUtensorMap* m, uint32_t bar, int c0, int c1, int c2, int c3) {
    asm volatile("cp.async.bulk.tensor.4d.shared::cluster.global.mbarrier::complete_tx::bytes.multicast::cluster [%0], [%1, {%3, %4, %5, %6}], [%2], %7;" ::"r"(dst), "l"(m), "r"(bar), "r"(c0), "r"(c1), "r"(c2), "r"(c3), "h"((uint16_t)3) : "memory");
}
__device__ __forceinline__ void tma_pf_3d(const CUtensorMap* m, int c0, int c1, int c2) {
    asm volatile("cp.async.bulk.prefetch.tensor.3d.L2.global [%0, {%1, %2, %3}];" ::"l"(m), "r"(c0), "r"(c1), "r"(c2) : "memory");
}
__device__ __forceinline__ void bulk_g2s(uint32_t dst, const void* src, uint32_t bytes, uint32_t bar) {
    asm volatile("cp.async.bulk.shared::cluster.global.mbarrier::complete_tx::bytes [%0], [%1], %2, [%3];" ::"r"(dst), "l"(src), "r"(bytes), "r"(bar) : "memory");
}
__device__ __forceinline__ void bulk_s2g(void* dst, uint32_t src, uint32_t bytes) {
    asm volatile("cp.async.bulk.global.shared::cta.bulk_group [%0], [%1], %2;" ::"l"(dst), "r"(src), "r"(bytes) : "memory");
}
__device__ __forceinline__ void bulk_s2c(uint32_t cdst, uint32_t src, uint32_t bytes, uint32_t cbar) {
    asm volatile("cp.async.bulk.shared::cluster.shared::cta.mbarrier::complete_tx::bytes [%0], [%1], %2, [%3];" ::"r"(cdst), "r"(src), "r"(bytes), "r"(cbar) : "memory");
}
__device__ __forceinline__ void cluster_wait() { asm volatile("barrier.cluster.wait.aligned;" ::: "memory"); }
__device__ __forceinline__ void fence_gpu() { asm volatile("fence.acq_rel.gpu;" ::: "memory"); }
__device__ __forceinline__ void fence_async_smem() { asm volatile("fence.proxy.async.shared::cta;" ::: "memory"); }
__device__ __forceinline__ void fence_async_gmem() { asm volatile("fence.proxy.async.global;" ::: "memory"); }
__device__ __forceinline__ void wg_fence() { asm volatile("wgmma.fence.sync.aligned;" ::: "memory"); }
__device__ __forceinline__ void wg_commit() { asm volatile("wgmma.commit_group.sync.aligned;" ::: "memory"); }
template <int N> __device__ __forceinline__ void wg_wait() { asm volatile("wgmma.wait_group.sync.aligned %0;" ::"n"(N) : "memory"); }
__device__ __forceinline__ uint64_t mkdesc(uint32_t lo, uint32_t hi) { return ((uint64_t)hi << 32) | lo; }
__host__ __device__ constexpr uint32_t dhi(uint32_t sbo, uint32_t mode) { return (sbo >> 4) | (mode << 30); }
__host__ __device__ constexpr uint32_t dlo(uint32_t off, uint32_t lbo) { return (off >> 4) + ((lbo >> 4) << 16); }
__device__ __forceinline__ bool elect_one() {
    uint32_t e;
    asm volatile("{\n.reg .pred p;\nelect.sync _|p, 0xffffffff;\nselp.u32 %0, 1, 0, p;\n}" : "=r"(e));
    return e;
}
template <int R> __device__ __forceinline__ void reg_inc() { asm volatile("setmaxnreg.inc.sync.aligned.u32 %0;" ::"n"(R)); }
template <int R> __device__ __forceinline__ void reg_dec() { asm volatile("setmaxnreg.dec.sync.aligned.u32 %0;" ::"n"(R)); }
__device__ __forceinline__ void bar_sync(int id, int n) { asm volatile("bar.sync %0, %1;" ::"r"(id), "r"(n) : "memory"); }
__device__ __forceinline__ void bar_arrive(int id, int n) { asm volatile("bar.arrive %0, %1;" ::"r"(id), "r"(n) : "memory"); }
__device__ __forceinline__ uint32_t pack_bf16(float lo, float hi) { uint32_t r; asm("cvt.rn.bf16x2.f32 %0, %1, %2;" : "=r"(r) : "f"(hi), "f"(lo)); return r; }
__device__ __forceinline__ uint32_t pack_here(float lo, float hi) { uint32_t r; asm volatile("cvt.rn.bf16x2.f32 %0, %1, %2;" : "=r"(r) : "f"(hi), "f"(lo)); return r; }
__device__ __forceinline__ float bf_lo(uint32_t u) { return __uint_as_float(u << 16); }
__device__ __forceinline__ float bf_hi(uint32_t u) { return __uint_as_float(u & 0xffff0000u); }
__device__ __forceinline__ float bf16r(float v) { return bf_lo(pack_bf16(v, 0.f)); }
__device__ __forceinline__ float rcp(float x) { float r; asm("rcp.approx.ftz.f32 %0, %1;" : "=f"(r) : "f"(x)); return r; }
__device__ __forceinline__ float ex2(float x) { float r; asm("ex2.approx.ftz.f32 %0, %1;" : "=f"(r) : "f"(x)); return r; }
__device__ __forceinline__ float sigmoidf(float v) { return rcp(1.f + ex2(v * -1.4426950408889634f)); }
__device__ __forceinline__ uint32_t movm(uint32_t a) { uint32_t d; asm volatile("movmatrix.sync.aligned.m8n8.trans.b16 %0, %1;" : "=r"(d) : "r"(a)); return d; }
__device__ __forceinline__ void mma16816(float (&c)[4], uint32_t a0, uint32_t a1, uint32_t a2, uint32_t a3, uint32_t b0, uint32_t b1) {
    asm volatile("mma.sync.aligned.m16n8k16.row.col.f32.bf16.bf16.f32 {%0,%1,%2,%3}, {%4,%5,%6,%7}, {%8,%9}, {%0,%1,%2,%3};"
                 : "+f"(c[0]), "+f"(c[1]), "+f"(c[2]), "+f"(c[3]) : "r"(a0), "r"(a1), "r"(a2), "r"(a3), "r"(b0), "r"(b1));
}
__device__ __forceinline__ void mma1688(float (&c)[4], uint32_t a0, uint32_t a1, uint32_t b0) {
    asm volatile("mma.sync.aligned.m16n8k8.row.col.f32.bf16.bf16.f32 {%0,%1,%2,%3}, {%4,%5}, {%6}, {%0,%1,%2,%3};"
                 : "+f"(c[0]), "+f"(c[1]), "+f"(c[2]), "+f"(c[3]) : "r"(a0), "r"(a1), "r"(b0));
}
__device__ __forceinline__ void stsm4(uint32_t a, uint32_t r0, uint32_t r1, uint32_t r2, uint32_t r3) {
    asm volatile("stmatrix.sync.aligned.m8n8.x4.shared.b16 [%0], {%1,%2,%3,%4};" ::"r"(a), "r"(r0), "r"(r1), "r"(r2), "r"(r3) : "memory");
}
__device__ __forceinline__ void ldsm4(uint32_t* r, uint32_t a) {
    asm volatile("ldmatrix.sync.aligned.m8n8.x4.shared.b16 {%0,%1,%2,%3}, [%4];" : "=r"(r[0]), "=r"(r[1]), "=r"(r[2]), "=r"(r[3]) : "r"(a) : "memory");
}
__device__ __forceinline__ void ldsm4t(uint32_t* r, uint32_t a) {
    asm volatile("ldmatrix.sync.aligned.m8n8.x4.trans.shared.b16 {%0,%1,%2,%3}, [%4];" : "=r"(r[0]), "=r"(r[1]), "=r"(r[2]), "=r"(r[3]) : "r"(a) : "memory");
}
__device__ __forceinline__ uint32_t ld_rlx(const void* p) { uint32_t v; asm volatile("ld.relaxed.gpu.global.u32 %0, [%1];" : "=r"(v) : "l"(p) : "memory"); return v; }
__device__ __forceinline__ uint32_t ld_acq(const void* p) { uint32_t v; asm volatile("ld.acquire.gpu.global.u32 %0, [%1];" : "=r"(v) : "l"(p) : "memory"); return v; }
__device__ __forceinline__ uint2 ld_rlx2(const void* p) { uint2 v; asm volatile("ld.relaxed.gpu.global.v2.u32 {%0,%1}, [%2];" : "=r"(v.x), "=r"(v.y) : "l"(p) : "memory"); return v; }
__device__ __forceinline__ uint4 ld_rlx4(const void* p) { uint4 v; asm volatile("ld.relaxed.gpu.global.v4.u32 {%0,%1,%2,%3}, [%4];" : "=r"(v.x), "=r"(v.y), "=r"(v.z), "=r"(v.w) : "l"(p) : "memory"); return v; }
__device__ __forceinline__ void st_rlx(void* p, uint32_t v) { asm volatile("st.relaxed.gpu.global.u32 [%0], %1;" ::"l"(p), "r"(v) : "memory"); }
__device__ __forceinline__ void st_rlx2(void* p, uint32_t a, uint32_t b) { asm volatile("st.relaxed.gpu.global.v2.u32 [%0], {%1,%2};" ::"l"(p), "r"(a), "r"(b) : "memory"); }
__device__ __forceinline__ void st_rlx4(void* p, uint32_t a, uint32_t b, uint32_t c, uint32_t d) { asm volatile("st.relaxed.gpu.global.v4.u32 [%0], {%1,%2,%3,%4};" ::"l"(p), "r"(a), "r"(b), "r"(c), "r"(d) : "memory"); }
__device__ __forceinline__ uint4 ldg_nc(const void* p) { uint4 v; asm volatile("ld.global.nc.v4.u32 {%0,%1,%2,%3}, [%4];" : "=r"(v.x), "=r"(v.y), "=r"(v.z), "=r"(v.w) : "l"(p)); return v; }
__device__ __forceinline__ void sts4(uint32_t a, uint32_t x, uint32_t y, uint32_t z, uint32_t w) { asm volatile("st.shared.v4.u32 [%0], {%1,%2,%3,%4};" ::"r"(a), "r"(x), "r"(y), "r"(z), "r"(w) : "memory"); }
__device__ __forceinline__ void sts2(uint32_t a, uint32_t x, uint32_t y) { asm volatile("st.shared.v2.u32 [%0], {%1,%2};" ::"r"(a), "r"(x), "r"(y) : "memory"); }
__device__ __forceinline__ void sts1(uint32_t a, uint32_t v) { asm volatile("st.shared.u32 [%0], %1;" ::"r"(a), "r"(v) : "memory"); }
__device__ __forceinline__ uint4 lds4(uint32_t a) { uint4 v; asm volatile("ld.shared.v4.u32 {%0,%1,%2,%3}, [%4];" : "=r"(v.x), "=r"(v.y), "=r"(v.z), "=r"(v.w) : "r"(a) : "memory"); return v; }
__device__ __forceinline__ float4 lds4f(uint32_t a) { float4 v; asm volatile("ld.shared.v4.f32 {%0,%1,%2,%3}, [%4];" : "=f"(v.x), "=f"(v.y), "=f"(v.z), "=f"(v.w) : "r"(a) : "memory"); return v; }
__device__ __forceinline__ float2 lds2f(uint32_t a) { float2 v; asm volatile("ld.shared.v2.f32 {%0,%1}, [%2];" : "=f"(v.x), "=f"(v.y) : "r"(a) : "memory"); return v; }
__device__ __forceinline__ float lds1f(uint32_t a) { float v; asm volatile("ld.shared.f32 %0, [%1];" : "=f"(v) : "r"(a) : "memory"); return v; }
__device__ __forceinline__ uint32_t lds1(uint32_t a) { uint32_t v; asm volatile("ld.shared.u32 %0, [%1];" : "=r"(v) : "r"(a) : "memory"); return v; }
__device__ __forceinline__ uint32_t redux_max(uint32_t v) { uint32_t r; asm volatile("redux.sync.max.u32 %0, %1, 0xffffffff;" : "=r"(r) : "r"(v)); return r; }
__device__ __forceinline__ uint32_t poll_all(const uint32_t* p, uint32_t mask, uint32_t want, int& budget) {
    uint32_t v;
#pragma unroll 1
    while (v = ld_acq(p), !__all_sync(0xffffffffu, (v & mask) == want) && --budget > 0) __nanosleep(POLL_NS);
    return v;
}

template <int TA, int TB>
__device__ __forceinline__ void wgmma_n192(float (&d)[96], uint64_t da, uint64_t db, int keep) {
    asm volatile("{\n.reg .pred p;\nsetp.ne.b32 p, %98, 0;\n"
        "wgmma.mma_async.sync.aligned.m64n192k16.f32.bf16.bf16 "
        "{%0, %1, %2, %3, %4, %5, %6, %7, %8, %9, %10, %11, %12, %13, %14, %15, "
        "%16, %17, %18, %19, %20, %21, %22, %23, %24, %25, %26, %27, %28, %29, %30, %31, "
        "%32, %33, %34, %35, %36, %37, %38, %39, %40, %41, %42, %43, %44, %45, %46, %47, "
        "%48, %49, %50, %51, %52, %53, %54, %55, %56, %57, %58, %59, %60, %61, %62, %63, "
        "%64, %65, %66, %67, %68, %69, %70, %71, %72, %73, %74, %75, %76, %77, %78, %79, "
        "%80, %81, %82, %83, %84, %85, %86, %87, %88, %89, %90, %91, %92, %93, %94, %95}, "
        "%96, %97, p, 1, 1, %99, %100;\n}\n"
        : "+f"(d[0]), "+f"(d[1]), "+f"(d[2]), "+f"(d[3]), "+f"(d[4]), "+f"(d[5]), "+f"(d[6]), "+f"(d[7]),
          "+f"(d[8]), "+f"(d[9]), "+f"(d[10]), "+f"(d[11]), "+f"(d[12]), "+f"(d[13]), "+f"(d[14]), "+f"(d[15]),
          "+f"(d[16]), "+f"(d[17]), "+f"(d[18]), "+f"(d[19]), "+f"(d[20]), "+f"(d[21]), "+f"(d[22]), "+f"(d[23]),
          "+f"(d[24]), "+f"(d[25]), "+f"(d[26]), "+f"(d[27]), "+f"(d[28]), "+f"(d[29]), "+f"(d[30]), "+f"(d[31]),
          "+f"(d[32]), "+f"(d[33]), "+f"(d[34]), "+f"(d[35]), "+f"(d[36]), "+f"(d[37]), "+f"(d[38]), "+f"(d[39]),
          "+f"(d[40]), "+f"(d[41]), "+f"(d[42]), "+f"(d[43]), "+f"(d[44]), "+f"(d[45]), "+f"(d[46]), "+f"(d[47]),
          "+f"(d[48]), "+f"(d[49]), "+f"(d[50]), "+f"(d[51]), "+f"(d[52]), "+f"(d[53]), "+f"(d[54]), "+f"(d[55]),
          "+f"(d[56]), "+f"(d[57]), "+f"(d[58]), "+f"(d[59]), "+f"(d[60]), "+f"(d[61]), "+f"(d[62]), "+f"(d[63]),
          "+f"(d[64]), "+f"(d[65]), "+f"(d[66]), "+f"(d[67]), "+f"(d[68]), "+f"(d[69]), "+f"(d[70]), "+f"(d[71]),
          "+f"(d[72]), "+f"(d[73]), "+f"(d[74]), "+f"(d[75]), "+f"(d[76]), "+f"(d[77]), "+f"(d[78]), "+f"(d[79]),
          "+f"(d[80]), "+f"(d[81]), "+f"(d[82]), "+f"(d[83]), "+f"(d[84]), "+f"(d[85]), "+f"(d[86]), "+f"(d[87]),
          "+f"(d[88]), "+f"(d[89]), "+f"(d[90]), "+f"(d[91]), "+f"(d[92]), "+f"(d[93]), "+f"(d[94]), "+f"(d[95])
        : "l"(da), "l"(db), "r"(keep), "n"(TA), "n"(TB));
}
template <int TA, int TB>
__device__ __forceinline__ void wgmma_n128(float (&d)[64], uint64_t da, uint64_t db, int keep) {
    asm volatile("{\n.reg .pred p;\nsetp.ne.b32 p, %66, 0;\n"
        "wgmma.mma_async.sync.aligned.m64n128k16.f32.bf16.bf16 "
        "{%0, %1, %2, %3, %4, %5, %6, %7, %8, %9, %10, %11, %12, %13, %14, %15, "
        "%16, %17, %18, %19, %20, %21, %22, %23, %24, %25, %26, %27, %28, %29, %30, %31, "
        "%32, %33, %34, %35, %36, %37, %38, %39, %40, %41, %42, %43, %44, %45, %46, %47, "
        "%48, %49, %50, %51, %52, %53, %54, %55, %56, %57, %58, %59, %60, %61, %62, %63}, "
        "%64, %65, p, 1, 1, %67, %68;\n}\n"
        : "+f"(d[0]), "+f"(d[1]), "+f"(d[2]), "+f"(d[3]), "+f"(d[4]), "+f"(d[5]), "+f"(d[6]), "+f"(d[7]),
          "+f"(d[8]), "+f"(d[9]), "+f"(d[10]), "+f"(d[11]), "+f"(d[12]), "+f"(d[13]), "+f"(d[14]), "+f"(d[15]),
          "+f"(d[16]), "+f"(d[17]), "+f"(d[18]), "+f"(d[19]), "+f"(d[20]), "+f"(d[21]), "+f"(d[22]), "+f"(d[23]),
          "+f"(d[24]), "+f"(d[25]), "+f"(d[26]), "+f"(d[27]), "+f"(d[28]), "+f"(d[29]), "+f"(d[30]), "+f"(d[31]),
          "+f"(d[32]), "+f"(d[33]), "+f"(d[34]), "+f"(d[35]), "+f"(d[36]), "+f"(d[37]), "+f"(d[38]), "+f"(d[39]),
          "+f"(d[40]), "+f"(d[41]), "+f"(d[42]), "+f"(d[43]), "+f"(d[44]), "+f"(d[45]), "+f"(d[46]), "+f"(d[47]),
          "+f"(d[48]), "+f"(d[49]), "+f"(d[50]), "+f"(d[51]), "+f"(d[52]), "+f"(d[53]), "+f"(d[54]), "+f"(d[55]),
          "+f"(d[56]), "+f"(d[57]), "+f"(d[58]), "+f"(d[59]), "+f"(d[60]), "+f"(d[61]), "+f"(d[62]), "+f"(d[63])
        : "l"(da), "l"(db), "r"(keep), "n"(TA), "n"(TB));
}
template <int TA, int TB>
__device__ __forceinline__ void wgmma_n8(float (&d)[4], uint64_t da, uint64_t db, int keep) {
    asm volatile("{\n.reg .pred p;\nsetp.ne.b32 p, %6, 0;\n"
        "wgmma.mma_async.sync.aligned.m64n8k16.f32.bf16.bf16 "
        "{%0, %1, %2, %3}, "
        "%4, %5, p, 1, 1, %7, %8;\n}\n"
        : "+f"(d[0]), "+f"(d[1]), "+f"(d[2]), "+f"(d[3])
        : "l"(da), "l"(db), "r"(keep), "n"(TA), "n"(TB));
}
__device__ __forceinline__ void wgmma_rs_n128(float (&d)[64], uint32_t a0, uint32_t a1, uint32_t a2, uint32_t a3, uint64_t db) {
    asm volatile("{\n.reg .pred p;\nsetp.ne.b32 p, 1, 0;\n"
        "wgmma.mma_async.sync.aligned.m64n128k16.f32.bf16.bf16 "
        "{%0, %1, %2, %3, %4, %5, %6, %7, %8, %9, %10, %11, %12, %13, %14, %15, "
        "%16, %17, %18, %19, %20, %21, %22, %23, %24, %25, %26, %27, %28, %29, %30, %31, "
        "%32, %33, %34, %35, %36, %37, %38, %39, %40, %41, %42, %43, %44, %45, %46, %47, "
        "%48, %49, %50, %51, %52, %53, %54, %55, %56, %57, %58, %59, %60, %61, %62, %63}, "
        "{%64, %65, %66, %67}, %68, p, 1, 1, 1;\n}\n"
        : "+f"(d[0]), "+f"(d[1]), "+f"(d[2]), "+f"(d[3]), "+f"(d[4]), "+f"(d[5]), "+f"(d[6]), "+f"(d[7]),
          "+f"(d[8]), "+f"(d[9]), "+f"(d[10]), "+f"(d[11]), "+f"(d[12]), "+f"(d[13]), "+f"(d[14]), "+f"(d[15]),
          "+f"(d[16]), "+f"(d[17]), "+f"(d[18]), "+f"(d[19]), "+f"(d[20]), "+f"(d[21]), "+f"(d[22]), "+f"(d[23]),
          "+f"(d[24]), "+f"(d[25]), "+f"(d[26]), "+f"(d[27]), "+f"(d[28]), "+f"(d[29]), "+f"(d[30]), "+f"(d[31]),
          "+f"(d[32]), "+f"(d[33]), "+f"(d[34]), "+f"(d[35]), "+f"(d[36]), "+f"(d[37]), "+f"(d[38]), "+f"(d[39]),
          "+f"(d[40]), "+f"(d[41]), "+f"(d[42]), "+f"(d[43]), "+f"(d[44]), "+f"(d[45]), "+f"(d[46]), "+f"(d[47]),
          "+f"(d[48]), "+f"(d[49]), "+f"(d[50]), "+f"(d[51]), "+f"(d[52]), "+f"(d[53]), "+f"(d[54]), "+f"(d[55]),
          "+f"(d[56]), "+f"(d[57]), "+f"(d[58]), "+f"(d[59]), "+f"(d[60]), "+f"(d[61]), "+f"(d[62]), "+f"(d[63])
        : "r"(a0), "r"(a1), "r"(a2), "r"(a3), "l"(db));
}
__device__ __forceinline__ void wgmma_rs_n192(float (&d)[96], uint32_t a0, uint32_t a1, uint32_t a2, uint32_t a3, uint64_t db) {
    asm volatile("{\n.reg .pred p;\nsetp.ne.b32 p, 1, 0;\n"
        "wgmma.mma_async.sync.aligned.m64n192k16.f32.bf16.bf16 "
        "{%0, %1, %2, %3, %4, %5, %6, %7, %8, %9, %10, %11, %12, %13, %14, %15, "
        "%16, %17, %18, %19, %20, %21, %22, %23, %24, %25, %26, %27, %28, %29, %30, %31, "
        "%32, %33, %34, %35, %36, %37, %38, %39, %40, %41, %42, %43, %44, %45, %46, %47, "
        "%48, %49, %50, %51, %52, %53, %54, %55, %56, %57, %58, %59, %60, %61, %62, %63, "
        "%64, %65, %66, %67, %68, %69, %70, %71, %72, %73, %74, %75, %76, %77, %78, %79, "
        "%80, %81, %82, %83, %84, %85, %86, %87, %88, %89, %90, %91, %92, %93, %94, %95}, "
        "{%96, %97, %98, %99}, %100, p, 1, 1, 1;\n}\n"
        : "+f"(d[0]), "+f"(d[1]), "+f"(d[2]), "+f"(d[3]), "+f"(d[4]), "+f"(d[5]), "+f"(d[6]), "+f"(d[7]),
          "+f"(d[8]), "+f"(d[9]), "+f"(d[10]), "+f"(d[11]), "+f"(d[12]), "+f"(d[13]), "+f"(d[14]), "+f"(d[15]),
          "+f"(d[16]), "+f"(d[17]), "+f"(d[18]), "+f"(d[19]), "+f"(d[20]), "+f"(d[21]), "+f"(d[22]), "+f"(d[23]),
          "+f"(d[24]), "+f"(d[25]), "+f"(d[26]), "+f"(d[27]), "+f"(d[28]), "+f"(d[29]), "+f"(d[30]), "+f"(d[31]),
          "+f"(d[32]), "+f"(d[33]), "+f"(d[34]), "+f"(d[35]), "+f"(d[36]), "+f"(d[37]), "+f"(d[38]), "+f"(d[39]),
          "+f"(d[40]), "+f"(d[41]), "+f"(d[42]), "+f"(d[43]), "+f"(d[44]), "+f"(d[45]), "+f"(d[46]), "+f"(d[47]),
          "+f"(d[48]), "+f"(d[49]), "+f"(d[50]), "+f"(d[51]), "+f"(d[52]), "+f"(d[53]), "+f"(d[54]), "+f"(d[55]),
          "+f"(d[56]), "+f"(d[57]), "+f"(d[58]), "+f"(d[59]), "+f"(d[60]), "+f"(d[61]), "+f"(d[62]), "+f"(d[63]),
          "+f"(d[64]), "+f"(d[65]), "+f"(d[66]), "+f"(d[67]), "+f"(d[68]), "+f"(d[69]), "+f"(d[70]), "+f"(d[71]),
          "+f"(d[72]), "+f"(d[73]), "+f"(d[74]), "+f"(d[75]), "+f"(d[76]), "+f"(d[77]), "+f"(d[78]), "+f"(d[79]),
          "+f"(d[80]), "+f"(d[81]), "+f"(d[82]), "+f"(d[83]), "+f"(d[84]), "+f"(d[85]), "+f"(d[86]), "+f"(d[87]),
          "+f"(d[88]), "+f"(d[89]), "+f"(d[90]), "+f"(d[91]), "+f"(d[92]), "+f"(d[93]), "+f"(d[94]), "+f"(d[95])
        : "r"(a0), "r"(a1), "r"(a2), "r"(a3), "l"(db));
}

template <int HS>
__device__ __forceinline__ void attn_pair(const uint32_t* q, const uint32_t* k, const uint32_t* v, const uint32_t* kh, const uint32_t* vh,
                                          const float* fu, const float* fn, const float* rk, float bias0, float bias1, uint32_t mU, uint32_t zero, uint32_t* o) {
    float s0[2][4] = {}, s1[2][4] = {}, s2[2][4] = {};
#pragma unroll
    for (int n = 0; n < 4; n++) {
        const int hd = n & 1, a = 8 * hd + 2 * (n & 2);
        mma16816(s1[hd], q[a], q[a + 1], q[a + 2], q[a + 3], k[a], k[a + 2]);
        mma16816(s2[hd], q[a], q[a + 1], q[a + 2], q[a + 3], k[a + 1], k[a + 3]);
    }
#pragma unroll
    for (int n = 0; n < 4; n++) {
        const int hd = n & 1, a = 8 * hd + 2 * (n & 2);
        mma16816(s0[hd], q[a], q[a + 1], q[a + 2], q[a + 3], kh[HS * (a / 2)], kh[HS * (a / 2 + 1)]);
    }
    float e[2][4], m[2][2];
#pragma unroll
    for (int hd = 0; hd < 2; hd++) {
        e[hd][2] = fmaf(s1[hd][2], fu[2], s2[hd][2] * fn[2]); e[hd][3] = fmaf(s1[hd][3], fu[3], s2[hd][3] * fn[3]);
        e[hd][0] = fmaf(s0[hd][0], fu[0], fmaf(s1[hd][0], fn[0], bias0)); e[hd][1] = fmaf(s0[hd][1], fu[1], fmaf(s1[hd][1], fn[1], bias1));
        m[hd][1] = fmaxf(e[hd][2], e[hd][3]); m[hd][0] = fmaxf(e[hd][0], e[hd][1]);
    }
#pragma unroll
    for (int x = 1; x < 3; x++)
#pragma unroll
        for (int n = 0; n < 4; n++) m[n & 1][1 - (n >> 1)] = fmaxf(m[n & 1][1 - (n >> 1)], __shfl_xor_sync(0xffffffffu, m[n & 1][1 - (n >> 1)], x));
    float c[2][4][4] = {};
#pragma unroll
    for (int hd = 0; hd < 2; hd++) {
#pragma unroll
        for (int n = 0; n < 4; n++) e[hd][n] = ex2(e[hd][n] - m[hd][n >> 1]);
        const uint32_t plo = pack_bf16(e[hd][0] * rk[0], e[hd][1] * rk[1]), phi = pack_bf16(e[hd][2] * rk[2], e[hd][3] * rk[3]);
        const uint32_t z0 = plo & zero, z1 = phi & zero;
        const uint32_t a0 = plo & ~mU, a1 = phi & mU, a3 = phi & ~mU, b0 = plo & mU;
#pragma unroll
        for (int jj = 0; jj < 4; jj++) mma16816(c[hd][jj], a0, a1, z0, a3, v[8 * hd + 2 * jj], v[8 * hd + 2 * jj + 1]);
#pragma unroll
        for (int jj = 0; jj < 4; jj++) mma1688(c[hd][jj], b0, z1, vh[HS * (4 * hd + jj)]);
        m[hd][0] = e[hd][0] + e[hd][1]; m[hd][1] = e[hd][2] + e[hd][3];
    }
#pragma unroll
    for (int x = 1; x < 3; x++)
#pragma unroll
        for (int n = 0; n < 4; n++) m[n >> 1][n & 1] += __shfl_xor_sync(0xffffffffu, m[n >> 1][n & 1], x);
#pragma unroll
    for (int hd = 0; hd < 2; hd++) {
        const float i0 = rcp(m[hd][0]), i1 = rcp(m[hd][1]);
#pragma unroll
        for (int jj = 0; jj < 4; jj++) {
            o[8 * hd + 2 * jj] = pack_bf16(c[hd][jj][0] * i0, c[hd][jj][1] * i0);
            o[8 * hd + 2 * jj + 1] = pack_bf16(c[hd][jj][2] * i1, c[hd][jj][3] * i1);
        }
    }
}

__device__ __forceinline__ uint32_t norm_pair(uint32_t u, float m, float rinv) {
    const uint32_t d = pack_bf16(bf_lo(u) - m, bf_hi(u) - m);
    return pack_bf16(bf_lo(d) * rinv, bf_hi(d) * rinv);
}

__global__ void __launch_bounds__(512, 1)
fused_kernel(const __grid_constant__ CUtensorMap mx, const __grid_constant__ CUtensorMap mw, const __grid_constant__ CUtensorMap mwo,
             const __grid_constant__ CUtensorMap mout, const __grid_constant__ CUtensorMap mgu, const __grid_constant__ CUtensorMap mwd,
             const __grid_constant__ CUtensorMap mo,
             const __nv_bfloat16* __restrict__ x, const __nv_bfloat16* __restrict__ wr, Scratch* __restrict__ scr, int swap_gu) {
    extern __shared__ __align__(1024) uint8_t smem[];
    const uint32_t sb = smem_u32(smem);
    const uint32_t bars = sb + OFF_BAR;
    const int tid = threadIdx.x, lane = tid & 31, warp = __shfl_sync(0xffffffffu, tid >> 5, 0);
    const uint32_t sd = (sb & 0x3FFFF) >> 4;
    const int hp = blockIdx.x & 1, cl = blockIdx.x >> 1;
    const int pr = cl < 4 ? 39 + 8 * cl : cl < 36 ? cl - 4 : cl < 64 ? cl - 4 + ((cl - 36) * 37 >> 8) : cl;
    const int b = pr * 2 + hp, mt = pr >> 3, p = pr & 7, nt = 2 * p + hp, rh = p & 1, cb = (p & 6) + hp;
    const int par = mt >> 2, j0 = (mt & 3) * 256;
    int budget = BUDGET;

    TSC(tid == 0, 0);
    auto load_w = [&](int k) {
        const uint32_t full = bars + 8 * (B_WFULL + (k & 3));
        mbar_expect_tx(full, W_BYTES);
        tma_3d(sb + OFF_W + (k & 3) * W_BYTES, &mw, full, nt * 64, k * 64, 0);
    };
    if (elect_one()) {
        const uint32_t cnt = warp < B_WEMPTY / 6 ? 1 : warp < B_G1DONE / 6 ? 2 : warp < B_STAGED / 6 ? 4 : 8;
#pragma unroll
        for (int i = 0; i < 6; i++) if (warp < (NBAR - i + 5) / 6) mbar_init(bars + 48 * warp + 8 * i, cnt);
        asm volatile("fence.mbarrier_init.release.cluster;" ::: "memory");
    }
    __syncthreads();

    if (b >= 128) {
        const int hc = b - 128, g = lane >> 2, t = lane & 3;
        if (warp < 12) {
            const int n = warp / 3, part = warp - 3 * n;
            auto load = [&](int k) {
                const uint32_t full = bars + 8 * (2 * n + (k & 1));
                mbar_expect_tx(full, W_BYTES);
                tma_3d(sb + (2 * n + (k & 1)) * W_BYTES, &mw, full, (4 * hc + n) * 64, k * 64, 0);
            };
            if (part == 0 && elect_one()) { load(0); load(1); }
            __syncwarp();
            float c0[4] = {0.f, 0.f, 0.f, 0.f}, c1[4] = {0.f, 0.f, 0.f, 0.f};
            const uint32_t sel = g == 0 ? 0x3f80u : g == 1 ? 0x3f800000u : 0u;
            const uint32_t a = sb + 2 * n * W_BYTES + part * BOX + t * 256 + ((g ^ (2 * t)) << 4);
#pragma unroll 1
            for (int k = 0; k < 16; k++) {
                mbar_wait(bars + 8 * (2 * n + (k & 1)), (k >> 1) & 1, budget);
                uint4 v[8], u[8];
#pragma unroll
                for (int i = 0; i < 8; i++) { v[i] = lds4(a + (k & 1) * W_BYTES + i * 1024); u[i] = lds4(((a + 128) ^ 16) + (k & 1) * W_BYTES + i * 1024); }
#pragma unroll
                for (int i = 0; i < 8; i++) { mma16816(c0, v[i].x, v[i].y, u[i].x, u[i].y, sel, sel); mma16816(c1, v[i].z, v[i].w, u[i].z, u[i].w, sel, sel); }
                bar_sync(1 + n, 96);
                if (part == 0 && k < 14 && elect_one()) load(k + 2);
                __syncwarp();
            }
            if (t == 0) {
#pragma unroll
                for (int r = 0; r < 3; r++) {
                    const uint32_t q0 = pack_bf16(c0[0], c0[1]), q1 = pack_bf16(c0[2], c0[3]), q2 = pack_bf16(c1[0], c1[1]), q3 = pack_bf16(c1[2], c1[3]);
                    st_rlx4(&scr->cs[4 * hc + n][16 + (part * 8 + g) * 32 + r * 4], q0, q1, q2, q3);
                    c0[0] -= bf_lo(q0); c0[1] -= bf_hi(q0); c0[2] -= bf_lo(q1); c0[3] -= bf_hi(q1);
                    c1[0] -= bf_lo(q2); c1[1] -= bf_hi(q2); c1[2] -= bf_lo(q3); c1[3] -= bf_hi(q3);
                }
            }
            bar_sync(5, 416);
            if (tid == 0) { fence_gpu(); st_rlx(&scr->csflag[hc], lds1(sb + OFF_EP)); }
            TSC(tid == 0, 19);
        } else {
            const int ta = tid - 384, wq = warp - 12, jl = 2 * hc + 1;
            const uint32_t ep = ld_rlx(&scr->epoch[0]) + 1;
            if (wq == 0) { if (lane == 0) sts1(sb + OFF_EP, ep); bar_arrive(5, 416); }
            uint32_t kv[16];
#pragma unroll 1
            do {
                uint32_t bad = 0;
#pragma unroll
                for (int n = 0; n < 8; n++) { const uint4 q = ld_rlx4(&scr->row[(n * 128 + ta) * 2]); kv[2 * n] = q.y; kv[2 * n + 1] = q.w; bad |= (q.y ^ ep) | (q.w ^ ep); }
                if ((bad & 31) == 0) break;
            } while (--budget > 0);
            __syncwarp();
            TSC(ta == 0, 17);
            uint32_t m1 = 0, m2 = 0, mine = 0;
#pragma unroll
            for (int n = 0; n < 16; n++) { m2 = max(m2, min(m1, kv[n])); m1 = max(m1, kv[n]); }
            bool spare = true;
#pragma unroll 1
            for (int r = 0; r <= jl; r++) {
                const uint32_t top = redux_max(m1);
                if (lane == r) mine = top;
                if (m1 == top) {
                    m1 = m2;
                    if (!spare) {
                        m1 = 0;
#pragma unroll
                        for (int n = 0; n < 16; n++) m1 = max(m1, kv[n] < top ? kv[n] : 0u);
                    }
                    spare = false;
                }
                __syncwarp();
            }
            if (lane < 8) sts1(sb + OFF_STAT + (wq * 8 + lane) * 4, mine);
            bar_sync(6, 128);
            const uint32_t c = lds1(sb + OFF_STAT + lane * 4);
            int rank = 0;
#pragma unroll
            for (int i = 0; i < 8; i++) { const uint4 q = lds4(sb + OFF_STAT + i * 16); rank += (q.x > c) + (q.y > c) + (q.z > c) + (q.w > c); }
            const uint32_t k0 = redux_max(rank == jl - 1 ? c : 0u), k1 = redux_max(rank == jl ? c : 0u);
            const int r0 = 2047 - ((k0 >> 5) & 2047), r1 = 2047 - ((k1 >> 5) & 2047);
            TSC(ta == 0, 18);
            const uint4 v0 = ldg_nc(x + (size_t)r0 * 1024 + ta * 8), v1 = ldg_nc(x + (size_t)r1 * 1024 + ta * 8);
            const uint32_t s0 = ld_rlx(&scr->row[r0]), s1 = ld_rlx(&scr->row[r1]);
            const float m0 = bf_lo(s0), i0 = rcp(bf_hi(s0)), mm1 = bf_lo(s1), i1 = rcp(bf_hi(s1));
            st_rlx4(&scr->xsel[ta * 32 + hc * 8], norm_pair(v0.x, m0, i0), norm_pair(v0.y, m0, i0), norm_pair(v0.z, m0, i0), norm_pair(v0.w, m0, i0));
            st_rlx4(&scr->xsel[ta * 32 + hc * 8 + 4], norm_pair(v1.x, mm1, i1), norm_pair(v1.y, mm1, i1), norm_pair(v1.z, mm1, i1), norm_pair(v1.w, mm1, i1));
            bar_sync(6, 128);
            if (ta == 0) { fence_gpu(); st_rlx2(&scr->sel[2 * hc], k0, k1); }
            TSC(ta == 0, 20);
        }
        TS_END();
        return;
    }
    asm volatile("barrier.cluster.arrive.relaxed.aligned;" ::: "memory");

    const int kc = b >> 4, c2 = b & 15;
    if (warp >= 12) {
        reg_dec<24>();
        if (warp == 12) {
            if (elect_one()) {
#pragma unroll 1
                for (int n = 0; n < 12; n++) {
                    const int w = n & 1, j = n < 8 ? (n >> 1) + 2 : (n >> 1) - 4;
                    const uint32_t full = bars + 8 * (B_XFULL + w * 6 + j);
                    mbar_expect_tx(full, BOX);
                    tma_4d(sb + w * OFF_X1 + j * BOX, &mx, full, par * 1024 + (n >> 2) * 64, 0, (j0 + w * 128) >> 5, (~n >> 1) & 1);
                    if (n == ROWS_AT) { mbar_expect_tx(bars + 8 * B_ROW, 4 * BOX); bulk_g2s(sb + OFF_FR, x + (size_t)b * 16 * 1024, 4 * BOX, bars + 8 * B_ROW); }
                    if (n == 0 || (n & 3) == 3) load_w((n + 1) >> 2);
                }
#pragma unroll 1
                for (int k = 4; k < 16; k++) {
                    mbar_wait(bars + 8 * (B_WEMPTY + (k & 3)), ((k >> 2) & 1) ^ 1, budget);
                    load_w(k);
#pragma unroll 1
                    for (int q = 2 * k - 8; q < 2 * k - 6; q++) {
                        if (q < 16) { if (b < 112) tma_pf_3d(&mgu, b * 32, q * 64, 0); }
                        else if (q == 16) tma_pf_3d(&mwo, 0, (b >> 3) * 64, (b & 7) * 2);
                        else tma_pf_3d(&mwd, 0, kc * 448 + (q - 17) * 64, c2);
                    }
                }
                TS(27);
                int s = 1;
#pragma unroll 1
                for (int i = 0; i < 16; i++) {
                    mbar_wait(bars + 8 * (i < 4 ? B_WEMPTY + min(i, 2) : i == 4 ? B_G1DONE : B_WOEMPTY + s), i < 4 || i >= 12, budget);
                    if (i == 4) {
#pragma unroll 1
                        for (int n = 0; n < 4; n++) {
                            const uint32_t f2 = bars + 8 * (B_XT + (n >> 1));
                            if (!(n & 1)) mbar_expect_tx(f2, 2 * BOX);
                            tma_4d(sb + (n >> 1) * OFF_O1 + (3 + (n & 1)) * BOX, &mx, f2, par * 1024 + cb * 128 + (n & 1) * 64, 0, (j0 + rh * 128) >> 5, 1 - (n >> 1));
                        }
                    }
                    const uint32_t full = bars + 8 * (B_WOFULL + s);
                    mbar_expect_tx(full, 2 * BOX);
                    tma_3d(sb + OFF_WO + s * 2 * BOX, &mwo, full, 0, ((2 * p + (i < 2 ? i ^ hp : i)) & 15) * 64, cb * 2);
                    TSC(TIMING % 10 == 4, 48 + i);
                    if (++s == NWO) s = 0;
                }
                TS(25);
            }
        } else {
            bar_sync(8, 224);
            const uint32_t ep = lds1(sb + OFF_EP);
            if (warp == 13) {
                cluster_wait();
                if (elect_one()) {
                    int j = 2; uint32_t ph = 0;
#pragma unroll 1
                    for (int n = 6; n < 32; n++) {
                        mbar_wait(bars + 8 * (B_XEMPTY + j), ph, budget);
                        tma_4d_mc(sb + hp * OFF_X1 + j * BOX, &mx, bars + 8 * (B_XFULL + hp * 6 + j), par * 1024 + (n >> 1) * 64, 0, (j0 + hp * 128) >> 5, ~n & 1);
                        if (++j == 6) j = 0;
                        if (j == 2) ph ^= 1;
                    }
                }
                __syncwarp();
                uint32_t* hs = &scr->halo[b - 16][lane * 4];
#pragma unroll 1
                for (int c = 0; c < 4; c += 2) {
                    uint4 v0 = make_uint4(0, 0, 0, 0), v1 = v0;
                    if (j0) {
#pragma unroll 1
                        do { v0 = ld_rlx4(hs + c * 128); v1 = ld_rlx4(hs + c * 128 + 128); } while ((v0.x == 0 || v1.x == 0) && --budget > 0);
                        st_rlx(hs + c * 128, 0); st_rlx(hs + c * 128 + 128, 0);
                    }
                    __syncwarp();
                    stsm4(sb + OFF_HIN + c * 512 + lane * 16, v0.x, v0.y, v0.z, v0.w);
                    stsm4(sb + OFF_HIN + c * 512 + 512 + lane * 16, v1.x, v1.y, v1.z, v1.w);
                }
                bar_arrive(11, 64);
                TSC(lane == 0, 31);
                const int src = ((mt * 2 + rh) * 2 + 1 - hp) * 1024;
                if (elect_one()) {
                    const uint32_t* fl = &scr->oflag[mt * 2 + 1 - hp][0];
                    const uint32_t inv = (ep & 1) - 1;
                    uint32_t ready = 0, ph = 0;
                    int s = 2;
#pragma unroll 1
                    for (int i = 2; i < 16; i++) {
                        const int kb = (2 * p + i) & 15;
#pragma unroll 1
                        while (!((ready >> kb) & 1) && --budget > 0) { ready = ld_acq(fl) ^ inv; fence_async_gmem(); }
                        TSC(i == 2, 30);
                        mbar_wait(bars + 8 * (B_OEMPTY + s), ph, budget);
                        tma_2d_mc(sb + hp * OFF_O1 + s * BOX, &mo, bars + 8 * (B_OFULL + hp * NO + s), 0, src + kb * 64);
                        TSC(TIMING % 10 == 4 && hp == 0, 32 + i);
                        if (++s == NO) s = 0;
                        if (s == 2) ph ^= 1;
                    }
                }
            } else if (warp == 14) {
                int s = 0; uint32_t ph = 0;
#pragma unroll 1
                for (int q = b < 112 ? 0 : 16; q < 23; q++) {
                    if (!(q & 15)) {
                        poll_all(q ? &scr->hflag[kc * 14 + min(lane, 13)] : &scr->sel[lane & 7], q ? ~0u : 31u, q ? ep : ep & 31, budget);
                        TSC(lane == 0, q ? 29 : 26);
                        if (b == 0 && q == 0 && lane == 0) st_rlx(&scr->epoch[0], ep);
                        fence_async_gmem();
                    }
                    if (elect_one()) {
                        const uint32_t full = bars + 8 * (B_FFULL + s), dst = sb + OFF_FR + s * F_BYTES;
                        mbar_wait(bars + 8 * (B_FEMPTY + s), ph, budget);
                        mbar_expect_tx(full, F_BYTES);
                        tma_3d(dst, q < 16 ? &mgu : &mwd, full, q < 16 ? b * 32 : 0, q < 16 ? q * 64 : kc * 448 + (q - 16) * 64, q < 16 ? 0 : c2);
                        bulk_g2s(dst + BOX, q < 16 ? scr->xsel + q * 256 : scr->h + (kc * 7 + q - 16) * 256, 1024, full);
                    }
                    budget = __shfl_sync(0xffffffffu, budget, 0);
                    if (++s == NF) { s = 0; ph ^= 1; }
                }
            } else {
                mbar_wait(bars + 8 * B_FEMPTY, 0, budget);
#pragma unroll 1
                for (int i = lane; i < 264; i += 32) {
                    const int j = j0 - 8 + i;
                    uint2 v = make_uint2(0x7f800000u, 0);
                    if (j >= 0) {
#pragma unroll 1
                        do { v = ld_rlx2(&scr->row[2 * j + par]); } while (((v.y ^ ep) & 31) && --budget > 0);
                    }
                    sts2(sb + OFF_STAT + i * 8, __float_as_uint(-bf_lo(v.x)), __float_as_uint(rcp(bf_hi(v.x))));
                }
                budget = __shfl_sync(0xffffffffu, budget, 0);
                poll_all(&scr->csflag[nt >> 2], ~0u, ep, budget);
                if (elect_one()) {
                    fence_async_gmem();
                    mbar_expect_tx(bars + 8 * B_AUX, CS_BYTES);
                    bulk_g2s(sb + OFF_CS, scr->cs[nt], CS_BYTES, bars + 8 * B_AUX);
                    TS(21);
#pragma unroll 1
                    for (int v = 0; v < 2; v++) {
                        const uint32_t ring = sb + v * OFF_O1, fb = bars + 8 * (B_OFULL + v * NO);
                        mbar_expect_tx(fb + 8, BOX);
                        mbar_wait(bars + 8 * B_G1DONE, 0, budget);
                        mbar_wait(bars + 8 * (B_STAGED + v), 0, budget);
                        TS(12 + 2 * v);
                        mbar_arrive(fb);
                        bulk_s2c(mapa(ring + BOX, hp ^ 1), ring, BOX, mapa(fb + 8, hp ^ 1));
                        fence_gpu();
                        asm volatile("red.relaxed.gpu.global.xor.b32 [%0], %1;" ::"l"(&scr->oflag[mt * 2 + 1 - v][0]), "r"(1u << nt) : "memory");
                        TS(13 + 2 * v);
                    }
                }
            }
        }
        TS_END();
    } else if (warp >= 8) {
        reg_dec<40>();
        const int wq = warp - 8, ta = tid - 256, g = lane >> 2, t = lane & 3;
        const uint32_t rbuf = sb + OFF_FR + wq * BOX, rbar = bars + 8 * B_ROW;
        const uint4 wv = ldg_nc(wr + ta * 8);
        if (ta == 0) sts1(sb + OFF_EP, ld_rlx(&scr->epoch[0]) + 1);
        sts4(sb + OFF_STAT + ta * 16, wv.x, wv.y, wv.z, wv.w);
        bar_sync(8, 224);
        const uint32_t ep = lds1(sb + OFF_EP);
        {
            float sw = 0.f;
#pragma unroll 1
            for (int i = 0; i < 16; i++) { const uint32_t q = lds1(sb + OFF_STAT + i * 128 + lane * 4); sw += bf_lo(q) + bf_hi(q); }
#pragma unroll 1
            for (int o = 16; o > 0; o >>= 1) sw += __shfl_xor_sync(0xffffffffu, sw, o);
            float s1 = 0.f, s2 = 0.f, sr = 0.f;
            const uint32_t xa = rbuf + (lane >> 3) * 2048 + (lane & 7) * 16, wa = sb + OFF_STAT + (lane & 7) * 16;
            mbar_wait(rbar, 0, budget);
            TSC(ta == 0, 17);
            uint4 u = lds4(xa), w4 = lds4(wa);
#pragma unroll kStatsUnroll
            for (int i = 1; i <= 16; i++) {
                const uint32_t o = (i * 128) & 2047;
                const uint4 un = lds4(xa + o), wn = lds4(wa + o);
#pragma unroll
                for (int c = 0; c < 4; c++) {
                    const float a0 = bf_lo((&u.x)[c]), a1 = bf_hi((&u.x)[c]);
                    s1 += a0; s2 = fmaf(a0, a0, s2); sr = fmaf(a0, bf_lo((&w4.x)[c]), sr);
                    s1 += a1; s2 = fmaf(a1, a1, s2); sr = fmaf(a1, bf_hi((&w4.x)[c]), sr);
                }
                u = un; w4 = wn;
            }
#pragma unroll 1
            for (int o = 1; o < 8; o <<= 1) {
                s1 += __shfl_xor_sync(0xffffffffu, s1, o); s2 += __shfl_xor_sync(0xffffffffu, s2, o); sr += __shfl_xor_sync(0xffffffffu, sr, o);
            }
            const float mean = s1 * (1.f / 1024.f), mb = bf16r(mean);
            float var = fmaf(-mean, mean, s2 * (1.f / 1024.f));
            sr = fmaf(-mb, sw, sr);
            if (__builtin_expect(__any_sync(0xffffffffu, mean * mean > 256.f * var), 0)) {
                float a2 = 0.f, ar = 0.f;
#pragma unroll 1
                for (int i = 0; i < 64; i++) {
                    const uint32_t o = (i >> 2) * 128 + (i & 3) * 4, q1 = lds1(xa + o), q2 = lds1(wa + o);
                    a2 = fmaf(bf_lo(q1) - mean, bf_lo(q1) - mean, fmaf(bf_hi(q1) - mean, bf_hi(q1) - mean, a2));
                    ar = fmaf(bf_lo(q1) - mb, bf_lo(q2), fmaf(bf_hi(q1) - mb, bf_hi(q2), ar));
                }
#pragma unroll 1
                for (int o = 1; o < 8; o <<= 1) { a2 += __shfl_xor_sync(0xffffffffu, a2, o); ar += __shfl_xor_sync(0xffffffffu, ar, o); }
                var = a2 * (1.f / 1024.f); sr = ar;
            }
            const int s = b * 16 + wq * 4 + (lane >> 3);
            float den;
            asm("sqrt.approx.f32 %0, %1;" : "=f"(den) : "f"(bf16r(bf16r(var) + 1e-5f)));
            const uint32_t st = pack_bf16(mb, den);
            const uint32_t rb = pack_bf16(0.f, sr * rcp(bf_hi(st)) + 0.f);
            uint32_t ord = (int)rb < 0 ? ~rb & 0xffff0000u : rb | 0x80000000u;
            if ((rb & 0x7fffffffu) > 0x7f800000u) ord = 0;
            if ((lane & 7) == 0) st_rlx2(&scr->row[s], st, ord | ((2047 - s) << 5) | (ep & 31));
            __syncwarp();
            if (lane < NF) mbar_arrive(bars + 8 * (B_FEMPTY + lane));
        }
        TSC(ta == 0, 18);
        {
            int s = 0; uint32_t fph = 0;
#pragma unroll 1
            for (int ph = b < 112 ? 0 : 1; ph < 2; ph++) {
                float acc[4] = {0.f, 0.f, 0.f, 0.f};
                const uint32_t alo = sd + (ph ? dlo(OFF_FR, 8192) : dlo(OFF_FR, 4096)), ahi = ph ? dhi(1024, 1) : dhi(512, 2), astep = ph ? 128 : 64;
                if (ph) mbar_wait(bars + 8 * (B_STAGED + 1), 0, budget);
#pragma unroll 1
                for (int q = ph ? 7 : 16; q > 0; q--) {
                    mbar_wait(bars + 8 * (B_FFULL + s), fph, budget);
                    TSC(TIMING % 10 == 3 && ta == 0, 32 + (ph ? 23 : 16) - q);
                    const uint32_t da = alo + s * (F_BYTES >> 4), db = sd + dlo(OFF_FR + BOX, 128) + s * (F_BYTES >> 4);
                    wg_fence();
#pragma unroll
                    for (int j = 0; j < 4; j++) wgmma_n8<1, 0>(acc, mkdesc(da + j * astep, ahi), mkdesc(db + j * 16, dhi(128, 0)), 1);
                    wg_commit();
                    wg_wait<0>();
                    if (lane == 0 && q > 1) mbar_arrive(bars + 8 * (B_FEMPTY + s));
                    if (++s == NF) { s = 0; fph ^= 1; }
                }
                if (ph == 0) {
                    const bool second = (wq >= 2) != (swap_gu != 0);
                    const uint32_t xa = sb + OFF_FR + ((wq & 1) * 32 + lane) * 16;
                    bar_sync(12, 128);
                    if (second) sts4(xa, __float_as_uint(acc[0]), __float_as_uint(acc[1]), __float_as_uint(acc[2]), __float_as_uint(acc[3]));
                    bar_sync(12, 128);
                    if (!second) {
                        const float4 up = lds4f(xa);
                        float hv[4];
#pragma unroll
                        for (int c = 0; c < 4; c++) { const float ga = bf16r(acc[c]); hv[c] = bf16r(ga * sigmoidf(ga)) * bf16r((&up.x)[c]); }
                        uint32_t* hd = &scr->h[(b * 4 + (wq & 1) * 2) * 32 + lane];
                        st_rlx(hd, movm(pack_bf16(hv[0], hv[1]))); st_rlx(hd + 32, movm(pack_bf16(hv[2], hv[3])));
                    }
                } else {
#pragma unroll
                    for (int c = 0; c < 4; c++) st_rlx(&scr->ypart[kc][2 * t + (c & 1)][c2 * 64 + wq * 16 + (c >> 1) * 8 + g], __float_as_uint(acc[c]));
                }
                bar_sync(12, 128);
                if (lane == 0) mbar_arrive(bars + 8 * B_FEMPTY);
                if (ta == 0) { fence_gpu(); st_rlx(&scr->hflag[ph * 128 + b], ep); }
                TSC(ta == 0, 22 + ph);
            }
        }
#pragma unroll 1
        for (int j = wq; j < 8; j += 4) {
            const uint32_t kj = ld_rlx(&scr->sel[j]);
            const int row = 2047 - ((kj >> 5) & 2047), jj = (row & 1) == par ? (row >> 1) - j0 : -1;
            float4 a = make_float4(0.f, 0.f, 0.f, 0.f);
            if ((jj >> 7) == rh) {
                poll_all(&scr->yflag[(lane & 7) * 16 + cb * 2 + (lane >> 4)], ~0u, ep, budget);
#pragma unroll 4
                for (int m = 0; m < 8; m++) {
                    const uint4 v = ld_rlx4(&scr->ypart[m][j][cb * 128 + lane * 4]);
                    a.x += __uint_as_float(v.x); a.y += __uint_as_float(v.y); a.z += __uint_as_float(v.z); a.w += __uint_as_float(v.w);
                }
            }
            const float sig = bf16r(sigmoidf(__uint_as_float(((int)kj < 0 ? kj & 0x7fffffffu : ~kj) & 0xffff0000u)));
            sts2(sb + OFF_UPD + (lane >> 4) * 1024 + j * 128 + ((((lane >> 1) & 7) ^ j) << 4) + (lane & 1) * 8,
                 pack_bf16(bf16r(a.x) * sig, bf16r(a.y) * sig), pack_bf16(bf16r(a.z) * sig, bf16r(a.w) * sig));
            sts1(sb + OFF_SEL + j * 4, jj);
        }
        fence_async_smem();
        __syncwarp();
        if (lane == 0) mbar_arrive(bars + 8 * B_UPD);
        TSC(ta == 0, 24);
        TS_END();
    } else {
        reg_inc<224>();
        const int w = warp >> 2, wi = warp & 3, g = lane >> 2, t = lane & 3;
        const bool elect = (tid & 127) == 0;
        const uint32_t mad = (lane & 15) * 128 + (((lane >> 4) ^ (lane & 7)) << 4);
        {
            float acc0[96], acc1[96];
            const uint32_t sta = sb + OFF_STAT + (8 + w * 128 + wi * 32) * 8;
            {
                const uint32_t xfull = bars + 8 * (B_XFULL + w * 6), xempty = mapa(bars + 8 * B_XEMPTY, w), dx0 = sd + dlo(w * OFF_X1, 16);
                int j = 2, pj = 0; uint32_t xph = 0;
                cluster_wait();
#pragma unroll 1
                for (int k = 0; k < 16; k++) {
                    const uint32_t dx = dx0 + j * (BOX >> 4), dw = sd + dlo(OFF_W, BOX) + (k & 3) * (W_BYTES >> 4);
                    mbar_wait(bars + 8 * (B_WFULL + (k & 3)), (k >> 2) & 1, budget);
                    mbar_wait(xfull + 8 * j, xph, budget);
                    TSC(elect && k == 0, 1 + 8 * w);
                    TSC(TIMING % 10 == 1 && tid == 0, 32 + k);
                    if (k == 15) {
                        mbar_wait(bars + 8 * B_AUX, 0, budget);
                        const uint32_t pm = t & 1 ? 0x4432 : 0x3232, ra = sta + ((t >> 1) * 16 + g) * 8, zero = budget >> 30;
                        const uint32_t a0 = __byte_perm(lds1(ra), 0, pm), a1 = __byte_perm(lds1(ra + 64), 0, pm), a2 = a0 & zero, a3 = a1 & zero;
                        wg_fence();
                        wgmma_rs_n192(acc0, a0, a1, a2, a3, mkdesc(sd + dlo(OFF_CS + 64, 0), dhi(128, 0)));
                        wgmma_rs_n192(acc1, a0, a1, a2, a3, mkdesc(sd + dlo(OFF_CS, 0), dhi(128, 0)));
                    }
                    wg_fence();
#pragma unroll
                    for (int kk = 0; kk < 4; kk++) wgmma_n192<0, 1>(acc1, mkdesc(dx + kk * 2, dhi(1024, 1)), mkdesc(dw + kk * 128, dhi(1024, 1)), kk ? 1 : k);
                    wg_commit();
                    wg_wait<1>();
                    if (elect && k > 0) {
                        mbar_arrive(bars + 8 * (B_WEMPTY + ((k - 1) & 3)));
                        if (k <= 13) { mbar_expect_tx(xfull + 8 * pj, BOX); mbar_arrive_at(xempty + 8 * pj); }
                    }
                    mbar_wait(xfull + 8 * j + 8, xph, budget);
                    wg_fence();
#pragma unroll
                    for (int kk = 0; kk < 4; kk++) wgmma_n192<0, 1>(acc0, mkdesc(dx + 512 + kk * 2, dhi(1024, 1)), mkdesc(dw + kk * 128, dhi(1024, 1)), kk ? 1 : k);
                    wg_commit();
                    wg_wait<1>();
                    if (elect && k <= 12) { mbar_expect_tx(xfull + 8 * j, BOX); mbar_arrive_at(xempty + 8 * j); }
                    pj = j + 1;
                    j += 2;
                    if (j == 6) j = 0;
                    if (j == 2) xph ^= 1;
                }
            }
            TSC(elect, 19 + w);
            uint32_t pk0[48], pk1[48], o[16];
#pragma unroll
            for (int j = 17; j < 48; j += 2) pk1[j] = pack_here(acc1[2 * j], acc1[2 * j + 1]);
            if (warp < 7) {
#pragma unroll
                for (int c = 0; c < 4; c++) stsm4(sb + (w ? OFF_H1 : OFF_H0) + wi * 2048 + c * 512 + lane * 16, pk1[17 + 8 * c], pk1[19 + 8 * c], pk1[21 + 8 * c], pk1[23 + 8 * c]);
                bar_arrive(1 + warp, 64);
            } else if (j0 != 768) {
#pragma unroll
                for (int c = 0; c < 4; c++) {
                    pk1[17 + 8 * c] = max(pk1[17 + 8 * c], 1u);
                    st_rlx4(&scr->halo[b][c * 128 + lane * 4], pk1[17 + 8 * c], pk1[19 + 8 * c], pk1[21 + 8 * c], pk1[23 + 8 * c]);
                }
            }
            TSC(tid == 224, 28);
#pragma unroll
            for (int j = 0; j < 48; j++) if (j < 16 || !(j & 1)) pk1[j] = pack_here(acc1[2 * j], acc1[2 * j + 1]);
            const bool u0 = 2 * t > g, u1 = 2 * t + 1 > g;
            uint32_t mU = (u0 ? 0xffffu : 0u) | (u1 ? 0xffff0000u : 0u), zero = budget >> 30;
            const uint32_t ka0 = sta + (2 * t - (u0 ? 8 : 0)) * 8 + 4, ka1 = sta + (2 * t + 1 - (u1 ? 8 : 0)) * 8 + 4;
            float rk[4], fu[4], fn[4];
            auto factors = [&](int h) {
#pragma unroll
                for (int e = 0; e < 2; e++) {
                    const float rq = lds1f(sta + (16 * h + 8 * e + g) * 8 + 4) * (0.17677669529663687f * 1.4426950408889634f);
                    rk[2 * e] = lds1f(ka0 + h * 128 + e * 64); rk[2 * e + 1] = lds1f(ka1 + h * 128 + e * 64);
                    const float f0 = rq * rk[2 * e], f1 = rq * rk[2 * e + 1];
                    fu[2 * e] = u0 ? f0 : 0.f; fn[2 * e] = f0 - fu[2 * e]; fu[2 * e + 1] = u1 ? f1 : 0.f; fn[2 * e + 1] = f1 - fu[2 * e + 1];
                }
            };
            factors(1);
#pragma unroll
            for (int n = 0; n < 4; n++) asm volatile("" : "+f"(fu[n]), "+f"(fn[n]));
            uint8_t* og = scr->o + ((size_t)(mt * 4 + w * 2) * 16 + nt) * BOX + wi * 256 + lane * 4;
            const uint32_t od = sb + wi * 256 + (lane >> 4) * 1024 + (lane & 15) * 16, g1peer = mapa(bars + 8 * B_G1DONE, hp ^ 1);
            asm volatile("" : "+l"(og), "+r"(mU));
            mbar_wait(bars + 8 * B_AUX, 0, budget);
            wg_wait<0>();
            bar_arrive(13 + w, 256);
            if (elect) { mbar_arrive(bars + 8 * B_G1DONE); mbar_arrive_at(g1peer); }
            TSC(elect, 2 + 8 * w);
            auto hand_over = [&](int v) {
#pragma unroll
                for (int i = 0; i < 16; i++) st_rlx(og + (1 - v) * 16 * BOX + (i >> 1) * 1024 + (i & 1) * 128, o[i]);
                if (v == 0) bar_sync(14 - w, 256);
                if (w == rh) {
#pragma unroll
                    for (int c = 0; c < 4; c++) stsm4(od + v * OFF_O1 + c * 2048, o[4 * c], o[4 * c + 1], o[4 * c + 2], o[4 * c + 3]);
                    fence_async_smem();
                }
                __syncwarp();
                if (lane == 0) mbar_arrive(bars + 8 * (B_STAGED + v));
            };
#pragma unroll
            for (int j = 17; j < 48; j += 2) pk0[j] = pack_here(acc0[2 * j], acc0[2 * j + 1]);
#pragma unroll
            for (int j = 32; j < 48; j++) pk1[j] = movm(pk1[j]);
#pragma unroll
            for (int j = 33; j < 48; j += 2) pk0[j] = movm(pk0[j]);
            attn_pair<2>(pk1, pk1 + 16, pk1 + 32, pk0 + 17, pk0 + 33, fu, fn, rk, 0.f, 0.f, mU, zero, o);
            hand_over(0);
            TSC(elect, 3 + 8 * w);
#pragma unroll
            for (int j = 0; j < 48; j++) if (j < 16 || !(j & 1)) pk0[j] = pack_here(acc0[2 * j], acc0[2 * j + 1]);
#pragma unroll
            for (int j = 32; j < 48; j += 2) pk0[j] = movm(pk0[j]);
            factors(0);
            const bool first = warp == 0 && j0 == 0;
            const float bias0 = first && u0 ? -INFINITY : 0.f, bias1 = first && u1 ? -INFINITY : 0.f;
            bar_sync(warp ? warp : 11, 64);
            uint32_t hl[16];
            const uint32_t ha = sb + (warp == 0 ? OFF_HIN : warp <= 4 ? OFF_H0 - 2048 : OFF_H1 - 5 * 2048) + warp * 2048 + lane * 16;
            ldsm4(hl, ha); ldsm4(hl + 4, ha + 512); ldsm4t(hl + 8, ha + 1024); ldsm4t(hl + 12, ha + 1536);
            attn_pair<1>(pk0, pk0 + 16, pk0 + 32, hl, hl + 8, fu, fn, rk, bias0, bias1, mU, zero, o);
            hand_over(1);
        }
        TSC(tid == 0, 4);
        float acc[64];
        const uint32_t ring = sb + w * OFF_O1, ofull = bars + 8 * (B_OFULL + w * NO), oempty = mapa(bars + 8 * B_OEMPTY, w);
        const int r0 = rh * 128 + wi * 32 + (1 - w) * 16 + g;
        {
            const float2 s0 = lds2f(sb + OFF_STAT + (8 + r0) * 8), s1 = lds2f(sb + OFF_STAT + (16 + r0) * 8);
            const float m0 = s0.x * s0.y, f0 = 1.f + s0.y, m1 = s1.x * s1.y, f1 = 1.f + s1.y;
            mbar_wait(bars + 8 * (B_XT + w), 0, budget);
#pragma unroll
            for (int j = 0; j < 8; j++) {
                uint32_t a0, a1, a2, a3;
                asm volatile("ldmatrix.sync.aligned.m8n8.x4.shared.b16 {%0,%1,%2,%3}, [%4];" : "=r"(a0), "=r"(a1), "=r"(a2), "=r"(a3)
                             : "r"(((ring + wi * 2048 + mad) ^ ((j & 3) * 32)) + (3 + (j >> 2)) * BOX) : "memory");
                acc[8 * j + 0] = fmaf(bf_lo(a0), f0, m0); acc[8 * j + 1] = fmaf(bf_hi(a0), f0, m0);
                acc[8 * j + 2] = fmaf(bf_lo(a1), f1, m1); acc[8 * j + 3] = fmaf(bf_hi(a1), f1, m1);
                acc[8 * j + 4] = fmaf(bf_lo(a2), f0, m0); acc[8 * j + 5] = fmaf(bf_hi(a2), f0, m0);
                acc[8 * j + 6] = fmaf(bf_lo(a3), f1, m1); acc[8 * j + 7] = fmaf(bf_hi(a3), f1, m1);
            }
        }
        bar_sync(9 + w, 128);
        if (elect) {
            mbar_arrive(bars + 8 * (B_WOEMPTY + 6)); mbar_arrive(bars + 8 * B_WOEMPTY);
#pragma unroll
            for (int i = 16; i < 40; i += 8) { mbar_expect_tx(ofull + i, BOX); mbar_arrive_at(oempty + i); }
        }
        TSC(tid == 0, 5);
        {
            const uint32_t da0 = sd + dlo(w * OFF_O1, 1024);
            int os = 0, ws = 1, pos = 0, pws = 0; uint32_t oph = 0, wph = 0;
#pragma unroll 1
            for (int i = 0; i < 16; i++) {
                const uint32_t da = da0 + os * (BOX >> 4), db = sd + dlo(OFF_WO, BOX) + ws * (2 * BOX >> 4);
                mbar_wait(bars + 8 * (B_WOFULL + ws), wph, budget);
                mbar_wait(ofull + 8 * os, oph, budget);
                TSC(TIMING % 10 == 1 && tid == 0, 48 + i);
                TSC(TIMING % 10 == 2 && elect, 32 + w * 16 + i);
                wg_fence();
#pragma unroll
                for (int kk = 0; kk < 4; kk++) wgmma_n128<0, 1>(acc, mkdesc(da + kk * 128, dhi(128, 0)), mkdesc(db + kk * 128, dhi(1024, 1)), 1);
                wg_commit();
                wg_wait<1>();
                if (elect && i > 0 && i <= 11) {
                    mbar_expect_tx(ofull + 8 * pos, BOX); mbar_arrive_at(oempty + 8 * pos);
                    if (i <= 9) mbar_arrive(bars + 8 * (B_WOEMPTY + pws));
                }
                pos = os; pws = ws;
                if (++os == NO) { os = 0; oph ^= 1; }
                if (++ws == NWO) ws = 0;
                if (ws == 1) wph ^= 1;
            }
            mbar_wait(bars + 8 * B_UPD, 0, budget);
            const float2 sl = lds2f(sb + OFF_SEL + t * 8);
            const int d0 = __float_as_int(sl.x) - r0, d1 = __float_as_int(sl.y) - r0;
            const uint32_t a0 = (d0 == 0 ? 0x3f80u : 0u) | (d1 == 0 ? 0x3f800000u : 0u), a1 = (d0 == 8 ? 0x3f80u : 0u) | (d1 == 8 ? 0x3f800000u : 0u);
            wg_fence();
            wgmma_rs_n128(acc, a0, a1, 0u, 0u, mkdesc(sd + dlo(OFF_UPD, 1024), dhi(0, 1)));
            wg_commit();
            wg_wait<0>();
            TSC(elect, 7 + 9 * w);
            const uint32_t os0 = ring + BOX + wi * 4096;
#pragma unroll
            for (int j = 0; j < 8; j++)
                stsm4(((os0 + mad) ^ ((j & 3) * 32)) + (j >> 2) * 2048, pack_bf16(acc[8 * j], acc[8 * j + 1]), pack_bf16(acc[8 * j + 2], acc[8 * j + 3]),
                      pack_bf16(acc[8 * j + 4], acc[8 * j + 5]), pack_bf16(acc[8 * j + 6], acc[8 * j + 7]));
            fence_async_smem();
            __syncwarp();
            if (elect_one()) {
                asm volatile("cp.async.bulk.tensor.5d.global.shared::cta.bulk_group [%0, {%2, %2, %3, %4, %5}], [%1];\ncp.async.bulk.commit_group;\ncp.async.bulk.wait_group.read 0;"
                             ::"l"(&mout), "r"(os0), "r"(0), "r"(((j0 + rh * 128) >> 5) + wi), "r"(1 - w), "r"(par * 16 + cb * 2) : "memory");
            }
            TSC(elect, 8 - 2 * w);
            TS_END();
        }
    }
}

typedef CUresult (*EncodeFn)(CUtensorMap*, CUtensorMapDataType, cuuint32_t, void*, const cuuint64_t*, const cuuint64_t*, const cuuint32_t*,
                             const cuuint32_t*, CUtensorMapInterleave, CUtensorMapSwizzle, CUtensorMapL2promotion, CUtensorMapFloatOOBfill);

CUtensorMap make_map(EncodeFn fn, const void* base, int rank, const cuuint64_t* dims, const cuuint64_t* strides, const cuuint32_t* box,
                     CUtensorMapSwizzle swz = CU_TENSOR_MAP_SWIZZLE_128B, CUtensorMapL2promotion pro = CU_TENSOR_MAP_L2_PROMOTION_L2_256B) {
    CUtensorMap m;
    cuuint32_t es[5] = {1, 1, 1, 1, 1};
    fn(&m, CU_TENSOR_MAP_DATA_TYPE_BFLOAT16, rank, (void*)base, dims, strides, box, es, CU_TENSOR_MAP_INTERLEAVE_NONE,
       swz, pro, CU_TENSOR_MAP_FLOAT_OOB_FILL_NONE);
    return m;
}

}

extern "C" void kernel_launch(void* const* d_in, const int* in_sizes, int n_in, void* d_out, int out_size) {
    (void)in_sizes; (void)n_in; (void)out_size;
    const __nv_bfloat16* x = (const __nv_bfloat16*)d_in[0];
    const __nv_bfloat16* wqkv = (const __nv_bfloat16*)d_in[1];
    const __nv_bfloat16* wo = (const __nv_bfloat16*)d_in[2];
    const __nv_bfloat16* wr = (const __nv_bfloat16*)d_in[4];
    const __nv_bfloat16* wg = (const __nv_bfloat16*)d_in[5];
    const __nv_bfloat16* wu = (const __nv_bfloat16*)d_in[6];
    const __nv_bfloat16* wd = (const __nv_bfloat16*)d_in[7];
    static EncodeFn fn = nullptr;
    static Scratch* scr = nullptr;
    if (!fn) {
        void* p = nullptr; cudaDriverEntryPointQueryResult q;
        cudaGetDriverEntryPoint("cuTensorMapEncodeTiled", &p, cudaEnableDefault, &q);
        fn = (EncodeFn)p;
        cudaFuncSetAttribute(fused_kernel, cudaFuncAttributeMaxDynamicSharedMemorySize, SMEM_LAUNCH);
        cudaGetSymbolAddress((void**)&scr, g_scr);
    }
    const cuuint64_t xd[4] = {2048, 16, 32, 2}, xs[4] = {4096, 131072, 65536, 128}, od[5] = {64, 16, 32, 2, 32};
    const cuuint32_t xb[4] = {64, 16, 4, 1}, ob[5] = {64, 16, 1, 1, 2};
    const cuuint64_t wdm[3] = {1024, 1024, 3}, wst[2] = {6144, 2048};
    const cuuint32_t wb[3] = {64, 64, 3};
    const cuuint64_t wod[3] = {64, 1024, 16}, wdd[3] = {64, 3584, 16}, wos[2] = {2048, 128};
    const cuuint32_t wob[3] = {64, 64, 2}, wdb[3] = {64, 64, 1};
    CUtensorMap mx = make_map(fn, x, 4, xd, xs, xb), mw = make_map(fn, wqkv, 3, wdm, wst, wb);
    CUtensorMap mwo = make_map(fn, wo, 3, wod, wos, wob), mout = make_map(fn, d_out, 5, od, xs, ob);
    const int swap_gu = wu < wg;
    const cuuint64_t gd[3] = {3584, 1024, 2}, gst[2] = {7168, (cuuint64_t)(swap_gu ? (const char*)wg - (const char*)wu : (const char*)wu - (const char*)wg)};
    const cuuint32_t gb[3] = {32, 64, 2};
    CUtensorMap mgu = make_map(fn, swap_gu ? wu : wg, 3, gd, gst, gb, CU_TENSOR_MAP_SWIZZLE_64B, CU_TENSOR_MAP_L2_PROMOTION_L2_128B);
    CUtensorMap mwd = make_map(fn, wd, 3, wdd, wos, wdb, CU_TENSOR_MAP_SWIZZLE_128B, CU_TENSOR_MAP_L2_PROMOTION_L2_128B);
    const cuuint64_t md[2] = {64, 32768}, ms[1] = {128};
    const cuuint32_t mb[2] = {64, 64};
    CUtensorMap mo = make_map(fn, scr, 2, md, ms, mb, CU_TENSOR_MAP_SWIZZLE_NONE, CU_TENSOR_MAP_L2_PROMOTION_NONE);
    cudaLaunchConfig_t cfg = {};
    cfg.gridDim = dim3(132); cfg.blockDim = dim3(512); cfg.dynamicSmemBytes = SMEM_LAUNCH; cfg.stream = cudaStreamPerThread;
    cudaLaunchAttribute at[1];
    at[0].id = cudaLaunchAttributeClusterDimension; at[0].val.clusterDim.x = 2; at[0].val.clusterDim.y = 1; at[0].val.clusterDim.z = 1;
    cfg.attrs = at; cfg.numAttrs = 1;
    cudaLaunchKernelEx(&cfg, fused_kernel, mx, mw, mwo, mout, mgu, mwd, mo, x, wr, scr, swap_gu);
}
```

```cpp
#include <cuda_runtime.h>
#include <cuda.h>
#include <cuda_bf16.h>
#include <stdint.h>

namespace {

constexpr int BOX = 8192, W_BYTES = 3 * BOX;
constexpr int OFF_W = 6 * BOX, OFF_E = 15 * BOX, OFF_X1 = 18 * BOX;
constexpr int OFF_WO = 5 * BOX, OFF_O1 = 19 * BOX;
constexpr int OFF_H0 = 5 * BOX, OFF_H1 = 18 * BOX;
constexpr int NO = 5, NWO = 7, F_BYTES = 9216;
constexpr int OFF_FR = 24 * BOX;
constexpr int CS_BYTES = 3136;
constexpr int OFF_CS = OFF_E + 2 * F_BYTES;
constexpr int OFF_UPD = OFF_FR + 3 * F_BYTES;
constexpr int OFF_HIN = OFF_UPD + 2048;
constexpr int OFF_STAT = OFF_FR + 32768;
constexpr int OFF_SEL = OFF_STAT + 2112;
constexpr int OFF_EP = OFF_SEL + 32;
constexpr int OFF_BAR = OFF_EP + 16;
constexpr int B_WFULL = 0, B_XFULL = 3, B_AUX = 15, B_XT = 16, B_WOFULL = 18, B_OFULL = 25, B_ROW = 35, B_FFULL = 36, B_F1DONE = 41;
constexpr int B_WEMPTY = 42, B_XEMPTY = 46, B_WOEMPTY = 52, B_OEMPTY = 59;
constexpr int B_G1DONE = 66, B_FEMPTY = 67, B_STAGED = 72, B_UPD = 74, NBAR = 78;
__device__ __forceinline__ uint32_t fslot(int s) { return s * F_BYTES + (s < 3 ? OFF_FR : OFF_E - 3 * F_BYTES); }
constexpr int SMEM_BYTES = OFF_BAR + NBAR * 8;
static_assert(OFF_HIN + 2048 <= OFF_STAT && OFF_CS >= 17 * BOX && OFF_CS + CS_BYTES <= OFF_X1 && SMEM_BYTES + 256 <= 232448 && OFF_BAR % 8 == 0 && OFF_UPD % 1024 == 0, "smem");
#define POLL_NS 100
#define HELP_AT 64
#define G1_DEPTH 0
#define NF1 5
#define FFN_DEPTH 1
constexpr uint32_t F1_PHASES = NF1 == 4 ? 0 : NF1 == 5 ? 0x1e : 6;
#define PF_RATE 8
#define PF_START 7
#define EARLY_W 2
#define PF_W 7
#define ROWS_AT 7
#define STATS_UNROLL 1
constexpr int kStatsUnroll = STATS_UNROLL;
constexpr int BUDGET = 1 << 18;

struct Scratch {
    uint8_t o[2048 * 1024 * 2];
    float ypart[8][8][1024];
    uint32_t halo[128][512];
    uint32_t h[14336];
    uint32_t xsel[4096];
    uint2 row[2048];
    uint32_t cs[16][800];
    uint32_t oflag[16][32];
    uint32_t fflag[128][8];
    uint32_t sel[32], csflag[32], epoch[32];
};
__device__ __align__(1024) Scratch g_scr;

#define TS(i) do {} while (0)
#define TS_END() do {} while (0)
#define TSC(c, i) do {} while (0)
constexpr int SMEM_LAUNCH = SMEM_BYTES;
__device__ __forceinline__ uint32_t smem_u32(const void* p) { return (uint32_t)__cvta_generic_to_shared(p); }
__device__ __forceinline__ void mbar_init(uint32_t bar, uint32_t cnt) { asm volatile("mbarrier.init.shared::cta.b64 [%0], %1;" ::"r"(bar), "r"(cnt) : "memory"); }
__device__ __forceinline__ void mbar_expect_tx(uint32_t bar, uint32_t bytes) { asm volatile("mbarrier.arrive.expect_tx.shared::cta.b64 _, [%0], %1;" ::"r"(bar), "r"(bytes) : "memory"); }
__device__ __forceinline__ void mbar_arrive(uint32_t bar) { asm volatile("mbarrier.arrive.shared::cta.b64 _, [%0];" ::"r"(bar) : "memory"); }
__device__ __forceinline__ uint32_t mapa(uint32_t a, uint32_t cta) { uint32_t r; asm("mapa.shared::cluster.u32 %0, %1, %2;" : "=r"(r) : "r"(a), "r"(cta)); return r; }
__device__ __forceinline__ void mbar_arrive_at(uint32_t cbar) { asm volatile("mbarrier.arrive.shared::cluster.b64 _, [%0];" ::"r"(cbar) : "memory"); }
__device__ __forceinline__ void mbar_wait(uint32_t bar, uint32_t parity, int& budget) {
    asm volatile("{\n.reg .pred p;\nLAB_WAIT:\nmbarrier.try_wait.parity.shared::cta.b64 p, [%1], %2;\n"
                 "add.s32 %0, %0, -1;\nsetp.gt.and.s32 p, %0, 0, !p;\n@p bra LAB_WAIT;\n}" : "+r"(budget) : "r"(bar), "r"(parity) : "memory");
}
__device__ __forceinline__ void tma_2d_mc(uint32_t dst, const CUtensorMap* m, uint32_t bar, int c0, int c1) {
    asm volatile("cp.async.bulk.tensor.2d.shared::cluster.global.mbarrier::complete_tx::bytes.multicast::cluster [%0], [%1, {%3, %4}], [%2], %5;" ::"r"(dst), "l"(m), "r"(bar), "r"(c0), "r"(c1), "h"((uint16_t)3) : "memory");
}
__device__ __forceinline__ void tma_3d(uint32_t dst, const CUtensorMap* m, uint32_t bar, int c0, int c1, int c2) {
    asm volatile("cp.async.bulk.tensor.3d.shared::cluster.global.mbarrier::complete_tx::bytes [%0], [%1, {%3, %4, %5}], [%2];" ::"r"(dst), "l"(m), "r"(bar), "r"(c0), "r"(c1), "r"(c2) : "memory");
}
__device__ __forceinline__ void tma_4d(uint32_t dst, const CUtensorMap* m, uint32_t bar, int c0, int c1, int c2, int c3) {
    asm volatile("cp.async.bulk.tensor.4d.shared::cluster.global.mbarrier::complete_tx::bytes [%0], [%1, {%3, %4, %5, %6}], [%2];" ::"r"(dst), "l"(m), "r"(bar), "r"(c0), "r"(c1), "r"(c2), "r"(c3) : "memory");
}
__device__ __forceinline__ void tma_4d_mc(uint32_t dst, const CUtensorMap* m, uint32_t bar, int c0, int c1, int c2, int c3) {
    asm volatile("cp.async.bulk.tensor.4d.shared::cluster.global.mbarrier::complete_tx::bytes.multicast::cluster [%0], [%1, {%3, %4, %5, %6}], [%2], %7;" ::"r"(dst), "l"(m), "r"(bar), "r"(c0), "r"(c1), "r"(c2), "r"(c3), "h"((uint16_t)3) : "memory");
}
__device__ __forceinline__ void tma_pf_3d(const CUtensorMap* m, int c0, int c1, int c2) {
    asm volatile("cp.async.bulk.prefetch.tensor.3d.L2.global [%0, {%1, %2, %3}];" ::"l"(m), "r"(c0), "r"(c1), "r"(c2) : "memory");
}
__device__ __forceinline__ void bulk_g2s(uint32_t dst, const void* src, uint32_t bytes, uint32_t bar) {
    asm volatile("cp.async.bulk.shared::cluster.global.mbarrier::complete_tx::bytes [%0], [%1], %2, [%3];" ::"r"(dst), "l"(src), "r"(bytes), "r"(bar) : "memory");
}
__device__ __forceinline__ void bulk_s2g(void* dst, uint32_t src, uint32_t bytes) {
    asm volatile("cp.async.bulk.global.shared::cta.bulk_group [%0], [%1], %2;" ::"l"(dst), "r"(src), "r"(bytes) : "memory");
}
__device__ __forceinline__ void bulk_s2c(uint32_t cdst, uint32_t src, uint32_t bytes, uint32_t cbar) {
    asm volatile("cp.async.bulk.shared::cluster.shared::cta.mbarrier::complete_tx::bytes [%0], [%1], %2, [%3];" ::"r"(cdst), "r"(src), "r"(bytes), "r"(cbar) : "memory");
}
__device__ __forceinline__ void cluster_wait() { asm volatile("barrier.cluster.wait.aligned;" ::: "memory"); }
__device__ __forceinline__ void fence_gpu() { asm volatile("fence.acq_rel.gpu;" ::: "memory"); }
__device__ __forceinline__ void fence_async_smem() { asm volatile("fence.proxy.async.shared::cta;" ::: "memory"); }
__device__ __forceinline__ void fence_async_gmem() { asm volatile("fence.proxy.async.global;" ::: "memory"); }
__device__ __forceinline__ void wg_fence() { asm volatile("wgmma.fence.sync.aligned;" ::: "memory"); }
__device__ __forceinline__ void wg_commit() { asm volatile("wgmma.commit_group.sync.aligned;" ::: "memory"); }
template <int N> __device__ __forceinline__ void wg_wait() { asm volatile("wgmma.wait_group.sync.aligned %0;" ::"n"(N) : "memory"); }
__device__ __forceinline__ uint64_t mkdesc(uint32_t lo, uint32_t hi) { return ((uint64_t)hi << 32) | lo; }
__host__ __device__ constexpr uint32_t dhi(uint32_t sbo, uint32_t mode) { return (sbo >> 4) | (mode << 30); }
__host__ __device__ constexpr uint32_t dlo(uint32_t off, uint32_t lbo) { return (off >> 4) + ((lbo >> 4) << 16); }
__device__ __forceinline__ bool elect_one() {
    uint32_t e;
    asm volatile("{\n.reg .pred p;\nelect.sync _|p, 0xffffffff;\nselp.u32 %0, 1, 0, p;\n}" : "=r"(e));
    return e;
}
template <int R> __device__ __forceinline__ void reg_inc() { asm volatile("setmaxnreg.inc.sync.aligned.u32 %0;" ::"n"(R)); }
template <int R> __device__ __forceinline__ void reg_dec() { asm volatile("setmaxnreg.dec.sync.aligned.u32 %0;" ::"n"(R)); }
__device__ __forceinline__ void bar_sync(int id, int n) { asm volatile("bar.sync %0, %1;" ::"r"(id), "r"(n) : "memory"); }
__device__ __forceinline__ void bar_arrive(int id, int n) { asm volatile("bar.arrive %0, %1;" ::"r"(id), "r"(n) : "memory"); }
__device__ __forceinline__ uint32_t pack_bf16(float lo, float hi) { uint32_t r; asm("cvt.rn.bf16x2.f32 %0, %1, %2;" : "=r"(r) : "f"(hi), "f"(lo)); return r; }
__device__ __forceinline__ uint32_t pack_here(float lo, float hi) { uint32_t r; asm volatile("cvt.rn.bf16x2.f32 %0, %1, %2;" : "=r"(r) : "f"(hi), "f"(lo)); return r; }
__device__ __forceinline__ float bf_lo(uint32_t u) { return __uint_as_float(u << 16); }
__device__ __forceinline__ float bf_hi(uint32_t u) { return __uint_as_float(u & 0xffff0000u); }
__device__ __forceinline__ float bf16r(float v) { return bf_lo(pack_bf16(v, 0.f)); }
__device__ __forceinline__ float rcp(float x) { float r; asm("rcp.approx.ftz.f32 %0, %1;" : "=f"(r) : "f"(x)); return r; }
__device__ __forceinline__ float ex2(float x) { float r; asm("ex2.approx.ftz.f32 %0, %1;" : "=f"(r) : "f"(x)); return r; }
__device__ __forceinline__ float sigmoidf(float v) { return rcp(1.f + ex2(v * -1.4426950408889634f)); }
__device__ __forceinline__ uint32_t movm(uint32_t a) { uint32_t d; asm volatile("movmatrix.sync.aligned.m8n8.trans.b16 %0, %1;" : "=r"(d) : "r"(a)); return d; }
__device__ __forceinline__ void mma16816(float (&c)[4], uint32_t a0, uint32_t a1, uint32_t a2, uint32_t a3, uint32_t b0, uint32_t b1) {
    asm volatile("mma.sync.aligned.m16n8k16.row.col.f32.bf16.bf16.f32 {%0,%1,%2,%3}, {%4,%5,%6,%7}, {%8,%9}, {%0,%1,%2,%3};"
                 : "+f"(c[0]), "+f"(c[1]), "+f"(c[2]), "+f"(c[3]) : "r"(a0), "r"(a1), "r"(a2), "r"(a3), "r"(b0), "r"(b1));
}
__device__ __forceinline__ void mma1688(float (&c)[4], uint32_t a0, uint32_t a1, uint32_t b0) {
    asm volatile("mma.sync.aligned.m16n8k8.row.col.f32.bf16.bf16.f32 {%0,%1,%2,%3}, {%4,%5}, {%6}, {%0,%1,%2,%3};"
                 : "+f"(c[0]), "+f"(c[1]), "+f"(c[2]), "+f"(c[3]) : "r"(a0), "r"(a1), "r"(b0));
}
__device__ __forceinline__ void stsm4(uint32_t a, uint32_t r0, uint32_t r1, uint32_t r2, uint32_t r3) {
    asm volatile("stmatrix.sync.aligned.m8n8.x4.shared.b16 [%0], {%1,%2,%3,%4};" ::"r"(a), "r"(r0), "r"(r1), "r"(r2), "r"(r3) : "memory");
}
__device__ __forceinline__ void ldsm4(uint32_t* r, uint32_t a) {
    asm volatile("ldmatrix.sync.aligned.m8n8.x4.shared.b16 {%0,%1,%2,%3}, [%4];" : "=r"(r[0]), "=r"(r[1]), "=r"(r[2]), "=r"(r[3]) : "r"(a) : "memory");
}
__device__ __forceinline__ void ldsm4t(uint32_t* r, uint32_t a) {
    asm volatile("ldmatrix.sync.aligned.m8n8.x4.trans.shared.b16 {%0,%1,%2,%3}, [%4];" : "=r"(r[0]), "=r"(r[1]), "=r"(r[2]), "=r"(r[3]) : "r"(a) : "memory");
}
__device__ __forceinline__ uint32_t ld_rlx(const void* p) { uint32_t v; asm volatile("ld.relaxed.gpu.global.u32 %0, [%1];" : "=r"(v) : "l"(p) : "memory"); return v; }
__device__ __forceinline__ uint32_t ld_acq(const void* p) { uint32_t v; asm volatile("ld.acquire.gpu.global.u32 %0, [%1];" : "=r"(v) : "l"(p) : "memory"); return v; }
__device__ __forceinline__ uint2 ld_rlx2(const void* p) { uint2 v; asm volatile("ld.relaxed.gpu.global.v2.u32 {%0,%1}, [%2];" : "=r"(v.x), "=r"(v.y) : "l"(p) : "memory"); return v; }
__device__ __forceinline__ uint4 ld_rlx4(const void* p) { uint4 v; asm volatile("ld.relaxed.gpu.global.v4.u32 {%0,%1,%2,%3}, [%4];" : "=r"(v.x), "=r"(v.y), "=r"(v.z), "=r"(v.w) : "l"(p) : "memory"); return v; }
__device__ __forceinline__ void st_rlx(void* p, uint32_t v) { asm volatile("st.relaxed.gpu.global.u32 [%0], %1;" ::"l"(p), "r"(v) : "memory"); }
__device__ __forceinline__ void st_rlx2(void* p, uint32_t a, uint32_t b) { asm volatile("st.relaxed.gpu.global.v2.u32 [%0], {%1,%2};" ::"l"(p), "r"(a), "r"(b) : "memory"); }
__device__ __forceinline__ void st_rlx4(void* p, uint32_t a, uint32_t b, uint32_t c, uint32_t d) { asm volatile("st.relaxed.gpu.global.v4.u32 [%0], {%1,%2,%3,%4};" ::"l"(p), "r"(a), "r"(b), "r"(c), "r"(d) : "memory"); }
__device__ __forceinline__ uint4 ldg_nc(const void* p) { uint4 v; asm volatile("ld.global.nc.v4.u32 {%0,%1,%2,%3}, [%4];" : "=r"(v.x), "=r"(v.y), "=r"(v.z), "=r"(v.w) : "l"(p)); return v; }
__device__ __forceinline__ void sts4(uint32_t a, uint32_t x, uint32_t y, uint32_t z, uint32_t w) { asm volatile("st.shared.v4.u32 [%0], {%1,%2,%3,%4};" ::"r"(a), "r"(x), "r"(y), "r"(z), "r"(w) : "memory"); }
__device__ __forceinline__ void sts2(uint32_t a, uint32_t x, uint32_t y) { asm volatile("st.shared.v2.u32 [%0], {%1,%2};" ::"r"(a), "r"(x), "r"(y) : "memory"); }
__device__ __forceinline__ void sts1(uint32_t a, uint32_t v) { asm volatile("st.shared.u32 [%0], %1;" ::"r"(a), "r"(v) : "memory"); }
__device__ __forceinline__ uint4 lds4(uint32_t a) { uint4 v; asm volatile("ld.shared.v4.u32 {%0,%1,%2,%3}, [%4];" : "=r"(v.x), "=r"(v.y), "=r"(v.z), "=r"(v.w) : "r"(a) : "memory"); return v; }
__device__ __forceinline__ float4 lds4f(uint32_t a) { float4 v; asm volatile("ld.shared.v4.f32 {%0,%1,%2,%3}, [%4];" : "=f"(v.x), "=f"(v.y), "=f"(v.z), "=f"(v.w) : "r"(a) : "memory"); return v; }
__device__ __forceinline__ float2 lds2f(uint32_t a) { float2 v; asm volatile("ld.shared.v2.f32 {%0,%1}, [%2];" : "=f"(v.x), "=f"(v.y) : "r"(a) : "memory"); return v; }
__device__ __forceinline__ float lds1f(uint32_t a) { float v; asm volatile("ld.shared.f32 %0, [%1];" : "=f"(v) : "r"(a) : "memory"); return v; }
__device__ __forceinline__ uint32_t lds1(uint32_t a) { uint32_t v; asm volatile("ld.shared.u32 %0, [%1];" : "=r"(v) : "r"(a) : "memory"); return v; }
__device__ __forceinline__ uint32_t redux_max(uint32_t v) { uint32_t r; asm volatile("redux.sync.max.u32 %0, %1, 0xffffffff;" : "=r"(r) : "r"(v)); return r; }
__device__ __forceinline__ uint32_t poll_all(const uint32_t* p, uint32_t mask, uint32_t want, int& budget) {
    uint32_t v;
#pragma unroll 1
    while (v = ld_acq(p), !__all_sync(0xffffffffu, (v & mask) == want) && --budget > 0) __nanosleep(POLL_NS);
    return v;
}

template <int TA, int TB>
__device__ __forceinline__ void wgmma_n192(float (&d)[96], uint64_t da, uint64_t db, int keep) {
    asm volatile("{\n.reg .pred p;\nsetp.ne.b32 p, %98, 0;\n"
        "wgmma.mma_async.sync.aligned.m64n192k16.f32.bf16.bf16 "
        "{%0, %1, %2, %3, %4, %5, %6, %7, %8, %9, %10, %11, %12, %13, %14, %15, "
        "%16, %17, %18, %19, %20, %21, %22, %23, %24, %25, %26, %27, %28, %29, %30, %31, "
        "%32, %33, %34, %35, %36, %37, %38, %39, %40, %41, %42, %43, %44, %45, %46, %47, "
        "%48, %49, %50, %51, %52, %53, %54, %55, %56, %57, %58, %59, %60, %61, %62, %63, "
        "%64, %65, %66, %67, %68, %69, %70, %71, %72, %73, %74, %75, %76, %77, %78, %79, "
        "%80, %81, %82, %83, %84, %85, %86, %87, %88, %89, %90, %91, %92, %93, %94, %95}, "
        "%96, %97, p, 1, 1, %99, %100;\n}\n"
        : "+f"(d[0]), "+f"(d[1]), "+f"(d[2]), "+f"(d[3]), "+f"(d[4]), "+f"(d[5]), "+f"(d[6]), "+f"(d[7]),
          "+f"(d[8]), "+f"(d[9]), "+f"(d[10]), "+f"(d[11]), "+f"(d[12]), "+f"(d[13]), "+f"(d[14]), "+f"(d[15]),
          "+f"(d[16]), "+f"(d[17]), "+f"(d[18]), "+f"(d[19]), "+f"(d[20]), "+f"(d[21]), "+f"(d[22]), "+f"(d[23]),
          "+f"(d[24]), "+f"(d[25]), "+f"(d[26]), "+f"(d[27]), "+f"(d[28]), "+f"(d[29]), "+f"(d[30]), "+f"(d[31]),
          "+f"(d[32]), "+f"(d[33]), "+f"(d[34]), "+f"(d[35]), "+f"(d[36]), "+f"(d[37]), "+f"(d[38]), "+f"(d[39]),
          "+f"(d[40]), "+f"(d[41]), "+f"(d[42]), "+f"(d[43]), "+f"(d[44]), "+f"(d[45]), "+f"(d[46]), "+f"(d[47]),
          "+f"(d[48]), "+f"(d[49]), "+f"(d[50]), "+f"(d[51]), "+f"(d[52]), "+f"(d[53]), "+f"(d[54]), "+f"(d[55]),
          "+f"(d[56]), "+f"(d[57]), "+f"(d[58]), "+f"(d[59]), "+f"(d[60]), "+f"(d[61]), "+f"(d[62]), "+f"(d[63]),
          "+f"(d[64]), "+f"(d[65]), "+f"(d[66]), "+f"(d[67]), "+f"(d[68]), "+f"(d[69]), "+f"(d[70]), "+f"(d[71]),
          "+f"(d[72]), "+f"(d[73]), "+f"(d[74]), "+f"(d[75]), "+f"(d[76]), "+f"(d[77]), "+f"(d[78]), "+f"(d[79]),
          "+f"(d[80]), "+f"(d[81]), "+f"(d[82]), "+f"(d[83]), "+f"(d[84]), "+f"(d[85]), "+f"(d[86]), "+f"(d[87]),
          "+f"(d[88]), "+f"(d[89]), "+f"(d[90]), "+f"(d[91]), "+f"(d[92]), "+f"(d[93]), "+f"(d[94]), "+f"(d[95])
        : "l"(da), "l"(db), "r"(keep), "n"(TA), "n"(TB));
}
template <int TA, int TB>
__device__ __forceinline__ void wgmma_n128(float (&d)[64], uint64_t da, uint64_t db, int keep) {
    asm volatile("{\n.reg .pred p;\nsetp.ne.b32 p, %66, 0;\n"
        "wgmma.mma_async.sync.aligned.m64n128k16.f32.bf16.bf16 "
        "{%0, %1, %2, %3, %4, %5, %6, %7, %8, %9, %10, %11, %12, %13, %14, %15, "
        "%16, %17, %18, %19, %20, %21, %22, %23, %24, %25, %26, %27, %28, %29, %30, %31, "
        "%32, %33, %34, %35, %36, %37, %38, %39, %40, %41, %42, %43, %44, %45, %46, %47, "
        "%48, %49, %50, %51, %52, %53, %54, %55, %56, %57, %58, %59, %60, %61, %62, %63}, "
        "%64, %65, p, 1, 1, %67, %68;\n}\n"
        : "+f"(d[0]), "+f"(d[1]), "+f"(d[2]), "+f"(d[3]), "+f"(d[4]), "+f"(d[5]), "+f"(d[6]), "+f"(d[7]),
          "+f"(d[8]), "+f"(d[9]), "+f"(d[10]), "+f"(d[11]), "+f"(d[12]), "+f"(d[13]), "+f"(d[14]), "+f"(d[15]),
          "+f"(d[16]), "+f"(d[17]), "+f"(d[18]), "+f"(d[19]), "+f"(d[20]), "+f"(d[21]), "+f"(d[22]), "+f"(d[23]),
          "+f"(d[24]), "+f"(d[25]), "+f"(d[26]), "+f"(d[27]), "+f"(d[28]), "+f"(d[29]), "+f"(d[30]), "+f"(d[31]),
          "+f"(d[32]), "+f"(d[33]), "+f"(d[34]), "+f"(d[35]), "+f"(d[36]), "+f"(d[37]), "+f"(d[38]), "+f"(d[39]),
          "+f"(d[40]), "+f"(d[41]), "+f"(d[42]), "+f"(d[43]), "+f"(d[44]), "+f"(d[45]), "+f"(d[46]), "+f"(d[47]),
          "+f"(d[48]), "+f"(d[49]), "+f"(d[50]), "+f"(d[51]), "+f"(d[52]), "+f"(d[53]), "+f"(d[54]), "+f"(d[55]),
          "+f"(d[56]), "+f"(d[57]), "+f"(d[58]), "+f"(d[59]), "+f"(d[60]), "+f"(d[61]), "+f"(d[62]), "+f"(d[63])
        : "l"(da), "l"(db), "r"(keep), "n"(TA), "n"(TB));
}
template <int TA, int TB>
__device__ __forceinline__ void wgmma_n8(float (&d)[4], uint64_t da, uint64_t db, int keep) {
    asm volatile("{\n.reg .pred p;\nsetp.ne.b32 p, %6, 0;\n"
        "wgmma.mma_async.sync.aligned.m64n8k16.f32.bf16.bf16 "
        "{%0, %1, %2, %3}, "
        "%4, %5, p, 1, 1, %7, %8;\n}\n"
        : "+f"(d[0]), "+f"(d[1]), "+f"(d[2]), "+f"(d[3])
        : "l"(da), "l"(db), "r"(keep), "n"(TA), "n"(TB));
}
__device__ __forceinline__ void wgmma_rs_n128(float (&d)[64], uint32_t a0, uint32_t a1, uint32_t a2, uint32_t a3, uint64_t db) {
    asm volatile("{\n.reg .pred p;\nsetp.ne.b32 p, 1, 0;\n"
        "wgmma.mma_async.sync.aligned.m64n128k16.f32.bf16.bf16 "
        "{%0, %1, %2, %3, %4, %5, %6, %7, %8, %9, %10, %11, %12, %13, %14, %15, "
        "%16, %17, %18, %19, %20, %21, %22, %23, %24, %25, %26, %27, %28, %29, %30, %31, "
        "%32, %33, %34, %35, %36, %37, %38, %39, %40, %41, %42, %43, %44, %45, %46, %47, "
        "%48, %49, %50, %51, %52, %53, %54, %55, %56, %57, %58, %59, %60, %61, %62, %63}, "
        "{%64, %65, %66, %67}, %68, p, 1, 1, 1;\n}\n"
        : "+f"(d[0]), "+f"(d[1]), "+f"(d[2]), "+f"(d[3]), "+f"(d[4]), "+f"(d[5]), "+f"(d[6]), "+f"(d[7]),
          "+f"(d[8]), "+f"(d[9]), "+f"(d[10]), "+f"(d[11]), "+f"(d[12]), "+f"(d[13]), "+f"(d[14]), "+f"(d[15]),
          "+f"(d[16]), "+f"(d[17]), "+f"(d[18]), "+f"(d[19]), "+f"(d[20]), "+f"(d[21]), "+f"(d[22]), "+f"(d[23]),
          "+f"(d[24]), "+f"(d[25]), "+f"(d[26]), "+f"(d[27]), "+f"(d[28]), "+f"(d[29]), "+f"(d[30]), "+f"(d[31]),
          "+f"(d[32]), "+f"(d[33]), "+f"(d[34]), "+f"(d[35]), "+f"(d[36]), "+f"(d[37]), "+f"(d[38]), "+f"(d[39]),
          "+f"(d[40]), "+f"(d[41]), "+f"(d[42]), "+f"(d[43]), "+f"(d[44]), "+f"(d[45]), "+f"(d[46]), "+f"(d[47]),
          "+f"(d[48]), "+f"(d[49]), "+f"(d[50]), "+f"(d[51]), "+f"(d[52]), "+f"(d[53]), "+f"(d[54]), "+f"(d[55]),
          "+f"(d[56]), "+f"(d[57]), "+f"(d[58]), "+f"(d[59]), "+f"(d[60]), "+f"(d[61]), "+f"(d[62]), "+f"(d[63])
        : "r"(a0), "r"(a1), "r"(a2), "r"(a3), "l"(db));
}
__device__ __forceinline__ void wgmma_rs_n192(float (&d)[96], uint32_t a0, uint32_t a1, uint32_t a2, uint32_t a3, uint64_t db) {
    asm volatile("{\n.reg .pred p;\nsetp.ne.b32 p, 1, 0;\n"
        "wgmma.mma_async.sync.aligned.m64n192k16.f32.bf16.bf16 "
        "{%0, %1, %2, %3, %4, %5, %6, %7, %8, %9, %10, %11, %12, %13, %14, %15, "
        "%16, %17, %18, %19, %20, %21, %22, %23, %24, %25, %26, %27, %28, %29, %30, %31, "
        "%32, %33, %34, %35, %36, %37, %38, %39, %40, %41, %42, %43, %44, %45, %46, %47, "
        "%48, %49, %50, %51, %52, %53, %54, %55, %56, %57, %58, %59, %60, %61, %62, %63, "
        "%64, %65, %66, %67, %68, %69, %70, %71, %72, %73, %74, %75, %76, %77, %78, %79, "
        "%80, %81, %82, %83, %84, %85, %86, %87, %88, %89, %90, %91, %92, %93, %94, %95}, "
        "{%96, %97, %98, %99}, %100, p, 1, 1, 1;\n}\n"
        : "+f"(d[0]), "+f"(d[1]), "+f"(d[2]), "+f"(d[3]), "+f"(d[4]), "+f"(d[5]), "+f"(d[6]), "+f"(d[7]),
          "+f"(d[8]), "+f"(d[9]), "+f"(d[10]), "+f"(d[11]), "+f"(d[12]), "+f"(d[13]), "+f"(d[14]), "+f"(d[15]),
          "+f"(d[16]), "+f"(d[17]), "+f"(d[18]), "+f"(d[19]), "+f"(d[20]), "+f"(d[21]), "+f"(d[22]), "+f"(d[23]),
          "+f"(d[24]), "+f"(d[25]), "+f"(d[26]), "+f"(d[27]), "+f"(d[28]), "+f"(d[29]), "+f"(d[30]), "+f"(d[31]),
          "+f"(d[32]), "+f"(d[33]), "+f"(d[34]), "+f"(d[35]), "+f"(d[36]), "+f"(d[37]), "+f"(d[38]), "+f"(d[39]),
          "+f"(d[40]), "+f"(d[41]), "+f"(d[42]), "+f"(d[43]), "+f"(d[44]), "+f"(d[45]), "+f"(d[46]), "+f"(d[47]),
          "+f"(d[48]), "+f"(d[49]), "+f"(d[50]), "+f"(d[51]), "+f"(d[52]), "+f"(d[53]), "+f"(d[54]), "+f"(d[55]),
          "+f"(d[56]), "+f"(d[57]), "+f"(d[58]), "+f"(d[59]), "+f"(d[60]), "+f"(d[61]), "+f"(d[62]), "+f"(d[63]),
          "+f"(d[64]), "+f"(d[65]), "+f"(d[66]), "+f"(d[67]), "+f"(d[68]), "+f"(d[69]), "+f"(d[70]), "+f"(d[71]),
          "+f"(d[72]), "+f"(d[73]), "+f"(d[74]), "+f"(d[75]), "+f"(d[76]), "+f"(d[77]), "+f"(d[78]), "+f"(d[79]),
          "+f"(d[80]), "+f"(d[81]), "+f"(d[82]), "+f"(d[83]), "+f"(d[84]), "+f"(d[85]), "+f"(d[86]), "+f"(d[87]),
          "+f"(d[88]), "+f"(d[89]), "+f"(d[90]), "+f"(d[91]), "+f"(d[92]), "+f"(d[93]), "+f"(d[94]), "+f"(d[95])
        : "r"(a0), "r"(a1), "r"(a2), "r"(a3), "l"(db));
}

template <int HS>
__device__ __forceinline__ void attn_pair(const uint32_t* q, const uint32_t* k, const uint32_t* v, const uint32_t* kh, const uint32_t* vh,
                                          const float* fu, const float* fn, const float* rk, float bias0, float bias1, uint32_t mU, uint32_t zero, uint32_t* o) {
    float s0[2][4] = {}, s1[2][4] = {}, s2[2][4] = {};
#pragma unroll
    for (int n = 0; n < 4; n++) {
        const int hd = n & 1, a = 8 * hd + 2 * (n & 2);
        mma16816(s1[hd], q[a], q[a + 1], q[a + 2], q[a + 3], k[a], k[a + 2]);
        mma16816(s2[hd], q[a], q[a + 1], q[a + 2], q[a + 3], k[a + 1], k[a + 3]);
    }
#pragma unroll
    for (int n = 0; n < 4; n++) {
        const int hd = n & 1, a = 8 * hd + 2 * (n & 2);
        mma16816(s0[hd], q[a], q[a + 1], q[a + 2], q[a + 3], kh[HS * (a / 2)], kh[HS * (a / 2 + 1)]);
    }
    float e[2][4], m[2][2];
#pragma unroll
    for (int hd = 0; hd < 2; hd++) {
        e[hd][2] = fmaf(s1[hd][2], fu[2], s2[hd][2] * fn[2]); e[hd][3] = fmaf(s1[hd][3], fu[3], s2[hd][3] * fn[3]);
        e[hd][0] = fmaf(s0[hd][0], fu[0], fmaf(s1[hd][0], fn[0], bias0)); e[hd][1] = fmaf(s0[hd][1], fu[1], fmaf(s1[hd][1], fn[1], bias1));
        m[hd][1] = fmaxf(e[hd][2], e[hd][3]); m[hd][0] = fmaxf(e[hd][0], e[hd][1]);
    }
#pragma unroll
    for (int x = 1; x < 3; x++)
#pragma unroll
        for (int n = 0; n < 4; n++) m[n & 1][1 - (n >> 1)] = fmaxf(m[n & 1][1 - (n >> 1)], __shfl_xor_sync(0xffffffffu, m[n & 1][1 - (n >> 1)], x));
    float c[2][4][4] = {};
#pragma unroll
    for (int hd = 0; hd < 2; hd++) {
#pragma unroll
        for (int n = 0; n < 4; n++) e[hd][n] = ex2(e[hd][n] - m[hd][n >> 1]);
        const uint32_t plo = pack_bf16(e[hd][0] * rk[0], e[hd][1] * rk[1]), phi = pack_bf16(e[hd][2] * rk[2], e[hd][3] * rk[3]);
        const uint32_t z0 = plo & zero, z1 = phi & zero;
        const uint32_t a0 = plo & ~mU, a1 = phi & mU, a3 = phi & ~mU, b0 = plo & mU;
#pragma unroll
        for (int jj = 0; jj < 4; jj++) mma16816(c[hd][jj], a0, a1, z0, a3, v[8 * hd + 2 * jj], v[8 * hd + 2 * jj + 1]);
#pragma unroll
        for (int jj = 0; jj < 4; jj++) mma1688(c[hd][jj], b0, z1, vh[HS * (4 * hd + jj)]);
        m[hd][0] = e[hd][0] + e[hd][1]; m[hd][1] = e[hd][2] + e[hd][3];
    }
#pragma unroll
    for (int x = 1; x < 3; x++)
#pragma unroll
        for (int n = 0; n < 4; n++) m[n >> 1][n & 1] += __shfl_xor_sync(0xffffffffu, m[n >> 1][n & 1], x);
#pragma unroll
    for (int hd = 0; hd < 2; hd++) {
        const float i0 = rcp(m[hd][0]), i1 = rcp(m[hd][1]);
#pragma unroll
        for (int jj = 0; jj < 4; jj++) {
            o[8 * hd + 2 * jj] = pack_bf16(c[hd][jj][0] * i0, c[hd][jj][1] * i0);
            o[8 * hd + 2 * jj + 1] = pack_bf16(c[hd][jj][2] * i1, c[hd][jj][3] * i1);
        }
    }
}

__device__ __forceinline__ uint32_t norm_pair(uint32_t u, float m, float rinv) {
    const uint32_t d = pack_bf16(bf_lo(u) - m, bf_hi(u) - m);
    return pack_bf16(bf_lo(d) * rinv, bf_hi(d) * rinv);
}

__global__ void __launch_bounds__(512, 1)
fused_kernel(const __grid_constant__ CUtensorMap mx, const __grid_constant__ CUtensorMap mw, const __grid_constant__ CUtensorMap mwo,
             const __grid_constant__ CUtensorMap mout, const __grid_constant__ CUtensorMap mgu, const __grid_constant__ CUtensorMap mwd,
             const __grid_constant__ CUtensorMap mo,
             const __nv_bfloat16* __restrict__ x, const __nv_bfloat16* __restrict__ wr, Scratch* __restrict__ scr, int swap_gu) {
    extern __shared__ __align__(1024) uint8_t smem[];
    const uint32_t sb = smem_u32(smem);
    const uint32_t bars = sb + OFF_BAR;
    const int tid = threadIdx.x, lane = tid & 31, warp = __shfl_sync(0xffffffffu, tid >> 5, 0);
    const uint32_t sd = (sb & 0x3FFFF) >> 4;
    const int hp = blockIdx.x & 1, cl = blockIdx.x >> 1;
    const int pr = cl < 4 ? 39 + 8 * cl : cl < 36 ? cl - 4 : cl < 64 ? cl - 4 + ((cl - 36) * 37 >> 8) : cl;
    const int b = pr * 2 + hp, mt = pr >> 3, p = pr & 7, nt = 2 * p + hp, rh = p & 1, cb = (p & 6) + hp;
    const int par = mt >> 2, j0 = (mt & 3) * 256;
    int budget = BUDGET;

    TSC(tid == 0, 0);
    auto load_w = [&](int k, int s) {
        const uint32_t full = bars + 8 * (B_WFULL + s);
        mbar_expect_tx(full, W_BYTES);
        tma_3d(sb + OFF_W + s * W_BYTES, &mw, full, nt * 64, k * 64, 0);
    };
    if (elect_one()) {
        const uint32_t cnt = warp < B_WEMPTY / 6 ? 1 : warp < B_G1DONE / 6 ? 2 : warp < B_STAGED / 6 ? 4 : 8;
        if (warp < NBAR / 6) {
#pragma unroll
            for (int i = 0; i < 6; i++) mbar_init(bars + 48 * warp + 8 * i, cnt);
        }
        asm volatile("fence.mbarrier_init.release.cluster;" ::: "memory");
    }
    __syncthreads();

    if (b >= 128) {
        const int hc = b - 128, g = lane >> 2, t = lane & 3;
        if (warp < 12) {
            const int n = warp / 3, part = warp - 3 * n;
            const uint32_t ep = ld_rlx(&scr->epoch[0]) + 1;
            auto load = [&](int k) {
                const uint32_t full = bars + 8 * (2 * n + (k & 1));
                mbar_expect_tx(full, W_BYTES);
                tma_3d(sb + (2 * n + (k & 1)) * W_BYTES, &mw, full, (4 * hc + n) * 64, k * 64, 0);
            };
            if (part == 0 && elect_one()) { load(0); load(1); }
            __syncwarp();
            float c0[4] = {0.f, 0.f, 0.f, 0.f}, c1[4] = {0.f, 0.f, 0.f, 0.f};
            const uint32_t sel = g == 0 ? 0x3f80u : g == 1 ? 0x3f800000u : 0u;
            const uint32_t a = sb + 2 * n * W_BYTES + part * BOX + t * 256 + ((g ^ (2 * t)) << 4);
#pragma unroll 1
            for (int k = 0; k < 16; k++) {
                mbar_wait(bars + 8 * (2 * n + (k & 1)), (k >> 1) & 1, budget);
                uint4 v[8], u[8];
#pragma unroll
                for (int i = 0; i < 8; i++) { v[i] = lds4(a + (k & 1) * W_BYTES + i * 1024); u[i] = lds4(((a + 128) ^ 16) + (k & 1) * W_BYTES + i * 1024); }
#pragma unroll
                for (int i = 0; i < 8; i++) { mma16816(c0, v[i].x, v[i].y, u[i].x, u[i].y, sel, sel); mma16816(c1, v[i].z, v[i].w, u[i].z, u[i].w, sel, sel); }
                bar_sync(1 + n, 96);
                if (part == 0 && k < 14 && elect_one()) load(k + 2);
                __syncwarp();
            }
            if (t == 0) {
#pragma unroll
                for (int r = 0; r < 3; r++) {
                    const uint32_t q0 = pack_bf16(c0[0], c0[1]), q1 = pack_bf16(c0[2], c0[3]), q2 = pack_bf16(c1[0], c1[1]), q3 = pack_bf16(c1[2], c1[3]);
                    st_rlx4(&scr->cs[4 * hc + n][16 + (part * 8 + g) * 32 + r * 4], q0, q1, q2, q3);
                    c0[0] -= bf_lo(q0); c0[1] -= bf_hi(q0); c0[2] -= bf_lo(q1); c0[3] -= bf_hi(q1);
                    c1[0] -= bf_lo(q2); c1[1] -= bf_hi(q2); c1[2] -= bf_lo(q3); c1[3] -= bf_hi(q3);
                }
            }
            bar_sync(7, 384);
            if (tid == 0) { fence_gpu(); st_rlx(&scr->csflag[hc], ep); }
            TSC(tid == 0, 19);
        }
        if (warp < 8) TS_END();
        return;
    }
    asm volatile("barrier.cluster.arrive.relaxed.aligned;" ::: "memory");

    const int kc = b >> 4, c2 = b & 15;
    if (warp >= 12) {
        reg_dec<24>();
        if (warp == 12) {
            if (elect_one()) {
#pragma unroll 1
                for (int n = 0; n < 12; n++) {
                    const int w = n & 1, j = n < 8 ? (n >> 1) + 2 : (n >> 1) - 4;
                    const uint32_t full = bars + 8 * (B_XFULL + w * 6 + j);
                    mbar_expect_tx(full, BOX);
                    tma_4d(sb + w * OFF_X1 + j * BOX, &mx, full, par * 1024 + (n >> 2) * 64, 0, (j0 + w * 128) >> 5, (~n >> 1) & 1);
                    if (n == ROWS_AT) { mbar_expect_tx(bars + 8 * B_ROW, 4 * BOX); bulk_g2s(sb + OFF_FR, x + (size_t)b * 16 * 1024, 4 * BOX, bars + 8 * B_ROW); }
                    if (n == 0 || n == 3 || n == 7) load_w((n + 1) >> 2, n ? n >> 2 : 2);
                }
                int s = 2; uint32_t ph = 0;
#pragma unroll 1
                for (int k = 3; k < 16; k++) {
                    mbar_wait(bars + 8 * (B_WEMPTY + s), ph, budget);
                    load_w(k, s);
                    if (++s == 3) s = 0;
                    if (s == 2) ph ^= 1;
                }
                TS(27);
                s = 1;
#pragma unroll 1
                for (int i = 0; i < 16; i++) {
                    mbar_wait(bars + 8 * (i < 2 ? B_WEMPTY + i : i < 4 ? B_G1DONE : i == 4 ? B_F1DONE : B_WOEMPTY + s), i >= 12, budget);
                    if (i == 2) {
#pragma unroll 1
                        for (int n = 0; n < 4; n++) {
                            const uint32_t f2 = bars + 8 * (B_XT + (n >> 1));
                            if (!(n & 1)) mbar_expect_tx(f2, 2 * BOX);
                            tma_4d(sb + (n >> 1) * OFF_O1 + (3 + (n & 1)) * BOX, &mx, f2, par * 1024 + cb * 128 + (n & 1) * 64, 0, (j0 + rh * 128) >> 5, 1 - (n >> 1));
                        }
                    }
                    const uint32_t full = bars + 8 * (B_WOFULL + s);
                    mbar_expect_tx(full, 2 * BOX);
                    tma_3d(sb + OFF_WO + s * 2 * BOX, &mwo, full, 0, ((2 * p + (i < 2 ? i ^ hp : i)) & 15) * 64, cb * 2);
                    TSC(TIMING % 10 == 4, 48 + i);
                    if (++s == NWO) s = 0;
                }
                TS(25);
            }
        } else {
            bar_sync(8, 224);
            const uint32_t ep = lds1(sb + OFF_EP);
            if (warp == 13) {
                cluster_wait();
                if (elect_one()) {
                    int j = 2, q = 0, left = BUDGET; uint32_t ph = 0;
#pragma unroll 1
                    for (int n = 6; n < 32; n++) {
                        mbar_wait(bars + 8 * (B_XEMPTY + j), ph, left);
                        tma_4d_mc(sb + hp * OFF_X1 + j * BOX, &mx, bars + 8 * (B_XFULL + hp * 6 + j), par * 1024 + (n >> 1) * 64, 0, (j0 + hp * 128) >> 5, ~n & 1);
                        if (++j == 6) j = 0;
                        if (j == 2) ph ^= 1;
                        if ((n == PF_W || n == PF_W + 2) && mt >= 2) tma_pf_3d(&mw, nt * 64, (2 * mt + (n > PF_W)) * 64, 0);
#pragma unroll 1
                        for (; q < (PF_RATE * (n - PF_START) >> 3); q++) {
                            if (q < 16) { if (b < 112) tma_pf_3d(&mgu, b * 32, q * 64, 0); }
                            else if (q == 16) tma_pf_3d(&mwo, 0, (b >> 3) * 64, (b & 7) * 2);
                            else if (q < 24) tma_pf_3d(&mwd, 0, kc * 448 + (q - 17) * 64, c2);
                        }
                    }
                }
                __syncwarp();
                uint32_t* hs = &scr->halo[b - 16][lane * 4];
                int tries = BUDGET;
#pragma unroll 1
                for (int c = 0; c < 4; c += 2) {
                    uint4 v0 = make_uint4(0, 0, 0, 0), v1 = v0;
                    if (j0) {
#pragma unroll 1
                        do { v0 = ld_rlx4(hs + c * 128); v1 = ld_rlx4(hs + c * 128 + 128); } while ((v0.x == 0 || v1.x == 0) && --tries > 0);
                        st_rlx(hs + c * 128, 0); st_rlx(hs + c * 128 + 128, 0);
                    }
                    __syncwarp();
                    stsm4(sb + OFF_HIN + c * 512 + lane * 16, v0.x, v0.y, v0.z, v0.w);
                    stsm4(sb + OFF_HIN + c * 512 + 512 + lane * 16, v1.x, v1.y, v1.z, v1.w);
                }
                bar_arrive(11, 64);
                TSC(lane == 0, 31);
                const int src = ((mt * 2 + rh) * 2 + 1 - hp) * 1024;
                if (elect_one()) {
                    const uint32_t* fl = &scr->oflag[mt * 2 + 1 - hp][0];
                    const uint32_t inv = (ep & 1) - 1;
                    uint32_t ready = 0, ph = 0;
                    int s = 2;
#pragma unroll 1
                    for (int i = 2; i < 16; i++) {
                        const int kb = (2 * p + i) & 15;
#pragma unroll 1
                        while (!((ready >> kb) & 1) && --budget > 0) { ready = ld_acq(fl) ^ inv; fence_async_gmem(); }
                        TSC(i == 2, 30);
                        mbar_wait(bars + 8 * (B_OEMPTY + s), ph, budget);
                        tma_2d_mc(sb + hp * OFF_O1 + s * BOX, &mo, bars + 8 * (B_OFULL + hp * NO + s), 0, src + kb * 64);
                        TSC(TIMING % 10 == 4 && hp == 0, 32 + i);
                        if (++s == NO) s = 0;
                        if (s == 2) ph ^= 1;
                    }
                }
            } else if (warp == 14) {
#pragma unroll 1
                for (int f = b < 112 ? 0 : 1; f < 2; f++) {
                    const int n = f ? 7 : 16, ns = f ? 3 : NF1;
                    const uint32_t* act = f ? scr->h + kc * 7 * 256 : scr->xsel;
#pragma unroll 1
                    for (int r = 0; r < 2; r++) {
                        const int ne = (EARLY_W >> f) & 1 ? ns : 0;
                        if (r) { poll_all(f ? &scr->fflag[kc * 14 + min(lane, 13)][0] : &scr->sel[lane & 7], f ? ~0u : 31u, f ? ep : ep & 31, budget); TSC(lane == 0, f ? 29 : 26); }
                        if (elect_one()) {
                            fence_async_gmem();
                            int s = f, left = BUDGET; uint32_t ph = f && b < 112 ? F1_PHASES : 0;
#pragma unroll 1
                            for (int q = 0; q < (r ? n : ne); q++) {
                                const uint32_t full = bars + 8 * (B_FFULL + s), dst = sb + fslot(s);
                                if (q >= r * ne) {
                                    mbar_wait(bars + 8 * (B_FEMPTY + s), (ph >> s) & 1, left);
                                    mbar_expect_tx(full, F_BYTES);
                                    tma_3d(dst, f ? &mwd : &mgu, full, f ? 0 : b * 32, (f ? kc * 7 + q : q) * 64, f ? c2 : 0);
                                }
                                if (r) bulk_g2s(dst + BOX, act + q * 256, 1024, full);
                                ph ^= 1u << s;
                                if (++s == ns) s = 0;
                            }
                        }
                        __syncwarp();
                    }
                }
            } else {
                mbar_wait(bars + 8 * B_FEMPTY, 0, budget);
                int tries = BUDGET;
#pragma unroll 1
                for (int i = lane; i < 264; i += 32) {
                    const int j = j0 - 8 + i;
                    uint2 v = make_uint2(0x7f800000u, 0);
                    if (j >= 0) {
#pragma unroll 1
                        do { v = ld_rlx2(&scr->row[2 * j + par]); } while (((v.y ^ ep) & 31) && --tries > 0);
                    }
                    sts2(sb + OFF_STAT + i * 8, __float_as_uint(-bf_lo(v.x)), __float_as_uint(rcp(bf_hi(v.x))));
                }
                __syncwarp();
                poll_all(&scr->csflag[lane & 3], ~0u, ep, budget);
                if (elect_one()) {
                    fence_async_gmem();
                    mbar_expect_tx(bars + 8 * B_AUX, CS_BYTES);
                    bulk_g2s(sb + OFF_CS, scr->cs[nt], CS_BYTES, bars + 8 * B_AUX);
                    TS(21);
#pragma unroll 1
                    for (int v = 0; v < 2; v++) {
                        const uint32_t ring = sb + v * OFF_O1, fb = bars + 8 * (B_OFULL + v * NO);
                        mbar_expect_tx(fb + 8, BOX);
                        mbar_wait(bars + 8 * B_G1DONE, 0, budget);
                        mbar_wait(bars + 8 * (B_STAGED + v), 0, budget);
                        TS(12 + 2 * v);
                        mbar_arrive(fb);
                        bulk_s2c(mapa(ring + BOX, hp ^ 1), ring, BOX, mapa(fb + 8, hp ^ 1));
                        fence_gpu();
                        asm volatile("red.relaxed.gpu.global.xor.b32 [%0], %1;" ::"l"(&scr->oflag[mt * 2 + 1 - v][0]), "r"(1u << nt) : "memory");
                        TS(13 + 2 * v);
                    }
                }
            }
        }
    } else if (warp >= 8) {
        reg_dec<40>();
        const int wq = warp - 8, ta = tid - 256, g = lane >> 2, t = lane & 3;
        const uint32_t rbuf = sb + OFF_FR + wq * BOX, rbar = bars + 8 * B_ROW;
        const uint4 wv = ldg_nc(wr + ta * 8);
        if (ta == 0) sts1(sb + OFF_EP, ld_rlx(&scr->epoch[0]) + 1);
        sts4(sb + OFF_STAT + ta * 16, wv.x, wv.y, wv.z, wv.w);
        bar_sync(8, 224);
        const uint32_t ep = lds1(sb + OFF_EP);
        {
            const int s = b * 16 + wq * 4 + (lane >> 3);
            if ((lane & 7) == 0) st_rlx2(&scr->row[s], 0, ep - 1);
            if (ta < 2) st_rlx4(&scr->fflag[b][ta * 4], ep - 1, ep - 1, 0, 0);
            float sw = 0.f;
#pragma unroll 1
            for (int i = 0; i < 16; i++) { const uint32_t q = lds1(sb + OFF_STAT + i * 128 + lane * 4); sw += bf_lo(q) + bf_hi(q); }
#pragma unroll 1
            for (int o = 16; o > 0; o >>= 1) sw += __shfl_xor_sync(0xffffffffu, sw, o);
            float s1 = 0.f, s2 = 0.f, sr = 0.f;
            const uint32_t xa = rbuf + (lane >> 3) * 2048 + (lane & 7) * 16, wa = sb + OFF_STAT + (lane & 7) * 16;
            mbar_wait(rbar, 0, budget);
            TSC(ta == 0, 17);
            uint4 u = lds4(xa), w4 = lds4(wa);
#pragma unroll kStatsUnroll
            for (int i = 1; i <= 16; i++) {
                const uint32_t o = (i * 128) & 2047;
                const uint4 un = lds4(xa + o), wn = lds4(wa + o);
#pragma unroll
                for (int c = 0; c < 4; c++) {
                    const float a0 = bf_lo((&u.x)[c]), a1 = bf_hi((&u.x)[c]);
                    s1 += a0; s2 = fmaf(a0, a0, s2); sr = fmaf(a0, bf_lo((&w4.x)[c]), sr);
                    s1 += a1; s2 = fmaf(a1, a1, s2); sr = fmaf(a1, bf_hi((&w4.x)[c]), sr);
                }
                u = un; w4 = wn;
            }
#pragma unroll 1
            for (int o = 1; o < 8; o <<= 1) {
                s1 += __shfl_xor_sync(0xffffffffu, s1, o); s2 += __shfl_xor_sync(0xffffffffu, s2, o); sr += __shfl_xor_sync(0xffffffffu, sr, o);
            }
            const float mean = s1 * (1.f / 1024.f), mb = bf16r(mean);
            float var = fmaf(-mean, mean, s2 * (1.f / 1024.f));
            sr = fmaf(-mb, sw, sr);
            if (__builtin_expect(__any_sync(0xffffffffu, mean * mean > 256.f * var), 0)) {
                float a2 = 0.f, ar = 0.f;
#pragma unroll 1
                for (int i = 0; i < 64; i++) {
                    const uint32_t o = (i >> 2) * 128 + (i & 3) * 4, q1 = lds1(xa + o), q2 = lds1(wa + o);
                    a2 = fmaf(bf_lo(q1) - mean, bf_lo(q1) - mean, fmaf(bf_hi(q1) - mean, bf_hi(q1) - mean, a2));
                    ar = fmaf(bf_lo(q1) - mb, bf_lo(q2), fmaf(bf_hi(q1) - mb, bf_hi(q2), ar));
                }
#pragma unroll 1
                for (int o = 1; o < 8; o <<= 1) { a2 += __shfl_xor_sync(0xffffffffu, a2, o); ar += __shfl_xor_sync(0xffffffffu, ar, o); }
                var = a2 * (1.f / 1024.f); sr = ar;
            }
            float den;
            asm("sqrt.approx.f32 %0, %1;" : "=f"(den) : "f"(bf16r(bf16r(var) + 1e-5f)));
            const uint32_t st = pack_bf16(mb, den);
            const uint32_t rb = pack_bf16(0.f, sr * rcp(bf_hi(st)) + 0.f);
            uint32_t ord = (int)rb < 0 ? ~rb & 0xffff0000u : rb | 0x80000000u;
            if ((rb & 0x7fffffffu) > 0x7f800000u) ord = 0;
            if ((lane & 7) == 0) st_rlx2(&scr->row[s], st, ord | ((2047 - s) << 5) | (ep & 31));
            __syncwarp();
            if (lane < 5) mbar_arrive(bars + 8 * (B_FEMPTY + lane));
        }
        TSC(ta == 0, 18);
        if ((b >> 3) == 14) {
            const uint32_t gm = sb + OFF_E, cnt = gm + 64, res = gm + 80, list = gm + 128;
            uint32_t kv[16];
            int tries = BUDGET;
#pragma unroll 1
            do {
                uint32_t bad = 0;
#pragma unroll
                for (int n = 0; n < 16; n++) kv[n] = ld_rlx(&scr->row[n * 128 + ta].y);
#pragma unroll
                for (int n = 0; n < 16; n++) bad |= kv[n] ^ ep;
                if ((bad & 31) == 0) break;
            } while (--tries > 0);
            __syncwarp();
            TSC(ta == 0, 26);
            uint32_t m = 0;
#pragma unroll
            for (int n = 0; n < 16; n++) m = max(m, kv[n]);
            uint32_t gmax = m;
#pragma unroll
            for (int o = 1; o < 8; o <<= 1) gmax = max(gmax, __shfl_xor_sync(0xffffffffu, gmax, o));
            sts1(gm + (ta >> 3) * 4, gmax);
            sts1(cnt, 0);
            bar_sync(12, 128);
            const uint32_t c = lds1(gm + (lane & 15) * 4);
            int rank = 0;
#pragma unroll
            for (int i = 0; i < 2; i++) { const uint4 q = lds4(gm + (lane >> 4) * 32 + i * 16); rank += (q.x > c) + (q.y > c) + (q.z > c) + (q.w > c); }
            rank += __shfl_xor_sync(0xffffffffu, rank, 16);
            const uint32_t thr = redux_max(rank == 7 ? c : 0u);
#pragma unroll 1
            while (m >= thr) {
                uint32_t at, m2 = 0;
                asm volatile("atom.shared.add.u32 %0, [%1], 1;" : "=r"(at) : "r"(cnt) : "memory");
#pragma unroll
                for (int n = 0; n < 16; n++) m2 = max(m2, kv[n] < m ? kv[n] : 0u);
                sts1(list + at * 4, m);
                if (m2 == 0) break;
                m = m2;
            }
            bar_sync(12, 128);
            const int nc = lds1(cnt);
#pragma unroll 1
            for (int i = ta >> 3; i < ((nc + 3) & ~3); i += 16) {
                const uint32_t ki = lds1(list + i * 4);
                int r = 0;
#pragma unroll 1
                for (int n = lane & 7; n < nc; n += 8) r += lds1(list + n * 4) > ki;
                __syncwarp();
#pragma unroll
                for (int o = 1; o < 8; o <<= 1) r += __shfl_xor_sync(0xffffffffu, r, o);
                if (r == (b & 7) && i < nc) sts1(res, ki);
            }
            bar_sync(12, 128);
            const uint32_t k0 = lds1(res);
            const int r0 = 2047 - ((k0 >> 5) & 2047);
            TSC(ta == 0, 22);
            const uint4 v0 = ldg_nc(x + (size_t)r0 * 1024 + ta * 8);
            const uint32_t s0 = ld_rlx(&scr->row[r0]);
            const float m0 = bf_lo(s0), i0 = rcp(bf_hi(s0));
            st_rlx4(&scr->xsel[(ta >> 3) * 256 + (b & 7) * 32 + ((ta ^ b) & 7) * 4], norm_pair(v0.x, m0, i0), norm_pair(v0.y, m0, i0), norm_pair(v0.z, m0, i0), norm_pair(v0.w, m0, i0));
            bar_sync(12, 128);
            if (ta == 0) { fence_gpu(); st_rlx(&scr->sel[b & 7], k0); }
        }
        {
            uint32_t fph = 0;
            if (b >= 112 && ta == 0) mbar_arrive(bars + 8 * B_F1DONE);
#pragma unroll 1
            for (int ph = b < 112 ? 0 : 1; ph < 2; ph++) {
                float acc[4] = {0.f, 0.f, 0.f, 0.f};
                const uint32_t alo = sd + (ph ? dlo(0, 8192) : dlo(0, 4096)), ahi = ph ? dhi(1024, 1) : dhi(512, 2), astep = ph ? 128 : 64;
                const uint32_t bhi = ph ? dhi(128, 0) : dhi(1024, 1), bstep = ph ? 16 : 2;
                const int ns = ph ? 3 : NF1;
                int s = ph, ps = -1;
                if (ph) mbar_wait(bars + 8 * (B_STAGED + 1), 0, budget);
#pragma unroll 1
                for (int q = ph ? 7 : 16; q > 0; q--) {
                    const uint32_t so = fslot(s) >> 4, da = alo + so, db = sd + dlo(BOX, 128) + so;
                    mbar_wait(bars + 8 * (B_FFULL + s), (fph >> s) & 1, budget);
                    TSC(TIMING % 10 == 3 && ta == 0, 32 + (ph ? 23 : 16) - q);
                    wg_fence();
#pragma unroll
                    for (int j = 0; j < 4; j++) wgmma_n8<1, 0>(acc, mkdesc(da + j * astep, ahi), mkdesc(db + j * bstep, bhi), 1);
                    wg_commit();
                    wg_wait<FFN_DEPTH>();
                    if (!FFN_DEPTH) ps = s;
                    if (lane == 0 && ps >= 0) mbar_arrive(bars + 8 * (B_FEMPTY + ps));
                    ps = s;
                    fph ^= 1u << s;
                    if (++s == ns) s = 0;
                }
                wg_wait<0>();
                if (FFN_DEPTH && lane == 0) mbar_arrive(bars + 8 * (B_FEMPTY + ps));
                if (ph == 0) {
                    const bool second = (wq >= 2) != (swap_gu != 0);
                    const uint32_t xa = sb + OFF_UPD + ((wq & 1) * 32 + lane) * 16;
                    if (second) sts4(xa, __float_as_uint(acc[0]), __float_as_uint(acc[1]), __float_as_uint(acc[2]), __float_as_uint(acc[3]));
                    bar_sync(12, 128);
                    if (ta == 0) mbar_arrive(bars + 8 * B_F1DONE);
                    if (!second) {
                        const float4 up = lds4f(xa);
                        float hv[4];
#pragma unroll
                        for (int c = 0; c < 4; c++) { const float ga = bf16r(acc[c]); hv[c] = bf16r(ga * sigmoidf(ga)) * bf16r((&up.x)[c]); }
                        uint32_t* hd = &scr->h[(b * 4 + (wq & 1) * 2) * 32 + lane];
                        st_rlx(hd, movm(pack_bf16(hv[0], hv[1]))); st_rlx(hd + 32, movm(pack_bf16(hv[2], hv[3])));
                    }
                } else {
#pragma unroll
                    for (int c = 0; c < 4; c++) st_rlx(&scr->ypart[kc][2 * t + (c & 1)][c2 * 64 + wq * 16 + (c >> 1) * 8 + g], __float_as_uint(acc[c]));
                }
                bar_sync(12, 128);
                if (ta == 0) {
                    fence_gpu(); st_rlx(&scr->fflag[b][ph], ep);
                    if (ph > b) st_rlx(&scr->epoch[0], ep);
                }
                TSC(ta == 0, 22 + ph);
            }
        }
#pragma unroll 1
        for (int j = wq; j < 8; j += 4) {
            const uint32_t kj = ld_rlx(&scr->sel[j]);
            const int row = 2047 - ((kj >> 5) & 2047), jj = (row & 1) == par ? (row >> 1) - j0 : -1;
            float4 a = make_float4(0.f, 0.f, 0.f, 0.f);
            if ((jj >> 7) == rh) {
                poll_all(&scr->fflag[(lane & 7) * 16 + cb * 2 + (lane >> 4)][1], ~0u, ep, budget);
#pragma unroll 4
                for (int m = 0; m < 8; m++) {
                    const uint4 v = ld_rlx4(&scr->ypart[m][j][cb * 128 + lane * 4]);
                    a.x += __uint_as_float(v.x); a.y += __uint_as_float(v.y); a.z += __uint_as_float(v.z); a.w += __uint_as_float(v.w);
                }
            }
            const float sig = bf16r(sigmoidf(__uint_as_float(((int)kj < 0 ? kj & 0x7fffffffu : ~kj) & 0xffff0000u)));
            sts2(sb + OFF_UPD + (lane >> 4) * 1024 + j * 128 + ((((lane >> 1) & 7) ^ j) << 4) + (lane & 1) * 8,
                 pack_bf16(bf16r(a.x) * sig, bf16r(a.y) * sig), pack_bf16(bf16r(a.z) * sig, bf16r(a.w) * sig));
            sts1(sb + OFF_SEL + j * 4, jj);
        }
        fence_async_smem();
        __syncwarp();
        if (lane < 2) mbar_arrive(bars + 8 * B_UPD);
        TSC(ta == 0, 24);
    } else {
        reg_inc<224>();
        const int w = warp >> 2, wi = warp & 3, g = lane >> 2, t = lane & 3;
        const bool elect = (tid & 127) == 0;
        const uint32_t mad = (lane & 15) * 128 + (((lane >> 4) ^ (lane & 7)) << 4);
        {
            float acc0[96], acc1[96];
            const uint32_t sta = sb + OFF_STAT + (8 + w * 128 + wi * 32) * 8;
            {
                const uint32_t xfull = bars + 8 * (B_XFULL + w * 6), xempty = mapa(bars + 8 * B_XEMPTY, w), dx0 = sd + dlo(w * OFF_X1, 16);
                int j = 2, pj = 0, ws = 2, pws = 0; uint32_t xph = 0;
                cluster_wait();
#pragma unroll 1
                for (int k = 0; k < 16; k++) {
                    const uint32_t dx = dx0 + j * (BOX >> 4), dw = sd + dlo(OFF_W, BOX) + ws * (W_BYTES >> 4);
                    mbar_wait(bars + 8 * (B_WFULL + ws), xph, budget);
                    mbar_wait(xfull + 8 * j, xph, budget);
                    TSC(elect && k == 0, 1 + 8 * w);
                    TSC(TIMING % 10 == 1 && tid == 0, 32 + k);
                    if (!G1_DEPTH) wg_wait<0>();
                    wg_fence();
#pragma unroll
                    for (int kk = 0; kk < 4; kk++) wgmma_n192<0, 1>(acc1, mkdesc(dx + kk * 2, dhi(1024, 1)), mkdesc(dw + kk * 128, dhi(1024, 1)), kk ? 1 : k);
                    wg_commit();
                    if (G1_DEPTH) wg_wait<1>();
                    if (elect && k > 0) {
                        mbar_arrive(bars + 8 * (B_WEMPTY + pws));
                        if (k <= 13) { mbar_expect_tx(xfull + 8 * pj, BOX); mbar_arrive_at(xempty + 8 * pj); }
                    }
                    if (k == 15) {
                        mbar_wait(bars + 8 * B_AUX, 0, budget);
                        const uint32_t pm = t & 1 ? 0x4432 : 0x3232, ra = sta + ((t >> 1) * 16 + g) * 8, zero = budget >> 30;
                        const uint32_t a0 = __byte_perm(lds1(ra), 0, pm), a1 = __byte_perm(lds1(ra + 64), 0, pm), a2 = a0 & zero, a3 = a1 & zero;
                        wg_fence();
                        wgmma_rs_n192(acc1, a0, a1, a2, a3, mkdesc(sd + dlo(OFF_CS, 0), dhi(128, 0)));
                        wgmma_rs_n192(acc0, a0, a1, a2, a3, mkdesc(sd + dlo(OFF_CS + 64, 0), dhi(128, 0)));
                        wg_commit();
                    }
                    mbar_wait(xfull + 8 * j + 8, xph, budget);
                    if (!G1_DEPTH) wg_wait<0>();
                    wg_fence();
#pragma unroll
                    for (int kk = 0; kk < 4; kk++) wgmma_n192<0, 1>(acc0, mkdesc(dx + 512 + kk * 2, dhi(1024, 1)), mkdesc(dw + kk * 128, dhi(1024, 1)), kk ? 1 : k);
                    wg_commit();
                    if (G1_DEPTH) wg_wait<1>();
                    if (elect && k <= 12) { mbar_expect_tx(xfull + 8 * j, BOX); mbar_arrive_at(xempty + 8 * j); }
                    pj = j + 1; pws = ws;
                    if (++ws == 3) ws = 0;
                    j += 2;
                    if (j == 6) j = 0;
                    if (j == 2) xph ^= 1;
                }
            }
            TSC(elect, 19 + w);
            uint32_t pk0[48], pk1[48], o[16];
#pragma unroll
            for (int j = 17; j < 48; j += 2) pk1[j] = pack_here(acc1[2 * j], acc1[2 * j + 1]);
            if (warp < 7) {
#pragma unroll
                for (int c = 0; c < 4; c++) stsm4(sb + (w ? OFF_H1 : OFF_H0) + wi * 2048 + c * 512 + lane * 16, pk1[17 + 8 * c], pk1[19 + 8 * c], pk1[21 + 8 * c], pk1[23 + 8 * c]);
                bar_arrive(1 + warp, 64);
            } else if (j0 != 768) {
#pragma unroll
                for (int c = 0; c < 4; c++) {
                    pk1[17 + 8 * c] = max(pk1[17 + 8 * c], 1u);
                    st_rlx4(&scr->halo[b][c * 128 + lane * 4], pk1[17 + 8 * c], pk1[19 + 8 * c], pk1[21 + 8 * c], pk1[23 + 8 * c]);
                }
            }
            TSC(tid == 224, 28);
#pragma unroll
            for (int j = 0; j < 48; j++) if (j < 16 || !(j & 1)) pk1[j] = pack_here(acc1[2 * j], acc1[2 * j + 1]);
            const bool u0 = 2 * t > g, u1 = 2 * t + 1 > g;
            uint32_t mU = (u0 ? 0xffffu : 0u) | (u1 ? 0xffff0000u : 0u), zero = budget >> 30;
            const uint32_t ka0 = sta + (2 * t - (u0 ? 8 : 0)) * 8 + 4, ka1 = sta + (2 * t + 1 - (u1 ? 8 : 0)) * 8 + 4;
            float rk[4], fu[4], fn[4];
            auto factors = [&](int h) {
#pragma unroll
                for (int e = 0; e < 2; e++) {
                    const float rq = lds1f(sta + (16 * h + 8 * e + g) * 8 + 4) * (0.17677669529663687f * 1.4426950408889634f);
                    rk[2 * e] = lds1f(ka0 + h * 128 + e * 64); rk[2 * e + 1] = lds1f(ka1 + h * 128 + e * 64);
                    const float f0 = rq * rk[2 * e], f1 = rq * rk[2 * e + 1];
                    fu[2 * e] = u0 ? f0 : 0.f; fn[2 * e] = f0 - fu[2 * e]; fu[2 * e + 1] = u1 ? f1 : 0.f; fn[2 * e + 1] = f1 - fu[2 * e + 1];
                }
            };
            factors(1);
#pragma unroll
            for (int n = 0; n < 4; n++) asm volatile("" : "+f"(fu[n]), "+f"(fn[n]));
            uint8_t* og = scr->o + ((size_t)(mt * 4 + w * 2) * 16 + nt) * BOX + wi * 256 + lane * 4;
            const uint32_t od = sb + wi * 256 + (lane >> 4) * 1024 + (lane & 15) * 16, g1peer = mapa(bars + 8 * B_G1DONE, hp ^ 1);
            asm volatile("" : "+l"(og), "+r"(mU));
            mbar_wait(bars + 8 * B_AUX, 0, budget);
            wg_wait<0>();
            bar_arrive(13 + w, 256);
            if (elect) { mbar_arrive(bars + 8 * B_G1DONE); mbar_arrive_at(g1peer); }
            TSC(elect, 2 + 8 * w);
            auto hand_over = [&](int v) {
#pragma unroll
                for (int i = 0; i < 16; i++) st_rlx(og + (1 - v) * 16 * BOX + (i >> 1) * 1024 + (i & 1) * 128, o[i]);
                if (v == 0) bar_sync(14 - w, 256);
                if (w == rh) {
#pragma unroll
                    for (int c = 0; c < 4; c++) stsm4(od + v * OFF_O1 + c * 2048, o[4 * c], o[4 * c + 1], o[4 * c + 2], o[4 * c + 3]);
                    fence_async_smem();
                }
                __syncwarp();
                if (lane == 0) mbar_arrive(bars + 8 * (B_STAGED + v));
            };
#pragma unroll
            for (int j = 17; j < 48; j += 2) pk0[j] = pack_here(acc0[2 * j], acc0[2 * j + 1]);
#pragma unroll
            for (int j = 32; j < 48; j++) pk1[j] = movm(pk1[j]);
#pragma unroll
            for (int j = 33; j < 48; j += 2) pk0[j] = movm(pk0[j]);
            attn_pair<2>(pk1, pk1 + 16, pk1 + 32, pk0 + 17, pk0 + 33, fu, fn, rk, 0.f, 0.f, mU, zero, o);
            hand_over(0);
            TSC(elect, 3 + 8 * w);
#pragma unroll
            for (int j = 0; j < 48; j++) if (j < 16 || !(j & 1)) pk0[j] = pack_here(acc0[2 * j], acc0[2 * j + 1]);
#pragma unroll
            for (int j = 32; j < 48; j += 2) pk0[j] = movm(pk0[j]);
            factors(0);
            const bool first = warp == 0 && j0 == 0;
            const float bias0 = first && u0 ? -INFINITY : 0.f, bias1 = first && u1 ? -INFINITY : 0.f;
            bar_sync(warp ? warp : 11, 64);
            uint32_t hl[16];
            const uint32_t ha = sb + (warp == 0 ? OFF_HIN : warp <= 4 ? OFF_H0 - 2048 : OFF_H1 - 5 * 2048) + warp * 2048 + lane * 16;
            ldsm4(hl, ha); ldsm4(hl + 4, ha + 512); ldsm4t(hl + 8, ha + 1024); ldsm4t(hl + 12, ha + 1536);
            attn_pair<1>(pk0, pk0 + 16, pk0 + 32, hl, hl + 8, fu, fn, rk, bias0, bias1, mU, zero, o);
            hand_over(1);
        }
        TSC(tid == 0, 4);
        float acc[64];
        const uint32_t ring = sb + w * OFF_O1, ofull = bars + 8 * (B_OFULL + w * NO), oempty = mapa(bars + 8 * B_OEMPTY, w);
        const int r0 = rh * 128 + wi * 32 + (1 - w) * 16 + g;
        {
            const float2 s0 = lds2f(sb + OFF_STAT + (8 + r0) * 8), s1 = lds2f(sb + OFF_STAT + (16 + r0) * 8);
            const float m0 = s0.x * s0.y, f0 = 1.f + s0.y, m1 = s1.x * s1.y, f1 = 1.f + s1.y;
            mbar_wait(bars + 8 * (B_XT + w), 0, budget);
#pragma unroll
            for (int j = 0; j < 8; j++) {
                uint32_t a0, a1, a2, a3;
                asm volatile("ldmatrix.sync.aligned.m8n8.x4.shared.b16 {%0,%1,%2,%3}, [%4];" : "=r"(a0), "=r"(a1), "=r"(a2), "=r"(a3)
                             : "r"(((ring + wi * 2048 + mad) ^ ((j & 3) * 32)) + (3 + (j >> 2)) * BOX) : "memory");
                acc[8 * j + 0] = fmaf(bf_lo(a0), f0, m0); acc[8 * j + 1] = fmaf(bf_hi(a0), f0, m0);
                acc[8 * j + 2] = fmaf(bf_lo(a1), f1, m1); acc[8 * j + 3] = fmaf(bf_hi(a1), f1, m1);
                acc[8 * j + 4] = fmaf(bf_lo(a2), f0, m0); acc[8 * j + 5] = fmaf(bf_hi(a2), f0, m0);
                acc[8 * j + 6] = fmaf(bf_lo(a3), f1, m1); acc[8 * j + 7] = fmaf(bf_hi(a3), f1, m1);
            }
        }
        bar_sync(9 + w, 128);
        if (elect) {
            mbar_arrive(bars + 8 * (B_WOEMPTY + 6)); mbar_arrive(bars + 8 * B_WOEMPTY);
#pragma unroll
            for (int i = 16; i < 40; i += 8) { mbar_expect_tx(ofull + i, BOX); mbar_arrive_at(oempty + i); }
        }
        TSC(tid == 0, 5);
        {
            const uint32_t da0 = sd + dlo(w * OFF_O1, 1024);
            int os = 0, ws = 1, pos = 0, pws = 0; uint32_t oph = 0, wph = 0;
#pragma unroll 1
            for (int i = 0; i < 16; i++) {
                const uint32_t da = da0 + os * (BOX >> 4), db = sd + dlo(OFF_WO, BOX) + ws * (2 * BOX >> 4);
                mbar_wait(bars + 8 * (B_WOFULL + ws), wph, budget);
                mbar_wait(ofull + 8 * os, oph, budget);
                TSC(TIMING % 10 == 1 && tid == 0, 48 + i);
                TSC(TIMING % 10 == 2 && elect, 32 + w * 16 + i);
                wg_fence();
#pragma unroll
                for (int kk = 0; kk < 4; kk++) wgmma_n128<0, 1>(acc, mkdesc(da + kk * 128, dhi(128, 0)), mkdesc(db + kk * 128, dhi(1024, 1)), 1);
                wg_commit();
                wg_wait<1>();
                if (elect && i > 0 && i <= 11) {
                    mbar_expect_tx(ofull + 8 * pos, BOX); mbar_arrive_at(oempty + 8 * pos);
                    if (i <= 9) mbar_arrive(bars + 8 * (B_WOEMPTY + pws));
                }
                pos = os; pws = ws;
                if (++os == NO) { os = 0; oph ^= 1; }
                if (++ws == NWO) ws = 0;
                if (ws == 1) wph ^= 1;
            }
            mbar_wait(bars + 8 * B_UPD, 0, budget);
            const float2 sl = lds2f(sb + OFF_SEL + t * 8);
            const int d0 = __float_as_int(sl.x) - r0, d1 = __float_as_int(sl.y) - r0;
            const uint32_t a0 = (d0 == 0 ? 0x3f80u : 0u) | (d1 == 0 ? 0x3f800000u : 0u), a1 = (d0 == 8 ? 0x3f80u : 0u) | (d1 == 8 ? 0x3f800000u : 0u);
            wg_fence();
            wgmma_rs_n128(acc, a0, a1, 0u, 0u, mkdesc(sd + dlo(OFF_UPD, 1024), dhi(0, 1)));
            wg_commit();
            wg_wait<0>();
            TSC(elect, 7 + 9 * w);
            const uint32_t os0 = ring + BOX + wi * 4096;
#pragma unroll
            for (int j = 0; j < 8; j++)
                stsm4(((os0 + mad) ^ ((j & 3) * 32)) + (j >> 2) * 2048, pack_bf16(acc[8 * j], acc[8 * j + 1]), pack_bf16(acc[8 * j + 2], acc[8 * j + 3]),
                      pack_bf16(acc[8 * j + 4], acc[8 * j + 5]), pack_bf16(acc[8 * j + 6], acc[8 * j + 7]));
            fence_async_smem();
            __syncwarp();
            if (elect_one()) {
                asm volatile("cp.async.bulk.tensor.5d.global.shared::cta.bulk_group [%0, {%2, %2, %3, %4, %5}], [%1];\ncp.async.bulk.commit_group;\ncp.async.bulk.wait_group.read 0;"
                             ::"l"(&mout), "r"(os0), "r"(0), "r"(((j0 + rh * 128) >> 5) + wi), "r"(1 - w), "r"(par * 16 + cb * 2) : "memory");
            }
            TSC(elect, 8 - 2 * w);
            TS_END();
        }
    }
}

typedef CUresult (*EncodeFn)(CUtensorMap*, CUtensorMapDataType, cuuint32_t, void*, const cuuint64_t*, const cuuint64_t*, const cuuint32_t*,
                             const cuuint32_t*, CUtensorMapInterleave, CUtensorMapSwizzle, CUtensorMapL2promotion, CUtensorMapFloatOOBfill);

CUtensorMap make_map(EncodeFn fn, const void* base, int rank, const cuuint64_t* dims, const cuuint64_t* strides, const cuuint32_t* box,
                     CUtensorMapSwizzle swz = CU_TENSOR_MAP_SWIZZLE_128B, CUtensorMapL2promotion pro = CU_TENSOR_MAP_L2_PROMOTION_L2_256B) {
    CUtensorMap m;
    cuuint32_t es[5] = {1, 1, 1, 1, 1};
    fn(&m, CU_TENSOR_MAP_DATA_TYPE_BFLOAT16, rank, (void*)base, dims, strides, box, es, CU_TENSOR_MAP_INTERLEAVE_NONE,
       swz, pro, CU_TENSOR_MAP_FLOAT_OOB_FILL_NONE);
    return m;
}

}

extern "C" void kernel_launch(void* const* d_in, const int* in_sizes, int n_in, void* d_out, int out_size) {
    (void)in_sizes; (void)n_in; (void)out_size;
    const __nv_bfloat16* x = (const __nv_bfloat16*)d_in[0];
    const __nv_bfloat16* wqkv = (const __nv_bfloat16*)d_in[1];
    const __nv_bfloat16* wo = (const __nv_bfloat16*)d_in[2];
    const __nv_bfloat16* wr = (const __nv_bfloat16*)d_in[4];
    const __nv_bfloat16* wg = (const __nv_bfloat16*)d_in[5];
    const __nv_bfloat16* wu = (const __nv_bfloat16*)d_in[6];
    const __nv_bfloat16* wd = (const __nv_bfloat16*)d_in[7];
    static EncodeFn fn = nullptr;
    static Scratch* scr = nullptr;
    if (!fn) {
        void* p = nullptr; cudaDriverEntryPointQueryResult q;
        cudaGetDriverEntryPoint("cuTensorMapEncodeTiled", &p, cudaEnableDefault, &q);
        fn = (EncodeFn)p;
        cudaFuncSetAttribute(fused_kernel, cudaFuncAttributeMaxDynamicSharedMemorySize, SMEM_LAUNCH);
        cudaGetSymbolAddress((void**)&scr, g_scr);
    }
    const cuuint64_t xd[4] = {2048, 16, 32, 2}, xs[4] = {4096, 131072, 65536, 128}, od[5] = {64, 16, 32, 2, 32};
    const cuuint32_t xb[4] = {64, 16, 4, 1}, ob[5] = {64, 16, 1, 1, 2};
    const cuuint64_t wdm[3] = {1024, 1024, 3}, wst[2] = {6144, 2048};
    const cuuint32_t wb[3] = {64, 64, 3};
    const cuuint64_t wod[3] = {64, 1024, 16}, wdd[3] = {64, 3584, 16}, wos[2] = {2048, 128};
    const cuuint32_t wob[3] = {64, 64, 2}, wdb[3] = {64, 64, 1};
    CUtensorMap mx = make_map(fn, x, 4, xd, xs, xb), mw = make_map(fn, wqkv, 3, wdm, wst, wb);
    CUtensorMap mwo = make_map(fn, wo, 3, wod, wos, wob), mout = make_map(fn, d_out, 5, od, xs, ob);
    const int swap_gu = wu < wg;
    const cuuint64_t gd[3] = {3584, 1024, 2}, gst[2] = {7168, (cuuint64_t)(swap_gu ? (const char*)wg - (const char*)wu : (const char*)wu - (const char*)wg)};
    const cuuint32_t gb[3] = {32, 64, 2};
    CUtensorMap mgu = make_map(fn, swap_gu ? wu : wg, 3, gd, gst, gb, CU_TENSOR_MAP_SWIZZLE_64B, CU_TENSOR_MAP_L2_PROMOTION_L2_128B);
    CUtensorMap mwd = make_map(fn, wd, 3, wdd, wos, wdb, CU_TENSOR_MAP_SWIZZLE_128B, CU_TENSOR_MAP_L2_PROMOTION_L2_128B);
    const cuuint64_t md[2] = {64, 32768}, ms[1] = {128};
    const cuuint32_t mb[2] = {64, 64};
    CUtensorMap mo = make_map(fn, scr, 2, md, ms, mb, CU_TENSOR_MAP_SWIZZLE_NONE, CU_TENSOR_MAP_L2_PROMOTION_NONE);
    cudaLaunchConfig_t cfg = {};
    cfg.gridDim = dim3(132); cfg.blockDim = dim3(512); cfg.dynamicSmemBytes = SMEM_LAUNCH; cfg.stream = cudaStreamPerThread;
    cudaLaunchAttribute at[1];
    at[0].id = cudaLaunchAttributeClusterDimension; at[0].val.clusterDim.x = 2; at[0].val.clusterDim.y = 1; at[0].val.clusterDim.z = 1;
    cfg.attrs = at; cfg.numAttrs = 1;
    cudaLaunchKernelEx(&cfg, fused_kernel, mx, mw, mwo, mout, mgu, mwd, mo, x, wr, scr, swap_gu);
}
```

```cpp
#include <cuda_runtime.h>
#include <cuda.h>
#include <cuda_bf16.h>
#include <stdint.h>

namespace {

constexpr int BOX = 8192, W_BYTES = 3 * BOX;
constexpr int OFF_E = 6 * BOX, OFF_W = 9 * BOX, OFF_X1 = 18 * BOX;
constexpr int OFF_WO = 6 * BOX;
constexpr int F_BYTES = 9216;
constexpr int OFF_FR = 24 * BOX;
constexpr int CS_BYTES = 3136;
constexpr int OFF_CS = OFF_E + 2 * F_BYTES;
constexpr int OFF_UPD = OFF_FR + 3 * F_BYTES;
constexpr int OFF_HIN = OFF_UPD + 2048;
constexpr int OFF_STAT = OFF_FR + 32768;
constexpr int OFF_SEL = OFF_STAT + 2112;
constexpr int OFF_EP = OFF_SEL + 32;
constexpr int OFF_BAR = OFF_EP + 16;
constexpr int B_WFULL = 0, B_XFULL = 3, B_AUX = 15, B_XT = 16, B_WOFULL = 18, B_OFULL = 24, B_FFULL = 36, B_ROW = 41;
constexpr int B_WEMPTY = 42, B_F1DONE = 45, B_XEMPTY = 46, B_WOEMPTY = 52, B_OEMPTY = 58;
constexpr int B_G1DONE = 66, B_FEMPTY = 67, B_STAGED = 72, B_UPD = 74, B_RDONE = 75, B_FREED = 76, NBAR = 78;
__device__ __forceinline__ uint32_t fslot(int s) { return s * F_BYTES + (s < 3 ? OFF_FR : OFF_E - 3 * F_BYTES); }
constexpr int SMEM_BYTES = OFF_BAR + NBAR * 8;
static_assert(OFF_HIN + 3072 <= OFF_STAT && OFF_CS + CS_BYTES <= OFF_W && SMEM_BYTES + 256 <= 232448 && OFF_BAR % 8 == 0 && OFF_UPD % 1024 == 0, "smem");
#define POLL_NS 100
#define HELP_AT 64
#define NF1 5
#define PF_RATE 8
#define PF_START 7
#define ZF_NS 40
#define FFN2_GATE B_G1DONE
#define PF_NW 6
#define PF_D 8
#define ROWS_AT 7
#define STATS_UNROLL 1
constexpr int kStatsUnroll = STATS_UNROLL;
constexpr int BUDGET = 1 << 18;

struct Scratch {
    uint8_t o[2048 * 1024 * 2];
    uint32_t ypart[8][8][1024];
    uint32_t halo[128][512];
    uint32_t act[14336 + 4096];
    uint2 row[2048];
    uint32_t cs[16][800];
    uint32_t oflag[16][32];
    uint32_t cnt[9][32];
    uint32_t sel[32], csflag[32], epoch[32];
};
__device__ __align__(1024) Scratch g_scr;
struct Weights { const char *wqkv, *wo, *wg, *wu, *wd; };

#define TS(i) do {} while (0)
#define TS_END() do {} while (0)
#define TSC(c, i) do {} while (0)
#define NRETRY() do {} while (0)
constexpr int SMEM_LAUNCH = SMEM_BYTES;
__device__ __forceinline__ uint32_t smem_u32(const void* p) { return (uint32_t)__cvta_generic_to_shared(p); }
__device__ __forceinline__ void mbar_init(uint32_t bar, uint32_t cnt) { asm volatile("mbarrier.init.shared::cta.b64 [%0], %1;" ::"r"(bar), "r"(cnt) : "memory"); }
__device__ __forceinline__ void mbar_expect_tx(uint32_t bar, uint32_t bytes) { asm volatile("mbarrier.arrive.expect_tx.shared::cta.b64 _, [%0], %1;" ::"r"(bar), "r"(bytes) : "memory"); }
__device__ __forceinline__ void mbar_arrive(uint32_t bar) { asm volatile("mbarrier.arrive.shared::cta.b64 _, [%0];" ::"r"(bar) : "memory"); }
__device__ __forceinline__ uint32_t mapa(uint32_t a, uint32_t cta) { uint32_t r; asm("mapa.shared::cluster.u32 %0, %1, %2;" : "=r"(r) : "r"(a), "r"(cta)); return r; }
__device__ __forceinline__ void mbar_arrive_at(uint32_t cbar) { asm volatile("mbarrier.arrive.shared::cluster.b64 _, [%0];" ::"r"(cbar) : "memory"); }
__device__ __forceinline__ void mbar_wait(uint32_t bar, uint32_t parity, int& budget) {
    asm volatile("{\n.reg .pred p;\nLAB_WAIT:\nmbarrier.try_wait.parity.shared::cta.b64 p, [%1], %2;\n"
                 "add.s32 %0, %0, -1;\nsetp.gt.and.s32 p, %0, 0, !p;\n@p bra LAB_WAIT;\n}" : "+r"(budget) : "r"(bar), "r"(parity) : "memory");
}
__device__ __forceinline__ void mbar_wait_hot(uint32_t bar, uint32_t parity, int& budget) {
    asm volatile("{\n.reg .pred p;\nmbarrier.try_wait.parity.shared::cta.b64 p, [%1], %2;\n@p bra LAB_DONE;\nLAB_WAIT:\nmbarrier.try_wait.parity.shared::cta.b64 p, [%1], %2;\n"
                 "add.s32 %0, %0, -1;\nsetp.gt.and.s32 p, %0, 0, !p;\n@p bra LAB_WAIT;\nLAB_DONE:\n}" : "+r"(budget) : "r"(bar), "r"(parity) : "memory");
}
__device__ __forceinline__ void tma_2d_mc(uint32_t dst, const CUtensorMap* m, uint32_t bar, int c0, int c1) {
    asm volatile("cp.async.bulk.tensor.2d.shared::cluster.global.mbarrier::complete_tx::bytes.multicast::cluster [%0], [%1, {%3, %4}], [%2], %5;" ::"r"(dst), "l"(m), "r"(bar), "r"(c0), "r"(c1), "h"((uint16_t)3) : "memory");
}
__device__ __forceinline__ void tma_3d(uint32_t dst, const CUtensorMap* m, uint32_t bar, int c0, int c1, int c2) {
    asm volatile("cp.async.bulk.tensor.3d.shared::cluster.global.mbarrier::complete_tx::bytes [%0], [%1, {%3, %4, %5}], [%2];" ::"r"(dst), "l"(m), "r"(bar), "r"(c0), "r"(c1), "r"(c2) : "memory");
}
__device__ __forceinline__ void tma_4d(uint32_t dst, const CUtensorMap* m, uint32_t bar, int c0, int c1, int c2, int c3) {
    asm volatile("cp.async.bulk.tensor.4d.shared::cluster.global.mbarrier::complete_tx::bytes [%0], [%1, {%3, %4, %5, %6}], [%2];" ::"r"(dst), "l"(m), "r"(bar), "r"(c0), "r"(c1), "r"(c2), "r"(c3) : "memory");
}
__device__ __forceinline__ void tma_4d_mc(uint32_t dst, const CUtensorMap* m, uint32_t bar, int c0, int c1, int c2, int c3) {
    asm volatile("cp.async.bulk.tensor.4d.shared::cluster.global.mbarrier::complete_tx::bytes.multicast::cluster [%0], [%1, {%3, %4, %5, %6}], [%2], %7;" ::"r"(dst), "l"(m), "r"(bar), "r"(c0), "r"(c1), "r"(c2), "r"(c3), "h"((uint16_t)3) : "memory");
}
__device__ __forceinline__ void bulk_pf(const void* p, uint32_t bytes) { asm volatile("cp.async.bulk.prefetch.L2.global [%0], %1;" ::"l"(p), "r"(bytes) : "memory"); }
__device__ __forceinline__ void bulk_g2s(uint32_t dst, const void* src, uint32_t bytes, uint32_t bar) {
    asm volatile("cp.async.bulk.shared::cluster.global.mbarrier::complete_tx::bytes [%0], [%1], %2, [%3];" ::"r"(dst), "l"(src), "r"(bytes), "r"(bar) : "memory");
}
__device__ __forceinline__ void bulk_s2c(uint32_t cdst, uint32_t src, uint32_t bytes, uint32_t cbar) {
    asm volatile("cp.async.bulk.shared::cluster.shared::cta.mbarrier::complete_tx::bytes [%0], [%1], %2, [%3];" ::"r"(cdst), "r"(src), "r"(bytes), "r"(cbar) : "memory");
}
__device__ __forceinline__ void cluster_wait() { asm volatile("barrier.cluster.wait.aligned;" ::: "memory"); }
__device__ __forceinline__ void fence_gpu() { asm volatile("fence.acq_rel.gpu;" ::: "memory"); }
__device__ __forceinline__ void fence_async_smem() { asm volatile("fence.proxy.async.shared::cta;" ::: "memory"); }
__device__ __forceinline__ void fence_async_gmem() { asm volatile("fence.proxy.async.global;" ::: "memory"); }
__device__ __forceinline__ void wg_fence() { asm volatile("wgmma.fence.sync.aligned;" ::: "memory"); }
__device__ __forceinline__ void wg_commit() { asm volatile("wgmma.commit_group.sync.aligned;" ::: "memory"); }
template <int N> __device__ __forceinline__ void wg_wait() { asm volatile("wgmma.wait_group.sync.aligned %0;" ::"n"(N) : "memory"); }
__device__ __forceinline__ uint64_t mkdesc(uint32_t lo, uint32_t hi) { return ((uint64_t)hi << 32) | lo; }
__host__ __device__ constexpr uint32_t dhi(uint32_t sbo, uint32_t mode) { return (sbo >> 4) | (mode << 30); }
__host__ __device__ constexpr uint32_t dlo(uint32_t off, uint32_t lbo) { return (off >> 4) + ((lbo >> 4) << 16); }
__device__ __forceinline__ bool elect_one() {
    uint32_t e;
    asm volatile("{\n.reg .pred p;\nelect.sync _|p, 0xffffffff;\nselp.u32 %0, 1, 0, p;\n}" : "=r"(e));
    return e;
}
template <int R> __device__ __forceinline__ void reg_inc() { asm volatile("setmaxnreg.inc.sync.aligned.u32 %0;" ::"n"(R)); }
template <int R> __device__ __forceinline__ void reg_dec() { asm volatile("setmaxnreg.dec.sync.aligned.u32 %0;" ::"n"(R)); }
__device__ __forceinline__ void bar_sync(int id, int n) { asm volatile("bar.sync %0, %1;" ::"r"(id), "r"(n) : "memory"); }
__device__ __forceinline__ void bar_arrive(int id, int n) { asm volatile("bar.arrive %0, %1;" ::"r"(id), "r"(n) : "memory"); }
__device__ __forceinline__ uint32_t pack_bf16(float lo, float hi) { uint32_t r; asm("cvt.rn.bf16x2.f32 %0, %1, %2;" : "=r"(r) : "f"(hi), "f"(lo)); return r; }
__device__ __forceinline__ uint32_t pack_here(float lo, float hi) { uint32_t r; asm volatile("cvt.rn.bf16x2.f32 %0, %1, %2;" : "=r"(r) : "f"(hi), "f"(lo)); return r; }
__device__ __forceinline__ float bf_lo(uint32_t u) { return __uint_as_float(u << 16); }
__device__ __forceinline__ float bf_hi(uint32_t u) { return __uint_as_float(u & 0xffff0000u); }
__device__ __forceinline__ float bf16r(float v) { return bf_lo(pack_bf16(v, 0.f)); }
__device__ __forceinline__ float rcp(float x) { float r; asm("rcp.approx.ftz.f32 %0, %1;" : "=f"(r) : "f"(x)); return r; }
__device__ __forceinline__ float ex2(float x) { float r; asm("ex2.approx.ftz.f32 %0, %1;" : "=f"(r) : "f"(x)); return r; }
__device__ __forceinline__ float sigmoidf(float v) { return rcp(1.f + ex2(v * -1.4426950408889634f)); }
__device__ __forceinline__ uint32_t movm(uint32_t a) { uint32_t d; asm volatile("movmatrix.sync.aligned.m8n8.trans.b16 %0, %1;" : "=r"(d) : "r"(a)); return d; }
__device__ __forceinline__ void mma16816(float (&c)[4], uint32_t a0, uint32_t a1, uint32_t a2, uint32_t a3, uint32_t b0, uint32_t b1) {
    asm volatile("mma.sync.aligned.m16n8k16.row.col.f32.bf16.bf16.f32 {%0,%1,%2,%3}, {%4,%5,%6,%7}, {%8,%9}, {%0,%1,%2,%3};"
                 : "+f"(c[0]), "+f"(c[1]), "+f"(c[2]), "+f"(c[3]) : "r"(a0), "r"(a1), "r"(a2), "r"(a3), "r"(b0), "r"(b1));
}
__device__ __forceinline__ void mma1688(float (&c)[4], uint32_t a0, uint32_t a1, uint32_t b0) {
    asm volatile("mma.sync.aligned.m16n8k8.row.col.f32.bf16.bf16.f32 {%0,%1,%2,%3}, {%4,%5}, {%6}, {%0,%1,%2,%3};"
                 : "+f"(c[0]), "+f"(c[1]), "+f"(c[2]), "+f"(c[3]) : "r"(a0), "r"(a1), "r"(b0));
}
__device__ __forceinline__ void stsm4(uint32_t a, uint32_t r0, uint32_t r1, uint32_t r2, uint32_t r3) {
    asm volatile("stmatrix.sync.aligned.m8n8.x4.shared.b16 [%0], {%1,%2,%3,%4};" ::"r"(a), "r"(r0), "r"(r1), "r"(r2), "r"(r3) : "memory");
}
__device__ __forceinline__ void ldsm4(uint32_t* r, uint32_t a) {
    asm volatile("ldmatrix.sync.aligned.m8n8.x4.shared.b16 {%0,%1,%2,%3}, [%4];" : "=r"(r[0]), "=r"(r[1]), "=r"(r[2]), "=r"(r[3]) : "r"(a) : "memory");
}
__device__ __forceinline__ void ldsm4t(uint32_t* r, uint32_t a) {
    asm volatile("ldmatrix.sync.aligned.m8n8.x4.trans.shared.b16 {%0,%1,%2,%3}, [%4];" : "=r"(r[0]), "=r"(r[1]), "=r"(r[2]), "=r"(r[3]) : "r"(a) : "memory");
}
__device__ __forceinline__ uint32_t ld_rlx(const void* p) { uint32_t v; asm volatile("ld.relaxed.gpu.global.u32 %0, [%1];" : "=r"(v) : "l"(p) : "memory"); return v; }
__device__ __forceinline__ uint32_t ld_acq(const void* p) { uint32_t v; asm volatile("ld.acquire.gpu.global.u32 %0, [%1];" : "=r"(v) : "l"(p) : "memory"); return v; }
__device__ __forceinline__ uint2 ld_rlx2(const void* p) { uint2 v; asm volatile("ld.relaxed.gpu.global.v2.u32 {%0,%1}, [%2];" : "=r"(v.x), "=r"(v.y) : "l"(p) : "memory"); return v; }
__device__ __forceinline__ uint4 ld_rlx4(const void* p) { uint4 v; asm volatile("ld.relaxed.gpu.global.v4.u32 {%0,%1,%2,%3}, [%4];" : "=r"(v.x), "=r"(v.y), "=r"(v.z), "=r"(v.w) : "l"(p) : "memory"); return v; }
__device__ __forceinline__ void st_rlx(void* p, uint32_t v) { asm volatile("st.relaxed.gpu.global.u32 [%0], %1;" ::"l"(p), "r"(v) : "memory"); }
__device__ __forceinline__ void st_rlx2(void* p, uint32_t a, uint32_t b) { asm volatile("st.relaxed.gpu.global.v2.u32 [%0], {%1,%2};" ::"l"(p), "r"(a), "r"(b) : "memory"); }
__device__ __forceinline__ void st_rlx4(void* p, uint32_t a, uint32_t b, uint32_t c, uint32_t d) { asm volatile("st.relaxed.gpu.global.v4.u32 [%0], {%1,%2,%3,%4};" ::"l"(p), "r"(a), "r"(b), "r"(c), "r"(d) : "memory"); }
__device__ __forceinline__ void red_add(uint32_t* p) { asm volatile("red.relaxed.gpu.global.add.u32 [%0], 1;" ::"l"(p) : "memory"); }
__device__ __forceinline__ uint4 ldg_nc(const void* p) { uint4 v; asm volatile("ld.global.nc.v4.u32 {%0,%1,%2,%3}, [%4];" : "=r"(v.x), "=r"(v.y), "=r"(v.z), "=r"(v.w) : "l"(p)); return v; }
__device__ __forceinline__ void sts4(uint32_t a, uint32_t x, uint32_t y, uint32_t z, uint32_t w) { asm volatile("st.shared.v4.u32 [%0], {%1,%2,%3,%4};" ::"r"(a), "r"(x), "r"(y), "r"(z), "r"(w) : "memory"); }
__device__ __forceinline__ void sts2(uint32_t a, uint32_t x, uint32_t y) { asm volatile("st.shared.v2.u32 [%0], {%1,%2};" ::"r"(a), "r"(x), "r"(y) : "memory"); }
__device__ __forceinline__ void sts1(uint32_t a, uint32_t v) { asm volatile("st.shared.u32 [%0], %1;" ::"r"(a), "r"(v) : "memory"); }
__device__ __forceinline__ uint4 lds4(uint32_t a) { uint4 v; asm volatile("ld.shared.v4.u32 {%0,%1,%2,%3}, [%4];" : "=r"(v.x), "=r"(v.y), "=r"(v.z), "=r"(v.w) : "r"(a) : "memory"); return v; }
__device__ __forceinline__ float4 lds4f(uint32_t a) { float4 v; asm volatile("ld.shared.v4.f32 {%0,%1,%2,%3}, [%4];" : "=f"(v.x), "=f"(v.y), "=f"(v.z), "=f"(v.w) : "r"(a) : "memory"); return v; }
__device__ __forceinline__ float2 lds2f(uint32_t a) { float2 v; asm volatile("ld.shared.v2.f32 {%0,%1}, [%2];" : "=f"(v.x), "=f"(v.y) : "r"(a) : "memory"); return v; }
__device__ __forceinline__ float lds1f(uint32_t a) { float v; asm volatile("ld.shared.f32 %0, [%1];" : "=f"(v) : "r"(a) : "memory"); return v; }
__device__ __forceinline__ uint32_t lds1(uint32_t a) { uint32_t v; asm volatile("ld.shared.u32 %0, [%1];" : "=r"(v) : "r"(a) : "memory"); return v; }
__device__ __forceinline__ uint32_t redux_max(uint32_t v) { uint32_t r; asm volatile("redux.sync.max.u32 %0, %1, 0xffffffff;" : "=r"(r) : "r"(v)); return r; }
__device__ __forceinline__ uint32_t poll_all(const uint32_t* p, uint32_t mask, uint32_t want, int& budget) {
    uint32_t v;
#pragma unroll 1
    while (v = ld_acq(p), !__all_sync(0xffffffffu, (v & mask) == want) && --budget > 0) __nanosleep(POLL_NS);
    return v;
}

template <int TA, int TB>
__device__ __forceinline__ void wgmma_n192(float (&d)[96], uint64_t da, uint64_t db, int keep) {
    asm volatile("{\n.reg .pred p;\nsetp.ne.b32 p, %98, 0;\n"
        "wgmma.mma_async.sync.aligned.m64n192k16.f32.bf16.bf16 "
        "{%0, %1, %2, %3, %4, %5, %6, %7, %8, %9, %10, %11, %12, %13, %14, %15, "
        "%16, %17, %18, %19, %20, %21, %22, %23, %24, %25, %26, %27, %28, %29, %30, %31, "
        "%32, %33, %34, %35, %36, %37, %38, %39, %40, %41, %42, %43, %44, %45, %46, %47, "
        "%48, %49, %50, %51, %52, %53, %54, %55, %56, %57, %58, %59, %60, %61, %62, %63, "
        "%64, %65, %66, %67, %68, %69, %70, %71, %72, %73, %74, %75, %76, %77, %78, %79, "
        "%80, %81, %82, %83, %84, %85, %86, %87, %88, %89, %90, %91, %92, %93, %94, %95}, "
        "%96, %97, p, 1, 1, %99, %100;\n}\n"
        : "+f"(d[0]), "+f"(d[1]), "+f"(d[2]), "+f"(d[3]), "+f"(d[4]), "+f"(d[5]), "+f"(d[6]), "+f"(d[7]),
          "+f"(d[8]), "+f"(d[9]), "+f"(d[10]), "+f"(d[11]), "+f"(d[12]), "+f"(d[13]), "+f"(d[14]), "+f"(d[15]),
          "+f"(d[16]), "+f"(d[17]), "+f"(d[18]), "+f"(d[19]), "+f"(d[20]), "+f"(d[21]), "+f"(d[22]), "+f"(d[23]),
          "+f"(d[24]), "+f"(d[25]), "+f"(d[26]), "+f"(d[27]), "+f"(d[28]), "+f"(d[29]), "+f"(d[30]), "+f"(d[31]),
          "+f"(d[32]), "+f"(d[33]), "+f"(d[34]), "+f"(d[35]), "+f"(d[36]), "+f"(d[37]), "+f"(d[38]), "+f"(d[39]),
          "+f"(d[40]), "+f"(d[41]), "+f"(d[42]), "+f"(d[43]), "+f"(d[44]), "+f"(d[45]), "+f"(d[46]), "+f"(d[47]),
          "+f"(d[48]), "+f"(d[49]), "+f"(d[50]), "+f"(d[51]), "+f"(d[52]), "+f"(d[53]), "+f"(d[54]), "+f"(d[55]),
          "+f"(d[56]), "+f"(d[57]), "+f"(d[58]), "+f"(d[59]), "+f"(d[60]), "+f"(d[61]), "+f"(d[62]), "+f"(d[63]),
          "+f"(d[64]), "+f"(d[65]), "+f"(d[66]), "+f"(d[67]), "+f"(d[68]), "+f"(d[69]), "+f"(d[70]), "+f"(d[71]),
          "+f"(d[72]), "+f"(d[73]), "+f"(d[74]), "+f"(d[75]), "+f"(d[76]), "+f"(d[77]), "+f"(d[78]), "+f"(d[79]),
          "+f"(d[80]), "+f"(d[81]), "+f"(d[82]), "+f"(d[83]), "+f"(d[84]), "+f"(d[85]), "+f"(d[86]), "+f"(d[87]),
          "+f"(d[88]), "+f"(d[89]), "+f"(d[90]), "+f"(d[91]), "+f"(d[92]), "+f"(d[93]), "+f"(d[94]), "+f"(d[95])
        : "l"(da), "l"(db), "r"(keep), "n"(TA), "n"(TB));
}
template <int TA, int TB>
__device__ __forceinline__ void wgmma_n128(float (&d)[64], uint64_t da, uint64_t db, int keep) {
    asm volatile("{\n.reg .pred p;\nsetp.ne.b32 p, %66, 0;\n"
        "wgmma.mma_async.sync.aligned.m64n128k16.f32.bf16.bf16 "
        "{%0, %1, %2, %3, %4, %5, %6, %7, %8, %9, %10, %11, %12, %13, %14, %15, "
        "%16, %17, %18, %19, %20, %21, %22, %23, %24, %25, %26, %27, %28, %29, %30, %31, "
        "%32, %33, %34, %35, %36, %37, %38, %39, %40, %41, %42, %43, %44, %45, %46, %47, "
        "%48, %49, %50, %51, %52, %53, %54, %55, %56, %57, %58, %59, %60, %61, %62, %63}, "
        "%64, %65, p, 1, 1, %67, %68;\n}\n"
        : "+f"(d[0]), "+f"(d[1]), "+f"(d[2]), "+f"(d[3]), "+f"(d[4]), "+f"(d[5]), "+f"(d[6]), "+f"(d[7]),
          "+f"(d[8]), "+f"(d[9]), "+f"(d[10]), "+f"(d[11]), "+f"(d[12]), "+f"(d[13]), "+f"(d[14]), "+f"(d[15]),
          "+f"(d[16]), "+f"(d[17]), "+f"(d[18]), "+f"(d[19]), "+f"(d[20]), "+f"(d[21]), "+f"(d[22]), "+f"(d[23]),
          "+f"(d[24]), "+f"(d[25]), "+f"(d[26]), "+f"(d[27]), "+f"(d[28]), "+f"(d[29]), "+f"(d[30]), "+f"(d[31]),
          "+f"(d[32]), "+f"(d[33]), "+f"(d[34]), "+f"(d[35]), "+f"(d[36]), "+f"(d[37]), "+f"(d[38]), "+f"(d[39]),
          "+f"(d[40]), "+f"(d[41]), "+f"(d[42]), "+f"(d[43]), "+f"(d[44]), "+f"(d[45]), "+f"(d[46]), "+f"(d[47]),
          "+f"(d[48]), "+f"(d[49]), "+f"(d[50]), "+f"(d[51]), "+f"(d[52]), "+f"(d[53]), "+f"(d[54]), "+f"(d[55]),
          "+f"(d[56]), "+f"(d[57]), "+f"(d[58]), "+f"(d[59]), "+f"(d[60]), "+f"(d[61]), "+f"(d[62]), "+f"(d[63])
        : "l"(da), "l"(db), "r"(keep), "n"(TA), "n"(TB));
}
template <int TA, int TB>
__device__ __forceinline__ void wgmma_n8(float (&d)[4], uint64_t da, uint64_t db, int keep) {
    asm volatile("{\n.reg .pred p;\nsetp.ne.b32 p, %6, 0;\n"
        "wgmma.mma_async.sync.aligned.m64n8k16.f32.bf16.bf16 "
        "{%0, %1, %2, %3}, "
        "%4, %5, p, 1, 1, %7, %8;\n}\n"
        : "+f"(d[0]), "+f"(d[1]), "+f"(d[2]), "+f"(d[3])
        : "l"(da), "l"(db), "r"(keep), "n"(TA), "n"(TB));
}
__device__ __forceinline__ void wgmma_rs_n128(float (&d)[64], uint32_t a0, uint32_t a1, uint32_t a2, uint32_t a3, uint64_t db) {
    asm volatile("{\n.reg .pred p;\nsetp.ne.b32 p, 1, 0;\n"
        "wgmma.mma_async.sync.aligned.m64n128k16.f32.bf16.bf16 "
        "{%0, %1, %2, %3, %4, %5, %6, %7, %8, %9, %10, %11, %12, %13, %14, %15, "
        "%16, %17, %18, %19, %20, %21, %22, %23, %24, %25, %26, %27, %28, %29, %30, %31, "
        "%32, %33, %34, %35, %36, %37, %38, %39, %40, %41, %42, %43, %44, %45, %46, %47, "
        "%48, %49, %50, %51, %52, %53, %54, %55, %56, %57, %58, %59, %60, %61, %62, %63}, "
        "{%64, %65, %66, %67}, %68, p, 1, 1, 1;\n}\n"
        : "+f"(d[0]), "+f"(d[1]), "+f"(d[2]), "+f"(d[3]), "+f"(d[4]), "+f"(d[5]), "+f"(d[6]), "+f"(d[7]),
          "+f"(d[8]), "+f"(d[9]), "+f"(d[10]), "+f"(d[11]), "+f"(d[12]), "+f"(d[13]), "+f"(d[14]), "+f"(d[15]),
          "+f"(d[16]), "+f"(d[17]), "+f"(d[18]), "+f"(d[19]), "+f"(d[20]), "+f"(d[21]), "+f"(d[22]), "+f"(d[23]),
          "+f"(d[24]), "+f"(d[25]), "+f"(d[26]), "+f"(d[27]), "+f"(d[28]), "+f"(d[29]), "+f"(d[30]), "+f"(d[31]),
          "+f"(d[32]), "+f"(d[33]), "+f"(d[34]), "+f"(d[35]), "+f"(d[36]), "+f"(d[37]), "+f"(d[38]), "+f"(d[39]),
          "+f"(d[40]), "+f"(d[41]), "+f"(d[42]), "+f"(d[43]), "+f"(d[44]), "+f"(d[45]), "+f"(d[46]), "+f"(d[47]),
          "+f"(d[48]), "+f"(d[49]), "+f"(d[50]), "+f"(d[51]), "+f"(d[52]), "+f"(d[53]), "+f"(d[54]), "+f"(d[55]),
          "+f"(d[56]), "+f"(d[57]), "+f"(d[58]), "+f"(d[59]), "+f"(d[60]), "+f"(d[61]), "+f"(d[62]), "+f"(d[63])
        : "r"(a0), "r"(a1), "r"(a2), "r"(a3), "l"(db));
}
__device__ __forceinline__ void wgmma_rs_n192(float (&d)[96], uint32_t a0, uint32_t a1, uint32_t a2, uint32_t a3, uint64_t db) {
    asm volatile("{\n.reg .pred p;\nsetp.ne.b32 p, 1, 0;\n"
        "wgmma.mma_async.sync.aligned.m64n192k16.f32.bf16.bf16 "
        "{%0, %1, %2, %3, %4, %5, %6, %7, %8, %9, %10, %11, %12, %13, %14, %15, "
        "%16, %17, %18, %19, %20, %21, %22, %23, %24, %25, %26, %27, %28, %29, %30, %31, "
        "%32, %33, %34, %35, %36, %37, %38, %39, %40, %41, %42, %43, %44, %45, %46, %47, "
        "%48, %49, %50, %51, %52, %53, %54, %55, %56, %57, %58, %59, %60, %61, %62, %63, "
        "%64, %65, %66, %67, %68, %69, %70, %71, %72, %73, %74, %75, %76, %77, %78, %79, "
        "%80, %81, %82, %83, %84, %85, %86, %87, %88, %89, %90, %91, %92, %93, %94, %95}, "
        "{%96, %97, %98, %99}, %100, p, 1, 1, 1;\n}\n"
        : "+f"(d[0]), "+f"(d[1]), "+f"(d[2]), "+f"(d[3]), "+f"(d[4]), "+f"(d[5]), "+f"(d[6]), "+f"(d[7]),
          "+f"(d[8]), "+f"(d[9]), "+f"(d[10]), "+f"(d[11]), "+f"(d[12]), "+f"(d[13]), "+f"(d[14]), "+f"(d[15]),
          "+f"(d[16]), "+f"(d[17]), "+f"(d[18]), "+f"(d[19]), "+f"(d[20]), "+f"(d[21]), "+f"(d[22]), "+f"(d[23]),
          "+f"(d[24]), "+f"(d[25]), "+f"(d[26]), "+f"(d[27]), "+f"(d[28]), "+f"(d[29]), "+f"(d[30]), "+f"(d[31]),
          "+f"(d[32]), "+f"(d[33]), "+f"(d[34]), "+f"(d[35]), "+f"(d[36]), "+f"(d[37]), "+f"(d[38]), "+f"(d[39]),
          "+f"(d[40]), "+f"(d[41]), "+f"(d[42]), "+f"(d[43]), "+f"(d[44]), "+f"(d[45]), "+f"(d[46]), "+f"(d[47]),
          "+f"(d[48]), "+f"(d[49]), "+f"(d[50]), "+f"(d[51]), "+f"(d[52]), "+f"(d[53]), "+f"(d[54]), "+f"(d[55]),
          "+f"(d[56]), "+f"(d[57]), "+f"(d[58]), "+f"(d[59]), "+f"(d[60]), "+f"(d[61]), "+f"(d[62]), "+f"(d[63]),
          "+f"(d[64]), "+f"(d[65]), "+f"(d[66]), "+f"(d[67]), "+f"(d[68]), "+f"(d[69]), "+f"(d[70]), "+f"(d[71]),
          "+f"(d[72]), "+f"(d[73]), "+f"(d[74]), "+f"(d[75]), "+f"(d[76]), "+f"(d[77]), "+f"(d[78]), "+f"(d[79]),
          "+f"(d[80]), "+f"(d[81]), "+f"(d[82]), "+f"(d[83]), "+f"(d[84]), "+f"(d[85]), "+f"(d[86]), "+f"(d[87]),
          "+f"(d[88]), "+f"(d[89]), "+f"(d[90]), "+f"(d[91]), "+f"(d[92]), "+f"(d[93]), "+f"(d[94]), "+f"(d[95])
        : "r"(a0), "r"(a1), "r"(a2), "r"(a3), "l"(db));
}

template <int HS>
__device__ __forceinline__ void attn_pair(const uint32_t* q, const uint32_t* k, const uint32_t* v, const uint32_t* kh, const uint32_t* vh,
                                          const float* fu, const float* fn, const float* rk, float bias0, float bias1, uint32_t mU, uint32_t zero, const float* ci, uint32_t* o) {
    float s0[2][4] = {}, s1[2][4] = {}, s2[2][4] = {};
#pragma unroll
    for (int n = 0; n < 4; n++) {
        const int hd = n & 1, a = 8 * hd + 2 * (n & 2);
        mma16816(s1[hd], q[a], q[a + 1], q[a + 2], q[a + 3], k[a], k[a + 2]);
        mma16816(s2[hd], q[a], q[a + 1], q[a + 2], q[a + 3], k[a + 1], k[a + 3]);
    }
#pragma unroll
    for (int n = 0; n < 4; n++) {
        const int hd = n & 1, a = 8 * hd + 2 * (n & 2);
        mma16816(s0[hd], q[a], q[a + 1], q[a + 2], q[a + 3], kh[HS * (a / 2)], kh[HS * (a / 2 + 1)]);
    }
    float e[2][4], m[2][2];
#pragma unroll
    for (int hd = 0; hd < 2; hd++) {
        e[hd][2] = fmaf(s1[hd][2], fu[2], s2[hd][2] * fn[2]); e[hd][3] = fmaf(s1[hd][3], fu[3], s2[hd][3] * fn[3]);
        e[hd][0] = fmaf(s0[hd][0], fu[0], fmaf(s1[hd][0], fn[0], bias0)); e[hd][1] = fmaf(s0[hd][1], fu[1], fmaf(s1[hd][1], fn[1], bias1));
        m[hd][1] = fmaxf(e[hd][2], e[hd][3]); m[hd][0] = fmaxf(e[hd][0], e[hd][1]);
    }
#pragma unroll
    for (int x = 1; x < 3; x++)
#pragma unroll
        for (int n = 0; n < 4; n++) m[n & 1][1 - (n >> 1)] = fmaxf(m[n & 1][1 - (n >> 1)], __shfl_xor_sync(0xffffffffu, m[n & 1][1 - (n >> 1)], x));
    float c[2][4][4] = {};
#pragma unroll
    for (int hd = 0; hd < 2; hd++) {
#pragma unroll
        for (int n = 0; n < 4; n++) e[hd][n] = ex2(e[hd][n] - m[hd][n >> 1]);
        const uint32_t plo = pack_bf16(e[hd][0] * rk[0], e[hd][1] * rk[1]), phi = pack_bf16(e[hd][2] * rk[2], e[hd][3] * rk[3]);
        const uint32_t z0 = plo & zero, z1 = phi & zero;
        const uint32_t a0 = plo & ~mU, a1 = phi & mU, a3 = phi & ~mU, b0 = plo & mU;
#pragma unroll
        for (int jj = 0; jj < 4; jj++) mma16816(c[hd][jj], a0, a1, z0, a3, v[8 * hd + 2 * jj], v[8 * hd + 2 * jj + 1]);
#pragma unroll
        for (int jj = 0; jj < 4; jj++) mma1688(c[hd][jj], b0, z1, vh[HS * (4 * hd + jj)]);
        m[hd][0] = e[hd][0] + e[hd][1]; m[hd][1] = e[hd][2] + e[hd][3];
    }
#pragma unroll
    for (int x = 1; x < 3; x++)
#pragma unroll
        for (int n = 0; n < 4; n++) m[n >> 1][n & 1] += __shfl_xor_sync(0xffffffffu, m[n >> 1][n & 1], x);
#pragma unroll
    for (int hd = 0; hd < 2; hd++) {
        const float i0 = rcp(m[hd][0]), i1 = rcp(m[hd][1]);
#pragma unroll
        for (int jj = 0; jj < 4; jj++) {
            o[8 * hd + 2 * jj] = pack_bf16(fmaf(c[hd][jj][0], i0, 0x1p-120f), c[hd][jj][1] * i0);
            o[8 * hd + 2 * jj + 1] = pack_bf16(fmaf(c[hd][jj][2], i1, 0x1p-120f), c[hd][jj][3] * i1);
        }
    }
}

__device__ __forceinline__ uint32_t norm_pair(uint32_t u, float m, float rinv) {
    const uint32_t d = pack_bf16(bf_lo(u) - m, bf_hi(u) - m);
    return pack_bf16(bf_lo(d) * rinv, bf_hi(d) * rinv);
}

__global__ void __launch_bounds__(512, 1)
fused_kernel(const __grid_constant__ CUtensorMap mx, const __grid_constant__ CUtensorMap mw, const __grid_constant__ CUtensorMap mwo,
             const __grid_constant__ CUtensorMap mout, const __grid_constant__ CUtensorMap mgu, const __grid_constant__ CUtensorMap mwd,
             const __grid_constant__ CUtensorMap mo,
             const __nv_bfloat16* __restrict__ x, const __nv_bfloat16* __restrict__ wr, Scratch* __restrict__ scr, int swap_gu, const Weights pf) {
    extern __shared__ __align__(1024) uint8_t smem[];
    const uint32_t sb = smem_u32(smem);
    const uint32_t bars = sb + OFF_BAR;
    const int tid = threadIdx.x, lane = tid & 31, warp = __shfl_sync(0xffffffffu, tid >> 5, 0);
    const uint32_t sd = (sb & 0x3FFFF) >> 4;
    const int hp = blockIdx.x & 1, cl = blockIdx.x >> 1;
    const int pr = cl < 4 ? 39 + 8 * cl : cl < 36 ? cl - 4 : cl < 64 ? cl - 4 + ((cl - 36) * 37 >> 8) : cl;
    const int b = pr * 2 + hp, mt = pr >> 3, p = pr & 7, nt = 2 * p + hp, rh = p & 1, cb = (p & 6) + hp;
    const int par = mt >> 2, j0 = (mt & 3) * 256;
    int budget = BUDGET;

    TSC(tid == 0, 0);
    auto load_w = [&](int k, int s) {
        const uint32_t full = bars + 8 * (B_WFULL + s);
        mbar_expect_tx(full, W_BYTES);
        tma_3d(sb + OFF_W + s * W_BYTES, &mw, full, nt * 64, k * 64, 0);
    };
    if (elect_one()) {
        const uint32_t cnt = warp < B_WEMPTY / 6 ? 1 : warp < B_G1DONE / 6 ? 2 : warp < B_STAGED / 6 ? 4 : 8;
        if (warp < NBAR / 6) {
#pragma unroll
            for (int i = 0; i < 6; i++) mbar_init(bars + 48 * warp + 8 * i, cnt);
        }
        asm volatile("fence.mbarrier_init.release.cluster;" ::: "memory");
    }
    __syncthreads();

    if (b >= 128) {
        const int hc = b - 128, g = lane >> 2, t = lane & 3;
        if (warp < 12) {
            const int n = warp / 3, part = warp - 3 * n;
            const uint32_t ep = ld_rlx(&scr->epoch[0]) + 1;
            auto load = [&](int k) {
                const uint32_t full = bars + 8 * (2 * n + (k & 1));
                mbar_expect_tx(full, W_BYTES);
                tma_3d(sb + (2 * n + (k & 1)) * W_BYTES, &mw, full, (4 * hc + n) * 64, k * 64, 0);
            };
            if (part == 0 && elect_one()) { load(0); load(1); }
            __syncwarp();
            float c0[4] = {0.f, 0.f, 0.f, 0.f}, c1[4] = {0.f, 0.f, 0.f, 0.f};
            const uint32_t sel = g == 0 ? 0x3f80u : g == 1 ? 0x3f800000u : 0u;
            const uint32_t a = sb + 2 * n * W_BYTES + part * BOX + t * 256 + ((g ^ (2 * t)) << 4);
#pragma unroll 1
            for (int k = 0; k < 16; k++) {
                mbar_wait(bars + 8 * (2 * n + (k & 1)), (k >> 1) & 1, budget);
                uint4 v[8], u[8];
#pragma unroll
                for (int i = 0; i < 8; i++) { v[i] = lds4(a + (k & 1) * W_BYTES + i * 1024); u[i] = lds4(((a + 128) ^ 16) + (k & 1) * W_BYTES + i * 1024); }
#pragma unroll
                for (int i = 0; i < 8; i++) { mma16816(c0, v[i].x, v[i].y, u[i].x, u[i].y, sel, sel); mma16816(c1, v[i].z, v[i].w, u[i].z, u[i].w, sel, sel); }
                bar_sync(1 + n, 96);
                if (part == 0 && k < 14 && elect_one()) load(k + 2);
                __syncwarp();
            }
            if (t == 0) {
#pragma unroll
                for (int r = 0; r < 3; r++) {
                    const uint32_t q0 = pack_bf16(c0[0], c0[1]), q1 = pack_bf16(c0[2], c0[3]), q2 = pack_bf16(c1[0], c1[1]), q3 = pack_bf16(c1[2], c1[3]);
                    st_rlx4(&scr->cs[4 * hc + n][16 + (part * 8 + g) * 32 + r * 4], q0, q1, q2, q3);
                    c0[0] -= bf_lo(q0); c0[1] -= bf_hi(q0); c0[2] -= bf_lo(q1); c0[3] -= bf_hi(q1);
                    c1[0] -= bf_lo(q2); c1[1] -= bf_hi(q2); c1[2] -= bf_lo(q3); c1[3] -= bf_hi(q3);
                }
            }
            bar_sync(7, 384);
            if (tid == 0) { fence_gpu(); st_rlx(&scr->csflag[hc], ep); }
            TSC(tid == 0, 19);
        }
        if (warp < 8) TS_END();
        return;
    }
    asm volatile("barrier.cluster.arrive.relaxed.aligned;" ::: "memory");

    const int kc = b >> 4, c2 = b & 15;
    if (warp >= 12) {
        reg_dec<24>();
        if (warp == 12) {
            if (elect_one()) {
#pragma unroll 1
                for (int n = 0; n < 12; n++) {
                    const int w = n & 1, j = n >> 1;
                    const uint32_t full = bars + 8 * (B_XFULL + w * 6 + j);
                    mbar_expect_tx(full, BOX);
                    tma_4d(sb + w * OFF_X1 + j * BOX, &mx, full, par * 1024 + (n >> 2) * 64, 0, (j0 + w * 128) >> 5, (~n >> 1) & 1);
                    if (n == ROWS_AT) { mbar_expect_tx(bars + 8 * B_ROW, 4 * BOX); bulk_g2s(sb + OFF_FR, x + (size_t)b * 16 * 1024, 4 * BOX, bars + 8 * B_ROW); }
                    if (n == 0 || n == 3 || n == 7) load_w((n + 1) >> 2, n ? n >> 2 : 2);
                }
                int s = 2; uint32_t ph = 0;
#pragma unroll 1
                for (int k = 3; k < 16; k++) {
                    mbar_wait(bars + 8 * (B_WEMPTY + s), ph, budget);
                    load_w(k, s);
                    if (++s == 3) s = 0;
                    if (s == 2) ph ^= 1;
                }
                TS(27);
                s = 2;
#pragma unroll 1
                for (int i = 0; i < 16; i++) {
                    mbar_wait(bars + 8 * (i < 2 ? B_WEMPTY + i : i < 4 ? B_G1DONE : i < 6 ? B_F1DONE : B_WOEMPTY + s), i >= 12, budget);
                    if (i == 1) {
                        mbar_expect_tx(bars + 8 * B_XT, 4 * BOX);
#pragma unroll 1
                        for (int n = 0; n < 4; n++)
                            tma_4d(sb + (n >> 1) * OFF_X1 + (4 + (n & 1)) * BOX, &mx, bars + 8 * B_XT, par * 1024 + cb * 128 + (n & 1) * 64, 0, (j0 + rh * 128) >> 5, 1 - (n >> 1));
                    }
                    const uint32_t full = bars + 8 * (B_WOFULL + s);
                    mbar_expect_tx(full, 2 * BOX);
                    tma_3d(sb + OFF_WO + s * 2 * BOX, &mwo, full, 0, ((2 * p + (i < 2 ? i ^ hp : i)) & 15) * 64, cb * 2);
                    TSC(TIMING % 10 == 4, 48 + i);
                    if (++s == 6) s = 0;
                }
                TS(25);
            }
        } else {
            bar_sync(8, 224);
            const uint32_t ep = lds1(sb + OFF_EP);
            if (warp == 13) {
                cluster_wait();
                if (elect_one()) {
                    int j = 0, q = 0, left = BUDGET; uint32_t ph = 0;
#pragma unroll 1
                    for (int n = 6; n < 32; n++) {
                        mbar_wait(bars + 8 * (B_XEMPTY + j), ph, left);
                        tma_4d_mc(sb + hp * OFF_X1 + j * BOX, &mx, bars + 8 * (B_XFULL + hp * 6 + j), par * 1024 + (n >> 1) * 64, 0, (j0 + hp * 128) >> 5, ~n & 1);
                        if (++j == 6) { j = 0; ph ^= 1; }
#pragma unroll 1
                        for (; q < (PF_RATE * (n - PF_START) >> 3) && q < 18 + PF_NW; q++) {
                            const int u = q - PF_NW;
                            if (u < 0) bulk_pf(pf.wqkv + (size_t)(1024 + 128 * u + b) * 6144, 6144);
                            else if (u < 16) bulk_pf((b < 64 ? pf.wg : pf.wu) + (size_t)(u * 64 + (b & 63)) * 7168, 7168);
                            else bulk_pf(pf.wo + (size_t)((u - 16) * 128 + b) * 8192, 8192);
                        }
                    }
                }
                __syncwarp();
                uint32_t* hs = &scr->halo[b - 16][lane * 4];
                int tries = BUDGET;
#pragma unroll 1
                for (int c = 0; c < 4; c += 2) {
                    uint4 v0 = make_uint4(0, 0, 0, 0), v1 = v0;
                    if (j0) {
#pragma unroll 1
                        do { v0 = ld_rlx4(hs + c * 128); v1 = ld_rlx4(hs + c * 128 + 128); } while ((v0.x == 0 || v1.x == 0) && --tries > 0);
                        st_rlx(hs + c * 128, 0); st_rlx(hs + c * 128 + 128, 0);
                    }
                    __syncwarp();
                    stsm4(sb + OFF_HIN + c * 512 + lane * 16, v0.x, v0.y, v0.z, v0.w);
                    stsm4(sb + OFF_HIN + c * 512 + 512 + lane * 16, v1.x, v1.y, v1.z, v1.w);
                }
                bar_arrive(11, 64);
                TSC(lane == 0, 31);
                const int src = ((mt * 2 + rh) * 2 + 1 - hp) * 1024;
                if (elect_one()) {
                    const uint32_t* fl = &scr->oflag[mt * 2 + 1 - hp][0];
                    const uint32_t inv = (ep & 1) - 1;
                    uint32_t ready = 0, ph = 0;
                    int s = 4;
#pragma unroll 1
                    for (int i = 2; i < 16; i++) {
                        const int kb = (2 * p + i) & 15;
#pragma unroll 1
                        while (!((ready >> kb) & 1) && --budget > 0) ready = ld_rlx(fl) ^ inv;
                        TSC(i == 2, 30);
                        mbar_wait(bars + 8 * (B_OEMPTY + s), ph, budget);
                        tma_2d_mc(sb + hp * OFF_X1 + s * BOX, &mo, bars + 8 * (B_OFULL + hp * 6 + s), 0, src + kb * 64);
                        TSC(TIMING % 10 == 4 && hp == 0, 32 + i);
                        if (++s == 6) s = 0;
                        if (s == 4) ph ^= 1;
                    }
                }
            } else if (warp == 14) {
                if (elect_one()) {
                    uint32_t ph = 0;
#pragma unroll 1
                    for (int f = b < 112 ? 0 : 1; f < 2; f++) {
                        const int n = f ? 7 : 16, ns = f ? 3 : NF1, wx = f ? 0 : b * 32, wy = f ? kc * 448 : 0, wz = f ? c2 : 0;
                        const uint32_t* act = scr->act + (f ? kc * 7 * 256 : 14336);
                        const CUtensorMap* wm = f ? &mwd : &mgu;
                        int s = f;
#pragma unroll 1
                        for (int q = -3 * f; q < n; q++) {
                            const uint32_t full = bars + 8 * (B_FFULL + s), dst = sb + fslot(s);
                            if (q == 0) {
#pragma unroll 1
                                while (ld_acq(&scr->cnt[f ? kc : 8][0]) != ep * (f ? 14 : 8) && --budget > 0) __nanosleep(POLL_NS);
                                fence_async_gmem();
                                TS(f ? 29 : 26);
                            }
                            if ((unsigned)q >= 3u * f) {
                                mbar_wait(bars + 8 * (B_FEMPTY + s), (ph >> s) & 1, budget);
                                ph ^= 1u << s;
                                mbar_expect_tx(full, F_BYTES);
                                tma_3d(dst, wm, full, wx, wy + (q < 0 ? q + 3 : q) * 64, wz);
                            }
                            if (q >= 0) bulk_g2s(dst + BOX, act + q * 256, 1024, full);
                            if (!f && q >= PF_D && q < PF_D + 8) bulk_pf(pf.wd + (size_t)((q - PF_D) * 112 + b) * 8192, 8192);
                            if (++s == ns) s = 0;
                        }
                    }
                }
            } else {
                mbar_wait(bars + 8 * B_ROW, 0, budget);
                uint8_t* oz = scr->o + ((size_t)mt * 64 + nt) * BOX + lane * 16;
#pragma unroll 1
                for (int i = 0; i < 64; i++) { st_rlx4(oz + (i >> 4) * 16 * BOX + (i & 15) * 512, 0, 0, 0, 0); __nanosleep(ZF_NS); }
                __syncwarp();
                fence_gpu();
                mbar_wait(bars + 8 * B_RDONE, 0, budget);
                int tries = BUDGET;
#pragma unroll 1
                for (int i = lane; i < 264; i += 32) {
                    const int j = j0 - 8 + i;
                    uint2 v = make_uint2(0x7f800000u, 0);
                    if (j >= 0) {
#pragma unroll 1
                        do { v = ld_rlx2(&scr->row[2 * j + par]); } while (((v.y ^ ep) & 31) && --tries > 0);
                    }
                    sts2(sb + OFF_STAT + i * 8, __float_as_uint(-bf_lo(v.x)), __float_as_uint(rcp(bf_hi(v.x))));
                }
                __syncwarp();
                poll_all(&scr->csflag[lane & 3], ~0u, ep, budget);
                if (elect_one()) {
                    fence_async_gmem();
                    mbar_expect_tx(bars + 8 * B_AUX, CS_BYTES);
                    bulk_g2s(sb + OFF_CS, scr->cs[nt], CS_BYTES, bars + 8 * B_AUX);
                    TS(21);
                    mbar_expect_tx(bars + 8 * (B_OFULL + 3), BOX); mbar_expect_tx(bars + 8 * (B_OFULL + 9), BOX);
#pragma unroll 1
                    for (int v = 0; v < 2; v++) {
                        const uint32_t ring = sb + v * OFF_X1 + 2 * BOX, fb = bars + 8 * (B_OFULL + v * 6 + 2);
                        mbar_wait(bars + 8 * (B_STAGED + v), 0, budget);
                        asm volatile("red.relaxed.gpu.global.xor.b32 [%0], %1;" ::"l"(&scr->oflag[mt * 2 + 1 - v][0]), "r"(1u << nt) : "memory");
                        TS(13 + 2 * v);
                        mbar_arrive(fb);
                        mbar_wait(bars + 8 * B_G1DONE, 0, budget);
                        bulk_s2c(mapa(ring + BOX, hp ^ 1), ring, BOX, mapa(fb + 8, hp ^ 1));
                        if (v == 0) {
                            mbar_wait(bars + 8 * B_FREED, 0, budget);
                            TS(14);
#pragma unroll
                            for (int n = 0; n < 8; n++) {
                                mbar_expect_tx(bars + 8 * (B_OFULL + (n >> 2) * 6 + (4 + (n & 3)) % 6), BOX);
                                mbar_arrive_at(mapa(bars + 8 * B_OEMPTY, n >> 2) + (4 + (n & 3)) % 6 * 8);
                            }
                        }
                    }
                }
            }
        }
    } else if (warp >= 8) {
        reg_dec<40>();
        const int wq = warp - 8, ta = tid - 256, g = lane >> 2, t = lane & 3;
        const uint32_t rbuf = sb + OFF_FR + wq * BOX, rbar = bars + 8 * B_ROW;
        const uint4 wv = ldg_nc(wr + ta * 8);
        if (ta == 0) sts1(sb + OFF_EP, ld_rlx(&scr->epoch[0]) + 1);
        sts4(sb + OFF_STAT + ta * 16, wv.x, wv.y, wv.z, wv.w);
        bar_sync(8, 224);
        const uint32_t ep = lds1(sb + OFF_EP);
        {
            const int s = b * 16 + wq * 4 + (lane >> 3);
            if ((lane & 7) == 0) st_rlx2(&scr->row[s], 0, ep - 1);
            float sw = 0.f;
#pragma unroll 1
            for (int i = 0; i < 16; i++) { const uint32_t q = lds1(sb + OFF_STAT + i * 128 + lane * 4); sw += bf_lo(q) + bf_hi(q); }
#pragma unroll 1
            for (int o = 16; o > 0; o >>= 1) sw += __shfl_xor_sync(0xffffffffu, sw, o);
            float s1 = 0.f, s2 = 0.f, sr = 0.f;
            const uint32_t xa = rbuf + (lane >> 3) * 2048 + (lane & 7) * 16, wa = sb + OFF_STAT + (lane & 7) * 16;
            mbar_wait(rbar, 0, budget);
            TSC(ta == 0, 17);
            uint4 u = lds4(xa), w4 = lds4(wa);
#pragma unroll kStatsUnroll
            for (int i = 1; i <= 16; i++) {
                const uint32_t o = (i * 128) & 2047;
                const uint4 un = lds4(xa + o), wn = lds4(wa + o);
#pragma unroll
                for (int c = 0; c < 4; c++) {
                    const float a0 = bf_lo((&u.x)[c]), a1 = bf_hi((&u.x)[c]);
                    s1 += a0; s2 = fmaf(a0, a0, s2); sr = fmaf(a0, bf_lo((&w4.x)[c]), sr);
                    s1 += a1; s2 = fmaf(a1, a1, s2); sr = fmaf(a1, bf_hi((&w4.x)[c]), sr);
                }
                u = un; w4 = wn;
            }
#pragma unroll 1
            for (int o = 1; o < 8; o <<= 1) {
                s1 += __shfl_xor_sync(0xffffffffu, s1, o); s2 += __shfl_xor_sync(0xffffffffu, s2, o); sr += __shfl_xor_sync(0xffffffffu, sr, o);
            }
            const float mean = s1 * (1.f / 1024.f), mb = bf16r(mean);
            float var = fmaf(-mean, mean, s2 * (1.f / 1024.f));
            sr = fmaf(-mb, sw, sr);
            if (__builtin_expect(__any_sync(0xffffffffu, mean * mean > 256.f * var), 0)) {
                float a2 = 0.f, ar = 0.f;
#pragma unroll 1
                for (int i = 0; i < 64; i++) {
                    const uint32_t o = (i >> 2) * 128 + (i & 3) * 4, q1 = lds1(xa + o), q2 = lds1(wa + o);
                    a2 = fmaf(bf_lo(q1) - mean, bf_lo(q1) - mean, fmaf(bf_hi(q1) - mean, bf_hi(q1) - mean, a2));
                    ar = fmaf(bf_lo(q1) - mb, bf_lo(q2), fmaf(bf_hi(q1) - mb, bf_hi(q2), ar));
                }
#pragma unroll 1
                for (int o = 1; o < 8; o <<= 1) { a2 += __shfl_xor_sync(0xffffffffu, a2, o); ar += __shfl_xor_sync(0xffffffffu, ar, o); }
                var = a2 * (1.f / 1024.f); sr = ar;
            }
            float den;
            asm("sqrt.approx.f32 %0, %1;" : "=f"(den) : "f"(bf16r(bf16r(var) + 1e-5f)));
            const uint32_t st = pack_bf16(mb, den);
            const uint32_t rb = pack_bf16(0.f, sr * rcp(bf_hi(st)) + 0.f);
            uint32_t ord = (int)rb < 0 ? ~rb & 0xffff0000u : rb | 0x80000000u;
            if ((rb & 0x7fffffffu) > 0x7f800000u) ord = 0;
            if ((lane & 7) == 0) st_rlx2(&scr->row[s], st, ord | ((2047 - s) << 5) | (ep & 31));
            __syncwarp();
            if (lane < 7) mbar_arrive(bars + 8 * (lane < 5 ? B_FEMPTY + lane : B_RDONE));
        }
        TSC(ta == 0, 18);
        if ((b >> 3) == 14) {
            const uint32_t gm = sb + OFF_E, cnt = gm + 64, res = gm + 80, list = gm + 128;
            uint32_t kv[16];
            int tries = BUDGET;
#pragma unroll 1
            do {
                uint32_t bad = 0;
#pragma unroll
                for (int n = 0; n < 16; n++) kv[n] = ld_rlx(&scr->row[n * 128 + ta].y);
#pragma unroll
                for (int n = 0; n < 16; n++) bad |= kv[n] ^ ep;
                if ((bad & 31) == 0) break;
            } while (--tries > 0);
            __syncwarp();
            TSC(ta == 0, 26);
            uint32_t m = 0;
#pragma unroll
            for (int n = 0; n < 16; n++) m = max(m, kv[n]);
            uint32_t gmax = m;
#pragma unroll
            for (int o = 1; o < 8; o <<= 1) gmax = max(gmax, __shfl_xor_sync(0xffffffffu, gmax, o));
            sts1(gm + (ta >> 3) * 4, gmax);
            sts1(cnt, 0);
            bar_sync(12, 128);
            const uint32_t c = lds1(gm + (lane & 15) * 4);
            int rank = 0;
#pragma unroll
            for (int i = 0; i < 2; i++) { const uint4 q = lds4(gm + (lane >> 4) * 32 + i * 16); rank += (q.x > c) + (q.y > c) + (q.z > c) + (q.w > c); }
            rank += __shfl_xor_sync(0xffffffffu, rank, 16);
            const uint32_t thr = redux_max(rank == 7 ? c : 0u);
#pragma unroll 1
            while (m >= thr) {
                uint32_t at, m2 = 0;
                asm volatile("atom.shared.add.u32 %0, [%1], 1;" : "=r"(at) : "r"(cnt) : "memory");
#pragma unroll
                for (int n = 0; n < 16; n++) m2 = max(m2, kv[n] < m ? kv[n] : 0u);
                sts1(list + at * 4, m);
                if (m2 == 0) break;
                m = m2;
            }
            bar_sync(12, 128);
            const int nc = lds1(cnt);
#pragma unroll 1
            for (int i = ta >> 3; i < ((nc + 3) & ~3); i += 16) {
                const uint32_t ki = lds1(list + i * 4);
                int r = 0;
#pragma unroll 1
                for (int n = lane & 7; n < nc; n += 8) r += lds1(list + n * 4) > ki;
                __syncwarp();
#pragma unroll
                for (int o = 1; o < 8; o <<= 1) r += __shfl_xor_sync(0xffffffffu, r, o);
                if (r == (b & 7) && i < nc) sts1(res, ki);
            }
            bar_sync(12, 128);
            const uint32_t k0 = lds1(res);
            const int r0 = 2047 - ((k0 >> 5) & 2047);
            TSC(ta == 0, 22);
            if (ta == 0) st_rlx(&scr->sel[b & 7], k0);
            const uint4 v0 = ldg_nc(x + (size_t)r0 * 1024 + ta * 8);
            const uint32_t s0 = ld_rlx(&scr->row[r0]);
            const float m0 = bf_lo(s0), i0 = rcp(bf_hi(s0));
            const int ao = 14336 + (ta >> 3) * 256 + (b & 7) * 32 + ((ta ^ b) & 7) * 4;
            st_rlx4(scr->act + ao, norm_pair(v0.x, m0, i0), norm_pair(v0.y, m0, i0), norm_pair(v0.z, m0, i0), norm_pair(v0.w, m0, i0));
            bar_sync(12, 128);
            if (ta == 0) { fence_gpu(); red_add(&scr->cnt[8][0]); }
        }
        uint32_t fph = 0, own = 0; float sig = 0.f;
#pragma unroll 1
        for (int ph = 0; ph < 2; ph++) {
            if (ph || b < 112) {
                float acc[4] = {0.f, 0.f, 0.f, 0.f};
                const uint32_t alo = sd + (ph ? dlo(0, 8192) : dlo(0, 4096)), ahi = ph ? dhi(1024, 1) : dhi(512, 2), astep = ph ? 128 : 64;
                const uint32_t bhi = ph ? dhi(128, 0) : dhi(1024, 1), bstep = ph ? 16 : 2;
                const int ns = ph ? 3 : NF1;
                int s = ph, ps = 0, left = BUDGET;
                if (ph) mbar_wait(bars + 8 * FFN2_GATE, 0, left);
                bool rel = false;
#pragma unroll 1
                for (int q = ph ? 7 : 16; q > 0; q--) {
                    const uint32_t so = fslot(s) >> 4, da = alo + so, db = sd + dlo(BOX, 128) + so;
                    mbar_wait_hot(bars + 8 * (B_FFULL + s), (fph >> s) & 1, left);
                    TSC(TIMING % 10 == 3 && ta == 0, 32 + (ph ? 23 : 16) - q);
                    wg_fence();
#pragma unroll
                    for (int j = 0; j < 4; j++) wgmma_n8<1, 0>(acc, mkdesc(da + j * astep, ahi), mkdesc(db + j * bstep, bhi), 1);
                    wg_commit();
                    wg_wait<1>();
                    if (rel) mbar_arrive(bars + 8 * (B_FEMPTY + ps));
                    rel = lane == 0; ps = s;
                    fph ^= 1u << s;
                    if (++s == ns) s = 0;
                }
                wg_wait<0>();
                if (ph == 0) {
                    if (rel) mbar_arrive(bars + 8 * (B_FEMPTY + 15 % NF1));
                    const bool second = (wq >= 2) != (swap_gu != 0);
                    const uint32_t xa = sb + OFF_HIN + 2048 + ((wq & 1) * 32 + lane) * 16;
                    if (second) sts4(xa, __float_as_uint(acc[0]), __float_as_uint(acc[1]), __float_as_uint(acc[2]), __float_as_uint(acc[3]));
                    bar_sync(12, 128);
                    if (!second) {
                        const float4 up = lds4f(xa);
                        float hv[4];
#pragma unroll
                        for (int c = 0; c < 4; c++) { const float ga = bf16r(acc[c]); hv[c] = bf16r(ga * sigmoidf(ga)) * bf16r((&up.x)[c]); }
                        const int ao = (b * 4 + (wq & 1) * 2) * 32 + lane;
                        st_rlx(scr->act + ao, movm(pack_bf16(hv[0], hv[1]))); st_rlx(scr->act + 32 + ao, movm(pack_bf16(hv[2], hv[3])));
                    }
                    bar_sync(12, 128);
                    if (ta == 0) { fence_gpu(); red_add(&scr->cnt[b / 14][0]); }
                } else {
#pragma unroll
                    for (int c = 0; c < 4; c++) st_rlx(&scr->ypart[kc][2 * t + (c & 1)][c2 * 64 + wq * 16 + (c >> 1) * 8 + g], (__float_as_uint(acc[c]) & ~1u) | (ep & 1));
                    if (b == 0 && ta == 0) st_rlx(&scr->epoch[0], ep);
                }
                TSC(ta == 0, 22 + ph);
            }
            if (ph == 0) {
                if ((ta & 126) == 64) mbar_arrive(bars + 8 * B_F1DONE);
                const uint32_t kj = poll_all(&scr->sel[lane & 7], 31u, ep & 31, budget);
                const int row = 2047 - ((kj >> 5) & 2047), jj = (row & 1) == par ? (row >> 1) - j0 : -1;
                sig = bf16r(sigmoidf(__uint_as_float(((int)kj < 0 ? kj & 0x7fffffffu : ~kj) & 0xffff0000u)));
                own = __ballot_sync(0xffffffffu, (jj >> 7) == rh) & 255;
                sts1(sb + OFF_SEL + (lane & 7) * 4, jj);
                sts4(sb + OFF_UPD + ta * 16, 0, 0, 0, 0);
            }
            if ((own != 0) == ph) {
#pragma unroll 1
                for (; own; own &= own - 1) {
                    const int j = __ffs(own) - 1;
                    const uint32_t* src = &scr->ypart[lane >> 3][j][cb * 128 + wq * 32 + (lane & 7) * 4];
                    uint4 v0, v1; int tries = BUDGET;
#pragma unroll 1
                    do { v0 = ld_rlx4(src); v1 = ld_rlx4(src + 4 * 8192); } while ((((v0.x ^ ep) | (v1.x ^ ep)) & 1) && --tries > 0);
                    __syncwarp();
                    float a[4];
                    const float sj = __shfl_sync(0xffffffffu, sig, j);
#pragma unroll
                    for (int c = 0; c < 4; c++) {
                        a[c] = __uint_as_float((&v0.x)[c]) + __uint_as_float((&v1.x)[c]);
                        a[c] += __shfl_xor_sync(0xffffffffu, a[c], 8); a[c] += __shfl_xor_sync(0xffffffffu, a[c], 16);
                        a[c] = bf16r(a[c]) * sj;
                    }
                    sts2(sb + OFF_UPD + (wq >> 1) * 1024 + j * 128 + ((((wq & 1) * 4 + ((lane >> 1) & 3)) ^ j) << 4) + (lane & 1) * 8, pack_bf16(a[0], a[1]), pack_bf16(a[2], a[3]));
                }
                fence_async_smem();
                __syncwarp();
                if (lane < 2) mbar_arrive(bars + 8 * B_UPD);
            }
        }
        TSC(ta == 0, 24);
    } else {
        reg_inc<224>();
        const int w = warp >> 2, wi = warp & 3, g = lane >> 2, t = lane & 3;
        const bool elect = (tid & 127) == 0;
        const uint32_t mad = (lane & 15) * 128 + (((lane >> 4) ^ (lane & 7)) << 4);
        float acc[64];
        const uint32_t ring = sb + w * OFF_X1, ofull = bars + 8 * (B_OFULL + w * 6), oempty = mapa(bars + 8 * B_OEMPTY, w);
        const int r0 = rh * 128 + wi * 32 + (1 - w) * 16 + g;
        {
            float acc0[96], acc1[96];
            const uint32_t sta = sb + OFF_STAT + (8 + w * 128 + wi * 32) * 8;
            {
                const uint32_t xfull = bars + 8 * (B_XFULL + w * 6), xempty = mapa(bars + 8 * B_XEMPTY, w), dx0 = sd + dlo(w * OFF_X1, 16);
                int j = 0, pj = 0, ws = 2, pws = 0; uint32_t xph = 0;
                cluster_wait();
#pragma unroll 1
                for (int k = 0;; k++) {
                    const uint32_t dx = dx0 + j * (BOX >> 4), dw = sd + dlo(OFF_W, BOX) + ws * (W_BYTES >> 4);
                    mbar_wait(bars + 8 * (B_WFULL + ws), xph, budget);
                    mbar_wait(xfull + 8 * j, xph, budget);
                    TSC(elect && k == 0, 1 + 8 * w);
                    TSC(TIMING % 10 == 1 && tid == 0, 32 + k);
                    wg_wait<0>();
                    wg_fence();
#pragma unroll
                    for (int kk = 0; kk < 4; kk++) wgmma_n192<0, 1>(acc1, mkdesc(dx + kk * 2, dhi(1024, 1)), mkdesc(dw + kk * 128, dhi(1024, 1)), kk ? 1 : k);
                    wg_commit();
                    if (elect && k > 0) {
                        mbar_arrive(bars + 8 * (B_WEMPTY + pws));
                        if (k <= 13) { mbar_expect_tx(xfull + 8 * pj, BOX); mbar_arrive_at(xempty + 8 * pj); }
                    }
                    if (k == 15) break;
                    mbar_wait(xfull + 8 * j + 8, xph, budget);
                    wg_wait<0>();
                    wg_fence();
#pragma unroll
                    for (int kk = 0; kk < 4; kk++) wgmma_n192<0, 1>(acc0, mkdesc(dx + 512 + kk * 2, dhi(1024, 1)), mkdesc(dw + kk * 128, dhi(1024, 1)), kk ? 1 : k);
                    wg_commit();
                    if (elect && k <= 12) { mbar_expect_tx(xfull + 8 * j, BOX); mbar_arrive_at(xempty + 8 * j); }
                    pj = j + 1; pws = ws;
                    if (++ws == 3) ws = 0;
                    j += 2;
                    if (j == 6) { j = 0; xph ^= 1; }
                }
            }
            mbar_wait(bars + 8 * B_AUX, 0, budget);
            const uint32_t zero = budget >> 30, pm = t & 1 ? 0x4432 : 0x3232, ra = sta + ((t >> 1) * 16 + g) * 8;
            const uint32_t a0 = __byte_perm(lds1(ra), 0, pm), a1 = __byte_perm(lds1(ra + 64), 0, pm), a2 = a0 & zero, a3 = a1 & zero;
            wg_fence();
            wgmma_rs_n192(acc1, a0, a1, a2, a3, mkdesc(sd + dlo(OFF_CS, 0), dhi(128, 0)));
            wg_commit();
            const bool u0 = 2 * t > g, u1 = 2 * t + 1 > g;
            uint32_t mU = (u0 ? 0xffffu : 0u) | (u1 ? 0xffff0000u : 0u);
            uint32_t ka0 = sta + (2 * t - (u0 ? 8 : 0)) * 8 + 4, ka1 = sta + (2 * t + 1 - (u1 ? 8 : 0)) * 8 + 4;
            float rk[2][4], fu[2][4], fn[2][4];
            auto factors = [&](int h) {
#pragma unroll
                for (int n = 0; n < 4; n += 2) {
                    const float rq = lds1f(sta + (16 * h + 4 * n + g) * 8 + 4) * (0.17677669529663687f * 1.4426950408889634f);
                    rk[h][n] = lds1f(ka0 + h * 128 + n * 32); rk[h][n + 1] = lds1f(ka1 + h * 128 + n * 32);
                    const float f0 = rq * rk[h][n], f1 = rq * rk[h][n + 1];
                    fu[h][n] = u0 ? f0 : 0.f; fn[h][n] = f0 - fu[h][n]; fu[h][n + 1] = u1 ? f1 : 0.f; fn[h][n + 1] = f1 - fu[h][n + 1];
                }
#pragma unroll
                for (int n = 0; n < 4; n++) asm volatile("" : "+f"(fu[h][n]), "+f"(fn[h][n]));
            };
            uint8_t* og = scr->o + ((size_t)(mt * 4 + w * 2) * 16 + nt) * BOX + wi * 256 + lane * 4;
            asm volatile("" : "+r"(ka0), "+r"(ka1));
            mbar_wait(bars + 8 * (B_XFULL + w * 6 + 1), 1, budget);
            wg_wait<0>();
            wg_fence();
#pragma unroll
            for (int kk = 0; kk < 4; kk++)
                wgmma_n192<0, 1>(acc0, mkdesc(sd + dlo(w * OFF_X1 + BOX, 16) + kk * 2, dhi(1024, 1)), mkdesc(sd + dlo(OFF_W + 2 * W_BYTES, BOX) + kk * 128, dhi(1024, 1)), 1);
            wgmma_rs_n192(acc0, a0, a1, a2, a3, mkdesc(sd + dlo(OFF_CS + 64, 0), dhi(128, 0)));
            wg_commit();
            TSC(elect, 19 + w);
            uint32_t pk0[48], pk1[48], o[16] = {};
#pragma unroll
            for (int j = 0; j < 48; j++) if (j < 16 || (j & 1)) pk1[j] = pack_here(acc1[2 * j], acc1[2 * j + 1]);
            if (warp < 7) {
#pragma unroll
                for (int c = 0; c < 4; c++) stsm4(ring + wi * 2048 + c * 512 + lane * 16, pk1[17 + 8 * c], pk1[19 + 8 * c], pk1[21 + 8 * c], pk1[23 + 8 * c]);
                bar_arrive(1 + warp, 64);
            } else if (j0 != 768) {
#pragma unroll
                for (int c = 0; c < 4; c++) {
                    pk1[17 + 8 * c] = max(pk1[17 + 8 * c], 1u);
                    st_rlx4(&scr->halo[b][c * 128 + lane * 4], pk1[17 + 8 * c], pk1[19 + 8 * c], pk1[21 + 8 * c], pk1[23 + 8 * c]);
                }
            }
            TSC(tid == 224, 28);
#pragma unroll
            for (int j = 16; j < 48; j += 2) pk1[j] = pack_here(acc1[2 * j], acc1[2 * j + 1]);
            factors(1);
            uint32_t od = sb + 2 * BOX + wi * 256 + (lane >> 4) * 1024 + (lane & 15) * 16, g1peer = mapa(bars + 8 * B_G1DONE, hp ^ 1);
            uint32_t ha = sb + (warp == 0 ? OFF_HIN : warp <= 4 ? -2048 : OFF_X1 - 5 * 2048) + warp * 2048 + lane * 16;
            const bool first = warp == 0 && j0 == 0;
            float bias0 = first && u0 ? -INFINITY : 0.f, bias1 = first && u1 ? -INFINITY : 0.f;
            float ci[4];
#pragma unroll
            for (int n = 0; n < 4; n++) ci[n] = __uint_as_float((0x03800000u + n) | zero);
            asm volatile("" : "+f"(ci[0]), "+f"(ci[1]), "+f"(ci[2]), "+f"(ci[3]));
            asm volatile("" : "+l"(og), "+r"(mU), "+r"(od), "+r"(ha), "+f"(bias0), "+f"(bias1));
            mbar_wait(bars + 8 * (B_WEMPTY + 1), 0, budget);
            wg_wait<0>();
            if (elect) { mbar_arrive(bars + 8 * B_G1DONE); mbar_arrive_at(g1peer); }
            TSC(elect, 2 + 8 * w);
            auto hand_over = [&](int v) {
                asm volatile("{\n.reg .pred p;\nsetp.ne.b32 p, %17, 0;\n"
                             "@p stmatrix.sync.aligned.m8n8.x4.shared.b16 [%16], {%0,%1,%2,%3};\n@p stmatrix.sync.aligned.m8n8.x4.shared.b16 [%16 + 2048], {%4,%5,%6,%7};\n"
                             "@p stmatrix.sync.aligned.m8n8.x4.shared.b16 [%16 + 4096], {%8,%9,%10,%11};\n@p stmatrix.sync.aligned.m8n8.x4.shared.b16 [%16 + 6144], {%12,%13,%14,%15};\n"
                             "fence.proxy.async.shared::cta;\n}"
                             ::"r"(o[0]), "r"(o[1]), "r"(o[2]), "r"(o[3]), "r"(o[4]), "r"(o[5]), "r"(o[6]), "r"(o[7]), "r"(o[8]), "r"(o[9]), "r"(o[10]), "r"(o[11]),
                               "r"(o[12]), "r"(o[13]), "r"(o[14]), "r"(o[15]), "r"(od + v * OFF_X1), "r"((int)(w == rh)) : "memory");
#pragma unroll
                for (int i = 0; i < 16; i++) asm volatile("st.global.u32 [%0], %1;" ::"l"(og + (1 - v) * 16 * BOX + (i >> 1) * 1024 + (i & 1) * 128), "r"(o[i]) : "memory");
                __syncwarp();
                if (lane == 0) mbar_arrive(bars + 8 * (B_STAGED + v));
            };
#pragma unroll
            for (int j = 32; j < 48; j++) pk1[j] = movm(pk1[j]);
#pragma unroll
            for (int j = 17; j < 48; j += 2) pk0[j] = pack_here(acc0[2 * j], acc0[2 * j + 1]);
#pragma unroll
            for (int j = 33; j < 48; j += 2) pk0[j] = movm(pk0[j]);
            factors(0);
            const float2 s0 = lds2f(sb + OFF_STAT + (8 + r0) * 8), s1 = lds2f(sb + OFF_STAT + (16 + r0) * 8);
            const float m0 = s0.x * s0.y, f0 = 1.f + s0.y, m1 = s1.x * s1.y, f1 = 1.f + s1.y;
            attn_pair<2>(pk1, pk1 + 16, pk1 + 32, pk0 + 17, pk0 + 33, fu[1], fn[1], rk[1], 0.f, 0.f, mU, zero, ci, o);
            hand_over(0);
            TSC(elect, 3 + 8 * w);
#pragma unroll
            for (int j = 0; j < 48; j++) if (j < 16 || !(j & 1)) pk0[j] = pack_here(acc0[2 * j], acc0[2 * j + 1]);
#pragma unroll
            for (int j = 32; j < 48; j += 2) pk0[j] = movm(pk0[j]);
            mbar_wait_hot(bars + 8 * B_XT, 0, budget);
#pragma unroll
            for (int j = 0; j < 8; j++) {
                uint32_t a[4];
                ldsm4(a, ((ring + wi * 2048 + mad) ^ ((j & 3) * 32)) + (4 + (j >> 2)) * BOX);
                acc[8 * j + 0] = fmaf(bf_lo(a[0]), f0, m0); acc[8 * j + 1] = fmaf(bf_hi(a[0]), f0, m0);
                acc[8 * j + 2] = fmaf(bf_lo(a[1]), f1, m1); acc[8 * j + 3] = fmaf(bf_hi(a[1]), f1, m1);
                acc[8 * j + 4] = fmaf(bf_lo(a[2]), f0, m0); acc[8 * j + 5] = fmaf(bf_hi(a[2]), f0, m0);
                acc[8 * j + 6] = fmaf(bf_lo(a[3]), f1, m1); acc[8 * j + 7] = fmaf(bf_hi(a[3]), f1, m1);
            }
            bar_sync(warp ? warp : 11, 64);
            uint32_t hl[16];
            ldsm4t(hl + 8, ha + 1024); ldsm4t(hl + 12, ha + 1536); ldsm4(hl, ha); ldsm4(hl + 4, ha + 512);
            __syncwarp();
            if (lane == 0) mbar_arrive(bars + 8 * B_FREED);
            attn_pair<1>(pk0, pk0 + 16, pk0 + 32, hl, hl + 8, fu[0], fn[0], rk[0], bias0, bias1, mU, zero, ci, o);
            hand_over(1);
        }
        TSC(tid == 0, 4);
        {
            const uint32_t da0 = sd + dlo(w * OFF_X1, 1024), db0 = sd + dlo(OFF_WO, BOX);
            const uint32_t chk = ring + wi * 256 + (lane >> 3) * 1032 + (lane & 7) * 32 + (lane & 4);
            uint32_t s8 = 16, ps8 = 0, ph = 0;
#pragma unroll 1
            for (int i = 0; i < 16; i++) {
                mbar_wait_hot(ofull + s8, ph, budget);
                const uint32_t seen0 = lds1(chk + s8 * (BOX / 8)), seen1 = lds1(chk + s8 * (BOX / 8) + 4096);
                mbar_wait_hot(bars + 8 * B_WOFULL + s8, ph, budget);
                if (__builtin_expect(__any_sync(0xffffffffu, min(seen0, seen1) == 0), 0)) {
                    const uint32_t at = wi * 256 + (lane >> 4) * 1024 + (lane & 15) * 16;
                    const uint8_t* src = scr->o + ((size_t)((mt * 2 + rh) * 2 + 1 - w) * 16 + ((2 * p + (i < 2 ? i ^ hp : i)) & 15)) * BOX + at;
#pragma unroll 1
                    for (int n = 0; n < 8192; n += 2048) {
                        uint4 v; int tries = 4096;
#pragma unroll 1
                        do { v = ld_rlx4(src + n); } while (v.x == 0 && --tries > 0);
                        sts4(ring + s8 * (BOX / 8) + at + n, v.x, v.y, v.z, v.w);
                    }
                    NRETRY();
                    fence_async_smem();
                    __syncwarp();
                }
                TSC(TIMING % 10 == 1 && tid == 0, 48 + i);
                TSC(TIMING % 10 == 2 && elect, 32 + w * 16 + i);
                const uint32_t da = da0 + s8 * (BOX >> 7), db = db0 + s8 * (BOX >> 6);
                wg_wait<1>();
                wg_fence();
#pragma unroll
                for (int kk = 0; kk < 4; kk++) {
                    wgmma_n128<0, 1>(acc, mkdesc(da + kk * 128, dhi(128, 0)), mkdesc(db + kk * 128, dhi(1024, 1)), 1);
                    if (kk & 1) wg_commit();
                }
                wg_wait<2>();
                if (elect && (unsigned)(i - 1) < 10) { mbar_expect_tx(ofull + ps8, BOX); mbar_arrive_at(oempty + ps8); mbar_arrive(bars + 8 * B_WOEMPTY + ps8); }
                ps8 = s8;
                s8 = s8 == 40 ? 0 : s8 + 8;
                if (s8 == 16) ph ^= 1;
            }
            mbar_wait(bars + 8 * B_UPD, 0, budget);
            const float2 sl = lds2f(sb + OFF_SEL + t * 8);
            const int d0 = __float_as_int(sl.x) - r0, d1 = __float_as_int(sl.y) - r0;
            const uint32_t a0 = (d0 == 0 ? 0x3f80u : 0u) | (d1 == 0 ? 0x3f800000u : 0u), a1 = (d0 == 8 ? 0x3f80u : 0u) | (d1 == 8 ? 0x3f800000u : 0u);
            wg_fence();
            wgmma_rs_n128(acc, a0, a1, 0u, 0u, mkdesc(sd + dlo(OFF_UPD, 1024), dhi(0, 1)));
            wg_commit();
            wg_wait<0>();
            TSC(elect, 7 + 9 * w);
            const uint32_t os0 = ring + wi * 4096;
#pragma unroll
            for (int j = 0; j < 8; j++)
                stsm4(((os0 + mad) ^ ((j & 3) * 32)) + (j >> 2) * 2048, pack_bf16(acc[8 * j], acc[8 * j + 1]), pack_bf16(acc[8 * j + 2], acc[8 * j + 3]),
                      pack_bf16(acc[8 * j + 4], acc[8 * j + 5]), pack_bf16(acc[8 * j + 6], acc[8 * j + 7]));
            fence_async_smem();
            __syncwarp();
            if (elect_one()) {
                asm volatile("cp.async.bulk.tensor.5d.global.shared::cta.bulk_group [%0, {%2, %2, %3, %4, %5}], [%1];\ncp.async.bulk.commit_group;\ncp.async.bulk.wait_group.read 0;"
                             ::"l"(&mout), "r"(os0), "r"(0), "r"(((j0 + rh * 128) >> 5) + wi), "r"(1 - w), "r"(par * 16 + cb * 2) : "memory");
            }
            TSC(elect, 8 - 2 * w);
            TS_END();
        }
    }
}

typedef CUresult (*EncodeFn)(CUtensorMap*, CUtensorMapDataType, cuuint32_t, void*, const cuuint64_t*, const cuuint64_t*, const cuuint32_t*,
                             const cuuint32_t*, CUtensorMapInterleave, CUtensorMapSwizzle, CUtensorMapL2promotion, CUtensorMapFloatOOBfill);

CUtensorMap make_map(EncodeFn fn, const void* base, int rank, const cuuint64_t* dims, const cuuint64_t* strides, const cuuint32_t* box,
                     CUtensorMapSwizzle swz = CU_TENSOR_MAP_SWIZZLE_128B, CUtensorMapL2promotion pro = CU_TENSOR_MAP_L2_PROMOTION_L2_256B) {
    CUtensorMap m;
    cuuint32_t es[5] = {1, 1, 1, 1, 1};
    fn(&m, CU_TENSOR_MAP_DATA_TYPE_BFLOAT16, rank, (void*)base, dims, strides, box, es, CU_TENSOR_MAP_INTERLEAVE_NONE,
       swz, pro, CU_TENSOR_MAP_FLOAT_OOB_FILL_NONE);
    return m;
}

}

extern "C" void kernel_launch(void* const* d_in, const int* in_sizes, int n_in, void* d_out, int out_size) {
    (void)in_sizes; (void)n_in; (void)out_size;
    const __nv_bfloat16* x = (const __nv_bfloat16*)d_in[0];
    const __nv_bfloat16* wqkv = (const __nv_bfloat16*)d_in[1];
    const __nv_bfloat16* wo = (const __nv_bfloat16*)d_in[2];
    const __nv_bfloat16* wr = (const __nv_bfloat16*)d_in[4];
    const __nv_bfloat16* wg = (const __nv_bfloat16*)d_in[5];
    const __nv_bfloat16* wu = (const __nv_bfloat16*)d_in[6];
    const __nv_bfloat16* wd = (const __nv_bfloat16*)d_in[7];
    static EncodeFn fn = nullptr;
    static Scratch* scr = nullptr;
    if (!fn) {
        void* p = nullptr; cudaDriverEntryPointQueryResult q;
        cudaGetDriverEntryPoint("cuTensorMapEncodeTiled", &p, cudaEnableDefault, &q);
        fn = (EncodeFn)p;
        cudaFuncSetAttribute(fused_kernel, cudaFuncAttributeMaxDynamicSharedMemorySize, SMEM_LAUNCH);
        cudaGetSymbolAddress((void**)&scr, g_scr);
    }
    const cuuint64_t xd[4] = {2048, 16, 32, 2}, xs[4] = {4096, 131072, 65536, 128}, od[5] = {64, 16, 32, 2, 32};
    const cuuint32_t xb[4] = {64, 16, 4, 1}, ob[5] = {64, 16, 1, 1, 2};
    const cuuint64_t wdm[3] = {1024, 1024, 3}, wst[2] = {6144, 2048};
    const cuuint32_t wb[3] = {64, 64, 3};
    const cuuint64_t wod[3] = {64, 1024, 16}, wdd[3] = {64, 3584, 16}, wos[2] = {2048, 128};
    const cuuint32_t wob[3] = {64, 64, 2}, wdb[3] = {64, 64, 1};
    CUtensorMap mx = make_map(fn, x, 4, xd, xs, xb), mw = make_map(fn, wqkv, 3, wdm, wst, wb);
    CUtensorMap mwo = make_map(fn, wo, 3, wod, wos, wob), mout = make_map(fn, d_out, 5, od, xs, ob);
    const int swap_gu = wu < wg;
    const cuuint64_t gd[3] = {3584, 1024, 2}, gst[2] = {7168, (cuuint64_t)(swap_gu ? (const char*)wg - (const char*)wu : (const char*)wu - (const char*)wg)};
    const cuuint32_t gb[3] = {32, 64, 2};
    CUtensorMap mgu = make_map(fn, swap_gu ? wu : wg, 3, gd, gst, gb, CU_TENSOR_MAP_SWIZZLE_64B, CU_TENSOR_MAP_L2_PROMOTION_L2_128B);
    CUtensorMap mwd = make_map(fn, wd, 3, wdd, wos, wdb, CU_TENSOR_MAP_SWIZZLE_128B, CU_TENSOR_MAP_L2_PROMOTION_L2_128B);
    const cuuint64_t md[2] = {64, 32768}, ms[1] = {128};
    const cuuint32_t mb[2] = {64, 64};
    CUtensorMap mo = make_map(fn, scr, 2, md, ms, mb, CU_TENSOR_MAP_SWIZZLE_NONE, CU_TENSOR_MAP_L2_PROMOTION_NONE);
    cudaLaunchConfig_t cfg = {};
    cfg.gridDim = dim3(132); cfg.blockDim = dim3(512); cfg.dynamicSmemBytes = SMEM_LAUNCH; cfg.stream = cudaStreamPerThread;
    cudaLaunchAttribute at[1];
    at[0].id = cudaLaunchAttributeClusterDimension; at[0].val.clusterDim.x = 2; at[0].val.clusterDim.y = 1; at[0].val.clusterDim.z = 1;
    cfg.attrs = at; cfg.numAttrs = 1;
    cudaLaunchKernelEx(&cfg, fused_kernel, mx, mw, mwo, mout, mgu, mwd, mo, x, wr, scr, swap_gu, Weights{(const char*)wqkv, (const char*)wo, (const char*)wg, (const char*)wu, (const char*)wd});
}
```

```cpp
#include <cuda_runtime.h>
#include <cuda.h>
#include <cuda_bf16.h>
#include <stdint.h>

namespace {

constexpr int BOX = 8192, W_BYTES = 3 * BOX;
constexpr int OFF_E = 6 * BOX, OFF_W = 9 * BOX, OFF_X1 = 18 * BOX;
constexpr int OFF_WO = 6 * BOX;
constexpr int F_BYTES = 9216;
constexpr int OFF_FR = 24 * BOX;
constexpr int CS_BYTES = 3136;
constexpr int OFF_CS = OFF_E + 2 * F_BYTES;
constexpr int OFF_UPD = OFF_FR + 3 * F_BYTES;
constexpr int OFF_HIN = OFF_UPD + 2048;
constexpr int OFF_STAT = OFF_FR + 32768;
constexpr int OFF_SEL = OFF_STAT + 2112;
constexpr int OFF_EP = OFF_SEL + 32;
constexpr int OFF_BAR = OFF_EP + 16;
constexpr int B_WFULL = 0, B_XFULL = 3, B_AUX = 15, B_XT = 16, B_WOFULL = 18, B_OFULL = 24, B_FFULL = 36, B_ROW = 41;
constexpr int B_WEMPTY = 42, B_F1DONE = 45, B_XEMPTY = 46, B_WOEMPTY = 52, B_OEMPTY = 58;
constexpr int B_G1DONE = 66, B_FEMPTY = 67, B_STAGED = 72, B_UPD = 74, B_RDONE = 75, B_FREED = 76, NBAR = 78;
__device__ __forceinline__ uint32_t fslot(int s) { return s * F_BYTES + (s < 3 ? OFF_FR : OFF_E - 3 * F_BYTES); }
constexpr int SMEM_BYTES = OFF_BAR + NBAR * 8;
static_assert(OFF_HIN + 3072 <= OFF_STAT && OFF_CS + CS_BYTES <= OFF_W && SMEM_BYTES + 256 <= 232448 && OFF_BAR % 8 == 0 && OFF_UPD % 1024 == 0, "smem");
#define POLL_NS 100
#define HELP_AT 64
#define NF1 5
#define PF_RATE 10
#define PF_START 7
#define ZF_NS 100
#define FFN2_GATE B_G1DONE
#define PF_NW 6
#define PF_D 8
#define ROWS_AT 7
#define STATS_UNROLL 1
constexpr int kStatsUnroll = STATS_UNROLL;
constexpr int BUDGET = 1 << 18;

struct Scratch {
    uint8_t o[2048 * 1024 * 2];
    uint32_t ypart[8][8][1024];
    uint32_t halo[128][512];
    uint32_t act[14336 + 4096];
    uint2 row[2048];
    uint32_t cs[16][800];
    uint32_t oflag[16][32];
    uint32_t cnt[9][32];
    uint32_t sel[32], csflag[32], epoch[32];
};
__device__ __align__(1024) Scratch g_scr;
struct Weights { const char *wqkv, *wo, *wg, *wu, *wd; };

#define TS(i) do {} while (0)
#define TS_END() do {} while (0)
#define TSC(c, i) do {} while (0)
#define NRETRY() do {} while (0)
constexpr int SMEM_LAUNCH = SMEM_BYTES;
__device__ __forceinline__ uint32_t smem_u32(const void* p) { return (uint32_t)__cvta_generic_to_shared(p); }
__device__ __forceinline__ void mbar_init(uint32_t bar, uint32_t cnt) { asm volatile("mbarrier.init.shared::cta.b64 [%0], %1;" ::"r"(bar), "r"(cnt) : "memory"); }
__device__ __forceinline__ void mbar_expect_tx(uint32_t bar, uint32_t bytes) { asm volatile("mbarrier.arrive.expect_tx.shared::cta.b64 _, [%0], %1;" ::"r"(bar), "r"(bytes) : "memory"); }
__device__ __forceinline__ void mbar_arrive(uint32_t bar) { asm volatile("mbarrier.arrive.shared::cta.b64 _, [%0];" ::"r"(bar) : "memory"); }
__device__ __forceinline__ uint32_t mapa(uint32_t a, uint32_t cta) { uint32_t r; asm("mapa.shared::cluster.u32 %0, %1, %2;" : "=r"(r) : "r"(a), "r"(cta)); return r; }
__device__ __forceinline__ void mbar_arrive_at(uint32_t cbar) { asm volatile("mbarrier.arrive.shared::cluster.b64 _, [%0];" ::"r"(cbar) : "memory"); }
__device__ __forceinline__ void mbar_wait(uint32_t bar, uint32_t parity, int& budget) {
    asm volatile("{\n.reg .pred p;\nLAB_WAIT:\nmbarrier.try_wait.parity.shared::cta.b64 p, [%1], %2;\n"
                 "add.s32 %0, %0, -1;\nsetp.gt.and.s32 p, %0, 0, !p;\n@p bra LAB_WAIT;\n}" : "+r"(budget) : "r"(bar), "r"(parity) : "memory");
}
__device__ __forceinline__ void mbar_wait_hot(uint32_t bar, uint32_t parity, int& budget) {
    asm volatile("{\n.reg .pred p;\nmbarrier.try_wait.parity.shared::cta.b64 p, [%1], %2;\n@p bra LAB_DONE;\nLAB_WAIT:\nmbarrier.try_wait.parity.shared::cta.b64 p, [%1], %2;\n"
                 "add.s32 %0, %0, -1;\nsetp.gt.and.s32 p, %0, 0, !p;\n@p bra LAB_WAIT;\nLAB_DONE:\n}" : "+r"(budget) : "r"(bar), "r"(parity) : "memory");
}
__device__ __forceinline__ void tma_2d_mc(uint32_t dst, const CUtensorMap* m, uint32_t bar, int c0, int c1) {
    asm volatile("cp.async.bulk.tensor.2d.shared::cluster.global.mbarrier::complete_tx::bytes.multicast::cluster [%0], [%1, {%3, %4}], [%2], %5;" ::"r"(dst), "l"(m), "r"(bar), "r"(c0), "r"(c1), "h"((uint16_t)3) : "memory");
}
__device__ __forceinline__ void tma_3d(uint32_t dst, const CUtensorMap* m, uint32_t bar, int c0, int c1, int c2) {
    asm volatile("cp.async.bulk.tensor.3d.shared::cluster.global.mbarrier::complete_tx::bytes [%0], [%1, {%3, %4, %5}], [%2];" ::"r"(dst), "l"(m), "r"(bar), "r"(c0), "r"(c1), "r"(c2) : "memory");
}
__device__ __forceinline__ void tma_4d(uint32_t dst, const CUtensorMap* m, uint32_t bar, int c0, int c1, int c2, int c3) {
    asm volatile("cp.async.bulk.tensor.4d.shared::cluster.global.mbarrier::complete_tx::bytes [%0], [%1, {%3, %4, %5, %6}], [%2];" ::"r"(dst), "l"(m), "r"(bar), "r"(c0), "r"(c1), "r"(c2), "r"(c3) : "memory");
}
__device__ __forceinline__ void tma_4d_mc(uint32_t dst, const CUtensorMap* m, uint32_t bar, int c0, int c1, int c2, int c3) {
    asm volatile("cp.async.bulk.tensor.4d.shared::cluster.global.mbarrier::complete_tx::bytes.multicast::cluster [%0], [%1, {%3, %4, %5, %6}], [%2], %7;" ::"r"(dst), "l"(m), "r"(bar), "r"(c0), "r"(c1), "r"(c2), "r"(c3), "h"((uint16_t)3) : "memory");
}
__device__ __forceinline__ void bulk_pf(const void* p, uint32_t bytes) { asm volatile("cp.async.bulk.prefetch.L2.global [%0], %1;" ::"l"(p), "r"(bytes) : "memory"); }
__device__ __forceinline__ void bulk_g2s(uint32_t dst, const void* src, uint32_t bytes, uint32_t bar) {
    asm volatile("cp.async.bulk.shared::cluster.global.mbarrier::complete_tx::bytes [%0], [%1], %2, [%3];" ::"r"(dst), "l"(src), "r"(bytes), "r"(bar) : "memory");
}
__device__ __forceinline__ void bulk_s2c(uint32_t cdst, uint32_t src, uint32_t bytes, uint32_t cbar) {
    asm volatile("cp.async.bulk.shared::cluster.shared::cta.mbarrier::complete_tx::bytes [%0], [%1], %2, [%3];" ::"r"(cdst), "r"(src), "r"(bytes), "r"(cbar) : "memory");
}
__device__ __forceinline__ void cluster_wait() { asm volatile("barrier.cluster.wait.aligned;" ::: "memory"); }
__device__ __forceinline__ void fence_gpu() { asm volatile("fence.acq_rel.gpu;" ::: "memory"); }
__device__ __forceinline__ void fence_async_smem() { asm volatile("fence.proxy.async.shared::cta;" ::: "memory"); }
__device__ __forceinline__ void fence_async_gmem() { asm volatile("fence.proxy.async.global;" ::: "memory"); }
__device__ __forceinline__ void wg_fence() { asm volatile("wgmma.fence.sync.aligned;" ::: "memory"); }
__device__ __forceinline__ void wg_commit() { asm volatile("wgmma.commit_group.sync.aligned;" ::: "memory"); }
template <int N> __device__ __forceinline__ void wg_wait() { asm volatile("wgmma.wait_group.sync.aligned %0;" ::"n"(N) : "memory"); }
__device__ __forceinline__ uint64_t mkdesc(uint32_t lo, uint32_t hi) { return ((uint64_t)hi << 32) | lo; }
__host__ __device__ constexpr uint32_t dhi(uint32_t sbo, uint32_t mode) { return (sbo >> 4) | (mode << 30); }
__host__ __device__ constexpr uint32_t dlo(uint32_t off, uint32_t lbo) { return (off >> 4) + ((lbo >> 4) << 16); }
__device__ __forceinline__ bool elect_one() {
    uint32_t e;
    asm volatile("{\n.reg .pred p;\nelect.sync _|p, 0xffffffff;\nselp.u32 %0, 1, 0, p;\n}" : "=r"(e));
    return e;
}
template <int R> __device__ __forceinline__ void reg_inc() { asm volatile("setmaxnreg.inc.sync.aligned.u32 %0;" ::"n"(R)); }
template <int R> __device__ __forceinline__ void reg_dec() { asm volatile("setmaxnreg.dec.sync.aligned.u32 %0;" ::"n"(R)); }
__device__ __forceinline__ void bar_sync(int id, int n) { asm volatile("bar.sync %0, %1;" ::"r"(id), "r"(n) : "memory"); }
__device__ __forceinline__ void bar_arrive(int id, int n) { asm volatile("bar.arrive %0, %1;" ::"r"(id), "r"(n) : "memory"); }
__device__ __forceinline__ uint32_t pack_bf16(float lo, float hi) { uint32_t r; asm("cvt.rn.bf16x2.f32 %0, %1, %2;" : "=r"(r) : "f"(hi), "f"(lo)); return r; }
__device__ __forceinline__ uint32_t pack_here(float lo, float hi) { uint32_t r; asm volatile("cvt.rn.bf16x2.f32 %0, %1, %2;" : "=r"(r) : "f"(hi), "f"(lo)); return r; }
__device__ __forceinline__ float bf_lo(uint32_t u) { return __uint_as_float(u << 16); }
__device__ __forceinline__ float bf_hi(uint32_t u) { return __uint_as_float(u & 0xffff0000u); }
__device__ __forceinline__ float bf16r(float v) { return bf_lo(pack_bf16(v, 0.f)); }
__device__ __forceinline__ float rcp(float x) { float r; asm("rcp.approx.ftz.f32 %0, %1;" : "=f"(r) : "f"(x)); return r; }
__device__ __forceinline__ float ex2(float x) { float r; asm("ex2.approx.ftz.f32 %0, %1;" : "=f"(r) : "f"(x)); return r; }
__device__ __forceinline__ float sigmoidf(float v) { return rcp(1.f + ex2(v * -1.4426950408889634f)); }
__device__ __forceinline__ uint32_t movm(uint32_t a) { uint32_t d; asm volatile("movmatrix.sync.aligned.m8n8.trans.b16 %0, %1;" : "=r"(d) : "r"(a)); return d; }
__device__ __forceinline__ void mma16816(float (&c)[4], uint32_t a0, uint32_t a1, uint32_t a2, uint32_t a3, uint32_t b0, uint32_t b1) {
    asm volatile("mma.sync.aligned.m16n8k16.row.col.f32.bf16.bf16.f32 {%0,%1,%2,%3}, {%4,%5,%6,%7}, {%8,%9}, {%0,%1,%2,%3};"
                 : "+f"(c[0]), "+f"(c[1]), "+f"(c[2]), "+f"(c[3]) : "r"(a0), "r"(a1), "r"(a2), "r"(a3), "r"(b0), "r"(b1));
}
__device__ __forceinline__ void mma1688(float (&c)[4], uint32_t a0, uint32_t a1, uint32_t b0) {
    asm volatile("mma.sync.aligned.m16n8k8.row.col.f32.bf16.bf16.f32 {%0,%1,%2,%3}, {%4,%5}, {%6}, {%0,%1,%2,%3};"
                 : "+f"(c[0]), "+f"(c[1]), "+f"(c[2]), "+f"(c[3]) : "r"(a0), "r"(a1), "r"(b0));
}
__device__ __forceinline__ void stsm4(uint32_t a, uint32_t r0, uint32_t r1, uint32_t r2, uint32_t r3) {
    asm volatile("stmatrix.sync.aligned.m8n8.x4.shared.b16 [%0], {%1,%2,%3,%4};" ::"r"(a), "r"(r0), "r"(r1), "r"(r2), "r"(r3) : "memory");
}
__device__ __forceinline__ void ldsm4(uint32_t* r, uint32_t a) {
    asm volatile("ldmatrix.sync.aligned.m8n8.x4.shared.b16 {%0,%1,%2,%3}, [%4];" : "=r"(r[0]), "=r"(r[1]), "=r"(r[2]), "=r"(r[3]) : "r"(a) : "memory");
}
__device__ __forceinline__ void ldsm4t(uint32_t* r, uint32_t a) {
    asm volatile("ldmatrix.sync.aligned.m8n8.x4.trans.shared.b16 {%0,%1,%2,%3}, [%4];" : "=r"(r[0]), "=r"(r[1]), "=r"(r[2]), "=r"(r[3]) : "r"(a) : "memory");
}
__device__ __forceinline__ uint32_t ld_rlx(const void* p) { uint32_t v; asm volatile("ld.relaxed.gpu.global.u32 %0, [%1];" : "=r"(v) : "l"(p) : "memory"); return v; }
__device__ __forceinline__ uint32_t ld_acq(const void* p) { uint32_t v; asm volatile("ld.acquire.gpu.global.u32 %0, [%1];" : "=r"(v) : "l"(p) : "memory"); return v; }
__device__ __forceinline__ uint2 ld_rlx2(const void* p) { uint2 v; asm volatile("ld.relaxed.gpu.global.v2.u32 {%0,%1}, [%2];" : "=r"(v.x), "=r"(v.y) : "l"(p) : "memory"); return v; }
__device__ __forceinline__ uint4 ld_rlx4(const void* p) { uint4 v; asm volatile("ld.relaxed.gpu.global.v4.u32 {%0,%1,%2,%3}, [%4];" : "=r"(v.x), "=r"(v.y), "=r"(v.z), "=r"(v.w) : "l"(p) : "memory"); return v; }
__device__ __forceinline__ void st_rlx(void* p, uint32_t v) { asm volatile("st.relaxed.gpu.global.u32 [%0], %1;" ::"l"(p), "r"(v) : "memory"); }
__device__ __forceinline__ void st_rlx2(void* p, uint32_t a, uint32_t b) { asm volatile("st.relaxed.gpu.global.v2.u32 [%0], {%1,%2};" ::"l"(p), "r"(a), "r"(b) : "memory"); }
__device__ __forceinline__ void st_rlx4(void* p, uint32_t a, uint32_t b, uint32_t c, uint32_t d) { asm volatile("st.relaxed.gpu.global.v4.u32 [%0], {%1,%2,%3,%4};" ::"l"(p), "r"(a), "r"(b), "r"(c), "r"(d) : "memory"); }
__device__ __forceinline__ void red_add(uint32_t* p) { asm volatile("red.relaxed.gpu.global.add.u32 [%0], 1;" ::"l"(p) : "memory"); }
__device__ __forceinline__ uint4 ldg_nc(const void* p) { uint4 v; asm volatile("ld.global.nc.v4.u32 {%0,%1,%2,%3}, [%4];" : "=r"(v.x), "=r"(v.y), "=r"(v.z), "=r"(v.w) : "l"(p)); return v; }
__device__ __forceinline__ void sts4(uint32_t a, uint32_t x, uint32_t y, uint32_t z, uint32_t w) { asm volatile("st.shared.v4.u32 [%0], {%1,%2,%3,%4};" ::"r"(a), "r"(x), "r"(y), "r"(z), "r"(w) : "memory"); }
__device__ __forceinline__ void sts2(uint32_t a, uint32_t x, uint32_t y) { asm volatile("st.shared.v2.u32 [%0], {%1,%2};" ::"r"(a), "r"(x), "r"(y) : "memory"); }
__device__ __forceinline__ void sts1(uint32_t a, uint32_t v) { asm volatile("st.shared.u32 [%0], %1;" ::"r"(a), "r"(v) : "memory"); }
__device__ __forceinline__ uint4 lds4(uint32_t a) { uint4 v; asm volatile("ld.shared.v4.u32 {%0,%1,%2,%3}, [%4];" : "=r"(v.x), "=r"(v.y), "=r"(v.z), "=r"(v.w) : "r"(a) : "memory"); return v; }
__device__ __forceinline__ float4 lds4f(uint32_t a) { float4 v; asm volatile("ld.shared.v4.f32 {%0,%1,%2,%3}, [%4];" : "=f"(v.x), "=f"(v.y), "=f"(v.z), "=f"(v.w) : "r"(a) : "memory"); return v; }
__device__ __forceinline__ float2 lds2f(uint32_t a) { float2 v; asm volatile("ld.shared.v2.f32 {%0,%1}, [%2];" : "=f"(v.x), "=f"(v.y) : "r"(a) : "memory"); return v; }
__device__ __forceinline__ float lds1f(uint32_t a) { float v; asm volatile("ld.shared.f32 %0, [%1];" : "=f"(v) : "r"(a) : "memory"); return v; }
__device__ __forceinline__ uint32_t lds1(uint32_t a) { uint32_t v; asm volatile("ld.shared.u32 %0, [%1];" : "=r"(v) : "r"(a) : "memory"); return v; }
__device__ __forceinline__ uint32_t redux_max(uint32_t v) { uint32_t r; asm volatile("redux.sync.max.u32 %0, %1, 0xffffffff;" : "=r"(r) : "r"(v)); return r; }
__device__ __forceinline__ uint32_t poll_all(const uint32_t* p, uint32_t mask, uint32_t want, int& budget) {
    uint32_t v;
#pragma unroll 1
    while (v = ld_acq(p), !__all_sync(0xffffffffu, (v & mask) == want) && --budget > 0) __nanosleep(POLL_NS);
    return v;
}

template <int TA, int TB>
__device__ __forceinline__ void wgmma_n192(float (&d)[96], uint64_t da, uint64_t db, int keep) {
    asm volatile("{\n.reg .pred p;\nsetp.ne.b32 p, %98, 0;\n"
        "wgmma.mma_async.sync.aligned.m64n192k16.f32.bf16.bf16 "
        "{%0, %1, %2, %3, %4, %5, %6, %7, %8, %9, %10, %11, %12, %13, %14, %15, "
        "%16, %17, %18, %19, %20, %21, %22, %23, %24, %25, %26, %27, %28, %29, %30, %31, "
        "%32, %33, %34, %35, %36, %37, %38, %39, %40, %41, %42, %43, %44, %45, %46, %47, "
        "%48, %49, %50, %51, %52, %53, %54, %55, %56, %57, %58, %59, %60, %61, %62, %63, "
        "%64, %65, %66, %67, %68, %69, %70, %71, %72, %73, %74, %75, %76, %77, %78, %79, "
        "%80, %81, %82, %83, %84, %85, %86, %87, %88, %89, %90, %91, %92, %93, %94, %95}, "
        "%96, %97, p, 1, 1, %99, %100;\n}\n"
        : "+f"(d[0]), "+f"(d[1]), "+f"(d[2]), "+f"(d[3]), "+f"(d[4]), "+f"(d[5]), "+f"(d[6]), "+f"(d[7]),
          "+f"(d[8]), "+f"(d[9]), "+f"(d[10]), "+f"(d[11]), "+f"(d[12]), "+f"(d[13]), "+f"(d[14]), "+f"(d[15]),
          "+f"(d[16]), "+f"(d[17]), "+f"(d[18]), "+f"(d[19]), "+f"(d[20]), "+f"(d[21]), "+f"(d[22]), "+f"(d[23]),
          "+f"(d[24]), "+f"(d[25]), "+f"(d[26]), "+f"(d[27]), "+f"(d[28]), "+f"(d[29]), "+f"(d[30]), "+f"(d[31]),
          "+f"(d[32]), "+f"(d[33]), "+f"(d[34]), "+f"(d[35]), "+f"(d[36]), "+f"(d[37]), "+f"(d[38]), "+f"(d[39]),
          "+f"(d[40]), "+f"(d[41]), "+f"(d[42]), "+f"(d[43]), "+f"(d[44]), "+f"(d[45]), "+f"(d[46]), "+f"(d[47]),
          "+f"(d[48]), "+f"(d[49]), "+f"(d[50]), "+f"(d[51]), "+f"(d[52]), "+f"(d[53]), "+f"(d[54]), "+f"(d[55]),
          "+f"(d[56]), "+f"(d[57]), "+f"(d[58]), "+f"(d[59]), "+f"(d[60]), "+f"(d[61]), "+f"(d[62]), "+f"(d[63]),
          "+f"(d[64]), "+f"(d[65]), "+f"(d[66]), "+f"(d[67]), "+f"(d[68]), "+f"(d[69]), "+f"(d[70]), "+f"(d[71]),
          "+f"(d[72]), "+f"(d[73]), "+f"(d[74]), "+f"(d[75]), "+f"(d[76]), "+f"(d[77]), "+f"(d[78]), "+f"(d[79]),
          "+f"(d[80]), "+f"(d[81]), "+f"(d[82]), "+f"(d[83]), "+f"(d[84]), "+f"(d[85]), "+f"(d[86]), "+f"(d[87]),
          "+f"(d[88]), "+f"(d[89]), "+f"(d[90]), "+f"(d[91]), "+f"(d[92]), "+f"(d[93]), "+f"(d[94]), "+f"(d[95])
        : "l"(da), "l"(db), "r"(keep), "n"(TA), "n"(TB));
}
template <int TA, int TB>
__device__ __forceinline__ void wgmma_n128(float (&d)[64], uint64_t da, uint64_t db, int keep) {
    asm volatile("{\n.reg .pred p;\nsetp.ne.b32 p, %66, 0;\n"
        "wgmma.mma_async.sync.aligned.m64n128k16.f32.bf16.bf16 "
        "{%0, %1, %2, %3, %4, %5, %6, %7, %8, %9, %10, %11, %12, %13, %14, %15, "
        "%16, %17, %18, %19, %20, %21, %22, %23, %24, %25, %26, %27, %28, %29, %30, %31, "
        "%32, %33, %34, %35, %36, %37, %38, %39, %40, %41, %42, %43, %44, %45, %46, %47, "
        "%48, %49, %50, %51, %52, %53, %54, %55, %56, %57, %58, %59, %60, %61, %62, %63}, "
        "%64, %65, p, 1, 1, %67, %68;\n}\n"
        : "+f"(d[0]), "+f"(d[1]), "+f"(d[2]), "+f"(d[3]), "+f"(d[4]), "+f"(d[5]), "+f"(d[6]), "+f"(d[7]),
          "+f"(d[8]), "+f"(d[9]), "+f"(d[10]), "+f"(d[11]), "+f"(d[12]), "+f"(d[13]), "+f"(d[14]), "+f"(d[15]),
          "+f"(d[16]), "+f"(d[17]), "+f"(d[18]), "+f"(d[19]), "+f"(d[20]), "+f"(d[21]), "+f"(d[22]), "+f"(d[23]),
          "+f"(d[24]), "+f"(d[25]), "+f"(d[26]), "+f"(d[27]), "+f"(d[28]), "+f"(d[29]), "+f"(d[30]), "+f"(d[31]),
          "+f"(d[32]), "+f"(d[33]), "+f"(d[34]), "+f"(d[35]), "+f"(d[36]), "+f"(d[37]), "+f"(d[38]), "+f"(d[39]),
          "+f"(d[40]), "+f"(d[41]), "+f"(d[42]), "+f"(d[43]), "+f"(d[44]), "+f"(d[45]), "+f"(d[46]), "+f"(d[47]),
          "+f"(d[48]), "+f"(d[49]), "+f"(d[50]), "+f"(d[51]), "+f"(d[52]), "+f"(d[53]), "+f"(d[54]), "+f"(d[55]),
          "+f"(d[56]), "+f"(d[57]), "+f"(d[58]), "+f"(d[59]), "+f"(d[60]), "+f"(d[61]), "+f"(d[62]), "+f"(d[63])
        : "l"(da), "l"(db), "r"(keep), "n"(TA), "n"(TB));
}
template <int TA, int TB>
__device__ __forceinline__ void wgmma_n8(float (&d)[4], uint64_t da, uint64_t db, int keep) {
    asm volatile("{\n.reg .pred p;\nsetp.ne.b32 p, %6, 0;\n"
        "wgmma.mma_async.sync.aligned.m64n8k16.f32.bf16.bf16 "
        "{%0, %1, %2, %3}, "
        "%4, %5, p, 1, 1, %7, %8;\n}\n"
        : "+f"(d[0]), "+f"(d[1]), "+f"(d[2]), "+f"(d[3])
        : "l"(da), "l"(db), "r"(keep), "n"(TA), "n"(TB));
}
__device__ __forceinline__ void wgmma_rs_n128(float (&d)[64], uint32_t a0, uint32_t a1, uint32_t a2, uint32_t a3, uint64_t db) {
    asm volatile("{\n.reg .pred p;\nsetp.ne.b32 p, 1, 0;\n"
        "wgmma.mma_async.sync.aligned.m64n128k16.f32.bf16.bf16 "
        "{%0, %1, %2, %3, %4, %5, %6, %7, %8, %9, %10, %11, %12, %13, %14, %15, "
        "%16, %17, %18, %19, %20, %21, %22, %23, %24, %25, %26, %27, %28, %29, %30, %31, "
        "%32, %33, %34, %35, %36, %37, %38, %39, %40, %41, %42, %43, %44, %45, %46, %47, "
        "%48, %49, %50, %51, %52, %53, %54, %55, %56, %57, %58, %59, %60, %61, %62, %63}, "
        "{%64, %65, %66, %67}, %68, p, 1, 1, 1;\n}\n"
        : "+f"(d[0]), "+f"(d[1]), "+f"(d[2]), "+f"(d[3]), "+f"(d[4]), "+f"(d[5]), "+f"(d[6]), "+f"(d[7]),
          "+f"(d[8]), "+f"(d[9]), "+f"(d[10]), "+f"(d[11]), "+f"(d[12]), "+f"(d[13]), "+f"(d[14]), "+f"(d[15]),
          "+f"(d[16]), "+f"(d[17]), "+f"(d[18]), "+f"(d[19]), "+f"(d[20]), "+f"(d[21]), "+f"(d[22]), "+f"(d[23]),
          "+f"(d[24]), "+f"(d[25]), "+f"(d[26]), "+f"(d[27]), "+f"(d[28]), "+f"(d[29]), "+f"(d[30]), "+f"(d[31]),
          "+f"(d[32]), "+f"(d[33]), "+f"(d[34]), "+f"(d[35]), "+f"(d[36]), "+f"(d[37]), "+f"(d[38]), "+f"(d[39]),
          "+f"(d[40]), "+f"(d[41]), "+f"(d[42]), "+f"(d[43]), "+f"(d[44]), "+f"(d[45]), "+f"(d[46]), "+f"(d[47]),
          "+f"(d[48]), "+f"(d[49]), "+f"(d[50]), "+f"(d[51]), "+f"(d[52]), "+f"(d[53]), "+f"(d[54]), "+f"(d[55]),
          "+f"(d[56]), "+f"(d[57]), "+f"(d[58]), "+f"(d[59]), "+f"(d[60]), "+f"(d[61]), "+f"(d[62]), "+f"(d[63])
        : "r"(a0), "r"(a1), "r"(a2), "r"(a3), "l"(db));
}
__device__ __forceinline__ void wgmma_rs_n192(float (&d)[96], uint32_t a0, uint32_t a1, uint32_t a2, uint32_t a3, uint64_t db) {
    asm volatile("{\n.reg .pred p;\nsetp.ne.b32 p, 1, 0;\n"
        "wgmma.mma_async.sync.aligned.m64n192k16.f32.bf16.bf16 "
        "{%0, %1, %2, %3, %4, %5, %6, %7, %8, %9, %10, %11, %12, %13, %14, %15, "
        "%16, %17, %18, %19, %20, %21, %22, %23, %24, %25, %26, %27, %28, %29, %30, %31, "
        "%32, %33, %34, %35, %36, %37, %38, %39, %40, %41, %42, %43, %44, %45, %46, %47, "
        "%48, %49, %50, %51, %52, %53, %54, %55, %56, %57, %58, %59, %60, %61, %62, %63, "
        "%64, %65, %66, %67, %68, %69, %70, %71, %72, %73, %74, %75, %76, %77, %78, %79, "
        "%80, %81, %82, %83, %84, %85, %86, %87, %88, %89, %90, %91, %92, %93, %94, %95}, "
        "{%96, %97, %98, %99}, %100, p, 1, 1, 1;\n}\n"
        : "+f"(d[0]), "+f"(d[1]), "+f"(d[2]), "+f"(d[3]), "+f"(d[4]), "+f"(d[5]), "+f"(d[6]), "+f"(d[7]),
          "+f"(d[8]), "+f"(d[9]), "+f"(d[10]), "+f"(d[11]), "+f"(d[12]), "+f"(d[13]), "+f"(d[14]), "+f"(d[15]),
          "+f"(d[16]), "+f"(d[17]), "+f"(d[18]), "+f"(d[19]), "+f"(d[20]), "+f"(d[21]), "+f"(d[22]), "+f"(d[23]),
          "+f"(d[24]), "+f"(d[25]), "+f"(d[26]), "+f"(d[27]), "+f"(d[28]), "+f"(d[29]), "+f"(d[30]), "+f"(d[31]),
          "+f"(d[32]), "+f"(d[33]), "+f"(d[34]), "+f"(d[35]), "+f"(d[36]), "+f"(d[37]), "+f"(d[38]), "+f"(d[39]),
          "+f"(d[40]), "+f"(d[41]), "+f"(d[42]), "+f"(d[43]), "+f"(d[44]), "+f"(d[45]), "+f"(d[46]), "+f"(d[47]),
          "+f"(d[48]), "+f"(d[49]), "+f"(d[50]), "+f"(d[51]), "+f"(d[52]), "+f"(d[53]), "+f"(d[54]), "+f"(d[55]),
          "+f"(d[56]), "+f"(d[57]), "+f"(d[58]), "+f"(d[59]), "+f"(d[60]), "+f"(d[61]), "+f"(d[62]), "+f"(d[63]),
          "+f"(d[64]), "+f"(d[65]), "+f"(d[66]), "+f"(d[67]), "+f"(d[68]), "+f"(d[69]), "+f"(d[70]), "+f"(d[71]),
          "+f"(d[72]), "+f"(d[73]), "+f"(d[74]), "+f"(d[75]), "+f"(d[76]), "+f"(d[77]), "+f"(d[78]), "+f"(d[79]),
          "+f"(d[80]), "+f"(d[81]), "+f"(d[82]), "+f"(d[83]), "+f"(d[84]), "+f"(d[85]), "+f"(d[86]), "+f"(d[87]),
          "+f"(d[88]), "+f"(d[89]), "+f"(d[90]), "+f"(d[91]), "+f"(d[92]), "+f"(d[93]), "+f"(d[94]), "+f"(d[95])
        : "r"(a0), "r"(a1), "r"(a2), "r"(a3), "l"(db));
}

template <int HS>
__device__ __forceinline__ void attn_pair(const uint32_t* q, const uint32_t* k, const uint32_t* v, const uint32_t* kh, const uint32_t* vh,
                                          const float* fu, const float* fn, const float* rk, float bias0, float bias1, uint32_t mU, uint32_t zero, const float* ci, uint32_t* o) {
    float s0[2][4] = {}, s1[2][4] = {}, s2[2][4] = {};
#pragma unroll
    for (int n = 0; n < 4; n++) {
        const int hd = n & 1, a = 8 * hd + 2 * (n & 2);
        mma16816(s1[hd], q[a], q[a + 1], q[a + 2], q[a + 3], k[a], k[a + 2]);
        mma16816(s2[hd], q[a], q[a + 1], q[a + 2], q[a + 3], k[a + 1], k[a + 3]);
    }
#pragma unroll
    for (int n = 0; n < 4; n++) {
        const int hd = n & 1, a = 8 * hd + 2 * (n & 2);
        mma16816(s0[hd], q[a], q[a + 1], q[a + 2], q[a + 3], kh[HS * (a / 2)], kh[HS * (a / 2 + 1)]);
    }
    float e[2][4], m[2][2];
#pragma unroll
    for (int hd = 0; hd < 2; hd++) {
        e[hd][2] = fmaf(s1[hd][2], fu[2], s2[hd][2] * fn[2]); e[hd][3] = fmaf(s1[hd][3], fu[3], s2[hd][3] * fn[3]);
        e[hd][0] = fmaf(s0[hd][0], fu[0], fmaf(s1[hd][0], fn[0], bias0)); e[hd][1] = fmaf(s0[hd][1], fu[1], fmaf(s1[hd][1], fn[1], bias1));
        m[hd][1] = fmaxf(e[hd][2], e[hd][3]); m[hd][0] = fmaxf(e[hd][0], e[hd][1]);
    }
#pragma unroll
    for (int x = 1; x < 3; x++)
#pragma unroll
        for (int n = 0; n < 4; n++) m[n & 1][1 - (n >> 1)] = fmaxf(m[n & 1][1 - (n >> 1)], __shfl_xor_sync(0xffffffffu, m[n & 1][1 - (n >> 1)], x));
    float c[2][4][4] = {};
#pragma unroll
    for (int hd = 0; hd < 2; hd++) {
#pragma unroll
        for (int n = 0; n < 4; n++) e[hd][n] = ex2(e[hd][n] - m[hd][n >> 1]);
        const uint32_t plo = pack_bf16(e[hd][0] * rk[0], e[hd][1] * rk[1]), phi = pack_bf16(e[hd][2] * rk[2], e[hd][3] * rk[3]);
        const uint32_t z0 = plo & zero, z1 = phi & zero;
        const uint32_t a0 = plo & ~mU, a1 = phi & mU, a3 = phi & ~mU, b0 = plo & mU;
#pragma unroll
        for (int jj = 0; jj < 4; jj++) mma16816(c[hd][jj], a0, a1, z0, a3, v[8 * hd + 2 * jj], v[8 * hd + 2 * jj + 1]);
#pragma unroll
        for (int jj = 0; jj < 4; jj++) mma1688(c[hd][jj], b0, z1, vh[HS * (4 * hd + jj)]);
        m[hd][0] = e[hd][0] + e[hd][1]; m[hd][1] = e[hd][2] + e[hd][3];
    }
#pragma unroll
    for (int x = 1; x < 3; x++)
#pragma unroll
        for (int n = 0; n < 4; n++) m[n >> 1][n & 1] += __shfl_xor_sync(0xffffffffu, m[n >> 1][n & 1], x);
#pragma unroll
    for (int hd = 0; hd < 2; hd++) {
        const float i0 = rcp(m[hd][0]), i1 = rcp(m[hd][1]);
#pragma unroll
        for (int jj = 0; jj < 4; jj++) {
            o[8 * hd + 2 * jj] = pack_bf16(fmaf(c[hd][jj][0], i0, 0x1p-120f), c[hd][jj][1] * i0);
            o[8 * hd + 2 * jj + 1] = pack_bf16(fmaf(c[hd][jj][2], i1, 0x1p-120f), c[hd][jj][3] * i1);
        }
    }
}

__device__ __forceinline__ uint32_t norm_pair(uint32_t u, float m, float rinv) {
    const uint32_t d = pack_bf16(bf_lo(u) - m, bf_hi(u) - m);
    return pack_bf16(bf_lo(d) * rinv, bf_hi(d) * rinv);
}

__global__ void __launch_bounds__(512, 1)
fused_kernel(const __grid_constant__ CUtensorMap mx, const __grid_constant__ CUtensorMap mw, const __grid_constant__ CUtensorMap mwo,
             const __grid_constant__ CUtensorMap mout, const __grid_constant__ CUtensorMap mgu, const __grid_constant__ CUtensorMap mwd,
             const __grid_constant__ CUtensorMap mo,
             const __nv_bfloat16* __restrict__ x, const __nv_bfloat16* __restrict__ wr, Scratch* __restrict__ scr, int swap_gu, const Weights pf) {
    extern __shared__ __align__(1024) uint8_t smem[];
    const uint32_t sb = smem_u32(smem);
    const uint32_t bars = sb + OFF_BAR;
    const int tid = threadIdx.x, lane = tid & 31, warp = __shfl_sync(0xffffffffu, tid >> 5, 0);
    const uint32_t sd = (sb & 0x3FFFF) >> 4;
    const int hp = blockIdx.x & 1, cl = blockIdx.x >> 1;
    const int pr = cl < 4 ? 39 + 8 * cl : cl < 36 ? cl - 4 : cl < 64 ? cl - 4 + ((cl - 36) * 37 >> 8) : cl;
    const int b = pr * 2 + hp, mt = pr >> 3, p = pr & 7, nt = 2 * p + hp, rh = p & 1, cb = (p & 6) + hp;
    const int par = mt >> 2, j0 = (mt & 3) * 256;
    int budget = BUDGET;

    TSC(tid == 0, 0);
    auto load_w = [&](int k, int s) {
        const uint32_t full = bars + 8 * (B_WFULL + s);
        mbar_expect_tx(full, W_BYTES);
        tma_3d(sb + OFF_W + s * W_BYTES, &mw, full, nt * 64, k * 64, 0);
    };
    if (elect_one()) {
        const uint32_t cnt = warp < B_WEMPTY / 6 ? 1 : warp < B_G1DONE / 6 ? 2 : warp < B_STAGED / 6 ? 4 : 8;
        if (warp < NBAR / 6) {
#pragma unroll
            for (int i = 0; i < 6; i++) mbar_init(bars + 48 * warp + 8 * i, cnt);
        }
        asm volatile("fence.mbarrier_init.release.cluster;" ::: "memory");
    }
    __syncthreads();

    if (b >= 128) {
        const int hc = b - 128, g = lane >> 2, t = lane & 3;
        if (warp < 12) {
            const int n = warp / 3, part = warp - 3 * n;
            const uint32_t ep = ld_rlx(&scr->epoch[0]) + 1;
            auto load = [&](int k) {
                const uint32_t full = bars + 8 * (2 * n + (k & 1));
                mbar_expect_tx(full, W_BYTES);
                tma_3d(sb + (2 * n + (k & 1)) * W_BYTES, &mw, full, (4 * hc + n) * 64, k * 64, 0);
            };
            if (part == 0 && elect_one()) { load(0); load(1); }
            __syncwarp();
            float c0[4] = {0.f, 0.f, 0.f, 0.f}, c1[4] = {0.f, 0.f, 0.f, 0.f};
            const uint32_t sel = g == 0 ? 0x3f80u : g == 1 ? 0x3f800000u : 0u;
            const uint32_t a = sb + 2 * n * W_BYTES + part * BOX + t * 256 + ((g ^ (2 * t)) << 4);
#pragma unroll 1
            for (int k = 0; k < 16; k++) {
                mbar_wait(bars + 8 * (2 * n + (k & 1)), (k >> 1) & 1, budget);
                uint4 v[8], u[8];
#pragma unroll
                for (int i = 0; i < 8; i++) { v[i] = lds4(a + (k & 1) * W_BYTES + i * 1024); u[i] = lds4(((a + 128) ^ 16) + (k & 1) * W_BYTES + i * 1024); }
#pragma unroll
                for (int i = 0; i < 8; i++) { mma16816(c0, v[i].x, v[i].y, u[i].x, u[i].y, sel, sel); mma16816(c1, v[i].z, v[i].w, u[i].z, u[i].w, sel, sel); }
                bar_sync(1 + n, 96);
                if (part == 0 && k < 14 && elect_one()) load(k + 2);
                __syncwarp();
            }
            if (t == 0) {
#pragma unroll
                for (int r = 0; r < 3; r++) {
                    const uint32_t q0 = pack_bf16(c0[0], c0[1]), q1 = pack_bf16(c0[2], c0[3]), q2 = pack_bf16(c1[0], c1[1]), q3 = pack_bf16(c1[2], c1[3]);
                    st_rlx4(&scr->cs[4 * hc + n][16 + (part * 8 + g) * 32 + r * 4], q0, q1, q2, q3);
                    c0[0] -= bf_lo(q0); c0[1] -= bf_hi(q0); c0[2] -= bf_lo(q1); c0[3] -= bf_hi(q1);
                    c1[0] -= bf_lo(q2); c1[1] -= bf_hi(q2); c1[2] -= bf_lo(q3); c1[3] -= bf_hi(q3);
                }
            }
            bar_sync(7, 384);
            if (tid == 0) { fence_gpu(); st_rlx(&scr->csflag[hc], ep); }
            TSC(tid == 0, 19);
        }
        if (warp < 8) TS_END();
        return;
    }
    asm volatile("barrier.cluster.arrive.relaxed.aligned;" ::: "memory");

    const int kc = b >> 4, c2 = b & 15;
    if (warp >= 12) {
        reg_dec<24>();
        if (warp == 12) {
            if (elect_one()) {
#pragma unroll 1
                for (int n = 0; n < 12; n++) {
                    const int w = n & 1, j = n >> 1;
                    const uint32_t full = bars + 8 * (B_XFULL + w * 6 + j);
                    mbar_expect_tx(full, BOX);
                    tma_4d(sb + w * OFF_X1 + j * BOX, &mx, full, par * 1024 + (n >> 2) * 64, 0, (j0 + w * 128) >> 5, (~n >> 1) & 1);
                    if (n == ROWS_AT) { mbar_expect_tx(bars + 8 * B_ROW, 4 * BOX); bulk_g2s(sb + OFF_FR, x + (size_t)b * 16 * 1024, 4 * BOX, bars + 8 * B_ROW); }
                    if (n == 0 || n == 3 || n == 7) load_w((n + 1) >> 2, n ? n >> 2 : 2);
                }
                int s = 2; uint32_t ph = 0;
#pragma unroll 1
                for (int k = 3; k < 16; k++) {
                    mbar_wait(bars + 8 * (B_WEMPTY + s), ph, budget);
                    load_w(k, s);
                    if (++s == 3) s = 0;
                    if (s == 2) ph ^= 1;
                }
                TS(27);
                s = 2;
#pragma unroll 1
                for (int i = 0; i < 16; i++) {
                    mbar_wait(bars + 8 * (i < 2 ? B_WEMPTY + i : i < 4 ? B_G1DONE : i < 6 ? B_F1DONE : B_WOEMPTY + s), i >= 12, budget);
                    if (i == 1) {
                        mbar_expect_tx(bars + 8 * B_XT, 4 * BOX);
#pragma unroll 1
                        for (int n = 0; n < 4; n++)
                            tma_4d(sb + (n >> 1) * OFF_X1 + (4 + (n & 1)) * BOX, &mx, bars + 8 * B_XT, par * 1024 + cb * 128 + (n & 1) * 64, 0, (j0 + rh * 128) >> 5, 1 - (n >> 1));
                    }
                    const uint32_t full = bars + 8 * (B_WOFULL + s);
                    mbar_expect_tx(full, 2 * BOX);
                    tma_3d(sb + OFF_WO + s * 2 * BOX, &mwo, full, 0, ((2 * p + (i < 2 ? i ^ hp : i)) & 15) * 64, cb * 2);
                    TSC(TIMING % 10 == 4, 48 + i);
                    if (++s == 6) s = 0;
                }
                TS(25);
            }
        } else {
            bar_sync(8, 224);
            const uint32_t ep = lds1(sb + OFF_EP);
            if (warp == 13) {
                cluster_wait();
                if (elect_one()) {
                    int j = 0, q = 0, left = BUDGET; uint32_t ph = 0;
#pragma unroll 1
                    for (int n = 6; n < 32; n++) {
                        mbar_wait(bars + 8 * (B_XEMPTY + j), ph, left);
                        tma_4d_mc(sb + hp * OFF_X1 + j * BOX, &mx, bars + 8 * (B_XFULL + hp * 6 + j), par * 1024 + (n >> 1) * 64, 0, (j0 + hp * 128) >> 5, ~n & 1);
                        if (++j == 6) { j = 0; ph ^= 1; }
#pragma unroll 1
                        for (; q < (PF_RATE * (n - PF_START) >> 3) && q < 18 + PF_NW; q++) {
                            const int u = q - PF_NW;
                            if (u < 0) bulk_pf(pf.wqkv + (size_t)(1024 + 128 * u + b) * 6144, 6144);
                            else if (u < 16) bulk_pf((b < 64 ? pf.wg : pf.wu) + (size_t)(u * 64 + (b & 63)) * 7168, 7168);
                            else bulk_pf(pf.wo + (size_t)((u - 16) * 128 + b) * 8192, 8192);
                        }
                    }
                }
                __syncwarp();
                uint32_t* hs = &scr->halo[b - 16][lane * 4];
                int tries = BUDGET;
#pragma unroll 1
                for (int c = 0; c < 4; c += 2) {
                    uint4 v0 = make_uint4(0, 0, 0, 0), v1 = v0;
                    if (j0) {
#pragma unroll 1
                        do { v0 = ld_rlx4(hs + c * 128); v1 = ld_rlx4(hs + c * 128 + 128); } while ((v0.x == 0 || v1.x == 0) && --tries > 0);
                        st_rlx(hs + c * 128, 0); st_rlx(hs + c * 128 + 128, 0);
                    }
                    __syncwarp();
                    stsm4(sb + OFF_HIN + c * 512 + lane * 16, v0.x, v0.y, v0.z, v0.w);
                    stsm4(sb + OFF_HIN + c * 512 + 512 + lane * 16, v1.x, v1.y, v1.z, v1.w);
                }
                bar_arrive(11, 64);
                TSC(lane == 0, 31);
                const int src = ((mt * 2 + rh) * 2 + 1 - hp) * 1024;
                if (elect_one()) {
                    const uint32_t* fl = &scr->oflag[mt * 2 + 1 - hp][0];
                    const uint32_t inv = (ep & 1) - 1;
                    uint32_t ready = 0, ph = 0;
                    int s = 4;
#pragma unroll 1
                    for (int i = 2; i < 16; i++) {
                        const int kb = (2 * p + i) & 15;
#pragma unroll 1
                        while (!((ready >> kb) & 1) && --budget > 0) ready = ld_rlx(fl) ^ inv;
                        TSC(i == 2, 30);
                        mbar_wait(bars + 8 * (B_OEMPTY + s), ph, budget);
                        tma_2d_mc(sb + hp * OFF_X1 + s * BOX, &mo, bars + 8 * (B_OFULL + hp * 6 + s), 0, src + kb * 64);
                        TSC(TIMING % 10 == 4 && hp == 0, 32 + i);
                        if (++s == 6) s = 0;
                        if (s == 4) ph ^= 1;
                    }
                }
            } else if (warp == 14) {
                if (elect_one()) {
                    uint32_t ph = 0;
#pragma unroll 1
                    for (int f = b < 112 ? 0 : 1; f < 2; f++) {
                        const int n = f ? 7 : 16, ns = f ? 3 : NF1, wx = f ? 0 : b * 32, wy = f ? kc * 448 : 0, wz = f ? c2 : 0;
                        const uint32_t* act = scr->act + (f ? kc * 7 * 256 : 14336);
                        const CUtensorMap* wm = f ? &mwd : &mgu;
                        int s = f;
#pragma unroll 1
                        for (int q = -3 * f; q < n; q++) {
                            const uint32_t full = bars + 8 * (B_FFULL + s), dst = sb + fslot(s);
                            if (q == 0) {
#pragma unroll 1
                                while (ld_acq(&scr->cnt[f ? kc : 8][0]) != ep * (f ? 14 : 8) && --budget > 0) __nanosleep(POLL_NS);
                                fence_async_gmem();
                                TS(f ? 29 : 26);
                            }
                            if ((unsigned)q >= 3u * f) {
                                mbar_wait(bars + 8 * (B_FEMPTY + s), (ph >> s) & 1, budget);
                                ph ^= 1u << s;
                                mbar_expect_tx(full, F_BYTES);
                                tma_3d(dst, wm, full, wx, wy + (q < 0 ? q + 3 : q) * 64, wz);
                            }
                            if (q >= 0) bulk_g2s(dst + BOX, act + q * 256, 1024, full);
                            if (!f && q >= PF_D && q < PF_D + 8) bulk_pf(pf.wd + (size_t)((q - PF_D) * 112 + b) * 8192, 8192);
                            if (++s == ns) s = 0;
                        }
                    }
                }
            } else {
                mbar_wait(bars + 8 * B_ROW, 0, budget);
                uint8_t* oz = scr->o + ((size_t)mt * 64 + nt) * BOX + lane * 16;
#pragma unroll 1
                for (int i = 0; i < 64; i++) { st_rlx4(oz + (i >> 4) * 16 * BOX + (i & 15) * 512, 0, 0, 0, 0); if ((i & 3) == 3) __nanosleep(ZF_NS); }
                __syncwarp();
                fence_gpu();
                mbar_wait(bars + 8 * B_RDONE, 0, budget);
                int tries = BUDGET;
#pragma unroll 1
                for (int i = lane; i < 88; i += 32) {
                    const uint2* rp = &scr->row[2 * (j0 - 8 + i) + par];
                    uint2 v0, v1, v2;
#pragma unroll 1
                    do { v0 = ld_rlx2(rp + (j0 + i < 8 ? 16 : 0)); v1 = ld_rlx2(rp + 176); v2 = ld_rlx2(rp + 352); } while ((((v0.y ^ ep) | (v1.y ^ ep) | (v2.y ^ ep)) & 31) && --tries > 0);
                    sts2(sb + OFF_STAT + i * 8, (v0.x << 16) ^ 0x80000000u, __float_as_uint(rcp(bf_hi(v0.x))));
                    sts2(sb + OFF_STAT + i * 8 + 704, (v1.x << 16) ^ 0x80000000u, __float_as_uint(rcp(bf_hi(v1.x))));
                    sts2(sb + OFF_STAT + i * 8 + 1408, (v2.x << 16) ^ 0x80000000u, __float_as_uint(rcp(bf_hi(v2.x))));
                }
                __syncwarp();
                poll_all(&scr->csflag[lane & 3], ~0u, ep, budget);
                if (elect_one()) {
                    fence_async_gmem();
                    mbar_expect_tx(bars + 8 * B_AUX, CS_BYTES);
                    bulk_g2s(sb + OFF_CS, scr->cs[nt], CS_BYTES, bars + 8 * B_AUX);
                    TS(21);
                    mbar_expect_tx(bars + 8 * (B_OFULL + 3), BOX); mbar_expect_tx(bars + 8 * (B_OFULL + 9), BOX);
#pragma unroll 1
                    for (int v = 0; v < 2; v++) {
                        const uint32_t ring = sb + v * OFF_X1 + 2 * BOX, fb = bars + 8 * (B_OFULL + v * 6 + 2);
                        mbar_wait(bars + 8 * (B_STAGED + v), 0, budget);
                        asm volatile("red.relaxed.gpu.global.xor.b32 [%0], %1;" ::"l"(&scr->oflag[mt * 2 + 1 - v][0]), "r"(1u << nt) : "memory");
                        TS(13 + 2 * v);
                        mbar_arrive(fb);
                        mbar_wait(bars + 8 * B_G1DONE, 0, budget);
                        bulk_s2c(mapa(ring + BOX, hp ^ 1), ring, BOX, mapa(fb + 8, hp ^ 1));
                        if (v == 0) {
                            mbar_wait(bars + 8 * B_FREED, 0, budget);
                            TS(14);
#pragma unroll
                            for (int n = 0; n < 8; n++) {
                                mbar_expect_tx(bars + 8 * (B_OFULL + (n >> 2) * 6 + (4 + (n & 3)) % 6), BOX);
                                mbar_arrive_at(mapa(bars + 8 * B_OEMPTY, n >> 2) + (4 + (n & 3)) % 6 * 8);
                            }
                        }
                    }
                }
            }
        }
    } else if (warp >= 8) {
        reg_dec<40>();
        const int wq = warp - 8, ta = tid - 256, g = lane >> 2, t = lane & 3;
        const uint32_t rbuf = sb + OFF_FR + wq * BOX, rbar = bars + 8 * B_ROW;
        const uint4 wv = ldg_nc(wr + ta * 8);
        if (ta == 0) sts1(sb + OFF_EP, ld_rlx(&scr->epoch[0]) + 1);
        sts4(sb + OFF_STAT + ta * 16, wv.x, wv.y, wv.z, wv.w);
        bar_sync(8, 224);
        const uint32_t ep = lds1(sb + OFF_EP);
        {
            const int s = b * 16 + wq * 4 + (lane >> 3);
            if ((lane & 7) == 0) st_rlx2(&scr->row[s], 0, ep - 1);
            float sw = 0.f;
#pragma unroll 1
            for (int i = 0; i < 16; i++) { const uint32_t q = lds1(sb + OFF_STAT + i * 128 + lane * 4); sw += bf_lo(q) + bf_hi(q); }
#pragma unroll 1
            for (int o = 16; o > 0; o >>= 1) sw += __shfl_xor_sync(0xffffffffu, sw, o);
            float s1 = 0.f, s2 = 0.f, sr = 0.f;
            const uint32_t xa = rbuf + (lane >> 3) * 2048 + (lane & 7) * 16, wa = sb + OFF_STAT + (lane & 7) * 16;
            mbar_wait(rbar, 0, budget);
            TSC(ta == 0, 17);
            uint4 u = lds4(xa), w4 = lds4(wa);
#pragma unroll kStatsUnroll
            for (int i = 1; i <= 16; i++) {
                const uint32_t o = (i * 128) & 2047;
                const uint4 un = lds4(xa + o), wn = lds4(wa + o);
#pragma unroll
                for (int c = 0; c < 4; c++) {
                    const float a0 = bf_lo((&u.x)[c]), a1 = bf_hi((&u.x)[c]);
                    s1 += a0; s2 = fmaf(a0, a0, s2); sr = fmaf(a0, bf_lo((&w4.x)[c]), sr);
                    s1 += a1; s2 = fmaf(a1, a1, s2); sr = fmaf(a1, bf_hi((&w4.x)[c]), sr);
                }
                u = un; w4 = wn;
            }
#pragma unroll 1
            for (int o = 1; o < 8; o <<= 1) {
                s1 += __shfl_xor_sync(0xffffffffu, s1, o); s2 += __shfl_xor_sync(0xffffffffu, s2, o); sr += __shfl_xor_sync(0xffffffffu, sr, o);
            }
            const float mean = s1 * (1.f / 1024.f), mb = bf16r(mean);
            float var = fmaf(-mean, mean, s2 * (1.f / 1024.f));
            sr = fmaf(-mb, sw, sr);
            if (__builtin_expect(__any_sync(0xffffffffu, mean * mean > 256.f * var), 0)) {
                float a2 = 0.f, ar = 0.f;
#pragma unroll 1
                for (int i = 0; i < 64; i++) {
                    const uint32_t o = (i >> 2) * 128 + (i & 3) * 4, q1 = lds1(xa + o), q2 = lds1(wa + o);
                    a2 = fmaf(bf_lo(q1) - mean, bf_lo(q1) - mean, fmaf(bf_hi(q1) - mean, bf_hi(q1) - mean, a2));
                    ar = fmaf(bf_lo(q1) - mb, bf_lo(q2), fmaf(bf_hi(q1) - mb, bf_hi(q2), ar));
                }
#pragma unroll 1
                for (int o = 1; o < 8; o <<= 1) { a2 += __shfl_xor_sync(0xffffffffu, a2, o); ar += __shfl_xor_sync(0xffffffffu, ar, o); }
                var = a2 * (1.f / 1024.f); sr = ar;
            }
            float den;
            asm("sqrt.approx.f32 %0, %1;" : "=f"(den) : "f"(bf16r(bf16r(var) + 1e-5f)));
            const uint32_t st = pack_bf16(mb, den);
            const uint32_t rb = pack_bf16(0.f, sr * rcp(bf_hi(st)) + 0.f);
            uint32_t ord = (int)rb < 0 ? ~rb & 0xffff0000u : rb | 0x80000000u;
            if ((rb & 0x7fffffffu) > 0x7f800000u) ord = 0;
            if ((lane & 7) == 0) st_rlx2(&scr->row[s], st, ord | ((2047 - s) << 5) | (ep & 31));
            __syncwarp();
            if (lane < 7) mbar_arrive(bars + 8 * (lane < 5 ? B_FEMPTY + lane : B_RDONE));
        }
        TSC(ta == 0, 18);
        if ((b >> 3) == 14) {
            const uint32_t gm = sb + OFF_E, cnt = gm + 64, res = gm + 80, list = gm + 128;
            uint32_t kv[16];
            int tries = BUDGET;
#pragma unroll 1
            do {
                uint32_t bad = 0;
#pragma unroll
                for (int n = 0; n < 16; n++) kv[n] = ld_rlx(&scr->row[n * 128 + ta].y);
#pragma unroll
                for (int n = 0; n < 16; n++) bad |= kv[n] ^ ep;
                if ((bad & 31) == 0) break;
            } while (--tries > 0);
            __syncwarp();
            TSC(ta == 0, 26);
            uint32_t m = 0;
#pragma unroll
            for (int n = 0; n < 16; n++) m = max(m, kv[n]);
            uint32_t gmax = m;
#pragma unroll
            for (int o = 1; o < 8; o <<= 1) gmax = max(gmax, __shfl_xor_sync(0xffffffffu, gmax, o));
            sts1(gm + (ta >> 3) * 4, gmax);
            sts1(cnt, 0);
            bar_sync(12, 128);
            const uint32_t c = lds1(gm + (lane & 15) * 4);
            int rank = 0;
#pragma unroll
            for (int i = 0; i < 2; i++) { const uint4 q = lds4(gm + (lane >> 4) * 32 + i * 16); rank += (q.x > c) + (q.y > c) + (q.z > c) + (q.w > c); }
            rank += __shfl_xor_sync(0xffffffffu, rank, 16);
            const uint32_t thr = redux_max(rank == 7 ? c : 0u);
#pragma unroll 1
            while (m >= thr) {
                uint32_t at, m2 = 0;
                asm volatile("atom.shared.add.u32 %0, [%1], 1;" : "=r"(at) : "r"(cnt) : "memory");
#pragma unroll
                for (int n = 0; n < 16; n++) m2 = max(m2, kv[n] < m ? kv[n] : 0u);
                sts1(list + at * 4, m);
                if (m2 == 0) break;
                m = m2;
            }
            bar_sync(12, 128);
            const int nc = lds1(cnt);
#pragma unroll 1
            for (int i = ta >> 3; i < ((nc + 3) & ~3); i += 16) {
                const uint32_t ki = lds1(list + i * 4);
                int r = 0;
#pragma unroll 1
                for (int n = lane & 7; n < nc; n += 8) r += lds1(list + n * 4) > ki;
                __syncwarp();
#pragma unroll
                for (int o = 1; o < 8; o <<= 1) r += __shfl_xor_sync(0xffffffffu, r, o);
                if (r == (b & 7) && i < nc) sts1(res, ki);
            }
            bar_sync(12, 128);
            const uint32_t k0 = lds1(res);
            const int r0 = 2047 - ((k0 >> 5) & 2047);
            TSC(ta == 0, 22);
            if (ta == 0) st_rlx(&scr->sel[b & 7], k0);
            const uint4 v0 = ldg_nc(x + (size_t)r0 * 1024 + ta * 8);
            const uint32_t s0 = ld_rlx(&scr->row[r0]);
            const float m0 = bf_lo(s0), i0 = rcp(bf_hi(s0));
            const int ao = 14336 + (ta >> 3) * 256 + (b & 7) * 32 + ((ta ^ b) & 7) * 4;
            st_rlx4(scr->act + ao, norm_pair(v0.x, m0, i0), norm_pair(v0.y, m0, i0), norm_pair(v0.z, m0, i0), norm_pair(v0.w, m0, i0));
            bar_sync(12, 128);
            if (ta == 0) { fence_gpu(); red_add(&scr->cnt[8][0]); }
        }
        uint32_t fph = 0, own = 0; float sig = 0.f;
#pragma unroll 1
        for (int ph = 0; ph < 2; ph++) {
            if (ph || b < 112) {
                float acc[4] = {0.f, 0.f, 0.f, 0.f};
                const uint32_t alo = sd + (ph ? dlo(0, 8192) : dlo(0, 4096)), ahi = ph ? dhi(1024, 1) : dhi(512, 2), astep = ph ? 128 : 64;
                const uint32_t bhi = ph ? dhi(128, 0) : dhi(1024, 1), bstep = ph ? 16 : 2;
                const int ns = ph ? 3 : NF1;
                int s = ph, ps = 0, left = BUDGET;
                if (ph) mbar_wait(bars + 8 * FFN2_GATE, 0, left);
                bool rel = false;
#pragma unroll 1
                for (int q = ph ? 7 : 16; q > 0; q--) {
                    const uint32_t so = fslot(s) >> 4, da = alo + so, db = sd + dlo(BOX, 128) + so;
                    mbar_wait_hot(bars + 8 * (B_FFULL + s), (fph >> s) & 1, left);
                    TSC(TIMING % 10 == 3 && ta == 0, 32 + (ph ? 23 : 16) - q);
                    wg_fence();
#pragma unroll
                    for (int j = 0; j < 4; j++) wgmma_n8<1, 0>(acc, mkdesc(da + j * astep, ahi), mkdesc(db + j * bstep, bhi), 1);
                    wg_commit();
                    wg_wait<1>();
                    if (rel) mbar_arrive(bars + 8 * (B_FEMPTY + ps));
                    rel = lane == 0; ps = s;
                    fph ^= 1u << s;
                    if (++s == ns) s = 0;
                }
                wg_wait<0>();
                if (ph == 0) {
                    if (rel) mbar_arrive(bars + 8 * (B_FEMPTY + 15 % NF1));
                    const bool second = (wq >= 2) != (swap_gu != 0);
                    const uint32_t xa = sb + OFF_HIN + 2048 + ((wq & 1) * 32 + lane) * 16;
                    if (second) sts4(xa, __float_as_uint(acc[0]), __float_as_uint(acc[1]), __float_as_uint(acc[2]), __float_as_uint(acc[3]));
                    bar_sync(12, 128);
                    if (!second) {
                        const float4 up = lds4f(xa);
                        float hv[4];
#pragma unroll
                        for (int c = 0; c < 4; c++) { const float ga = bf16r(acc[c]); hv[c] = bf16r(ga * sigmoidf(ga)) * bf16r((&up.x)[c]); }
                        const int ao = (b * 4 + (wq & 1) * 2) * 32 + lane;
                        st_rlx(scr->act + ao, movm(pack_bf16(hv[0], hv[1]))); st_rlx(scr->act + 32 + ao, movm(pack_bf16(hv[2], hv[3])));
                    }
                    bar_sync(12, 128);
                    if (ta == 0) { fence_gpu(); red_add(&scr->cnt[b / 14][0]); }
                } else {
#pragma unroll
                    for (int c = 0; c < 4; c++) st_rlx(&scr->ypart[kc][2 * t + (c & 1)][c2 * 64 + wq * 16 + (c >> 1) * 8 + g], (__float_as_uint(acc[c]) & ~1u) | (ep & 1));
                    if (b == 0 && ta == 0) st_rlx(&scr->epoch[0], ep);
                }
                TSC(ta == 0, 22 + ph);
            }
            if (ph == 0) {
                if ((ta & 126) == 64) mbar_arrive(bars + 8 * B_F1DONE);
                const uint32_t kj = poll_all(&scr->sel[lane & 7], 31u, ep & 31, budget);
                const int row = 2047 - ((kj >> 5) & 2047), jj = (row & 1) == par ? (row >> 1) - j0 : -1;
                sig = bf16r(sigmoidf(__uint_as_float(((int)kj < 0 ? kj & 0x7fffffffu : ~kj) & 0xffff0000u)));
                own = __ballot_sync(0xffffffffu, (jj >> 7) == rh) & 255;
                sts1(sb + OFF_SEL + (lane & 7) * 4, jj);
                sts4(sb + OFF_UPD + ta * 16, 0, 0, 0, 0);
            }
            if ((own != 0) == ph) {
#pragma unroll 1
                for (; own; own &= own - 1) {
                    const int j = __ffs(own) - 1;
                    const uint32_t* src = &scr->ypart[lane >> 3][j][cb * 128 + wq * 32 + (lane & 7) * 4];
                    uint4 v0, v1; int tries = BUDGET;
#pragma unroll 1
                    do { v0 = ld_rlx4(src); v1 = ld_rlx4(src + 4 * 8192); } while ((((v0.x ^ ep) | (v1.x ^ ep)) & 1) && --tries > 0);
                    __syncwarp();
                    float a[4];
                    const float sj = __shfl_sync(0xffffffffu, sig, j);
#pragma unroll
                    for (int c = 0; c < 4; c++) {
                        a[c] = __uint_as_float((&v0.x)[c]) + __uint_as_float((&v1.x)[c]);
                        a[c] += __shfl_xor_sync(0xffffffffu, a[c], 8); a[c] += __shfl_xor_sync(0xffffffffu, a[c], 16);
                        a[c] = bf16r(a[c]) * sj;
                    }
                    sts2(sb + OFF_UPD + (wq >> 1) * 1024 + j * 128 + ((((wq & 1) * 4 + ((lane >> 1) & 3)) ^ j) << 4) + (lane & 1) * 8, pack_bf16(a[0], a[1]), pack_bf16(a[2], a[3]));
                }
                fence_async_smem();
                __syncwarp();
                if (lane < 2) mbar_arrive(bars + 8 * B_UPD);
            }
        }
        TSC(ta == 0, 24);
    } else {
        reg_inc<224>();
        const int w = warp >> 2, wi = warp & 3, g = lane >> 2, t = lane & 3;
        const bool elect = (tid & 127) == 0;
        const uint32_t mad = (lane & 15) * 128 + (((lane >> 4) ^ (lane & 7)) << 4);
        float acc[64];
        const uint32_t ring = sb + w * OFF_X1, ofull = bars + 8 * (B_OFULL + w * 6), oempty = mapa(bars + 8 * B_OEMPTY, w);
        const int r0 = rh * 128 + wi * 32 + (1 - w) * 16 + g;
        {
            float acc0[96], acc1[96];
            const uint32_t sta = sb + OFF_STAT + (8 + w * 128 + wi * 32) * 8;
            {
                const uint32_t xfull = bars + 8 * (B_XFULL + w * 6), xempty = mapa(bars + 8 * B_XEMPTY, w), dx0 = sd + dlo(w * OFF_X1, 16);
                int j = 0, pj = 0, ws = 2, pws = 0; uint32_t xph = 0;
                cluster_wait();
#pragma unroll 1
                for (int k = 0;; k++) {
                    const uint32_t dx = dx0 + j * (BOX >> 4), dw = sd + dlo(OFF_W, BOX) + ws * (W_BYTES >> 4);
                    mbar_wait(bars + 8 * (B_WFULL + ws), xph, budget);
                    mbar_wait(xfull + 8 * j, xph, budget);
                    TSC(elect && k == 0, 1 + 8 * w);
                    TSC(TIMING % 10 == 1 && tid == 0, 32 + k);
                    wg_wait<0>();
                    wg_fence();
#pragma unroll
                    for (int kk = 0; kk < 4; kk++) wgmma_n192<0, 1>(acc1, mkdesc(dx + kk * 2, dhi(1024, 1)), mkdesc(dw + kk * 128, dhi(1024, 1)), kk ? 1 : k);
                    wg_commit();
                    if (elect && k > 0) {
                        mbar_arrive(bars + 8 * (B_WEMPTY + pws));
                        if (k <= 13) { mbar_expect_tx(xfull + 8 * pj, BOX); mbar_arrive_at(xempty + 8 * pj); }
                    }
                    if (k == 15) break;
                    mbar_wait(xfull + 8 * j + 8, xph, budget);
                    wg_wait<0>();
                    wg_fence();
#pragma unroll
                    for (int kk = 0; kk < 4; kk++) wgmma_n192<0, 1>(acc0, mkdesc(dx + 512 + kk * 2, dhi(1024, 1)), mkdesc(dw + kk * 128, dhi(1024, 1)), kk ? 1 : k);
                    wg_commit();
                    if (elect && k <= 12) { mbar_expect_tx(xfull + 8 * j, BOX); mbar_arrive_at(xempty + 8 * j); }
                    pj = j + 1; pws = ws;
                    if (++ws == 3) ws = 0;
                    j += 2;
                    if (j == 6) { j = 0; xph ^= 1; }
                }
            }
            mbar_wait(bars + 8 * B_AUX, 0, budget);
            const uint32_t zero = budget >> 30, pm = t & 1 ? 0x4432 : 0x3232, ra = sta + ((t >> 1) * 16 + g) * 8;
            const uint32_t a0 = __byte_perm(lds1(ra), 0, pm), a1 = __byte_perm(lds1(ra + 64), 0, pm), a2 = a0 & zero, a3 = a1 & zero;
            wg_fence();
            wgmma_rs_n192(acc1, a0, a1, a2, a3, mkdesc(sd + dlo(OFF_CS, 0), dhi(128, 0)));
            wg_commit();
            const bool u0 = 2 * t > g, u1 = 2 * t + 1 > g;
            uint32_t mU = (u0 ? 0xffffu : 0u) | (u1 ? 0xffff0000u : 0u);
            uint32_t ka0 = sta + (2 * t - (u0 ? 8 : 0)) * 8 + 4, ka1 = sta + (2 * t + 1 - (u1 ? 8 : 0)) * 8 + 4;
            float rk[2][4], fu[2][4], fn[2][4];
            auto factors = [&](int h) {
#pragma unroll
                for (int n = 0; n < 4; n += 2) {
                    const float rq = lds1f(sta + (16 * h + 4 * n + g) * 8 + 4) * (0.17677669529663687f * 1.4426950408889634f);
                    rk[h][n] = lds1f(ka0 + h * 128 + n * 32); rk[h][n + 1] = lds1f(ka1 + h * 128 + n * 32);
                    const float f0 = rq * rk[h][n], f1 = rq * rk[h][n + 1];
                    fu[h][n] = u0 ? f0 : 0.f; fn[h][n] = f0 - fu[h][n]; fu[h][n + 1] = u1 ? f1 : 0.f; fn[h][n + 1] = f1 - fu[h][n + 1];
                }
#pragma unroll
                for (int n = 0; n < 4; n++) asm volatile("" : "+f"(fu[h][n]), "+f"(fn[h][n]));
            };
            uint8_t* og = scr->o + ((size_t)(mt * 4 + w * 2) * 16 + nt) * BOX + wi * 256 + lane * 4;
            asm volatile("" : "+r"(ka0), "+r"(ka1));
            mbar_wait(bars + 8 * (B_XFULL + w * 6 + 1), 1, budget);
            wg_wait<0>();
            wg_fence();
#pragma unroll
            for (int kk = 0; kk < 4; kk++)
                wgmma_n192<0, 1>(acc0, mkdesc(sd + dlo(w * OFF_X1 + BOX, 16) + kk * 2, dhi(1024, 1)), mkdesc(sd + dlo(OFF_W + 2 * W_BYTES, BOX) + kk * 128, dhi(1024, 1)), 1);
            wgmma_rs_n192(acc0, a0, a1, a2, a3, mkdesc(sd + dlo(OFF_CS + 64, 0), dhi(128, 0)));
            wg_commit();
            TSC(elect, 19 + w);
            uint32_t pk0[48], pk1[48], o[16] = {};
#pragma unroll
            for (int j = 0; j < 48; j++) if (j < 16 || (j & 1)) pk1[j] = pack_here(acc1[2 * j], acc1[2 * j + 1]);
            if (warp < 7) {
#pragma unroll
                for (int c = 0; c < 4; c++) stsm4(ring + wi * 2048 + c * 512 + lane * 16, pk1[17 + 8 * c], pk1[19 + 8 * c], pk1[21 + 8 * c], pk1[23 + 8 * c]);
                bar_arrive(1 + warp, 64);
            } else if (j0 != 768) {
#pragma unroll
                for (int c = 0; c < 4; c++) {
                    pk1[17 + 8 * c] = max(pk1[17 + 8 * c], 1u);
                    st_rlx4(&scr->halo[b][c * 128 + lane * 4], pk1[17 + 8 * c], pk1[19 + 8 * c], pk1[21 + 8 * c], pk1[23 + 8 * c]);
                }
            }
            TSC(tid == 224, 28);
#pragma unroll
            for (int j = 16; j < 48; j += 2) pk1[j] = pack_here(acc1[2 * j], acc1[2 * j + 1]);
            factors(1);
            uint32_t od = sb + 2 * BOX + wi * 256 + (lane >> 4) * 1024 + (lane & 15) * 16, g1peer = mapa(bars + 8 * B_G1DONE, hp ^ 1);
            uint32_t ha = sb + (warp == 0 ? OFF_HIN : warp <= 4 ? -2048 : OFF_X1 - 5 * 2048) + warp * 2048 + lane * 16;
            const bool first = warp == 0 && j0 == 0;
            float bias0 = first && u0 ? -INFINITY : 0.f, bias1 = first && u1 ? -INFINITY : 0.f;
            float ci[4];
#pragma unroll
            for (int n = 0; n < 4; n++) ci[n] = __uint_as_float((0x03800000u + n) | zero);
            asm volatile("" : "+f"(ci[0]), "+f"(ci[1]), "+f"(ci[2]), "+f"(ci[3]));
            asm volatile("" : "+l"(og), "+r"(mU), "+r"(od), "+r"(ha), "+f"(bias0), "+f"(bias1));
            mbar_wait(bars + 8 * (B_WEMPTY + 1), 0, budget);
            wg_wait<0>();
            if (elect) { mbar_arrive(bars + 8 * B_G1DONE); mbar_arrive_at(g1peer); }
            TSC(elect, 2 + 8 * w);
            auto hand_over = [&](int v) {
                asm volatile("{\n.reg .pred p;\nsetp.ne.b32 p, %17, 0;\n"
                             "@p stmatrix.sync.aligned.m8n8.x4.shared.b16 [%16], {%0,%1,%2,%3};\n@p stmatrix.sync.aligned.m8n8.x4.shared.b16 [%16 + 2048], {%4,%5,%6,%7};\n"
                             "@p stmatrix.sync.aligned.m8n8.x4.shared.b16 [%16 + 4096], {%8,%9,%10,%11};\n@p stmatrix.sync.aligned.m8n8.x4.shared.b16 [%16 + 6144], {%12,%13,%14,%15};\n"
                             "fence.proxy.async.shared::cta;\n}"
                             ::"r"(o[0]), "r"(o[1]), "r"(o[2]), "r"(o[3]), "r"(o[4]), "r"(o[5]), "r"(o[6]), "r"(o[7]), "r"(o[8]), "r"(o[9]), "r"(o[10]), "r"(o[11]),
                               "r"(o[12]), "r"(o[13]), "r"(o[14]), "r"(o[15]), "r"(od + v * OFF_X1), "r"((int)(w == rh)) : "memory");
#pragma unroll
                for (int i = 0; i < 16; i++) asm volatile("st.global.u32 [%0], %1;" ::"l"(og + (1 - v) * 16 * BOX + (i >> 1) * 1024 + (i & 1) * 128), "r"(o[i]) : "memory");
                __syncwarp();
                if (lane == 0) mbar_arrive(bars + 8 * (B_STAGED + v));
            };
#pragma unroll
            for (int j = 32; j < 48; j++) pk1[j] = movm(pk1[j]);
#pragma unroll
            for (int j = 17; j < 48; j += 2) pk0[j] = pack_here(acc0[2 * j], acc0[2 * j + 1]);
#pragma unroll
            for (int j = 33; j < 48; j += 2) pk0[j] = movm(pk0[j]);
            factors(0);
            const float2 s0 = lds2f(sb + OFF_STAT + (8 + r0) * 8), s1 = lds2f(sb + OFF_STAT + (16 + r0) * 8);
            const float m0 = s0.x * s0.y, f0 = 1.f + s0.y, m1 = s1.x * s1.y, f1 = 1.f + s1.y;
            attn_pair<2>(pk1, pk1 + 16, pk1 + 32, pk0 + 17, pk0 + 33, fu[1], fn[1], rk[1], 0.f, 0.f, mU, zero, ci, o);
            hand_over(0);
            TSC(elect, 3 + 8 * w);
#pragma unroll
            for (int j = 0; j < 48; j++) if (j < 16 || !(j & 1)) pk0[j] = pack_here(acc0[2 * j], acc0[2 * j + 1]);
#pragma unroll
            for (int j = 32; j < 48; j += 2) pk0[j] = movm(pk0[j]);
            mbar_wait_hot(bars + 8 * B_XT, 0, budget);
#pragma unroll
            for (int j = 0; j < 8; j++) {
                uint32_t a[4];
                ldsm4(a, ((ring + wi * 2048 + mad) ^ ((j & 3) * 32)) + (4 + (j >> 2)) * BOX);
                acc[8 * j + 0] = fmaf(bf_lo(a[0]), f0, m0); acc[8 * j + 1] = fmaf(bf_hi(a[0]), f0, m0);
                acc[8 * j + 2] = fmaf(bf_lo(a[1]), f1, m1); acc[8 * j + 3] = fmaf(bf_hi(a[1]), f1, m1);
                acc[8 * j + 4] = fmaf(bf_lo(a[2]), f0, m0); acc[8 * j + 5] = fmaf(bf_hi(a[2]), f0, m0);
                acc[8 * j + 6] = fmaf(bf_lo(a[3]), f1, m1); acc[8 * j + 7] = fmaf(bf_hi(a[3]), f1, m1);
            }
            bar_sync(warp ? warp : 11, 64);
            uint32_t hl[16];
            ldsm4t(hl + 8, ha + 1024); ldsm4t(hl + 12, ha + 1536); ldsm4(hl, ha); ldsm4(hl + 4, ha + 512);
            __syncwarp();
            if (lane == 0) mbar_arrive(bars + 8 * B_FREED);
            attn_pair<1>(pk0, pk0 + 16, pk0 + 32, hl, hl + 8, fu[0], fn[0], rk[0], bias0, bias1, mU, zero, ci, o);
            hand_over(1);
        }
        TSC(tid == 0, 4);
        {
            const uint32_t da0 = sd + dlo(w * OFF_X1, 1024), db0 = sd + dlo(OFF_WO, BOX);
            const uint32_t chk = ring + wi * 256 + (lane >> 3) * 1032 + (lane & 7) * 32 + (lane & 4);
            uint32_t s8 = 16, ps8 = 0, ph = 0;
#pragma unroll 1
            for (int i = 0; i < 16; i++) {
                mbar_wait_hot(ofull + s8, ph, budget);
                const uint32_t seen0 = lds1(chk + s8 * (BOX / 8)), seen1 = lds1(chk + s8 * (BOX / 8) + 4096);
                mbar_wait_hot(bars + 8 * B_WOFULL + s8, ph, budget);
                if (__builtin_expect(__any_sync(0xffffffffu, min(seen0, seen1) == 0), 0)) {
                    const uint32_t at = wi * 256 + (lane >> 4) * 1024 + (lane & 15) * 16;
                    const uint8_t* src = scr->o + ((size_t)((mt * 2 + rh) * 2 + 1 - w) * 16 + ((2 * p + (i < 2 ? i ^ hp : i)) & 15)) * BOX + at;
#pragma unroll 1
                    for (int n = 0; n < 8192; n += 2048) {
                        uint4 v; int tries = 4096;
#pragma unroll 1
                        do { v = ld_rlx4(src + n); } while (v.x == 0 && --tries > 0);
                        sts4(ring + s8 * (BOX / 8) + at + n, v.x, v.y, v.z, v.w);
                    }
                    NRETRY();
                    fence_async_smem();
                    __syncwarp();
                }
                TSC(TIMING % 10 == 1 && tid == 0, 48 + i);
                TSC(TIMING % 10 == 2 && elect, 32 + w * 16 + i);
                const uint32_t da = da0 + s8 * (BOX >> 7), db = db0 + s8 * (BOX >> 6);
                wg_wait<1>();
                wg_fence();
#pragma unroll
                for (int kk = 0; kk < 4; kk++) {
                    wgmma_n128<0, 1>(acc, mkdesc(da + kk * 128, dhi(128, 0)), mkdesc(db + kk * 128, dhi(1024, 1)), 1);
                    if (kk & 1) wg_commit();
                }
                wg_wait<2>();
                if (elect && (unsigned)(i - 1) < 10) { mbar_expect_tx(ofull + ps8, BOX); mbar_arrive_at(oempty + ps8); mbar_arrive(bars + 8 * B_WOEMPTY + ps8); }
                ps8 = s8;
                s8 = s8 == 40 ? 0 : s8 + 8;
                if (s8 == 16) ph ^= 1;
            }
            mbar_wait(bars + 8 * B_UPD, 0, budget);
            const float2 sl = lds2f(sb + OFF_SEL + t * 8);
            const int d0 = __float_as_int(sl.x) - r0, d1 = __float_as_int(sl.y) - r0;
            const uint32_t a0 = (d0 == 0 ? 0x3f80u : 0u) | (d1 == 0 ? 0x3f800000u : 0u), a1 = (d0 == 8 ? 0x3f80u : 0u) | (d1 == 8 ? 0x3f800000u : 0u);
            wg_fence();
            wgmma_rs_n128(acc, a0, a1, 0u, 0u, mkdesc(sd + dlo(OFF_UPD, 1024), dhi(0, 1)));
            wg_commit();
            wg_wait<0>();
            TSC(elect, 7 + 9 * w);
            const uint32_t os0 = ring + wi * 4096;
#pragma unroll
            for (int j = 0; j < 8; j++)
                stsm4(((os0 + mad) ^ ((j & 3) * 32)) + (j >> 2) * 2048, pack_bf16(acc[8 * j], acc[8 * j + 1]), pack_bf16(acc[8 * j + 2], acc[8 * j + 3]),
                      pack_bf16(acc[8 * j + 4], acc[8 * j + 5]), pack_bf16(acc[8 * j + 6], acc[8 * j + 7]));
            fence_async_smem();
            __syncwarp();
            if (elect_one()) {
                asm volatile("cp.async.bulk.tensor.5d.global.shared::cta.bulk_group [%0, {%2, %2, %3, %4, %5}], [%1];\ncp.async.bulk.commit_group;\ncp.async.bulk.wait_group.read 0;"
                             ::"l"(&mout), "r"(os0), "r"(0), "r"(((j0 + rh * 128) >> 5) + wi), "r"(1 - w), "r"(par * 16 + cb * 2) : "memory");
            }
            TSC(elect, 8 - 2 * w);
            TS_END();
        }
    }
}

typedef CUresult (*EncodeFn)(CUtensorMap*, CUtensorMapDataType, cuuint32_t, void*, const cuuint64_t*, const cuuint64_t*, const cuuint32_t*,
                             const cuuint32_t*, CUtensorMapInterleave, CUtensorMapSwizzle, CUtensorMapL2promotion, CUtensorMapFloatOOBfill);

CUtensorMap make_map(EncodeFn fn, const void* base, int rank, const cuuint64_t* dims, const cuuint64_t* strides, const cuuint32_t* box,
                     CUtensorMapSwizzle swz = CU_TENSOR_MAP_SWIZZLE_128B, CUtensorMapL2promotion pro = CU_TENSOR_MAP_L2_PROMOTION_L2_256B) {
    CUtensorMap m;
    cuuint32_t es[5] = {1, 1, 1, 1, 1};
    fn(&m, CU_TENSOR_MAP_DATA_TYPE_BFLOAT16, rank, (void*)base, dims, strides, box, es, CU_TENSOR_MAP_INTERLEAVE_NONE,
       swz, pro, CU_TENSOR_MAP_FLOAT_OOB_FILL_NONE);
    return m;
}

}

extern "C" void kernel_launch(void* const* d_in, const int* in_sizes, int n_in, void* d_out, int out_size) {
    (void)in_sizes; (void)n_in; (void)out_size;
    const __nv_bfloat16* x = (const __nv_bfloat16*)d_in[0];
    const __nv_bfloat16* wqkv = (const __nv_bfloat16*)d_in[1];
    const __nv_bfloat16* wo = (const __nv_bfloat16*)d_in[2];
    const __nv_bfloat16* wr = (const __nv_bfloat16*)d_in[4];
    const __nv_bfloat16* wg = (const __nv_bfloat16*)d_in[5];
    const __nv_bfloat16* wu = (const __nv_bfloat16*)d_in[6];
    const __nv_bfloat16* wd = (const __nv_bfloat16*)d_in[7];
    static EncodeFn fn = nullptr;
    static Scratch* scr = nullptr;
    if (!fn) {
        void* p = nullptr; cudaDriverEntryPointQueryResult q;
        cudaGetDriverEntryPoint("cuTensorMapEncodeTiled", &p, cudaEnableDefault, &q);
        fn = (EncodeFn)p;
        cudaFuncSetAttribute(fused_kernel, cudaFuncAttributeMaxDynamicSharedMemorySize, SMEM_LAUNCH);
        cudaGetSymbolAddress((void**)&scr, g_scr);
    }
    const cuuint64_t xd[4] = {2048, 16, 32, 2}, xs[4] = {4096, 131072, 65536, 128}, od[5] = {64, 16, 32, 2, 32};
    const cuuint32_t xb[4] = {64, 16, 4, 1}, ob[5] = {64, 16, 1, 1, 2};
    const cuuint64_t wdm[3] = {1024, 1024, 3}, wst[2] = {6144, 2048};
    const cuuint32_t wb[3] = {64, 64, 3};
    const cuuint64_t wod[3] = {64, 1024, 16}, wdd[3] = {64, 3584, 16}, wos[2] = {2048, 128};
    const cuuint32_t wob[3] = {64, 64, 2}, wdb[3] = {64, 64, 1};
    CUtensorMap mx = make_map(fn, x, 4, xd, xs, xb), mw = make_map(fn, wqkv, 3, wdm, wst, wb);
    CUtensorMap mwo = make_map(fn, wo, 3, wod, wos, wob), mout = make_map(fn, d_out, 5, od, xs, ob);
    const int swap_gu = wu < wg;
    const cuuint64_t gd[3] = {3584, 1024, 2}, gst[2] = {7168, (cuuint64_t)(swap_gu ? (const char*)wg - (const char*)wu : (const char*)wu - (const char*)wg)};
    const cuuint32_t gb[3] = {32, 64, 2};
    CUtensorMap mgu = make_map(fn, swap_gu ? wu : wg, 3, gd, gst, gb, CU_TENSOR_MAP_SWIZZLE_64B, CU_TENSOR_MAP_L2_PROMOTION_L2_128B);
    CUtensorMap mwd = make_map(fn, wd, 3, wdd, wos, wdb, CU_TENSOR_MAP_SWIZZLE_128B, CU_TENSOR_MAP_L2_PROMOTION_L2_128B);
    const cuuint64_t md[2] = {64, 32768}, ms[1] = {128};
    const cuuint32_t mb[2] = {64, 64};
    CUtensorMap mo = make_map(fn, scr, 2, md, ms, mb, CU_TENSOR_MAP_SWIZZLE_NONE, CU_TENSOR_MAP_L2_PROMOTION_NONE);
    cudaLaunchConfig_t cfg = {};
    cfg.gridDim = dim3(132); cfg.blockDim = dim3(512); cfg.dynamicSmemBytes = SMEM_LAUNCH; cfg.stream = cudaStreamPerThread;
    cudaLaunchAttribute at[1];
    at[0].id = cudaLaunchAttributeClusterDimension; at[0].val.clusterDim.x = 2; at[0].val.clusterDim.y = 1; at[0].val.clusterDim.z = 1;
    cfg.attrs = at; cfg.numAttrs = 1;
    cudaLaunchKernelEx(&cfg, fused_kernel, mx, mw, mwo, mout, mgu, mwd, mo, x, wr, scr, swap_gu, Weights{(const char*)wqkv, (const char*)wo, (const char*)wg, (const char*)wu, (const char*)wd});
}
```

```cpp
#include <cuda_runtime.h>
#include <cuda.h>
#include <cuda_bf16.h>
#include <stdint.h>

namespace {

constexpr int BOX = 8192, W_BYTES = 3 * BOX;
constexpr int OFF_E = 6 * BOX, OFF_W = 9 * BOX, OFF_X1 = 18 * BOX;
constexpr int OFF_WO = 6 * BOX;
constexpr int F_BYTES = 9216;
constexpr int OFF_FR = 24 * BOX;
constexpr int CS_BYTES = 3136;
constexpr int OFF_CS = OFF_E + 2 * F_BYTES;
constexpr int OFF_UPD = OFF_FR + 3 * F_BYTES;
constexpr int OFF_HIN = OFF_UPD + 2048;
constexpr int OFF_STAT = OFF_FR + 32768;
constexpr int OFF_SEL = OFF_STAT + 2112;
constexpr int OFF_EP = OFF_SEL + 32;
constexpr int OFF_BAR = OFF_EP + 16;
constexpr int B_WFULL = 0, B_XFULL = 3, B_AUX = 15, B_XT = 16, B_ROW = 17, B_WOFULL = 18, B_OFULL = 24, B_FFULL = 36;
constexpr int B_WEMPTY = 42, B_F1DONE = 45, B_XEMPTY = 46, B_WOEMPTY = 52, B_OEMPTY = 58;
constexpr int B_G1DONE = 66, B_FEMPTY = 67, B_STAGED = 72, B_UPD = 74, B_RDONE = 75, B_FREED = 76, NBAR = 78;
__device__ __forceinline__ uint32_t fslot(int s) { return s * F_BYTES + (s < 3 ? OFF_FR : OFF_E - 3 * F_BYTES); }
constexpr int SMEM_BYTES = OFF_BAR + NBAR * 8;
static_assert(OFF_HIN + 3072 <= OFF_STAT && OFF_CS + CS_BYTES <= OFF_W && SMEM_BYTES + 256 <= 232448 && OFF_BAR % 8 == 0 && OFF_UPD % 1024 == 0, "smem");
#define POLL_NS 100
#define NF1 5
#define PF_RATE 10
#define PF_START 7
#define ZF_NS 100
#define FFN2_GATE B_G1DONE
#define PF_NW 6
#define PF_D 8
#define EARLY_PF 1
#define ROWS_AT 11
#define STATS_UNROLL 1
constexpr int kStatsUnroll = STATS_UNROLL;
constexpr int BUDGET = 1 << 18;

struct Scratch {
    uint8_t o[2048 * 1024 * 2];
    uint32_t ypart[8][8][1024];
    uint32_t halo[128][512];
    uint32_t act[14336 + 4096];
    uint2 row[2048];
    uint32_t cs[16][800];
    uint32_t oflag[16][32];
    uint32_t cnt[9][32];
    uint32_t sel[32], csflag[32], epoch[32];
};
__device__ __align__(1024) Scratch g_scr;
struct Weights { const char *wqkv, *wo, *wg, *wu, *wd; };

#define TS(i) do {} while (0)
#define TS_END() do {} while (0)
#define TSC(c, i) do {} while (0)
#define NRETRY() do {} while (0)
constexpr int SMEM_LAUNCH = SMEM_BYTES;
__device__ __forceinline__ uint32_t smem_u32(const void* p) { return (uint32_t)__cvta_generic_to_shared(p); }
__device__ __forceinline__ void mbar_init(uint32_t bar, uint32_t cnt) { asm volatile("mbarrier.init.shared::cta.b64 [%0], %1;" ::"r"(bar), "r"(cnt) : "memory"); }
__device__ __forceinline__ void mbar_expect_tx(uint32_t bar, uint32_t bytes) { asm volatile("mbarrier.arrive.expect_tx.shared::cta.b64 _, [%0], %1;" ::"r"(bar), "r"(bytes) : "memory"); }
__device__ __forceinline__ void mbar_arrive(uint32_t bar) { asm volatile("mbarrier.arrive.shared::cta.b64 _, [%0];" ::"r"(bar) : "memory"); }
__device__ __forceinline__ uint32_t mapa(uint32_t a, uint32_t cta) { uint32_t r; asm("mapa.shared::cluster.u32 %0, %1, %2;" : "=r"(r) : "r"(a), "r"(cta)); return r; }
__device__ __forceinline__ void mbar_arrive_at(uint32_t cbar) { asm volatile("mbarrier.arrive.shared::cluster.b64 _, [%0];" ::"r"(cbar) : "memory"); }
__device__ __forceinline__ void mbar_wait(uint32_t bar, uint32_t parity, int& budget) {
    asm volatile("{\n.reg .pred p;\nLAB_WAIT:\nmbarrier.try_wait.parity.shared::cta.b64 p, [%1], %2;\n"
                 "add.s32 %0, %0, -1;\nsetp.gt.and.s32 p, %0, 0, !p;\n@p bra LAB_WAIT;\n}" : "+r"(budget) : "r"(bar), "r"(parity) : "memory");
}
__device__ __forceinline__ void mbar_wait_hot(uint32_t bar, uint32_t parity, int& budget) {
    asm volatile("{\n.reg .pred p;\nmbarrier.try_wait.parity.shared::cta.b64 p, [%1], %2;\n@p bra LAB_DONE;\nLAB_WAIT:\nmbarrier.try_wait.parity.shared::cta.b64 p, [%1], %2;\n"
                 "add.s32 %0, %0, -1;\nsetp.gt.and.s32 p, %0, 0, !p;\n@p bra LAB_WAIT;\nLAB_DONE:\n}" : "+r"(budget) : "r"(bar), "r"(parity) : "memory");
}
__device__ __forceinline__ void tma_2d_mc(uint32_t dst, const CUtensorMap* m, uint32_t bar, int c0, int c1) {
    asm volatile("cp.async.bulk.tensor.2d.shared::cluster.global.mbarrier::complete_tx::bytes.multicast::cluster [%0], [%1, {%3, %4}], [%2], %5;" ::"r"(dst), "l"(m), "r"(bar), "r"(c0), "r"(c1), "h"((uint16_t)3) : "memory");
}
__device__ __forceinline__ void tma_3d(uint32_t dst, const CUtensorMap* m, uint32_t bar, int c0, int c1, int c2) {
    asm volatile("cp.async.bulk.tensor.3d.shared::cluster.global.mbarrier::complete_tx::bytes [%0], [%1, {%3, %4, %5}], [%2];" ::"r"(dst), "l"(m), "r"(bar), "r"(c0), "r"(c1), "r"(c2) : "memory");
}
__device__ __forceinline__ void tma_4d(uint32_t dst, const CUtensorMap* m, uint32_t bar, int c0, int c1, int c2, int c3) {
    asm volatile("cp.async.bulk.tensor.4d.shared::cluster.global.mbarrier::complete_tx::bytes [%0], [%1, {%3, %4, %5, %6}], [%2];" ::"r"(dst), "l"(m), "r"(bar), "r"(c0), "r"(c1), "r"(c2), "r"(c3) : "memory");
}
__device__ __forceinline__ void tma_4d_mc(uint32_t dst, const CUtensorMap* m, uint32_t bar, int c0, int c1, int c2, int c3) {
    asm volatile("cp.async.bulk.tensor.4d.shared::cluster.global.mbarrier::complete_tx::bytes.multicast::cluster [%0], [%1, {%3, %4, %5, %6}], [%2], %7;" ::"r"(dst), "l"(m), "r"(bar), "r"(c0), "r"(c1), "r"(c2), "r"(c3), "h"((uint16_t)3) : "memory");
}
__device__ __forceinline__ void bulk_pf(const void* p, uint32_t bytes) { asm volatile("cp.async.bulk.prefetch.L2.global [%0], %1;" ::"l"(p), "r"(bytes) : "memory"); }
__device__ __forceinline__ void bulk_g2s(uint32_t dst, const void* src, uint32_t bytes, uint32_t bar) {
    asm volatile("cp.async.bulk.shared::cluster.global.mbarrier::complete_tx::bytes [%0], [%1], %2, [%3];" ::"r"(dst), "l"(src), "r"(bytes), "r"(bar) : "memory");
}
__device__ __forceinline__ void bulk_s2c(uint32_t cdst, uint32_t src, uint32_t bytes, uint32_t cbar) {
    asm volatile("cp.async.bulk.shared::cluster.shared::cta.mbarrier::complete_tx::bytes [%0], [%1], %2, [%3];" ::"r"(cdst), "r"(src), "r"(bytes), "r"(cbar) : "memory");
}
__device__ __forceinline__ void cluster_wait() { asm volatile("barrier.cluster.wait.aligned;" ::: "memory"); }
__device__ __forceinline__ void fence_gpu() { asm volatile("fence.acq_rel.gpu;" ::: "memory"); }
__device__ __forceinline__ void fence_async_smem() { asm volatile("fence.proxy.async.shared::cta;" ::: "memory"); }
__device__ __forceinline__ void fence_async_gmem() { asm volatile("fence.proxy.async.global;" ::: "memory"); }
__device__ __forceinline__ void wg_fence() { asm volatile("wgmma.fence.sync.aligned;" ::: "memory"); }
__device__ __forceinline__ void wg_commit() { asm volatile("wgmma.commit_group.sync.aligned;" ::: "memory"); }
template <int N> __device__ __forceinline__ void wg_wait() { asm volatile("wgmma.wait_group.sync.aligned %0;" ::"n"(N) : "memory"); }
__device__ __forceinline__ uint64_t mkdesc(uint32_t lo, uint32_t hi) { return ((uint64_t)hi << 32) | lo; }
__host__ __device__ constexpr uint32_t dhi(uint32_t sbo, uint32_t mode) { return (sbo >> 4) | (mode << 30); }
__host__ __device__ constexpr uint32_t dlo(uint32_t off, uint32_t lbo) { return (off >> 4) + ((lbo >> 4) << 16); }
__device__ __forceinline__ bool elect_one() {
    uint32_t e;
    asm volatile("{\n.reg .pred p;\nelect.sync _|p, 0xffffffff;\nselp.u32 %0, 1, 0, p;\n}" : "=r"(e));
    return e;
}
template <int R> __device__ __forceinline__ void reg_inc() { asm volatile("setmaxnreg.inc.sync.aligned.u32 %0;" ::"n"(R)); }
template <int R> __device__ __forceinline__ void reg_dec() { asm volatile("setmaxnreg.dec.sync.aligned.u32 %0;" ::"n"(R)); }
__device__ __forceinline__ void bar_sync(int id, int n) { asm volatile("bar.sync %0, %1;" ::"r"(id), "r"(n) : "memory"); }
__device__ __forceinline__ void bar_arrive(int id, int n) { asm volatile("bar.arrive %0, %1;" ::"r"(id), "r"(n) : "memory"); }
__device__ __forceinline__ uint32_t pack_bf16(float lo, float hi) { uint32_t r; asm("cvt.rn.bf16x2.f32 %0, %1, %2;" : "=r"(r) : "f"(hi), "f"(lo)); return r; }
__device__ __forceinline__ uint32_t pack_here(float lo, float hi) { uint32_t r; asm volatile("cvt.rn.bf16x2.f32 %0, %1, %2;" : "=r"(r) : "f"(hi), "f"(lo)); return r; }
__device__ __forceinline__ float bf_lo(uint32_t u) { return __uint_as_float(u << 16); }
__device__ __forceinline__ float bf_hi(uint32_t u) { return __uint_as_float(u & 0xffff0000u); }
__device__ __forceinline__ float bf16r(float v) { return bf_lo(pack_bf16(v, 0.f)); }
__device__ __forceinline__ float rcp(float x) { float r; asm("rcp.approx.ftz.f32 %0, %1;" : "=f"(r) : "f"(x)); return r; }
__device__ __forceinline__ float ex2(float x) { float r; asm("ex2.approx.ftz.f32 %0, %1;" : "=f"(r) : "f"(x)); return r; }
__device__ __forceinline__ float sigmoidf(float v) { return rcp(1.f + ex2(v * -1.4426950408889634f)); }
__device__ __forceinline__ uint32_t movm(uint32_t a) { uint32_t d; asm volatile("movmatrix.sync.aligned.m8n8.trans.b16 %0, %1;" : "=r"(d) : "r"(a)); return d; }
__device__ __forceinline__ void mma16816(float (&c)[4], uint32_t a0, uint32_t a1, uint32_t a2, uint32_t a3, uint32_t b0, uint32_t b1) {
    asm volatile("mma.sync.aligned.m16n8k16.row.col.f32.bf16.bf16.f32 {%0,%1,%2,%3}, {%4,%5,%6,%7}, {%8,%9}, {%0,%1,%2,%3};"
                 : "+f"(c[0]), "+f"(c[1]), "+f"(c[2]), "+f"(c[3]) : "r"(a0), "r"(a1), "r"(a2), "r"(a3), "r"(b0), "r"(b1));
}
__device__ __forceinline__ void mma1688(float (&c)[4], uint32_t a0, uint32_t a1, uint32_t b0) {
    asm volatile("mma.sync.aligned.m16n8k8.row.col.f32.bf16.bf16.f32 {%0,%1,%2,%3}, {%4,%5}, {%6}, {%0,%1,%2,%3};"
                 : "+f"(c[0]), "+f"(c[1]), "+f"(c[2]), "+f"(c[3]) : "r"(a0), "r"(a1), "r"(b0));
}
__device__ __forceinline__ void stsm4(uint32_t a, uint32_t r0, uint32_t r1, uint32_t r2, uint32_t r3) {
    asm volatile("stmatrix.sync.aligned.m8n8.x4.shared.b16 [%0], {%1,%2,%3,%4};" ::"r"(a), "r"(r0), "r"(r1), "r"(r2), "r"(r3) : "memory");
}
__device__ __forceinline__ void ldsm4(uint32_t* r, uint32_t a) {
    asm volatile("ldmatrix.sync.aligned.m8n8.x4.shared.b16 {%0,%1,%2,%3}, [%4];" : "=r"(r[0]), "=r"(r[1]), "=r"(r[2]), "=r"(r[3]) : "r"(a) : "memory");
}
__device__ __forceinline__ void ldsm4t(uint32_t* r, uint32_t a) {
    asm volatile("ldmatrix.sync.aligned.m8n8.x4.trans.shared.b16 {%0,%1,%2,%3}, [%4];" : "=r"(r[0]), "=r"(r[1]), "=r"(r[2]), "=r"(r[3]) : "r"(a) : "memory");
}
__device__ __forceinline__ uint32_t ld_rlx(const void* p) { uint32_t v; asm volatile("ld.relaxed.gpu.global.u32 %0, [%1];" : "=r"(v) : "l"(p) : "memory"); return v; }
__device__ __forceinline__ uint32_t ld_acq(const void* p) { uint32_t v; asm volatile("ld.acquire.gpu.global.u32 %0, [%1];" : "=r"(v) : "l"(p) : "memory"); return v; }
__device__ __forceinline__ uint2 ld_rlx2(const void* p) { uint2 v; asm volatile("ld.relaxed.gpu.global.v2.u32 {%0,%1}, [%2];" : "=r"(v.x), "=r"(v.y) : "l"(p) : "memory"); return v; }
__device__ __forceinline__ uint4 ld_rlx4(const void* p) { uint4 v; asm volatile("ld.relaxed.gpu.global.v4.u32 {%0,%1,%2,%3}, [%4];" : "=r"(v.x), "=r"(v.y), "=r"(v.z), "=r"(v.w) : "l"(p) : "memory"); return v; }
__device__ __forceinline__ void st_rlx(void* p, uint32_t v) { asm volatile("st.relaxed.gpu.global.u32 [%0], %1;" ::"l"(p), "r"(v) : "memory"); }
__device__ __forceinline__ void st_rlx2(void* p, uint32_t a, uint32_t b) { asm volatile("st.relaxed.gpu.global.v2.u32 [%0], {%1,%2};" ::"l"(p), "r"(a), "r"(b) : "memory"); }
__device__ __forceinline__ void st_rlx4(void* p, uint32_t a, uint32_t b, uint32_t c, uint32_t d) { asm volatile("st.relaxed.gpu.global.v4.u32 [%0], {%1,%2,%3,%4};" ::"l"(p), "r"(a), "r"(b), "r"(c), "r"(d) : "memory"); }
__device__ __forceinline__ void red_add(uint32_t* p) { asm volatile("red.relaxed.gpu.global.add.u32 [%0], 1;" ::"l"(p) : "memory"); }
__device__ __forceinline__ uint4 ldg_nc(const void* p) { uint4 v; asm volatile("ld.global.nc.v4.u32 {%0,%1,%2,%3}, [%4];" : "=r"(v.x), "=r"(v.y), "=r"(v.z), "=r"(v.w) : "l"(p)); return v; }
__device__ __forceinline__ void sts4(uint32_t a, uint32_t x, uint32_t y, uint32_t z, uint32_t w) { asm volatile("st.shared.v4.u32 [%0], {%1,%2,%3,%4};" ::"r"(a), "r"(x), "r"(y), "r"(z), "r"(w) : "memory"); }
__device__ __forceinline__ void sts2(uint32_t a, uint32_t x, uint32_t y) { asm volatile("st.shared.v2.u32 [%0], {%1,%2};" ::"r"(a), "r"(x), "r"(y) : "memory"); }
__device__ __forceinline__ void sts1(uint32_t a, uint32_t v) { asm volatile("st.shared.u32 [%0], %1;" ::"r"(a), "r"(v) : "memory"); }
__device__ __forceinline__ uint4 lds4(uint32_t a) { uint4 v; asm volatile("ld.shared.v4.u32 {%0,%1,%2,%3}, [%4];" : "=r"(v.x), "=r"(v.y), "=r"(v.z), "=r"(v.w) : "r"(a) : "memory"); return v; }
__device__ __forceinline__ float4 lds4f(uint32_t a) { float4 v; asm volatile("ld.shared.v4.f32 {%0,%1,%2,%3}, [%4];" : "=f"(v.x), "=f"(v.y), "=f"(v.z), "=f"(v.w) : "r"(a) : "memory"); return v; }
__device__ __forceinline__ float2 lds2f(uint32_t a) { float2 v; asm volatile("ld.shared.v2.f32 {%0,%1}, [%2];" : "=f"(v.x), "=f"(v.y) : "r"(a) : "memory"); return v; }
__device__ __forceinline__ float lds1f(uint32_t a) { float v; asm volatile("ld.shared.f32 %0, [%1];" : "=f"(v) : "r"(a) : "memory"); return v; }
__device__ __forceinline__ uint32_t lds1(uint32_t a) { uint32_t v; asm volatile("ld.shared.u32 %0, [%1];" : "=r"(v) : "r"(a) : "memory"); return v; }
__device__ __forceinline__ uint32_t redux_max(uint32_t v) { uint32_t r; asm volatile("redux.sync.max.u32 %0, %1, 0xffffffff;" : "=r"(r) : "r"(v)); return r; }
__device__ __forceinline__ uint32_t poll_all(const uint32_t* p, uint32_t mask, uint32_t want, int& budget) {
    uint32_t v;
#pragma unroll 1
    while (v = ld_acq(p), !__all_sync(0xffffffffu, (v & mask) == want) && --budget > 0) __nanosleep(POLL_NS);
    return v;
}

template <int TA, int TB>
__device__ __forceinline__ void wgmma_n192(float (&d)[96], uint64_t da, uint64_t db, int keep) {
    asm volatile("{\n.reg .pred p;\nsetp.ne.b32 p, %98, 0;\n"
        "wgmma.mma_async.sync.aligned.m64n192k16.f32.bf16.bf16 "
        "{%0, %1, %2, %3, %4, %5, %6, %7, %8, %9, %10, %11, %12, %13, %14, %15, "
        "%16, %17, %18, %19, %20, %21, %22, %23, %24, %25, %26, %27, %28, %29, %30, %31, "
        "%32, %33, %34, %35, %36, %37, %38, %39, %40, %41, %42, %43, %44, %45, %46, %47, "
        "%48, %49, %50, %51, %52, %53, %54, %55, %56, %57, %58, %59, %60, %61, %62, %63, "
        "%64, %65, %66, %67, %68, %69, %70, %71, %72, %73, %74, %75, %76, %77, %78, %79, "
        "%80, %81, %82, %83, %84, %85, %86, %87, %88, %89, %90, %91, %92, %93, %94, %95}, "
        "%96, %97, p, 1, 1, %99, %100;\n}\n"
        : "+f"(d[0]), "+f"(d[1]), "+f"(d[2]), "+f"(d[3]), "+f"(d[4]), "+f"(d[5]), "+f"(d[6]), "+f"(d[7]),
          "+f"(d[8]), "+f"(d[9]), "+f"(d[10]), "+f"(d[11]), "+f"(d[12]), "+f"(d[13]), "+f"(d[14]), "+f"(d[15]),
          "+f"(d[16]), "+f"(d[17]), "+f"(d[18]), "+f"(d[19]), "+f"(d[20]), "+f"(d[21]), "+f"(d[22]), "+f"(d[23]),
          "+f"(d[24]), "+f"(d[25]), "+f"(d[26]), "+f"(d[27]), "+f"(d[28]), "+f"(d[29]), "+f"(d[30]), "+f"(d[31]),
          "+f"(d[32]), "+f"(d[33]), "+f"(d[34]), "+f"(d[35]), "+f"(d[36]), "+f"(d[37]), "+f"(d[38]), "+f"(d[39]),
          "+f"(d[40]), "+f"(d[41]), "+f"(d[42]), "+f"(d[43]), "+f"(d[44]), "+f"(d[45]), "+f"(d[46]), "+f"(d[47]),
          "+f"(d[48]), "+f"(d[49]), "+f"(d[50]), "+f"(d[51]), "+f"(d[52]), "+f"(d[53]), "+f"(d[54]), "+f"(d[55]),
          "+f"(d[56]), "+f"(d[57]), "+f"(d[58]), "+f"(d[59]), "+f"(d[60]), "+f"(d[61]), "+f"(d[62]), "+f"(d[63]),
          "+f"(d[64]), "+f"(d[65]), "+f"(d[66]), "+f"(d[67]), "+f"(d[68]), "+f"(d[69]), "+f"(d[70]), "+f"(d[71]),
          "+f"(d[72]), "+f"(d[73]), "+f"(d[74]), "+f"(d[75]), "+f"(d[76]), "+f"(d[77]), "+f"(d[78]), "+f"(d[79]),
          "+f"(d[80]), "+f"(d[81]), "+f"(d[82]), "+f"(d[83]), "+f"(d[84]), "+f"(d[85]), "+f"(d[86]), "+f"(d[87]),
          "+f"(d[88]), "+f"(d[89]), "+f"(d[90]), "+f"(d[91]), "+f"(d[92]), "+f"(d[93]), "+f"(d[94]), "+f"(d[95])
        : "l"(da), "l"(db), "r"(keep), "n"(TA), "n"(TB));
}
template <int TA, int TB>
__device__ __forceinline__ void wgmma_n128(float (&d)[64], uint64_t da, uint64_t db, int keep) {
    asm volatile("{\n.reg .pred p;\nsetp.ne.b32 p, %66, 0;\n"
        "wgmma.mma_async.sync.aligned.m64n128k16.f32.bf16.bf16 "
        "{%0, %1, %2, %3, %4, %5, %6, %7, %8, %9, %10, %11, %12, %13, %14, %15, "
        "%16, %17, %18, %19, %20, %21, %22, %23, %24, %25, %26, %27, %28, %29, %30, %31, "
        "%32, %33, %34, %35, %36, %37, %38, %39, %40, %41, %42, %43, %44, %45, %46, %47, "
        "%48, %49, %50, %51, %52, %53, %54, %55, %56, %57, %58, %59, %60, %61, %62, %63}, "
        "%64, %65, p, 1, 1, %67, %68;\n}\n"
        : "+f"(d[0]), "+f"(d[1]), "+f"(d[2]), "+f"(d[3]), "+f"(d[4]), "+f"(d[5]), "+f"(d[6]), "+f"(d[7]),
          "+f"(d[8]), "+f"(d[9]), "+f"(d[10]), "+f"(d[11]), "+f"(d[12]), "+f"(d[13]), "+f"(d[14]), "+f"(d[15]),
          "+f"(d[16]), "+f"(d[17]), "+f"(d[18]), "+f"(d[19]), "+f"(d[20]), "+f"(d[21]), "+f"(d[22]), "+f"(d[23]),
          "+f"(d[24]), "+f"(d[25]), "+f"(d[26]), "+f"(d[27]), "+f"(d[28]), "+f"(d[29]), "+f"(d[30]), "+f"(d[31]),
          "+f"(d[32]), "+f"(d[33]), "+f"(d[34]), "+f"(d[35]), "+f"(d[36]), "+f"(d[37]), "+f"(d[38]), "+f"(d[39]),
          "+f"(d[40]), "+f"(d[41]), "+f"(d[42]), "+f"(d[43]), "+f"(d[44]), "+f"(d[45]), "+f"(d[46]), "+f"(d[47]),
          "+f"(d[48]), "+f"(d[49]), "+f"(d[50]), "+f"(d[51]), "+f"(d[52]), "+f"(d[53]), "+f"(d[54]), "+f"(d[55]),
          "+f"(d[56]), "+f"(d[57]), "+f"(d[58]), "+f"(d[59]), "+f"(d[60]), "+f"(d[61]), "+f"(d[62]), "+f"(d[63])
        : "l"(da), "l"(db), "r"(keep), "n"(TA), "n"(TB));
}
template <int TA, int TB>
__device__ __forceinline__ void wgmma_n8(float (&d)[4], uint64_t da, uint64_t db, int keep) {
    asm volatile("{\n.reg .pred p;\nsetp.ne.b32 p, %6, 0;\n"
        "wgmma.mma_async.sync.aligned.m64n8k16.f32.bf16.bf16 "
        "{%0, %1, %2, %3}, "
        "%4, %5, p, 1, 1, %7, %8;\n}\n"
        : "+f"(d[0]), "+f"(d[1]), "+f"(d[2]), "+f"(d[3])
        : "l"(da), "l"(db), "r"(keep), "n"(TA), "n"(TB));
}
__device__ __forceinline__ void wgmma_rs_n128(float (&d)[64], uint32_t a0, uint32_t a1, uint32_t a2, uint32_t a3, uint64_t db) {
    asm volatile("{\n.reg .pred p;\nsetp.ne.b32 p, 1, 0;\n"
        "wgmma.mma_async.sync.aligned.m64n128k16.f32.bf16.bf16 "
        "{%0, %1, %2, %3, %4, %5, %6, %7, %8, %9, %10, %11, %12, %13, %14, %15, "
        "%16, %17, %18, %19, %20, %21, %22, %23, %24, %25, %26, %27, %28, %29, %30, %31, "
        "%32, %33, %34, %35, %36, %37, %38, %39, %40, %41, %42, %43, %44, %45, %46, %47, "
        "%48, %49, %50, %51, %52, %53, %54, %55, %56, %57, %58, %59, %60, %61, %62, %63}, "
        "{%64, %65, %66, %67}, %68, p, 1, 1, 1;\n}\n"
        : "+f"(d[0]), "+f"(d[1]), "+f"(d[2]), "+f"(d[3]), "+f"(d[4]), "+f"(d[5]), "+f"(d[6]), "+f"(d[7]),
          "+f"(d[8]), "+f"(d[9]), "+f"(d[10]), "+f"(d[11]), "+f"(d[12]), "+f"(d[13]), "+f"(d[14]), "+f"(d[15]),
          "+f"(d[16]), "+f"(d[17]), "+f"(d[18]), "+f"(d[19]), "+f"(d[20]), "+f"(d[21]), "+f"(d[22]), "+f"(d[23]),
          "+f"(d[24]), "+f"(d[25]), "+f"(d[26]), "+f"(d[27]), "+f"(d[28]), "+f"(d[29]), "+f"(d[30]), "+f"(d[31]),
          "+f"(d[32]), "+f"(d[33]), "+f"(d[34]), "+f"(d[35]), "+f"(d[36]), "+f"(d[37]), "+f"(d[38]), "+f"(d[39]),
          "+f"(d[40]), "+f"(d[41]), "+f"(d[42]), "+f"(d[43]), "+f"(d[44]), "+f"(d[45]), "+f"(d[46]), "+f"(d[47]),
          "+f"(d[48]), "+f"(d[49]), "+f"(d[50]), "+f"(d[51]), "+f"(d[52]), "+f"(d[53]), "+f"(d[54]), "+f"(d[55]),
          "+f"(d[56]), "+f"(d[57]), "+f"(d[58]), "+f"(d[59]), "+f"(d[60]), "+f"(d[61]), "+f"(d[62]), "+f"(d[63])
        : "r"(a0), "r"(a1), "r"(a2), "r"(a3), "l"(db));
}
__device__ __forceinline__ void wgmma_rs_n192(float (&d)[96], uint32_t a0, uint32_t a1, uint32_t a2, uint32_t a3, uint64_t db) {
    asm volatile("{\n.reg .pred p;\nsetp.ne.b32 p, 1, 0;\n"
        "wgmma.mma_async.sync.aligned.m64n192k16.f32.bf16.bf16 "
        "{%0, %1, %2, %3, %4, %5, %6, %7, %8, %9, %10, %11, %12, %13, %14, %15, "
        "%16, %17, %18, %19, %20, %21, %22, %23, %24, %25, %26, %27, %28, %29, %30, %31, "
        "%32, %33, %34, %35, %36, %37, %38, %39, %40, %41, %42, %43, %44, %45, %46, %47, "
        "%48, %49, %50, %51, %52, %53, %54, %55, %56, %57, %58, %59, %60, %61, %62, %63, "
        "%64, %65, %66, %67, %68, %69, %70, %71, %72, %73, %74, %75, %76, %77, %78, %79, "
        "%80, %81, %82, %83, %84, %85, %86, %87, %88, %89, %90, %91, %92, %93, %94, %95}, "
        "{%96, %97, %98, %99}, %100, p, 1, 1, 1;\n}\n"
        : "+f"(d[0]), "+f"(d[1]), "+f"(d[2]), "+f"(d[3]), "+f"(d[4]), "+f"(d[5]), "+f"(d[6]), "+f"(d[7]),
          "+f"(d[8]), "+f"(d[9]), "+f"(d[10]), "+f"(d[11]), "+f"(d[12]), "+f"(d[13]), "+f"(d[14]), "+f"(d[15]),
          "+f"(d[16]), "+f"(d[17]), "+f"(d[18]), "+f"(d[19]), "+f"(d[20]), "+f"(d[21]), "+f"(d[22]), "+f"(d[23]),
          "+f"(d[24]), "+f"(d[25]), "+f"(d[26]), "+f"(d[27]), "+f"(d[28]), "+f"(d[29]), "+f"(d[30]), "+f"(d[31]),
          "+f"(d[32]), "+f"(d[33]), "+f"(d[34]), "+f"(d[35]), "+f"(d[36]), "+f"(d[37]), "+f"(d[38]), "+f"(d[39]),
          "+f"(d[40]), "+f"(d[41]), "+f"(d[42]), "+f"(d[43]), "+f"(d[44]), "+f"(d[45]), "+f"(d[46]), "+f"(d[47]),
          "+f"(d[48]), "+f"(d[49]), "+f"(d[50]), "+f"(d[51]), "+f"(d[52]), "+f"(d[53]), "+f"(d[54]), "+f"(d[55]),
          "+f"(d[56]), "+f"(d[57]), "+f"(d[58]), "+f"(d[59]), "+f"(d[60]), "+f"(d[61]), "+f"(d[62]), "+f"(d[63]),
          "+f"(d[64]), "+f"(d[65]), "+f"(d[66]), "+f"(d[67]), "+f"(d[68]), "+f"(d[69]), "+f"(d[70]), "+f"(d[71]),
          "+f"(d[72]), "+f"(d[73]), "+f"(d[74]), "+f"(d[75]), "+f"(d[76]), "+f"(d[77]), "+f"(d[78]), "+f"(d[79]),
          "+f"(d[80]), "+f"(d[81]), "+f"(d[82]), "+f"(d[83]), "+f"(d[84]), "+f"(d[85]), "+f"(d[86]), "+f"(d[87]),
          "+f"(d[88]), "+f"(d[89]), "+f"(d[90]), "+f"(d[91]), "+f"(d[92]), "+f"(d[93]), "+f"(d[94]), "+f"(d[95])
        : "r"(a0), "r"(a1), "r"(a2), "r"(a3), "l"(db));
}

template <int HS>
__device__ __forceinline__ void attn_pair(const uint32_t* q, const uint32_t* k, const uint32_t* v, const uint32_t* kh, const uint32_t* vh,
                                          const float* fu, const float* fn, const float* rk, float bias0, float bias1, uint32_t mU, uint32_t zero, const float* ci, uint32_t* o) {
    float s0[2][4] = {}, s1[2][4] = {}, s2[2][4] = {};
#pragma unroll
    for (int n = 0; n < 4; n++) {
        const int hd = n & 1, a = 8 * hd + 2 * (n & 2);
        mma16816(s1[hd], q[a], q[a + 1], q[a + 2], q[a + 3], k[a], k[a + 2]);
        mma16816(s2[hd], q[a], q[a + 1], q[a + 2], q[a + 3], k[a + 1], k[a + 3]);
    }
#pragma unroll
    for (int n = 0; n < 4; n++) {
        const int hd = n & 1, a = 8 * hd + 2 * (n & 2);
        mma16816(s0[hd], q[a], q[a + 1], q[a + 2], q[a + 3], kh[HS * (a / 2)], kh[HS * (a / 2 + 1)]);
    }
    float e[2][4], m[2][2];
#pragma unroll
    for (int hd = 0; hd < 2; hd++) {
        e[hd][2] = fmaf(s1[hd][2], fu[2], s2[hd][2] * fn[2]); e[hd][3] = fmaf(s1[hd][3], fu[3], s2[hd][3] * fn[3]);
        e[hd][0] = fmaf(s0[hd][0], fu[0], fmaf(s1[hd][0], fn[0], bias0)); e[hd][1] = fmaf(s0[hd][1], fu[1], fmaf(s1[hd][1], fn[1], bias1));
        m[hd][1] = fmaxf(e[hd][2], e[hd][3]); m[hd][0] = fmaxf(e[hd][0], e[hd][1]);
    }
#pragma unroll
    for (int x = 1; x < 3; x++)
#pragma unroll
        for (int n = 0; n < 4; n++) m[n & 1][1 - (n >> 1)] = fmaxf(m[n & 1][1 - (n >> 1)], __shfl_xor_sync(0xffffffffu, m[n & 1][1 - (n >> 1)], x));
    float c[2][4][4] = {};
#pragma unroll
    for (int hd = 0; hd < 2; hd++) {
#pragma unroll
        for (int n = 0; n < 4; n++) e[hd][n] = ex2(e[hd][n] - m[hd][n >> 1]);
        const uint32_t plo = pack_bf16(e[hd][0] * rk[0], e[hd][1] * rk[1]), phi = pack_bf16(e[hd][2] * rk[2], e[hd][3] * rk[3]);
        const uint32_t z0 = plo & zero, z1 = phi & zero;
        const uint32_t a0 = plo & ~mU, a1 = phi & mU, a3 = phi & ~mU, b0 = plo & mU;
#pragma unroll
        for (int jj = 0; jj < 4; jj++) mma16816(c[hd][jj], a0, a1, z0, a3, v[8 * hd + 2 * jj], v[8 * hd + 2 * jj + 1]);
#pragma unroll
        for (int jj = 0; jj < 4; jj++) mma1688(c[hd][jj], b0, z1, vh[HS * (4 * hd + jj)]);
        m[hd][0] = e[hd][0] + e[hd][1]; m[hd][1] = e[hd][2] + e[hd][3];
    }
#pragma unroll
    for (int x = 1; x < 3; x++)
#pragma unroll
        for (int n = 0; n < 4; n++) m[n >> 1][n & 1] += __shfl_xor_sync(0xffffffffu, m[n >> 1][n & 1], x);
#pragma unroll
    for (int hd = 0; hd < 2; hd++) {
        const float i0 = rcp(m[hd][0]), i1 = rcp(m[hd][1]);
#pragma unroll
        for (int jj = 0; jj < 4; jj++) {
            o[8 * hd + 2 * jj] = pack_bf16(fmaf(c[hd][jj][0], i0, 0x1p-120f), c[hd][jj][1] * i0);
            o[8 * hd + 2 * jj + 1] = pack_bf16(fmaf(c[hd][jj][2], i1, 0x1p-120f), c[hd][jj][3] * i1);
        }
    }
}

__device__ __forceinline__ uint32_t norm_pair(uint32_t u, float m, float rinv) {
    const uint32_t d = pack_bf16(bf_lo(u) - m, bf_hi(u) - m);
    return pack_bf16(bf_lo(d) * rinv, bf_hi(d) * rinv);
}

__global__ void __launch_bounds__(512, 1)
fused_kernel(const __grid_constant__ CUtensorMap mx, const __grid_constant__ CUtensorMap mw, const __grid_constant__ CUtensorMap mwo,
             const __grid_constant__ CUtensorMap mout, const __grid_constant__ CUtensorMap mgu, const __grid_constant__ CUtensorMap mwd,
             const __grid_constant__ CUtensorMap mo,
             const __nv_bfloat16* __restrict__ x, const __nv_bfloat16* __restrict__ wr, Scratch* __restrict__ scr, int swap_gu, const Weights pf) {
    extern __shared__ __align__(1024) uint8_t smem[];
    const uint32_t sb = smem_u32(smem);
    const uint32_t bars = sb + OFF_BAR;
    const int tid = threadIdx.x, lane = tid & 31, warp = __shfl_sync(0xffffffffu, tid >> 5, 0);
    const uint32_t sd = (sb & 0x3FFFF) >> 4;
    const int hp = blockIdx.x & 1, cl = blockIdx.x >> 1;
    int pr = cl - 4 + (max(cl - 36, 0) * 37 >> 8);
    asm("{\n.reg .pred p;\nsetp.lt.s32 p, %1, 4;\nselp.s32 %0, %2, %0, p;\n}" : "+r"(pr) : "r"(cl), "r"(39 + 8 * cl));
    const int b = pr * 2 + hp, mt = pr >> 3, p = pr & 7, nt = 2 * p + hp, rh = p & 1, cb = (p & 6) + hp;
    const int par = mt >> 2, j0 = (mt & 3) * 256;
    int budget = BUDGET;

    TSC(tid == 0, 0);
    if (b < 128 && tid >= 32 && tid < 112) {
        const char* a = tid < 64 ? (const char*)x + (size_t)(16 * b + ((tid >> 1) & 15)) * 2048 + (tid & 1) * 128 : pf.wqkv + (size_t)b * 6144 + (tid - 64) * 128;
        asm volatile("prefetch.global.L2 [%0];" ::"l"(a));
    }
    auto load_w = [&](int k, int s) {
        const uint32_t full = bars + 8 * (B_WFULL + s);
        mbar_expect_tx(full, W_BYTES);
        tma_3d(sb + OFF_W + s * W_BYTES, &mw, full, nt * 64, k * 64, 0);
    };
    auto load_x = [&](int n) {
        const int w = n & 1, j = n >> 1;
        const uint32_t full = bars + 8 * (B_XFULL + w * 6 + j);
        mbar_expect_tx(full, BOX);
        tma_4d(sb + w * OFF_X1 + j * BOX, &mx, full, par * 1024 + (n >> 2) * 64, 0, (j0 + w * 128) >> 5, (~n >> 1) & 1);
    };
    if (warp < NBAR / 6 && elect_one()) {
        const uint32_t cnt = warp < B_WEMPTY / 6 ? 1 : warp < B_G1DONE / 6 ? 2 : warp < B_STAGED / 6 ? 4 : 8;
#pragma unroll
        for (int i = 0; i < 6; i++) mbar_init(bars + 48 * warp + 8 * i, cnt);
        asm volatile("fence.mbarrier_init.release.cluster;" ::: "memory");
        if (warp == 0 && b < 128) { TS(12); load_x(0); load_w(0, 2); TS(14); }
    }
    __syncthreads();

    if (b >= 128) {
        const int hc = b - 128, g = lane >> 2, t = lane & 3;
        if (warp < 12) {
            const int n = warp / 3, part = warp - 3 * n;
            const uint32_t ep = ld_rlx(&scr->epoch[0]) + 1;
            auto load = [&](int k) {
                const uint32_t full = bars + 8 * (2 * n + (k & 1));
                mbar_expect_tx(full, W_BYTES);
                tma_3d(sb + (2 * n + (k & 1)) * W_BYTES, &mw, full, (4 * hc + n) * 64, k * 64, 0);
            };
            if (part == 0 && elect_one()) { load(0); load(1); }
            __syncwarp();
            float c0[4] = {0.f, 0.f, 0.f, 0.f}, c1[4] = {0.f, 0.f, 0.f, 0.f};
            const uint32_t sel = g == 0 ? 0x3f80u : g == 1 ? 0x3f800000u : 0u;
            const uint32_t a = sb + 2 * n * W_BYTES + part * BOX + t * 256 + ((g ^ (2 * t)) << 4);
#pragma unroll 1
            for (int k = 0; k < 16; k++) {
                mbar_wait(bars + 8 * (2 * n + (k & 1)), (k >> 1) & 1, budget);
                uint4 v[8], u[8];
#pragma unroll
                for (int i = 0; i < 8; i++) { v[i] = lds4(a + (k & 1) * W_BYTES + i * 1024); u[i] = lds4(((a + 128) ^ 16) + (k & 1) * W_BYTES + i * 1024); }
#pragma unroll
                for (int i = 0; i < 8; i++) { mma16816(c0, v[i].x, v[i].y, u[i].x, u[i].y, sel, sel); mma16816(c1, v[i].z, v[i].w, u[i].z, u[i].w, sel, sel); }
                bar_sync(1 + n, 96);
                if (part == 0 && k < 14 && elect_one()) load(k + 2);
                __syncwarp();
            }
            if (t == 0) {
#pragma unroll
                for (int r = 0; r < 3; r++) {
                    const uint32_t q0 = pack_bf16(c0[0], c0[1]), q1 = pack_bf16(c0[2], c0[3]), q2 = pack_bf16(c1[0], c1[1]), q3 = pack_bf16(c1[2], c1[3]);
                    st_rlx4(&scr->cs[4 * hc + n][16 + (part * 8 + g) * 32 + r * 4], q0, q1, q2, q3);
                    c0[0] -= bf_lo(q0); c0[1] -= bf_hi(q0); c0[2] -= bf_lo(q1); c0[3] -= bf_hi(q1);
                    c1[0] -= bf_lo(q2); c1[1] -= bf_hi(q2); c1[2] -= bf_lo(q3); c1[3] -= bf_hi(q3);
                }
            }
            bar_sync(7, 384);
            if (tid == 0) { fence_gpu(); st_rlx(&scr->csflag[hc], ep); }
            TSC(tid == 0, 19);
        }
        if (warp < 8) TS_END();
        return;
    }
    asm volatile("barrier.cluster.arrive.relaxed.aligned;" ::: "memory");

    const int kc = b >> 4, c2 = b & 15;
    if (warp >= 12) {
        reg_dec<24>();
        if (warp == 12) {
            if (elect_one()) {
#pragma unroll 1
                for (int n = 1; n < 12; n++) {
                    load_x(n);
                    if (n == ROWS_AT) { mbar_expect_tx(bars + 8 * B_ROW, 4 * BOX); bulk_g2s(sb + OFF_FR, x + (size_t)b * 16 * 1024, 4 * BOX, bars + 8 * B_ROW); }
                    if (n == 3 || n == 7) load_w((n + 1) >> 2, n >> 2);
                }
                int s = 2; uint32_t ph = 0;
#pragma unroll 1
                for (int k = 3; k < 16; k++) {
                    mbar_wait(bars + 8 * (B_WEMPTY + s), ph, budget);
                    load_w(k, s);
                    if (++s == 3) s = 0;
                    if (s == 2) ph ^= 1;
                }
                TS(27);
                s = 2;
#pragma unroll 1
                for (int i = 0; i < 16; i++) {
                    mbar_wait(bars + 8 * (i < 2 ? B_WEMPTY + i : i < 4 ? B_G1DONE : i < 6 ? B_F1DONE : B_WOEMPTY + s), i >= 12, budget);
                    if (i == 1) {
                        mbar_expect_tx(bars + 8 * B_XT, 4 * BOX);
#pragma unroll 1
                        for (int n = 0; n < 4; n++)
                            tma_4d(sb + (n >> 1) * OFF_X1 + (4 + (n & 1)) * BOX, &mx, bars + 8 * B_XT, par * 1024 + cb * 128 + (n & 1) * 64, 0, (j0 + rh * 128) >> 5, 1 - (n >> 1));
                    }
                    const uint32_t full = bars + 8 * (B_WOFULL + s);
                    mbar_expect_tx(full, 2 * BOX);
                    tma_3d(sb + OFF_WO + s * 2 * BOX, &mwo, full, 0, ((2 * p + (i < 2 ? i ^ hp : i)) & 15) * 64, cb * 2);
                    TSC(TIMING % 10 == 4, 48 + i);
                    if (++s == 6) s = 0;
                }
                TS(25);
            }
        } else {
            bar_sync(8, 224);
            const uint32_t ep = lds1(sb + OFF_EP);
            if (warp == 13) {
                cluster_wait();
                if (elect_one()) {
                    int j = 0, q = 0, left = BUDGET; uint32_t ph = 0;
#pragma unroll 1
                    for (int n = 6; n < 32; n++) {
                        mbar_wait(bars + 8 * (B_XEMPTY + j), ph, left);
                        tma_4d_mc(sb + hp * OFF_X1 + j * BOX, &mx, bars + 8 * (B_XFULL + hp * 6 + j), par * 1024 + (n >> 1) * 64, 0, (j0 + hp * 128) >> 5, ~n & 1);
                        if (++j == 6) { j = 0; ph ^= 1; }
#pragma unroll 1
                        for (; q < (PF_RATE * (n - PF_START) >> 3) && q < 18 + PF_NW; q++) {
                            const int u = q - PF_NW;
                            if (u < 0) bulk_pf(pf.wqkv + (size_t)(1024 + 128 * u + b) * 6144, 6144);
                            else if (u < 16) bulk_pf((b < 64 ? pf.wg : pf.wu) + (size_t)(u * 64 + (b & 63)) * 7168, 7168);
                            else bulk_pf(pf.wo + (size_t)((u - 16) * 128 + b) * 8192, 8192);
                        }
                    }
                }
                __syncwarp();
                uint32_t* hs = &scr->halo[b - 16][lane * 4];
                int tries = BUDGET;
#pragma unroll 1
                for (int c = 0; c < 4; c += 2) {
                    uint4 v0 = make_uint4(0, 0, 0, 0), v1 = v0;
                    if (j0) {
#pragma unroll 1
                        do { v0 = ld_rlx4(hs + c * 128); v1 = ld_rlx4(hs + c * 128 + 128); } while ((v0.x == 0 || v1.x == 0) && --tries > 0);
                        st_rlx(hs + c * 128, 0); st_rlx(hs + c * 128 + 128, 0);
                    }
                    __syncwarp();
                    stsm4(sb + OFF_HIN + c * 512 + lane * 16, v0.x, v0.y, v0.z, v0.w);
                    stsm4(sb + OFF_HIN + c * 512 + 512 + lane * 16, v1.x, v1.y, v1.z, v1.w);
                }
                bar_arrive(11, 64);
                TSC(lane == 0, 31);
                const int src = ((mt * 2 + rh) * 2 + 1 - hp) * 1024;
                if (elect_one()) {
                    const uint32_t* fl = &scr->oflag[mt * 2 + 1 - hp][0];
                    const uint32_t inv = (ep & 1) - 1;
                    uint32_t ready = 0, ph = 0;
                    int s = 4;
#pragma unroll 1
                    for (int i = 2; i < 16; i++) {
                        const int kb = (2 * p + i) & 15;
#pragma unroll 1
                        while (!((ready >> kb) & 1) && --budget > 0) ready = ld_rlx(fl) ^ inv;
                        TSC(i == 2, 30);
                        mbar_wait(bars + 8 * (B_OEMPTY + s), ph, budget);
                        tma_2d_mc(sb + hp * OFF_X1 + s * BOX, &mo, bars + 8 * (B_OFULL + hp * 6 + s), 0, src + kb * 64);
                        TSC(TIMING % 10 == 4 && hp == 0, 32 + i);
                        if (++s == 6) s = 0;
                        if (s == 4) ph ^= 1;
                    }
                }
            } else if (warp == 14) {
                if (elect_one()) {
                    uint32_t ph = 0;
#pragma unroll 1
                    for (int f = b < 112 ? 0 : 1; f < 2; f++) {
                        const int n = f ? 7 : 16, ns = f ? 3 : NF1, wx = f ? 0 : b * 32, wy = f ? kc * 448 : 0, wz = f ? c2 : 0;
                        const uint32_t* act = scr->act + (f ? kc * 7 * 256 : 14336);
                        const CUtensorMap* wm = f ? &mwd : &mgu;
                        int s = f;
#pragma unroll 1
                        for (int q = -3 * f; q < n; q++) {
                            const uint32_t full = bars + 8 * (B_FFULL + s), dst = sb + fslot(s);
                            if (q == 0) {
#pragma unroll 1
                                while (ld_acq(&scr->cnt[f ? kc : 8][0]) != ep * (f ? 14 : 8) && --budget > 0) __nanosleep(POLL_NS);
                                fence_async_gmem();
                                TS(f ? 29 : 26);
                            }
                            if ((unsigned)q >= 3u * f) {
                                mbar_wait(bars + 8 * (B_FEMPTY + s), (ph >> s) & 1, budget);
                                ph ^= 1u << s;
                                mbar_expect_tx(full, F_BYTES);
                                tma_3d(dst, wm, full, wx, wy + (q < 0 ? q + 3 : q) * 64, wz);
                            }
                            if (q >= 0) bulk_g2s(dst + BOX, act + q * 256, 1024, full);
                            if (!f && q >= PF_D && q < PF_D + 8) bulk_pf(pf.wd + (size_t)((q - PF_D) * 112 + b) * 8192, 8192);
                            if (++s == ns) s = 0;
                        }
                    }
                }
            } else {
                mbar_wait(bars + 8 * B_ROW, 0, budget);
                uint8_t* oz = scr->o + ((size_t)mt * 64 + nt) * BOX + lane * 16;
#pragma unroll 1
                for (int i = 0; i < 64; i++) { st_rlx4(oz + (i >> 4) * 16 * BOX + (i & 15) * 512, 0, 0, 0, 0); if ((i & 3) == 3) __nanosleep(ZF_NS); }
                __syncwarp();
                fence_gpu();
                mbar_wait(bars + 8 * B_RDONE, 0, budget);
                int tries = BUDGET;
#pragma unroll 1
                for (int i = lane; i < 88; i += 32) {
                    const uint2* rp = &scr->row[2 * (j0 - 8 + i) + par];
                    uint2 v0, v1, v2;
#pragma unroll 1
                    do { v0 = ld_rlx2(rp + (j0 + i < 8 ? 16 : 0)); v1 = ld_rlx2(rp + 176); v2 = ld_rlx2(rp + 352); } while ((((v0.y ^ ep) | (v1.y ^ ep) | (v2.y ^ ep)) & 31) && --tries > 0);
                    sts2(sb + OFF_STAT + i * 8, (v0.x << 16) ^ 0x80000000u, __float_as_uint(rcp(bf_hi(v0.x))));
                    sts2(sb + OFF_STAT + i * 8 + 704, (v1.x << 16) ^ 0x80000000u, __float_as_uint(rcp(bf_hi(v1.x))));
                    sts2(sb + OFF_STAT + i * 8 + 1408, (v2.x << 16) ^ 0x80000000u, __float_as_uint(rcp(bf_hi(v2.x))));
                }
                __syncwarp();
                poll_all(&scr->csflag[lane & 3], ~0u, ep, budget);
                if (elect_one()) {
                    fence_async_gmem();
                    mbar_expect_tx(bars + 8 * B_AUX, CS_BYTES);
                    bulk_g2s(sb + OFF_CS, scr->cs[nt], CS_BYTES, bars + 8 * B_AUX);
                    TS(21);
                    mbar_expect_tx(bars + 8 * (B_OFULL + 3), BOX); mbar_expect_tx(bars + 8 * (B_OFULL + 9), BOX);
#pragma unroll 1
                    for (int v = 0; v < 2; v++) {
                        const uint32_t ring = sb + v * OFF_X1 + 2 * BOX, fb = bars + 8 * (B_OFULL + v * 6 + 2);
                        mbar_wait(bars + 8 * (B_STAGED + v), 0, budget);
                        asm volatile("red.relaxed.gpu.global.xor.b32 [%0], %1;" ::"l"(&scr->oflag[mt * 2 + 1 - v][0]), "r"(1u << nt) : "memory");
                        TS(13 + 2 * v);
                        mbar_arrive(fb);
                        mbar_wait(bars + 8 * B_G1DONE, 0, budget);
                        bulk_s2c(mapa(ring + BOX, hp ^ 1), ring, BOX, mapa(fb + 8, hp ^ 1));
                        if (v == 0) {
                            mbar_wait(bars + 8 * B_FREED, 0, budget);
#pragma unroll
                            for (int n = 0; n < 8; n++) {
                                mbar_expect_tx(bars + 8 * (B_OFULL + (n >> 2) * 6 + (4 + (n & 3)) % 6), BOX);
                                mbar_arrive_at(mapa(bars + 8 * B_OEMPTY, n >> 2) + (4 + (n & 3)) % 6 * 8);
                            }
                        }
                    }
                }
            }
        }
    } else if (warp >= 8) {
        reg_dec<40>();
        const int wq = warp - 8, ta = tid - 256, g = lane >> 2, t = lane & 3;
        const uint32_t rbuf = sb + OFF_FR + wq * BOX, rbar = bars + 8 * B_ROW;
        const uint4 wv = ldg_nc(wr + ta * 8);
        if (ta == 0) sts1(sb + OFF_EP, ld_rlx(&scr->epoch[0]) + 1);
        sts4(sb + OFF_STAT + ta * 16, wv.x, wv.y, wv.z, wv.w);
        bar_sync(8, 224);
        const uint32_t ep = lds1(sb + OFF_EP);
        {
            const int s = b * 16 + wq * 4 + (lane >> 3);
            if ((lane & 7) == 0) st_rlx2(&scr->row[s], 0, ep - 1);
            float sw = 0.f;
#pragma unroll 1
            for (int i = 0; i < 16; i++) { const uint32_t q = lds1(sb + OFF_STAT + i * 128 + lane * 4); sw += bf_lo(q) + bf_hi(q); }
#pragma unroll 1
            for (int o = 16; o > 0; o >>= 1) sw += __shfl_xor_sync(0xffffffffu, sw, o);
            float s1 = 0.f, s2 = 0.f, sr = 0.f;
            const uint32_t xa = rbuf + (lane >> 3) * 2048 + (lane & 7) * 16, wa = sb + OFF_STAT + (lane & 7) * 16;
            mbar_wait(rbar, 0, budget);
            TSC(ta == 0, 17);
            uint4 u = lds4(xa), w4 = lds4(wa);
#pragma unroll kStatsUnroll
            for (int i = 1; i <= 16; i++) {
                const uint32_t o = (i * 128) & 2047;
                const uint4 un = lds4(xa + o), wn = lds4(wa + o);
#pragma unroll
                for (int c = 0; c < 4; c++) {
                    const float a0 = bf_lo((&u.x)[c]), a1 = bf_hi((&u.x)[c]);
                    s1 += a0; s2 = fmaf(a0, a0, s2); sr = fmaf(a0, bf_lo((&w4.x)[c]), sr);
                    s1 += a1; s2 = fmaf(a1, a1, s2); sr = fmaf(a1, bf_hi((&w4.x)[c]), sr);
                }
                u = un; w4 = wn;
            }
#pragma unroll 1
            for (int o = 1; o < 8; o <<= 1) {
                s1 += __shfl_xor_sync(0xffffffffu, s1, o); s2 += __shfl_xor_sync(0xffffffffu, s2, o); sr += __shfl_xor_sync(0xffffffffu, sr, o);
            }
            const float mean = s1 * (1.f / 1024.f), mb = bf16r(mean);
            float var = fmaf(-mean, mean, s2 * (1.f / 1024.f));
            sr = fmaf(-mb, sw, sr);
            if (__builtin_expect(__any_sync(0xffffffffu, mean * mean > 256.f * var), 0)) {
                float a2 = 0.f, ar = 0.f;
#pragma unroll 1
                for (int i = 0; i < 64; i++) {
                    const uint32_t o = (i >> 2) * 128 + (i & 3) * 4, q1 = lds1(xa + o), q2 = lds1(wa + o);
                    a2 = fmaf(bf_lo(q1) - mean, bf_lo(q1) - mean, fmaf(bf_hi(q1) - mean, bf_hi(q1) - mean, a2));
                    ar = fmaf(bf_lo(q1) - mb, bf_lo(q2), fmaf(bf_hi(q1) - mb, bf_hi(q2), ar));
                }
#pragma unroll 1
                for (int o = 1; o < 8; o <<= 1) { a2 += __shfl_xor_sync(0xffffffffu, a2, o); ar += __shfl_xor_sync(0xffffffffu, ar, o); }
                var = a2 * (1.f / 1024.f); sr = ar;
            }
            float den;
            asm("sqrt.approx.f32 %0, %1;" : "=f"(den) : "f"(bf16r(bf16r(var) + 1e-5f)));
            const uint32_t st = pack_bf16(mb, den);
            const uint32_t rb = pack_bf16(0.f, sr * rcp(bf_hi(st)) + 0.f);
            uint32_t ord = (int)rb < 0 ? ~rb & 0xffff0000u : rb | 0x80000000u;
            if ((rb & 0x7fffffffu) > 0x7f800000u) ord = 0;
            if ((lane & 7) == 0) st_rlx2(&scr->row[s], st, ord | ((2047 - s) << 5) | (ep & 31));
            __syncwarp();
            if (lane < 7) mbar_arrive(bars + 8 * (lane < 5 ? B_FEMPTY + lane : B_RDONE));
        }
        TSC(ta == 0, 18);
        if ((b >> 3) == 14) {
            const uint32_t gm = sb + OFF_E, cnt = gm + 64, res = gm + 80, list = gm + 128;
            uint32_t kv[16];
            int tries = BUDGET;
#pragma unroll 1
            do {
                uint32_t bad = 0;
#pragma unroll
                for (int n = 0; n < 16; n++) kv[n] = ld_rlx(&scr->row[n * 128 + ta].y);
#pragma unroll
                for (int n = 0; n < 16; n++) bad |= kv[n] ^ ep;
                if ((bad & 31) == 0) break;
            } while (--tries > 0);
            __syncwarp();
            TSC(ta == 0, 26);
            uint32_t m = 0;
#pragma unroll
            for (int n = 0; n < 16; n++) m = max(m, kv[n]);
            uint32_t gmax = m;
#pragma unroll
            for (int o = 1; o < 8; o <<= 1) gmax = max(gmax, __shfl_xor_sync(0xffffffffu, gmax, o));
            sts1(gm + (ta >> 3) * 4, gmax);
            sts1(cnt, 0);
            bar_sync(12, 128);
            const uint32_t c = lds1(gm + (lane & 15) * 4);
            int rank = 0;
#pragma unroll
            for (int i = 0; i < 2; i++) { const uint4 q = lds4(gm + (lane >> 4) * 32 + i * 16); rank += (q.x > c) + (q.y > c) + (q.z > c) + (q.w > c); }
            rank += __shfl_xor_sync(0xffffffffu, rank, 16);
            const uint32_t thr = redux_max(rank == 7 ? c : 0u);
#pragma unroll 1
            while (m >= thr) {
                uint32_t at, m2 = 0;
                asm volatile("atom.shared.add.u32 %0, [%1], 1;" : "=r"(at) : "r"(cnt) : "memory");
#pragma unroll
                for (int n = 0; n < 16; n++) m2 = max(m2, kv[n] < m ? kv[n] : 0u);
                sts1(list + at * 4, m);
                if (m2 == 0) break;
                m = m2;
            }
            bar_sync(12, 128);
            const int nc = lds1(cnt);
#pragma unroll 1
            for (int i = ta >> 3; i < ((nc + 3) & ~3); i += 16) {
                const uint32_t ki = lds1(list + i * 4);
                int r = 0;
#pragma unroll 1
                for (int n = lane & 7; n < nc; n += 8) r += lds1(list + n * 4) > ki;
                __syncwarp();
#pragma unroll
                for (int o = 1; o < 8; o <<= 1) r += __shfl_xor_sync(0xffffffffu, r, o);
                if (r == (b & 7) && i < nc) sts1(res, ki);
            }
            bar_sync(12, 128);
            const uint32_t k0 = lds1(res);
            const int r0 = 2047 - ((k0 >> 5) & 2047);
            TSC(ta == 0, 22);
            if (ta == 0) st_rlx(&scr->sel[b & 7], k0);
            const uint4 v0 = ldg_nc(x + (size_t)r0 * 1024 + ta * 8);
            const uint32_t s0 = ld_rlx(&scr->row[r0]);
            const float m0 = bf_lo(s0), i0 = rcp(bf_hi(s0));
            const int ao = 14336 + (ta >> 3) * 256 + (b & 7) * 32 + ((ta ^ b) & 7) * 4;
            st_rlx4(scr->act + ao, norm_pair(v0.x, m0, i0), norm_pair(v0.y, m0, i0), norm_pair(v0.z, m0, i0), norm_pair(v0.w, m0, i0));
            bar_sync(12, 128);
            if (ta == 0) { fence_gpu(); red_add(&scr->cnt[8][0]); }
        }
        uint32_t fph = 0, own = 0; float sig = 0.f;
#pragma unroll 1
        for (int ph = 0; ph < 2; ph++) {
            if (ph || b < 112) {
                float acc[4] = {0.f, 0.f, 0.f, 0.f};
                const uint32_t alo = sd + (ph ? dlo(0, 8192) : dlo(0, 4096)), ahi = ph ? dhi(1024, 1) : dhi(512, 2), astep = ph ? 128 : 64;
                const uint32_t bhi = ph ? dhi(128, 0) : dhi(1024, 1), bstep = ph ? 16 : 2;
                const int ns = ph ? 3 : NF1;
                int s = ph, ps = 0, left = BUDGET;
                if (ph) mbar_wait(bars + 8 * FFN2_GATE, 0, left);
                bool rel = false;
#pragma unroll 1
                for (int q = ph ? 7 : 16; q > 0; q--) {
                    const uint32_t so = fslot(s) >> 4, da = alo + so, db = sd + dlo(BOX, 128) + so;
                    mbar_wait_hot(bars + 8 * (B_FFULL + s), (fph >> s) & 1, left);
                    TSC(TIMING % 10 == 3 && ta == 0, 32 + (ph ? 23 : 16) - q);
                    wg_fence();
#pragma unroll
                    for (int j = 0; j < 4; j++) wgmma_n8<1, 0>(acc, mkdesc(da + j * astep, ahi), mkdesc(db + j * bstep, bhi), 1);
                    wg_commit();
                    wg_wait<1>();
                    if (rel) mbar_arrive(bars + 8 * (B_FEMPTY + ps));
                    rel = lane == 0; ps = s;
                    fph ^= 1u << s;
                    if (++s == ns) s = 0;
                }
                wg_wait<0>();
                if (ph == 0) {
                    if (rel) mbar_arrive(bars + 8 * (B_FEMPTY + 15 % NF1));
                    const bool second = (wq >= 2) != (swap_gu != 0);
                    const uint32_t xa = sb + OFF_HIN + 2048 + ((wq & 1) * 32 + lane) * 16;
                    if (second) sts4(xa, __float_as_uint(acc[0]), __float_as_uint(acc[1]), __float_as_uint(acc[2]), __float_as_uint(acc[3]));
                    bar_sync(12, 128);
                    if (!second) {
                        const float4 up = lds4f(xa);
                        float hv[4];
#pragma unroll
                        for (int c = 0; c < 4; c++) { const float ga = bf16r(acc[c]); hv[c] = bf16r(ga * sigmoidf(ga)) * bf16r((&up.x)[c]); }
                        const int ao = (b * 4 + (wq & 1) * 2) * 32 + lane;
                        st_rlx(scr->act + ao, movm(pack_bf16(hv[0], hv[1]))); st_rlx(scr->act + 32 + ao, movm(pack_bf16(hv[2], hv[3])));
                    }
                    bar_sync(12, 128);
                    if (ta == 0) { fence_gpu(); red_add(&scr->cnt[b / 14][0]); }
                } else {
#pragma unroll
                    for (int c = 0; c < 4; c++) st_rlx(&scr->ypart[kc][2 * t + (c & 1)][c2 * 64 + wq * 16 + (c >> 1) * 8 + g], (__float_as_uint(acc[c]) & ~1u) | (ep & 1));
                    if (b == 0 && ta == 0) st_rlx(&scr->epoch[0], ep);
                }
                TSC(ta == 0, 22 + ph);
            }
            if (ph == 0) {
                if ((ta & 126) == 64) mbar_arrive(bars + 8 * B_F1DONE);
                const uint32_t kj = poll_all(&scr->sel[lane & 7], 31u, ep & 31, budget);
                const int row = 2047 - ((kj >> 5) & 2047), jj = (row & 1) == par ? (row >> 1) - j0 : -1;
                sig = bf16r(sigmoidf(__uint_as_float(((int)kj < 0 ? kj & 0x7fffffffu : ~kj) & 0xffff0000u)));
                own = __ballot_sync(0xffffffffu, (jj >> 7) == rh) & 255;
                sts1(sb + OFF_SEL + (lane & 7) * 4, jj);
                sts4(sb + OFF_UPD + ta * 16, 0, 0, 0, 0);
            }
            if ((own != 0) == ph) {
#pragma unroll 1
                for (; own; own &= own - 1) {
                    const int j = __ffs(own) - 1;
                    const uint32_t* src = &scr->ypart[lane >> 3][j][cb * 128 + wq * 32 + (lane & 7) * 4];
                    uint4 v0, v1; int tries = BUDGET;
#pragma unroll 1
                    do { v0 = ld_rlx4(src); v1 = ld_rlx4(src + 4 * 8192); } while ((((v0.x ^ ep) | (v1.x ^ ep)) & 1) && --tries > 0);
                    __syncwarp();
                    float a[4];
                    const float sj = __shfl_sync(0xffffffffu, sig, j);
#pragma unroll
                    for (int c = 0; c < 4; c++) {
                        a[c] = __uint_as_float((&v0.x)[c]) + __uint_as_float((&v1.x)[c]);
                        a[c] += __shfl_xor_sync(0xffffffffu, a[c], 8); a[c] += __shfl_xor_sync(0xffffffffu, a[c], 16);
                        a[c] = bf16r(a[c]) * sj;
                    }
                    sts2(sb + OFF_UPD + (wq >> 1) * 1024 + j * 128 + ((((wq & 1) * 4 + ((lane >> 1) & 3)) ^ j) << 4) + (lane & 1) * 8, pack_bf16(a[0], a[1]), pack_bf16(a[2], a[3]));
                }
                fence_async_smem();
                __syncwarp();
                if (lane < 2) mbar_arrive(bars + 8 * B_UPD);
            }
        }
        TSC(ta == 0, 24);
    } else {
        reg_inc<224>();
        const int w = warp >> 2, wi = warp & 3, g = lane >> 2, t = lane & 3;
        const bool elect = (tid & 127) == 0;
        const uint32_t mad = (lane & 15) * 128 + (((lane >> 4) ^ (lane & 7)) << 4);
        float acc[64];
        const uint32_t ring = sb + w * OFF_X1, ofull = bars + 8 * (B_OFULL + w * 6), oempty = mapa(bars + 8 * B_OEMPTY, w);
        const int r0 = rh * 128 + wi * 32 + (1 - w) * 16 + g;
        {
            float acc0[96], acc1[96];
            const uint32_t sta = sb + OFF_STAT + (8 + w * 128 + wi * 32) * 8;
            {
                const uint32_t xfull = bars + 8 * (B_XFULL + w * 6), xempty = mapa(bars + 8 * B_XEMPTY, w), dx0 = sd + dlo(w * OFF_X1, 16);
                int j = 0, pj = 0, ws = 2, pws = 0; uint32_t xph = 0;
                cluster_wait();
#pragma unroll 1
                for (int k = 0;; k++) {
                    const uint32_t dx = dx0 + j * (BOX >> 4), dw = sd + dlo(OFF_W, BOX) + ws * (W_BYTES >> 4);
                    mbar_wait(bars + 8 * (B_WFULL + ws), xph, budget);
                    mbar_wait(xfull + 8 * j, xph, budget);
                    TSC(elect && k == 0, 1 + 8 * w);
                    TSC(TIMING % 10 == 1 && tid == 0, 32 + k);
                    wg_wait<0>();
                    wg_fence();
#pragma unroll
                    for (int kk = 0; kk < 4; kk++) wgmma_n192<0, 1>(acc1, mkdesc(dx + kk * 2, dhi(1024, 1)), mkdesc(dw + kk * 128, dhi(1024, 1)), kk ? 1 : k);
                    wg_commit();
                    if (elect && k > 0) {
                        mbar_arrive(bars + 8 * (B_WEMPTY + pws));
                        if (k <= 13) { mbar_expect_tx(xfull + 8 * pj, BOX); mbar_arrive_at(xempty + 8 * pj); }
                    }
                    if (k == 15) break;
                    mbar_wait(xfull + 8 * j + 8, xph, budget);
                    wg_wait<0>();
                    wg_fence();
#pragma unroll
                    for (int kk = 0; kk < 4; kk++) wgmma_n192<0, 1>(acc0, mkdesc(dx + 512 + kk * 2, dhi(1024, 1)), mkdesc(dw + kk * 128, dhi(1024, 1)), kk ? 1 : k);
                    wg_commit();
                    if (elect && k <= 12) { mbar_expect_tx(xfull + 8 * j, BOX); mbar_arrive_at(xempty + 8 * j); }
                    pj = j + 1; pws = ws;
                    if (++ws == 3) ws = 0;
                    j += 2;
                    if (j == 6) { j = 0; xph ^= 1; }
                }
            }
            mbar_wait(bars + 8 * B_AUX, 0, budget);
            const uint32_t zero = budget >> 30, pm = t & 1 ? 0x4432 : 0x3232, ra = sta + ((t >> 1) * 16 + g) * 8;
            const uint32_t a0 = __byte_perm(lds1(ra), 0, pm), a1 = __byte_perm(lds1(ra + 64), 0, pm), a2 = a0 & zero, a3 = a1 & zero;
            wg_fence();
            wgmma_rs_n192(acc1, a0, a1, a2, a3, mkdesc(sd + dlo(OFF_CS, 0), dhi(128, 0)));
            wg_commit();
            const bool u0 = 2 * t > g, u1 = 2 * t + 1 > g;
            uint32_t mU = (u0 ? 0xffffu : 0u) | (u1 ? 0xffff0000u : 0u);
            uint32_t ka0 = sta + (2 * t - (u0 ? 8 : 0)) * 8 + 4, ka1 = sta + (2 * t + 1 - (u1 ? 8 : 0)) * 8 + 4;
            float rk[2][4], fu[2][4], fn[2][4];
            auto factors = [&](int h) {
#pragma unroll
                for (int n = 0; n < 4; n += 2) {
                    const float rq = lds1f(sta + (16 * h + 4 * n + g) * 8 + 4) * (0.17677669529663687f * 1.4426950408889634f);
                    rk[h][n] = lds1f(ka0 + h * 128 + n * 32); rk[h][n + 1] = lds1f(ka1 + h * 128 + n * 32);
                    const float f0 = rq * rk[h][n], f1 = rq * rk[h][n + 1];
                    fu[h][n] = u0 ? f0 : 0.f; fn[h][n] = f0 - fu[h][n]; fu[h][n + 1] = u1 ? f1 : 0.f; fn[h][n + 1] = f1 - fu[h][n + 1];
                }
#pragma unroll
                for (int n = 0; n < 4; n++) asm volatile("" : "+f"(fu[h][n]), "+f"(fn[h][n]));
            };
            uint8_t* og = scr->o + ((size_t)(mt * 4 + w * 2) * 16 + nt) * BOX + wi * 256 + lane * 4;
            asm volatile("" : "+r"(ka0), "+r"(ka1));
            mbar_wait(bars + 8 * (B_XFULL + w * 6 + 1), 1, budget);
            wg_wait<0>();
            wg_fence();
#pragma unroll
            for (int kk = 0; kk < 4; kk++)
                wgmma_n192<0, 1>(acc0, mkdesc(sd + dlo(w * OFF_X1 + BOX, 16) + kk * 2, dhi(1024, 1)), mkdesc(sd + dlo(OFF_W + 2 * W_BYTES, BOX) + kk * 128, dhi(1024, 1)), 1);
            wgmma_rs_n192(acc0, a0, a1, a2, a3, mkdesc(sd + dlo(OFF_CS + 64, 0), dhi(128, 0)));
            wg_commit();
            TSC(elect, 19 + w);
            uint32_t pk0[48], pk1[48], o[16] = {};
#pragma unroll
            for (int j = 0; j < 48; j++) if (j < 16 || (j & 1)) pk1[j] = pack_here(acc1[2 * j], acc1[2 * j + 1]);
            if (warp < 7) {
#pragma unroll
                for (int c = 0; c < 4; c++) stsm4(ring + wi * 2048 + c * 512 + lane * 16, pk1[17 + 8 * c], pk1[19 + 8 * c], pk1[21 + 8 * c], pk1[23 + 8 * c]);
                bar_arrive(1 + warp, 64);
            } else if (j0 != 768) {
#pragma unroll
                for (int c = 0; c < 4; c++) {
                    pk1[17 + 8 * c] = max(pk1[17 + 8 * c], 1u);
                    st_rlx4(&scr->halo[b][c * 128 + lane * 4], pk1[17 + 8 * c], pk1[19 + 8 * c], pk1[21 + 8 * c], pk1[23 + 8 * c]);
                }
            }
            TSC(tid == 224, 28);
#pragma unroll
            for (int j = 16; j < 48; j += 2) pk1[j] = pack_here(acc1[2 * j], acc1[2 * j + 1]);
            factors(1);
            uint32_t od = sb + 2 * BOX + wi * 256 + (lane >> 4) * 1024 + (lane & 15) * 16, g1peer = mapa(bars + 8 * B_G1DONE, hp ^ 1);
            uint32_t ha = sb + (warp == 0 ? OFF_HIN : warp <= 4 ? -2048 : OFF_X1 - 5 * 2048) + warp * 2048 + lane * 16;
            const bool first = warp == 0 && j0 == 0;
            float bias0 = first && u0 ? -INFINITY : 0.f, bias1 = first && u1 ? -INFINITY : 0.f;
            float ci[4];
#pragma unroll
            for (int n = 0; n < 4; n++) ci[n] = __uint_as_float((0x03800000u + n) | zero);
            asm volatile("" : "+f"(ci[0]), "+f"(ci[1]), "+f"(ci[2]), "+f"(ci[3]));
            asm volatile("" : "+l"(og), "+r"(mU), "+r"(od), "+r"(ha), "+f"(bias0), "+f"(bias1));
            mbar_wait(bars + 8 * (B_WEMPTY + 1), 0, budget);
            wg_wait<0>();
            if (elect) { mbar_arrive(bars + 8 * B_G1DONE); mbar_arrive_at(g1peer); }
            TSC(elect, 2 + 8 * w);
            auto hand_over = [&](int v) {
                asm volatile("{\n.reg .pred p;\nsetp.ne.b32 p, %17, 0;\n"
                             "@p stmatrix.sync.aligned.m8n8.x4.shared.b16 [%16], {%0,%1,%2,%3};\n@p stmatrix.sync.aligned.m8n8.x4.shared.b16 [%16 + 2048], {%4,%5,%6,%7};\n"
                             "@p stmatrix.sync.aligned.m8n8.x4.shared.b16 [%16 + 4096], {%8,%9,%10,%11};\n@p stmatrix.sync.aligned.m8n8.x4.shared.b16 [%16 + 6144], {%12,%13,%14,%15};\n"
                             "fence.proxy.async.shared::cta;\n}"
                             ::"r"(o[0]), "r"(o[1]), "r"(o[2]), "r"(o[3]), "r"(o[4]), "r"(o[5]), "r"(o[6]), "r"(o[7]), "r"(o[8]), "r"(o[9]), "r"(o[10]), "r"(o[11]),
                               "r"(o[12]), "r"(o[13]), "r"(o[14]), "r"(o[15]), "r"(od + v * OFF_X1), "r"((int)(w == rh)) : "memory");
#pragma unroll
                for (int i = 0; i < 16; i++) asm volatile("st.global.u32 [%0], %1;" ::"l"(og + (1 - v) * 16 * BOX + (i >> 1) * 1024 + (i & 1) * 128), "r"(o[i]) : "memory");
                __syncwarp();
                if (lane == 0) mbar_arrive(bars + 8 * (B_STAGED + v));
            };
#pragma unroll
            for (int j = 32; j < 48; j++) pk1[j] = movm(pk1[j]);
#pragma unroll
            for (int j = 17; j < 48; j += 2) pk0[j] = pack_here(acc0[2 * j], acc0[2 * j + 1]);
#pragma unroll
            for (int j = 33; j < 48; j += 2) pk0[j] = movm(pk0[j]);
            factors(0);
            const float2 s0 = lds2f(sb + OFF_STAT + (8 + r0) * 8), s1 = lds2f(sb + OFF_STAT + (16 + r0) * 8);
            const float m0 = s0.x * s0.y, f0 = 1.f + s0.y, m1 = s1.x * s1.y, f1 = 1.f + s1.y;
            attn_pair<2>(pk1, pk1 + 16, pk1 + 32, pk0 + 17, pk0 + 33, fu[1], fn[1], rk[1], 0.f, 0.f, mU, zero, ci, o);
            hand_over(0);
            TSC(elect, 3 + 8 * w);
#pragma unroll
            for (int j = 0; j < 48; j++) if (j < 16 || !(j & 1)) pk0[j] = pack_here(acc0[2 * j], acc0[2 * j + 1]);
#pragma unroll
            for (int j = 32; j < 48; j += 2) pk0[j] = movm(pk0[j]);
            mbar_wait_hot(bars + 8 * B_XT, 0, budget);
#pragma unroll
            for (int j = 0; j < 8; j++) {
                uint32_t a[4];
                ldsm4(a, ((ring + wi * 2048 + mad) ^ ((j & 3) * 32)) + (4 + (j >> 2)) * BOX);
                acc[8 * j + 0] = fmaf(bf_lo(a[0]), f0, m0); acc[8 * j + 1] = fmaf(bf_hi(a[0]), f0, m0);
                acc[8 * j + 2] = fmaf(bf_lo(a[1]), f1, m1); acc[8 * j + 3] = fmaf(bf_hi(a[1]), f1, m1);
                acc[8 * j + 4] = fmaf(bf_lo(a[2]), f0, m0); acc[8 * j + 5] = fmaf(bf_hi(a[2]), f0, m0);
                acc[8 * j + 6] = fmaf(bf_lo(a[3]), f1, m1); acc[8 * j + 7] = fmaf(bf_hi(a[3]), f1, m1);
            }
            bar_sync(warp ? warp : 11, 64);
            uint32_t hl[16];
            ldsm4t(hl + 8, ha + 1024); ldsm4t(hl + 12, ha + 1536); ldsm4(hl, ha); ldsm4(hl + 4, ha + 512);
            __syncwarp();
            if (lane == 0) mbar_arrive(bars + 8 * B_FREED);
            attn_pair<1>(pk0, pk0 + 16, pk0 + 32, hl, hl + 8, fu[0], fn[0], rk[0], bias0, bias1, mU, zero, ci, o);
            hand_over(1);
        }
        TSC(tid == 0, 4);
        {
            const uint32_t da0 = sd + dlo(w * OFF_X1, 1024), db0 = sd + dlo(OFF_WO, BOX);
            const uint32_t chk = ring + wi * 256 + (lane >> 3) * 1032 + (lane & 7) * 32 + (lane & 4);
            uint32_t s8 = 16, ps8 = 0, ph = 0;
#pragma unroll 1
            for (int i = 0; i < 16; i++) {
                mbar_wait_hot(ofull + s8, ph, budget);
                const uint32_t seen0 = lds1(chk + s8 * (BOX / 8)), seen1 = lds1(chk + s8 * (BOX / 8) + 4096);
                mbar_wait_hot(bars + 8 * B_WOFULL + s8, ph, budget);
                if (__builtin_expect(__any_sync(0xffffffffu, min(seen0, seen1) == 0), 0)) {
                    const uint32_t at = wi * 256 + (lane >> 4) * 1024 + (lane & 15) * 16;
                    const uint8_t* src = scr->o + ((size_t)((mt * 2 + rh) * 2 + 1 - w) * 16 + ((2 * p + (i < 2 ? i ^ hp : i)) & 15)) * BOX + at;
#pragma unroll 1
                    for (int n = 0; n < 8192; n += 2048) {
                        uint4 v; int tries = 4096;
#pragma unroll 1
                        do { v = ld_rlx4(src + n); } while (v.x == 0 && --tries > 0);
                        sts4(ring + s8 * (BOX / 8) + at + n, v.x, v.y, v.z, v.w);
                    }
                    NRETRY();
                    fence_async_smem();
                    __syncwarp();
                }
                TSC(TIMING % 10 == 1 && tid == 0, 48 + i);
                TSC(TIMING % 10 == 2 && elect, 32 + w * 16 + i);
                const uint32_t da = da0 + s8 * (BOX >> 7), db = db0 + s8 * (BOX >> 6);
                wg_wait<1>();
                wg_fence();
#pragma unroll
                for (int kk = 0; kk < 4; kk++) {
                    wgmma_n128<0, 1>(acc, mkdesc(da + kk * 128, dhi(128, 0)), mkdesc(db + kk * 128, dhi(1024, 1)), 1);
                    if (kk & 1) wg_commit();
                }
                wg_wait<2>();
                if (elect && (unsigned)(i - 1) < 10) { mbar_expect_tx(ofull + ps8, BOX); mbar_arrive_at(oempty + ps8); mbar_arrive(bars + 8 * B_WOEMPTY + ps8); }
                ps8 = s8;
                s8 = s8 == 40 ? 0 : s8 + 8;
                if (s8 == 16) ph ^= 1;
            }
            mbar_wait(bars + 8 * B_UPD, 0, budget);
            const float2 sl = lds2f(sb + OFF_SEL + t * 8);
            const int d0 = __float_as_int(sl.x) - r0, d1 = __float_as_int(sl.y) - r0;
            const uint32_t a0 = (d0 == 0 ? 0x3f80u : 0u) | (d1 == 0 ? 0x3f800000u : 0u), a1 = (d0 == 8 ? 0x3f80u : 0u) | (d1 == 8 ? 0x3f800000u : 0u);
            wg_fence();
            wgmma_rs_n128(acc, a0, a1, 0u, 0u, mkdesc(sd + dlo(OFF_UPD, 1024), dhi(0, 1)));
            wg_commit();
            wg_wait<0>();
            TSC(elect, 7 + 9 * w);
            const uint32_t os0 = ring + wi * 4096;
#pragma unroll
            for (int j = 0; j < 8; j++)
                stsm4(((os0 + mad) ^ ((j & 3) * 32)) + (j >> 2) * 2048, pack_bf16(acc[8 * j], acc[8 * j + 1]), pack_bf16(acc[8 * j + 2], acc[8 * j + 3]),
                      pack_bf16(acc[8 * j + 4], acc[8 * j + 5]), pack_bf16(acc[8 * j + 6], acc[8 * j + 7]));
            fence_async_smem();
            __syncwarp();
            if (elect_one()) {
                asm volatile("cp.async.bulk.tensor.5d.global.shared::cta.bulk_group [%0, {%2, %2, %3, %4, %5}], [%1];\ncp.async.bulk.commit_group;\ncp.async.bulk.wait_group.read 0;"
                             ::"l"(&mout), "r"(os0), "r"(0), "r"(((j0 + rh * 128) >> 5) + wi), "r"(1 - w), "r"(par * 16 + cb * 2) : "memory");
            }
            TSC(elect, 8 - 2 * w);
            TS_END();
        }
    }
}

typedef CUresult (*EncodeFn)(CUtensorMap*, CUtensorMapDataType, cuuint32_t, void*, const cuuint64_t*, const cuuint64_t*, const cuuint32_t*,
                             const cuuint32_t*, CUtensorMapInterleave, CUtensorMapSwizzle, CUtensorMapL2promotion, CUtensorMapFloatOOBfill);

CUtensorMap make_map(EncodeFn fn, const void* base, int rank, const cuuint64_t* dims, const cuuint64_t* strides, const cuuint32_t* box,
                     CUtensorMapSwizzle swz = CU_TENSOR_MAP_SWIZZLE_128B, CUtensorMapL2promotion pro = CU_TENSOR_MAP_L2_PROMOTION_L2_256B) {
    CUtensorMap m;
    cuuint32_t es[5] = {1, 1, 1, 1, 1};
    fn(&m, CU_TENSOR_MAP_DATA_TYPE_BFLOAT16, rank, (void*)base, dims, strides, box, es, CU_TENSOR_MAP_INTERLEAVE_NONE,
       swz, pro, CU_TENSOR_MAP_FLOAT_OOB_FILL_NONE);
    return m;
}

}

extern "C" void kernel_launch(void* const* d_in, const int* in_sizes, int n_in, void* d_out, int out_size) {
    (void)in_sizes; (void)n_in; (void)out_size;
    const __nv_bfloat16* x = (const __nv_bfloat16*)d_in[0];
    const __nv_bfloat16* wqkv = (const __nv_bfloat16*)d_in[1];
    const __nv_bfloat16* wo = (const __nv_bfloat16*)d_in[2];
    const __nv_bfloat16* wr = (const __nv_bfloat16*)d_in[4];
    const __nv_bfloat16* wg = (const __nv_bfloat16*)d_in[5];
    const __nv_bfloat16* wu = (const __nv_bfloat16*)d_in[6];
    const __nv_bfloat16* wd = (const __nv_bfloat16*)d_in[7];
    static EncodeFn fn = nullptr;
    static Scratch* scr = nullptr;
    if (!fn) {
        void* p = nullptr; cudaDriverEntryPointQueryResult q;
        cudaGetDriverEntryPoint("cuTensorMapEncodeTiled", &p, cudaEnableDefault, &q);
        fn = (EncodeFn)p;
        cudaFuncSetAttribute(fused_kernel, cudaFuncAttributeMaxDynamicSharedMemorySize, SMEM_LAUNCH);
        cudaGetSymbolAddress((void**)&scr, g_scr);
    }
    const cuuint64_t xd[4] = {2048, 16, 32, 2}, xs[4] = {4096, 131072, 65536, 128}, od[5] = {64, 16, 32, 2, 32};
    const cuuint32_t xb[4] = {64, 16, 4, 1}, ob[5] = {64, 16, 1, 1, 2};
    const cuuint64_t wdm[3] = {1024, 1024, 3}, wst[2] = {6144, 2048};
    const cuuint32_t wb[3] = {64, 64, 3};
    const cuuint64_t wod[3] = {64, 1024, 16}, wdd[3] = {64, 3584, 16}, wos[2] = {2048, 128};
    const cuuint32_t wob[3] = {64, 64, 2}, wdb[3] = {64, 64, 1};
    CUtensorMap mx = make_map(fn, x, 4, xd, xs, xb), mw = make_map(fn, wqkv, 3, wdm, wst, wb);
    CUtensorMap mwo = make_map(fn, wo, 3, wod, wos, wob), mout = make_map(fn, d_out, 5, od, xs, ob);
    const int swap_gu = wu < wg;
    const cuuint64_t gd[3] = {3584, 1024, 2}, gst[2] = {7168, (cuuint64_t)(swap_gu ? (const char*)wg - (const char*)wu : (const char*)wu - (const char*)wg)};
    const cuuint32_t gb[3] = {32, 64, 2};
    CUtensorMap mgu = make_map(fn, swap_gu ? wu : wg, 3, gd, gst, gb, CU_TENSOR_MAP_SWIZZLE_64B, CU_TENSOR_MAP_L2_PROMOTION_L2_128B);
    CUtensorMap mwd = make_map(fn, wd, 3, wdd, wos, wdb, CU_TENSOR_MAP_SWIZZLE_128B, CU_TENSOR_MAP_L2_PROMOTION_L2_128B);
    const cuuint64_t md[2] = {64, 32768}, ms[1] = {128};
    const cuuint32_t mb[2] = {64, 64};
    CUtensorMap mo = make_map(fn, scr, 2, md, ms, mb, CU_TENSOR_MAP_SWIZZLE_NONE, CU_TENSOR_MAP_L2_PROMOTION_NONE);
    cudaLaunchConfig_t cfg = {};
    cfg.gridDim = dim3(132); cfg.blockDim = dim3(512); cfg.dynamicSmemBytes = SMEM_LAUNCH; cfg.stream = cudaStreamPerThread;
    cudaLaunchAttribute at[1];
    at[0].id = cudaLaunchAttributeClusterDimension; at[0].val.clusterDim.x = 2; at[0].val.clusterDim.y = 1; at[0].val.clusterDim.z = 1;
    cfg.attrs = at; cfg.numAttrs = 1;
    cudaLaunchKernelEx(&cfg, fused_kernel, mx, mw, mwo, mout, mgu, mwd, mo, x, wr, scr, swap_gu, Weights{(const char*)wqkv, (const char*)wo, (const char*)wg, (const char*)wu, (const char*)wd});
}
```

```cpp
#include <cuda_runtime.h>
#include <cuda.h>
#include <cuda_bf16.h>
#include <stdint.h>

namespace {

constexpr int BOX = 8192, W_BYTES = 3 * BOX;
constexpr int OFF_X1 = 6 * BOX, OFF_FR = 12 * BOX, OFF_E = 16 * BOX, OFF_W = 19 * BOX;
constexpr int OFF_WO = OFF_E;
constexpr int OFF_UPD = OFF_FR, OFF_HIN = OFF_UPD + 2048, OFF_GU = OFF_HIN + 2048, OFF_FS = OFF_GU + 1024;
constexpr int F_BYTES = 9216;
constexpr int CS_BYTES = 3136;
constexpr int OFF_CS = OFF_FS + 5 * F_BYTES;
constexpr int OFF_STAT = 28 * BOX;
constexpr int OFF_SEL = OFF_STAT + 2112;
constexpr int OFF_EP = OFF_SEL + 32;
constexpr int OFF_BAR = OFF_EP + 16;
constexpr int B_WFULL = 0, B_XFULL = 3, B_AUX = 15, B_XT = 16, B_ROW = 17, B_WOFULL = 18, B_OFULL = 24, B_FFULL = 36;
constexpr int B_WEMPTY = 42, B_F1DONE = 45, B_XEMPTY = 46, B_WOEMPTY = 52, B_OEMPTY = 58;
constexpr int B_G1DONE = 66, B_FEMPTY = 67, B_STAGED = 72, B_UPD = 74, B_RDONE = 75, B_FREED = 76, NBAR = 78;
constexpr int SMEM_BYTES = OFF_BAR + NBAR * 8;
static_assert(OFF_FS + 3 * F_BYTES == OFF_E && OFF_CS + CS_BYTES <= OFF_W && SMEM_BYTES + 256 <= 232448 && OFF_BAR % 8 == 0 && OFF_UPD % 1024 == 0, "smem");
#define POLL_NS 30
#define PF_RATE 10
#define PF_START 7
#define ZF_NS 100
#define FFN2_GATE B_G1DONE
#define PF_NW 6
#define EARLY_PF 1
#define ROWS_AT 11
#define STATS_UNROLL 1
constexpr int kStatsUnroll = STATS_UNROLL;
constexpr int BUDGET = 1 << 18;

struct Scratch {
    uint8_t o[2048 * 1024 * 2];
    uint32_t ypart[8][8][1024];
    uint32_t halo[128][512];
    uint32_t act[2][14336 + 4096];
    uint2 row[2048];
    uint32_t cs[16][800];
    uint32_t oflag[16][32];
    uint32_t cnt[9][32];
    uint32_t sel[32], csflag[32], epoch[32];
};
__device__ __align__(1024) Scratch g_scr;
struct Weights { const char *wqkv, *wo, *wg, *wu, *wd; };

#define TS(i) do {} while (0)
#define TS_END() do {} while (0)
#define TSC(c, i) do {} while (0)
#define NRETRY() do {} while (0)
constexpr int SMEM_LAUNCH = SMEM_BYTES;
__device__ __forceinline__ uint32_t smem_u32(const void* p) { return (uint32_t)__cvta_generic_to_shared(p); }
__device__ __forceinline__ void mbar_init(uint32_t bar, uint32_t cnt) { asm volatile("mbarrier.init.shared::cta.b64 [%0], %1;" ::"r"(bar), "r"(cnt) : "memory"); }
__device__ __forceinline__ void mbar_expect_tx(uint32_t bar, uint32_t bytes) { asm volatile("mbarrier.arrive.expect_tx.shared::cta.b64 _, [%0], %1;" ::"r"(bar), "r"(bytes) : "memory"); }
__device__ __forceinline__ void mbar_arrive(uint32_t bar) { asm volatile("mbarrier.arrive.shared::cta.b64 _, [%0];" ::"r"(bar) : "memory"); }
__device__ __forceinline__ uint32_t mapa(uint32_t a, uint32_t cta) { uint32_t r; asm("mapa.shared::cluster.u32 %0, %1, %2;" : "=r"(r) : "r"(a), "r"(cta)); return r; }
__device__ __forceinline__ void mbar_arrive_at(uint32_t cbar) { asm volatile("mbarrier.arrive.shared::cluster.b64 _, [%0];" ::"r"(cbar) : "memory"); }
__device__ __forceinline__ void mbar_wait(uint32_t bar, uint32_t parity, int& budget) {
    asm volatile("{\n.reg .pred p;\nLAB_WAIT:\nmbarrier.try_wait.parity.shared::cta.b64 p, [%1], %2;\n"
                 "add.s32 %0, %0, -1;\nsetp.gt.and.s32 p, %0, 0, !p;\n@p bra LAB_WAIT;\n}" : "+r"(budget) : "r"(bar), "r"(parity) : "memory");
}
__device__ __forceinline__ void mbar_wait_hot(uint32_t bar, uint32_t parity, int& budget) {
    asm volatile("{\n.reg .pred p;\nmbarrier.try_wait.parity.shared::cta.b64 p, [%1], %2;\n@p bra LAB_DONE;\nLAB_WAIT:\nmbarrier.try_wait.parity.shared::cta.b64 p, [%1], %2;\n"
                 "add.s32 %0, %0, -1;\nsetp.gt.and.s32 p, %0, 0, !p;\n@p bra LAB_WAIT;\nLAB_DONE:\n}" : "+r"(budget) : "r"(bar), "r"(parity) : "memory");
}
__device__ __forceinline__ void tma_2d_mc(uint32_t dst, const CUtensorMap* m, uint32_t bar, int c0, int c1) {
    asm volatile("cp.async.bulk.tensor.2d.shared::cluster.global.mbarrier::complete_tx::bytes.multicast::cluster [%0], [%1, {%3, %4}], [%2], %5;" ::"r"(dst), "l"(m), "r"(bar), "r"(c0), "r"(c1), "h"((uint16_t)3) : "memory");
}
__device__ __forceinline__ void tma_3d(uint32_t dst, const CUtensorMap* m, uint32_t bar, int c0, int c1, int c2) {
    asm volatile("cp.async.bulk.tensor.3d.shared::cluster.global.mbarrier::complete_tx::bytes [%0], [%1, {%3, %4, %5}], [%2];" ::"r"(dst), "l"(m), "r"(bar), "r"(c0), "r"(c1), "r"(c2) : "memory");
}
__device__ __forceinline__ void tma_4d(uint32_t dst, const CUtensorMap* m, uint32_t bar, int c0, int c1, int c2, int c3) {
    asm volatile("cp.async.bulk.tensor.4d.shared::cluster.global.mbarrier::complete_tx::bytes [%0], [%1, {%3, %4, %5, %6}], [%2];" ::"r"(dst), "l"(m), "r"(bar), "r"(c0), "r"(c1), "r"(c2), "r"(c3) : "memory");
}
__device__ __forceinline__ void tma_4d_mc(uint32_t dst, const CUtensorMap* m, uint32_t bar, int c0, int c1, int c2, int c3) {
    asm volatile("cp.async.bulk.tensor.4d.shared::cluster.global.mbarrier::complete_tx::bytes.multicast::cluster [%0], [%1, {%3, %4, %5, %6}], [%2], %7;" ::"r"(dst), "l"(m), "r"(bar), "r"(c0), "r"(c1), "r"(c2), "r"(c3), "h"((uint16_t)3) : "memory");
}
__device__ __forceinline__ void bulk_pf(const void* p, uint32_t bytes) { asm volatile("cp.async.bulk.prefetch.L2.global [%0], %1;" ::"l"(p), "r"(bytes) : "memory"); }
__device__ __forceinline__ void bulk_g2s(uint32_t dst, const void* src, uint32_t bytes, uint32_t bar) {
    asm volatile("cp.async.bulk.shared::cluster.global.mbarrier::complete_tx::bytes [%0], [%1], %2, [%3];" ::"r"(dst), "l"(src), "r"(bytes), "r"(bar) : "memory");
}
__device__ __forceinline__ void bulk_s2c(uint32_t cdst, uint32_t src, uint32_t bytes, uint32_t cbar) {
    asm volatile("cp.async.bulk.shared::cluster.shared::cta.mbarrier::complete_tx::bytes [%0], [%1], %2, [%3];" ::"r"(cdst), "r"(src), "r"(bytes), "r"(cbar) : "memory");
}
__device__ __forceinline__ void cluster_wait() { asm volatile("barrier.cluster.wait.aligned;" ::: "memory"); }
__device__ __forceinline__ void fence_gpu() { asm volatile("fence.acq_rel.gpu;" ::: "memory"); }
__device__ __forceinline__ void fence_async_smem() { asm volatile("fence.proxy.async.shared::cta;" ::: "memory"); }
__device__ __forceinline__ void fence_async_gmem() { asm volatile("fence.proxy.async.global;" ::: "memory"); }
__device__ __forceinline__ void wg_fence() { asm volatile("wgmma.fence.sync.aligned;" ::: "memory"); }
__device__ __forceinline__ void wg_commit() { asm volatile("wgmma.commit_group.sync.aligned;" ::: "memory"); }
template <int N> __device__ __forceinline__ void wg_wait() { asm volatile("wgmma.wait_group.sync.aligned %0;" ::"n"(N) : "memory"); }
__device__ __forceinline__ uint64_t mkdesc(uint32_t lo, uint32_t hi) { return ((uint64_t)hi << 32) | lo; }
__host__ __device__ constexpr uint32_t dhi(uint32_t sbo, uint32_t mode) { return (sbo >> 4) | (mode << 30); }
__host__ __device__ constexpr uint32_t dlo(uint32_t off, uint32_t lbo) { return (off >> 4) + ((lbo >> 4) << 16); }
__device__ __forceinline__ bool elect_one() {
    uint32_t e;
    asm volatile("{\n.reg .pred p;\nelect.sync _|p, 0xffffffff;\nselp.u32 %0, 1, 0, p;\n}" : "=r"(e));
    return e;
}
template <int R> __device__ __forceinline__ void reg_inc() { asm volatile("setmaxnreg.inc.sync.aligned.u32 %0;" ::"n"(R)); }
template <int R> __device__ __forceinline__ void reg_dec() { asm volatile("setmaxnreg.dec.sync.aligned.u32 %0;" ::"n"(R)); }
__device__ __forceinline__ void bar_sync(int id, int n) { asm volatile("bar.sync %0, %1;" ::"r"(id), "r"(n) : "memory"); }
__device__ __forceinline__ void bar_arrive(int id, int n) { asm volatile("bar.arrive %0, %1;" ::"r"(id), "r"(n) : "memory"); }
__device__ __forceinline__ uint32_t pack_bf16(float lo, float hi) { uint32_t r; asm("cvt.rn.bf16x2.f32 %0, %1, %2;" : "=r"(r) : "f"(hi), "f"(lo)); return r; }
__device__ __forceinline__ uint32_t pack_here(float lo, float hi) { uint32_t r; asm volatile("cvt.rn.bf16x2.f32 %0, %1, %2;" : "=r"(r) : "f"(hi), "f"(lo)); return r; }
__device__ __forceinline__ float bf_lo(uint32_t u) { return __uint_as_float(u << 16); }
__device__ __forceinline__ float bf_hi(uint32_t u) { return __uint_as_float(u & 0xffff0000u); }
__device__ __forceinline__ float bf16r(float v) { return bf_lo(pack_bf16(v, 0.f)); }
__device__ __forceinline__ float rcp(float x) { float r; asm("rcp.approx.ftz.f32 %0, %1;" : "=f"(r) : "f"(x)); return r; }
__device__ __forceinline__ float ex2(float x) { float r; asm("ex2.approx.ftz.f32 %0, %1;" : "=f"(r) : "f"(x)); return r; }
__device__ __forceinline__ float sigmoidf(float v) { return rcp(1.f + ex2(v * -1.4426950408889634f)); }
__device__ __forceinline__ uint32_t movm(uint32_t a) { uint32_t d; asm volatile("movmatrix.sync.aligned.m8n8.trans.b16 %0, %1;" : "=r"(d) : "r"(a)); return d; }
__device__ __forceinline__ void mma16816(float (&c)[4], uint32_t a0, uint32_t a1, uint32_t a2, uint32_t a3, uint32_t b0, uint32_t b1) {
    asm volatile("mma.sync.aligned.m16n8k16.row.col.f32.bf16.bf16.f32 {%0,%1,%2,%3}, {%4,%5,%6,%7}, {%8,%9}, {%0,%1,%2,%3};"
                 : "+f"(c[0]), "+f"(c[1]), "+f"(c[2]), "+f"(c[3]) : "r"(a0), "r"(a1), "r"(a2), "r"(a3), "r"(b0), "r"(b1));
}
__device__ __forceinline__ void mma1688(float (&c)[4], uint32_t a0, uint32_t a1, uint32_t b0) {
    asm volatile("mma.sync.aligned.m16n8k8.row.col.f32.bf16.bf16.f32 {%0,%1,%2,%3}, {%4,%5}, {%6}, {%0,%1,%2,%3};"
                 : "+f"(c[0]), "+f"(c[1]), "+f"(c[2]), "+f"(c[3]) : "r"(a0), "r"(a1), "r"(b0));
}
__device__ __forceinline__ void stsm4(uint32_t a, uint32_t r0, uint32_t r1, uint32_t r2, uint32_t r3) {
    asm volatile("stmatrix.sync.aligned.m8n8.x4.shared.b16 [%0], {%1,%2,%3,%4};" ::"r"(a), "r"(r0), "r"(r1), "r"(r2), "r"(r3) : "memory");
}
__device__ __forceinline__ void ldsm4(uint32_t* r, uint32_t a) {
    asm volatile("ldmatrix.sync.aligned.m8n8.x4.shared.b16 {%0,%1,%2,%3}, [%4];" : "=r"(r[0]), "=r"(r[1]), "=r"(r[2]), "=r"(r[3]) : "r"(a) : "memory");
}
__device__ __forceinline__ void ldsm4t(uint32_t* r, uint32_t a) {
    asm volatile("ldmatrix.sync.aligned.m8n8.x4.trans.shared.b16 {%0,%1,%2,%3}, [%4];" : "=r"(r[0]), "=r"(r[1]), "=r"(r[2]), "=r"(r[3]) : "r"(a) : "memory");
}
__device__ __forceinline__ uint32_t ld_rlx(const void* p) { uint32_t v; asm volatile("ld.relaxed.gpu.global.u32 %0, [%1];" : "=r"(v) : "l"(p) : "memory"); return v; }
__device__ __forceinline__ uint32_t ld_acq(const void* p) { uint32_t v; asm volatile("ld.acquire.gpu.global.u32 %0, [%1];" : "=r"(v) : "l"(p) : "memory"); return v; }
__device__ __forceinline__ uint2 ld_rlx2(const void* p) { uint2 v; asm volatile("ld.relaxed.gpu.global.v2.u32 {%0,%1}, [%2];" : "=r"(v.x), "=r"(v.y) : "l"(p) : "memory"); return v; }
__device__ __forceinline__ uint4 ld_rlx4(const void* p) { uint4 v; asm volatile("ld.relaxed.gpu.global.v4.u32 {%0,%1,%2,%3}, [%4];" : "=r"(v.x), "=r"(v.y), "=r"(v.z), "=r"(v.w) : "l"(p) : "memory"); return v; }
__device__ __forceinline__ void st_rlx(void* p, uint32_t v) { asm volatile("st.relaxed.gpu.global.u32 [%0], %1;" ::"l"(p), "r"(v) : "memory"); }
__device__ __forceinline__ void st_rlx2(void* p, uint32_t a, uint32_t b) { asm volatile("st.relaxed.gpu.global.v2.u32 [%0], {%1,%2};" ::"l"(p), "r"(a), "r"(b) : "memory"); }
__device__ __forceinline__ void st_rlx4(void* p, uint32_t a, uint32_t b, uint32_t c, uint32_t d) { asm volatile("st.relaxed.gpu.global.v4.u32 [%0], {%1,%2,%3,%4};" ::"l"(p), "r"(a), "r"(b), "r"(c), "r"(d) : "memory"); }
__device__ __forceinline__ void red_add(uint32_t* p) { asm volatile("red.relaxed.gpu.global.add.u32 [%0], 1;" ::"l"(p) : "memory"); }
__device__ __forceinline__ uint4 ldg_nc(const void* p) { uint4 v; asm volatile("ld.global.nc.v4.u32 {%0,%1,%2,%3}, [%4];" : "=r"(v.x), "=r"(v.y), "=r"(v.z), "=r"(v.w) : "l"(p)); return v; }
__device__ __forceinline__ void sts4(uint32_t a, uint32_t x, uint32_t y, uint32_t z, uint32_t w) { asm volatile("st.shared.v4.u32 [%0], {%1,%2,%3,%4};" ::"r"(a), "r"(x), "r"(y), "r"(z), "r"(w) : "memory"); }
__device__ __forceinline__ void sts2(uint32_t a, uint32_t x, uint32_t y) { asm volatile("st.shared.v2.u32 [%0], {%1,%2};" ::"r"(a), "r"(x), "r"(y) : "memory"); }
__device__ __forceinline__ void sts1(uint32_t a, uint32_t v) { asm volatile("st.shared.u32 [%0], %1;" ::"r"(a), "r"(v) : "memory"); }
__device__ __forceinline__ uint4 lds4(uint32_t a) { uint4 v; asm volatile("ld.shared.v4.u32 {%0,%1,%2,%3}, [%4];" : "=r"(v.x), "=r"(v.y), "=r"(v.z), "=r"(v.w) : "r"(a) : "memory"); return v; }
__device__ __forceinline__ float4 lds4f(uint32_t a) { float4 v; asm volatile("ld.shared.v4.f32 {%0,%1,%2,%3}, [%4];" : "=f"(v.x), "=f"(v.y), "=f"(v.z), "=f"(v.w) : "r"(a) : "memory"); return v; }
__device__ __forceinline__ float2 lds2f(uint32_t a) { float2 v; asm volatile("ld.shared.v2.f32 {%0,%1}, [%2];" : "=f"(v.x), "=f"(v.y) : "r"(a) : "memory"); return v; }
__device__ __forceinline__ float lds1f(uint32_t a) { float v; asm volatile("ld.shared.f32 %0, [%1];" : "=f"(v) : "r"(a) : "memory"); return v; }
__device__ __forceinline__ uint32_t lds1(uint32_t a) { uint32_t v; asm volatile("ld.shared.u32 %0, [%1];" : "=r"(v) : "r"(a) : "memory"); return v; }
__device__ __forceinline__ uint32_t redux_max(uint32_t v) { uint32_t r; asm volatile("redux.sync.max.u32 %0, %1, 0xffffffff;" : "=r"(r) : "r"(v)); return r; }
__device__ __forceinline__ uint32_t poll_all(const uint32_t* p, uint32_t mask, uint32_t want, int& budget) {
    uint32_t v;
#pragma unroll 1
    while (v = ld_acq(p), !__all_sync(0xffffffffu, (v & mask) == want) && --budget > 0) __nanosleep(POLL_NS);
    return v;
}

template <int TA, int TB>
__device__ __forceinline__ void wgmma_n192(float (&d)[96], uint64_t da, uint64_t db, int keep) {
    asm volatile("{\n.reg .pred p;\nsetp.ne.b32 p, %98, 0;\n"
        "wgmma.mma_async.sync.aligned.m64n192k16.f32.bf16.bf16 "
        "{%0, %1, %2, %3, %4, %5, %6, %7, %8, %9, %10, %11, %12, %13, %14, %15, "
        "%16, %17, %18, %19, %20, %21, %22, %23, %24, %25, %26, %27, %28, %29, %30, %31, "
        "%32, %33, %34, %35, %36, %37, %38, %39, %40, %41, %42, %43, %44, %45, %46, %47, "
        "%48, %49, %50, %51, %52, %53, %54, %55, %56, %57, %58, %59, %60, %61, %62, %63, "
        "%64, %65, %66, %67, %68, %69, %70, %71, %72, %73, %74, %75, %76, %77, %78, %79, "
        "%80, %81, %82, %83, %84, %85, %86, %87, %88, %89, %90, %91, %92, %93, %94, %95}, "
        "%96, %97, p, 1, 1, %99, %100;\n}\n"
        : "+f"(d[0]), "+f"(d[1]), "+f"(d[2]), "+f"(d[3]), "+f"(d[4]), "+f"(d[5]), "+f"(d[6]), "+f"(d[7]),
          "+f"(d[8]), "+f"(d[9]), "+f"(d[10]), "+f"(d[11]), "+f"(d[12]), "+f"(d[13]), "+f"(d[14]), "+f"(d[15]),
          "+f"(d[16]), "+f"(d[17]), "+f"(d[18]), "+f"(d[19]), "+f"(d[20]), "+f"(d[21]), "+f"(d[22]), "+f"(d[23]),
          "+f"(d[24]), "+f"(d[25]), "+f"(d[26]), "+f"(d[27]), "+f"(d[28]), "+f"(d[29]), "+f"(d[30]), "+f"(d[31]),
          "+f"(d[32]), "+f"(d[33]), "+f"(d[34]), "+f"(d[35]), "+f"(d[36]), "+f"(d[37]), "+f"(d[38]), "+f"(d[39]),
          "+f"(d[40]), "+f"(d[41]), "+f"(d[42]), "+f"(d[43]), "+f"(d[44]), "+f"(d[45]), "+f"(d[46]), "+f"(d[47]),
          "+f"(d[48]), "+f"(d[49]), "+f"(d[50]), "+f"(d[51]), "+f"(d[52]), "+f"(d[53]), "+f"(d[54]), "+f"(d[55]),
          "+f"(d[56]), "+f"(d[57]), "+f"(d[58]), "+f"(d[59]), "+f"(d[60]), "+f"(d[61]), "+f"(d[62]), "+f"(d[63]),
          "+f"(d[64]), "+f"(d[65]), "+f"(d[66]), "+f"(d[67]), "+f"(d[68]), "+f"(d[69]), "+f"(d[70]), "+f"(d[71]),
          "+f"(d[72]), "+f"(d[73]), "+f"(d[74]), "+f"(d[75]), "+f"(d[76]), "+f"(d[77]), "+f"(d[78]), "+f"(d[79]),
          "+f"(d[80]), "+f"(d[81]), "+f"(d[82]), "+f"(d[83]), "+f"(d[84]), "+f"(d[85]), "+f"(d[86]), "+f"(d[87]),
          "+f"(d[88]), "+f"(d[89]), "+f"(d[90]), "+f"(d[91]), "+f"(d[92]), "+f"(d[93]), "+f"(d[94]), "+f"(d[95])
        : "l"(da), "l"(db), "r"(keep), "n"(TA), "n"(TB));
}
template <int TA, int TB>
__device__ __forceinline__ void wgmma_n128(float (&d)[64], uint64_t da, uint64_t db, int keep) {
    asm volatile("{\n.reg .pred p;\nsetp.ne.b32 p, %66, 0;\n"
        "wgmma.mma_async.sync.aligned.m64n128k16.f32.bf16.bf16 "
        "{%0, %1, %2, %3, %4, %5, %6, %7, %8, %9, %10, %11, %12, %13, %14, %15, "
        "%16, %17, %18, %19, %20, %21, %22, %23, %24, %25, %26, %27, %28, %29, %30, %31, "
        "%32, %33, %34, %35, %36, %37, %38, %39, %40, %41, %42, %43, %44, %45, %46, %47, "
        "%48, %49, %50, %51, %52, %53, %54, %55, %56, %57, %58, %59, %60, %61, %62, %63}, "
        "%64, %65, p, 1, 1, %67, %68;\n}\n"
        : "+f"(d[0]), "+f"(d[1]), "+f"(d[2]), "+f"(d[3]), "+f"(d[4]), "+f"(d[5]), "+f"(d[6]), "+f"(d[7]),
          "+f"(d[8]), "+f"(d[9]), "+f"(d[10]), "+f"(d[11]), "+f"(d[12]), "+f"(d[13]), "+f"(d[14]), "+f"(d[15]),
          "+f"(d[16]), "+f"(d[17]), "+f"(d[18]), "+f"(d[19]), "+f"(d[20]), "+f"(d[21]), "+f"(d[22]), "+f"(d[23]),
          "+f"(d[24]), "+f"(d[25]), "+f"(d[26]), "+f"(d[27]), "+f"(d[28]), "+f"(d[29]), "+f"(d[30]), "+f"(d[31]),
          "+f"(d[32]), "+f"(d[33]), "+f"(d[34]), "+f"(d[35]), "+f"(d[36]), "+f"(d[37]), "+f"(d[38]), "+f"(d[39]),
          "+f"(d[40]), "+f"(d[41]), "+f"(d[42]), "+f"(d[43]), "+f"(d[44]), "+f"(d[45]), "+f"(d[46]), "+f"(d[47]),
          "+f"(d[48]), "+f"(d[49]), "+f"(d[50]), "+f"(d[51]), "+f"(d[52]), "+f"(d[53]), "+f"(d[54]), "+f"(d[55]),
          "+f"(d[56]), "+f"(d[57]), "+f"(d[58]), "+f"(d[59]), "+f"(d[60]), "+f"(d[61]), "+f"(d[62]), "+f"(d[63])
        : "l"(da), "l"(db), "r"(keep), "n"(TA), "n"(TB));
}
template <int TA, int TB>
__device__ __forceinline__ void wgmma_n8(float (&d)[4], uint64_t da, uint64_t db, int keep) {
    asm volatile("{\n.reg .pred p;\nsetp.ne.b32 p, %6, 0;\n"
        "wgmma.mma_async.sync.aligned.m64n8k16.f32.bf16.bf16 "
        "{%0, %1, %2, %3}, "
        "%4, %5, p, 1, 1, %7, %8;\n}\n"
        : "+f"(d[0]), "+f"(d[1]), "+f"(d[2]), "+f"(d[3])
        : "l"(da), "l"(db), "r"(keep), "n"(TA), "n"(TB));
}
__device__ __forceinline__ void wgmma_rs_n128(float (&d)[64], uint32_t a0, uint32_t a1, uint32_t a2, uint32_t a3, uint64_t db) {
    asm volatile("{\n.reg .pred p;\nsetp.ne.b32 p, 1, 0;\n"
        "wgmma.mma_async.sync.aligned.m64n128k16.f32.bf16.bf16 "
        "{%0, %1, %2, %3, %4, %5, %6, %7, %8, %9, %10, %11, %12, %13, %14, %15, "
        "%16, %17, %18, %19, %20, %21, %22, %23, %24, %25, %26, %27, %28, %29, %30, %31, "
        "%32, %33, %34, %35, %36, %37, %38, %39, %40, %41, %42, %43, %44, %45, %46, %47, "
        "%48, %49, %50, %51, %52, %53, %54, %55, %56, %57, %58, %59, %60, %61, %62, %63}, "
        "{%64, %65, %66, %67}, %68, p, 1, 1, 1;\n}\n"
        : "+f"(d[0]), "+f"(d[1]), "+f"(d[2]), "+f"(d[3]), "+f"(d[4]), "+f"(d[5]), "+f"(d[6]), "+f"(d[7]),
          "+f"(d[8]), "+f"(d[9]), "+f"(d[10]), "+f"(d[11]), "+f"(d[12]), "+f"(d[13]), "+f"(d[14]), "+f"(d[15]),
          "+f"(d[16]), "+f"(d[17]), "+f"(d[18]), "+f"(d[19]), "+f"(d[20]), "+f"(d[21]), "+f"(d[22]), "+f"(d[23]),
          "+f"(d[24]), "+f"(d[25]), "+f"(d[26]), "+f"(d[27]), "+f"(d[28]), "+f"(d[29]), "+f"(d[30]), "+f"(d[31]),
          "+f"(d[32]), "+f"(d[33]), "+f"(d[34]), "+f"(d[35]), "+f"(d[36]), "+f"(d[37]), "+f"(d[38]), "+f"(d[39]),
          "+f"(d[40]), "+f"(d[41]), "+f"(d[42]), "+f"(d[43]), "+f"(d[44]), "+f"(d[45]), "+f"(d[46]), "+f"(d[47]),
          "+f"(d[48]), "+f"(d[49]), "+f"(d[50]), "+f"(d[51]), "+f"(d[52]), "+f"(d[53]), "+f"(d[54]), "+f"(d[55]),
          "+f"(d[56]), "+f"(d[57]), "+f"(d[58]), "+f"(d[59]), "+f"(d[60]), "+f"(d[61]), "+f"(d[62]), "+f"(d[63])
        : "r"(a0), "r"(a1), "r"(a2), "r"(a3), "l"(db));
}
__device__ __forceinline__ void wgmma_rs_n192(float (&d)[96], uint32_t a0, uint32_t a1, uint32_t a2, uint32_t a3, uint64_t db) {
    asm volatile("{\n.reg .pred p;\nsetp.ne.b32 p, 1, 0;\n"
        "wgmma.mma_async.sync.aligned.m64n192k16.f32.bf16.bf16 "
        "{%0, %1, %2, %3, %4, %5, %6, %7, %8, %9, %10, %11, %12, %13, %14, %15, "
        "%16, %17, %18, %19, %20, %21, %22, %23, %24, %25, %26, %27, %28, %29, %30, %31, "
        "%32, %33, %34, %35, %36, %37, %38, %39, %40, %41, %42, %43, %44, %45, %46, %47, "
        "%48, %49, %50, %51, %52, %53, %54, %55, %56, %57, %58, %59, %60, %61, %62, %63, "
        "%64, %65, %66, %67, %68, %69, %70, %71, %72, %73, %74, %75, %76, %77, %78, %79, "
        "%80, %81, %82, %83, %84, %85, %86, %87, %88, %89, %90, %91, %92, %93, %94, %95}, "
        "{%96, %97, %98, %99}, %100, p, 1, 1, 1;\n}\n"
        : "+f"(d[0]), "+f"(d[1]), "+f"(d[2]), "+f"(d[3]), "+f"(d[4]), "+f"(d[5]), "+f"(d[6]), "+f"(d[7]),
          "+f"(d[8]), "+f"(d[9]), "+f"(d[10]), "+f"(d[11]), "+f"(d[12]), "+f"(d[13]), "+f"(d[14]), "+f"(d[15]),
          "+f"(d[16]), "+f"(d[17]), "+f"(d[18]), "+f"(d[19]), "+f"(d[20]), "+f"(d[21]), "+f"(d[22]), "+f"(d[23]),
          "+f"(d[24]), "+f"(d[25]), "+f"(d[26]), "+f"(d[27]), "+f"(d[28]), "+f"(d[29]), "+f"(d[30]), "+f"(d[31]),
          "+f"(d[32]), "+f"(d[33]), "+f"(d[34]), "+f"(d[35]), "+f"(d[36]), "+f"(d[37]), "+f"(d[38]), "+f"(d[39]),
          "+f"(d[40]), "+f"(d[41]), "+f"(d[42]), "+f"(d[43]), "+f"(d[44]), "+f"(d[45]), "+f"(d[46]), "+f"(d[47]),
          "+f"(d[48]), "+f"(d[49]), "+f"(d[50]), "+f"(d[51]), "+f"(d[52]), "+f"(d[53]), "+f"(d[54]), "+f"(d[55]),
          "+f"(d[56]), "+f"(d[57]), "+f"(d[58]), "+f"(d[59]), "+f"(d[60]), "+f"(d[61]), "+f"(d[62]), "+f"(d[63]),
          "+f"(d[64]), "+f"(d[65]), "+f"(d[66]), "+f"(d[67]), "+f"(d[68]), "+f"(d[69]), "+f"(d[70]), "+f"(d[71]),
          "+f"(d[72]), "+f"(d[73]), "+f"(d[74]), "+f"(d[75]), "+f"(d[76]), "+f"(d[77]), "+f"(d[78]), "+f"(d[79]),
          "+f"(d[80]), "+f"(d[81]), "+f"(d[82]), "+f"(d[83]), "+f"(d[84]), "+f"(d[85]), "+f"(d[86]), "+f"(d[87]),
          "+f"(d[88]), "+f"(d[89]), "+f"(d[90]), "+f"(d[91]), "+f"(d[92]), "+f"(d[93]), "+f"(d[94]), "+f"(d[95])
        : "r"(a0), "r"(a1), "r"(a2), "r"(a3), "l"(db));
}

template <int HS>
__device__ __forceinline__ void attn_pair(const uint32_t* q, const uint32_t* k, const uint32_t* v, const uint32_t* kh, const uint32_t* vh,
                                          const float* fu, const float* fn, const float* rk, float bias0, float bias1, uint32_t mU, uint32_t zero, const float* ci, uint32_t* o) {
    float s0[2][4] = {}, s1[2][4] = {}, s2[2][4] = {};
#pragma unroll
    for (int n = 0; n < 4; n++) {
        const int hd = n & 1, a = 8 * hd + 2 * (n & 2);
        mma16816(s1[hd], q[a], q[a + 1], q[a + 2], q[a + 3], k[a], k[a + 2]);
        mma16816(s2[hd], q[a], q[a + 1], q[a + 2], q[a + 3], k[a + 1], k[a + 3]);
    }
#pragma unroll
    for (int n = 0; n < 4; n++) {
        const int hd = n & 1, a = 8 * hd + 2 * (n & 2);
        mma16816(s0[hd], q[a], q[a + 1], q[a + 2], q[a + 3], kh[HS * (a / 2)], kh[HS * (a / 2 + 1)]);
    }
    float e[2][4], m[2][2];
#pragma unroll
    for (int hd = 0; hd < 2; hd++) {
        e[hd][2] = fmaf(s1[hd][2], fu[2], s2[hd][2] * fn[2]); e[hd][3] = fmaf(s1[hd][3], fu[3], s2[hd][3] * fn[3]);
        e[hd][0] = fmaf(s0[hd][0], fu[0], fmaf(s1[hd][0], fn[0], bias0)); e[hd][1] = fmaf(s0[hd][1], fu[1], fmaf(s1[hd][1], fn[1], bias1));
        m[hd][1] = fmaxf(e[hd][2], e[hd][3]); m[hd][0] = fmaxf(e[hd][0], e[hd][1]);
    }
#pragma unroll
    for (int x = 1; x < 3; x++)
#pragma unroll
        for (int n = 0; n < 4; n++) m[n & 1][1 - (n >> 1)] = fmaxf(m[n & 1][1 - (n >> 1)], __shfl_xor_sync(0xffffffffu, m[n & 1][1 - (n >> 1)], x));
    float c[2][4][4] = {};
#pragma unroll
    for (int hd = 0; hd < 2; hd++) {
#pragma unroll
        for (int n = 0; n < 4; n++) e[hd][n] = ex2(e[hd][n] - m[hd][n >> 1]);
        const uint32_t plo = pack_bf16(e[hd][0] * rk[0], e[hd][1] * rk[1]), phi = pack_bf16(e[hd][2] * rk[2], e[hd][3] * rk[3]);
        const uint32_t z0 = plo & zero, z1 = phi & zero;
        const uint32_t a0 = plo & ~mU, a1 = phi & mU, a3 = phi & ~mU, b0 = plo & mU;
#pragma unroll
        for (int jj = 0; jj < 4; jj++) mma16816(c[hd][jj], a0, a1, z0, a3, v[8 * hd + 2 * jj], v[8 * hd + 2 * jj + 1]);
#pragma unroll
        for (int jj = 0; jj < 4; jj++) mma1688(c[hd][jj], b0, z1, vh[HS * (4 * hd + jj)]);
        m[hd][0] = e[hd][0] + e[hd][1]; m[hd][1] = e[hd][2] + e[hd][3];
    }
#pragma unroll
    for (int x = 1; x < 3; x++)
#pragma unroll
        for (int n = 0; n < 4; n++) m[n >> 1][n & 1] += __shfl_xor_sync(0xffffffffu, m[n >> 1][n & 1], x);
#pragma unroll
    for (int hd = 0; hd < 2; hd++) {
        const float i0 = rcp(m[hd][0]), i1 = rcp(m[hd][1]);
#pragma unroll
        for (int jj = 0; jj < 4; jj++) {
            o[8 * hd + 2 * jj] = pack_bf16(fmaf(c[hd][jj][0], i0, 0x1p-120f), c[hd][jj][1] * i0);
            o[8 * hd + 2 * jj + 1] = pack_bf16(fmaf(c[hd][jj][2], i1, 0x1p-120f), c[hd][jj][3] * i1);
        }
    }
}

__device__ __forceinline__ uint32_t norm_pair(uint32_t u, float m, float rinv) {
    const uint32_t d = pack_bf16(bf_lo(u) - m, bf_hi(u) - m);
    return max(pack_bf16(bf_lo(d) * rinv, bf_hi(d) * rinv), 1u);
}

__global__ void __launch_bounds__(512, 1)
fused_kernel(const __grid_constant__ CUtensorMap mx, const __grid_constant__ CUtensorMap mw, const __grid_constant__ CUtensorMap mwo,
             const __grid_constant__ CUtensorMap mout, const __grid_constant__ CUtensorMap mgu, const __grid_constant__ CUtensorMap mwd,
             const __grid_constant__ CUtensorMap mo,
             const __nv_bfloat16* __restrict__ x, const __nv_bfloat16* __restrict__ wr, Scratch* __restrict__ scr, int swap_gu, const Weights pf) {
    extern __shared__ __align__(1024) uint8_t smem[];
    const uint32_t sb = smem_u32(smem);
    const uint32_t bars = sb + OFF_BAR;
    const int tid = threadIdx.x, lane = tid & 31, warp = __shfl_sync(0xffffffffu, tid >> 5, 0);
    const uint32_t sd = (sb & 0x3FFFF) >> 4;
    const int hp = blockIdx.x & 1, cl = blockIdx.x >> 1;
    int pr = cl - 4 + (max(cl - 36, 0) * 37 >> 8);
    asm("{\n.reg .pred p;\nsetp.lt.s32 p, %1, 4;\nselp.s32 %0, %2, %0, p;\n}" : "+r"(pr) : "r"(cl), "r"(39 + 8 * cl));
    const int b = pr * 2 + hp, mt = pr >> 3, p = pr & 7, nt = 2 * p + hp, rh = p & 1, cb = (p & 6) + hp;
    const int par = mt >> 2, j0 = (mt & 3) * 256;
    int budget = BUDGET;

    TSC(tid == 0, 0);
    if (b < 128 && tid >= 32 && tid < 112) {
        const char* a = tid < 64 ? (const char*)x + (size_t)(16 * b + ((tid >> 1) & 15)) * 2048 + (tid & 1) * 128 : pf.wqkv + (size_t)b * 6144 + (tid - 64) * 128;
        asm volatile("prefetch.global.L2 [%0];" ::"l"(a));
    }
    auto load_w = [&](int k, int s) {
        const uint32_t full = bars + 8 * (B_WFULL + s);
        mbar_expect_tx(full, W_BYTES);
        tma_3d(sb + OFF_W + s * W_BYTES, &mw, full, nt * 64, k * 64, 0);
    };
    auto load_x = [&](int n) {
        const int w = n & 1, j = n >> 1;
        const uint32_t full = bars + 8 * (B_XFULL + w * 6 + j);
        mbar_expect_tx(full, BOX);
        tma_4d(sb + w * OFF_X1 + j * BOX, &mx, full, par * 1024 + (n >> 2) * 64, 0, (j0 + w * 128) >> 5, (~n >> 1) & 1);
    };
    if (warp < NBAR / 6 && elect_one()) {
        const uint32_t cnt = warp < B_WEMPTY / 6 ? 1 : warp < B_G1DONE / 6 ? 2 : warp < B_STAGED / 6 ? 4 : 8;
#pragma unroll
        for (int i = 0; i < 6; i++) mbar_init(bars + 48 * warp + 8 * i, cnt);
        asm volatile("fence.mbarrier_init.release.cluster;" ::: "memory");
        if (warp == 0 && b < 128) { load_x(0); load_w(0, 2); }
    }
    __syncthreads();

    if (b >= 128) {
        const int hc = b - 128, g = lane >> 2, t = lane & 3;
        if (warp < 12) {
            const int n = warp / 3, part = warp - 3 * n;
            const uint32_t ep = ld_rlx(&scr->epoch[0]) + 1;
            auto load = [&](int k) {
                const uint32_t full = bars + 8 * (2 * n + (k & 1));
                mbar_expect_tx(full, W_BYTES);
                tma_3d(sb + (2 * n + (k & 1)) * W_BYTES, &mw, full, (4 * hc + n) * 64, k * 64, 0);
            };
            if (part == 0 && elect_one()) { load(0); load(1); }
            __syncwarp();
            float c0[4] = {0.f, 0.f, 0.f, 0.f}, c1[4] = {0.f, 0.f, 0.f, 0.f};
            const uint32_t sel = g == 0 ? 0x3f80u : g == 1 ? 0x3f800000u : 0u;
            const uint32_t a = sb + 2 * n * W_BYTES + part * BOX + t * 256 + ((g ^ (2 * t)) << 4);
#pragma unroll 1
            for (int k = 0; k < 16; k++) {
                mbar_wait(bars + 8 * (2 * n + (k & 1)), (k >> 1) & 1, budget);
                uint4 v[8], u[8];
#pragma unroll
                for (int i = 0; i < 8; i++) { v[i] = lds4(a + (k & 1) * W_BYTES + i * 1024); u[i] = lds4(((a + 128) ^ 16) + (k & 1) * W_BYTES + i * 1024); }
#pragma unroll
                for (int i = 0; i < 8; i++) { mma16816(c0, v[i].x, v[i].y, u[i].x, u[i].y, sel, sel); mma16816(c1, v[i].z, v[i].w, u[i].z, u[i].w, sel, sel); }
                bar_sync(1 + n, 96);
                if (part == 0 && k < 14 && elect_one()) load(k + 2);
                __syncwarp();
            }
            if (t == 0) {
#pragma unroll
                for (int r = 0; r < 3; r++) {
                    const uint32_t q0 = pack_bf16(c0[0], c0[1]), q1 = pack_bf16(c0[2], c0[3]), q2 = pack_bf16(c1[0], c1[1]), q3 = pack_bf16(c1[2], c1[3]);
                    st_rlx4(&scr->cs[4 * hc + n][16 + (part * 8 + g) * 32 + r * 4], q0, q1, q2, q3);
                    c0[0] -= bf_lo(q0); c0[1] -= bf_hi(q0); c0[2] -= bf_lo(q1); c0[3] -= bf_hi(q1);
                    c1[0] -= bf_lo(q2); c1[1] -= bf_hi(q2); c1[2] -= bf_lo(q3); c1[3] -= bf_hi(q3);
                }
            }
            bar_sync(7, 384);
            if (tid == 0) { fence_gpu(); st_rlx(&scr->csflag[hc], ep); }
            TSC(tid == 0, 19);
        }
        if (warp < 8) TS_END();
        return;
    }
    asm volatile("barrier.cluster.arrive.relaxed.aligned;" ::: "memory");

    const int kc = b >> 4, c2 = b & 15;
    if (warp >= 12) {
        reg_dec<24>();
        if (warp == 12) {
            if (elect_one()) {
#pragma unroll 1
                for (int n = 1; n < 12; n++) {
                    load_x(n);
                    if (n == ROWS_AT) { mbar_expect_tx(bars + 8 * B_ROW, 4 * BOX); bulk_g2s(sb + OFF_FR, x + (size_t)b * 16 * 1024, 4 * BOX, bars + 8 * B_ROW); }
                    if (n == 3 || n == 7) load_w((n + 1) >> 2, n >> 2);
                }
                int s = 2; uint32_t ph = 0;
#pragma unroll 1
                for (int k = 3; k < 16; k++) {
                    mbar_wait(bars + 8 * (B_WEMPTY + s), ph, budget);
                    load_w(k, s);
                    if (++s == 3) s = 0;
                    if (s == 2) ph ^= 1;
                }
                TS(27);
                s = 2;
#pragma unroll 1
                for (int i = 0; i < 16; i++) {
                    mbar_wait(bars + 8 * (i < 2 ? B_WEMPTY + i : i < 4 ? B_G1DONE : i < 6 ? B_F1DONE : B_WOEMPTY + s), i >= 12, budget);
                    if (i == 1) {
                        mbar_expect_tx(bars + 8 * B_XT, 4 * BOX);
#pragma unroll 1
                        for (int n = 0; n < 4; n++)
                            tma_4d(sb + (n >> 1) * OFF_X1 + (4 + (n & 1)) * BOX, &mx, bars + 8 * B_XT, par * 1024 + cb * 128 + (n & 1) * 64, 0, (j0 + rh * 128) >> 5, 1 - (n >> 1));
                    }
                    const uint32_t full = bars + 8 * (B_WOFULL + s);
                    mbar_expect_tx(full, 2 * BOX);
                    tma_3d(sb + OFF_WO + s * 2 * BOX, &mwo, full, 0, ((2 * p + (i < 2 ? i ^ hp : i)) & 15) * 64, cb * 2);
                    TSC(TIMING % 10 == 4, 48 + i);
                    if (++s == 6) s = 0;
                }
                TS(25);
            }
        } else {
            bar_sync(8, 224);
            const uint32_t ep = __shfl_sync(0xffffffffu, lds1(sb + OFF_EP), 0);
            if (warp == 13) {
                cluster_wait();
                if (elect_one()) {
                    int j = 0, q = 0, left = BUDGET; uint32_t ph = 0;
#pragma unroll 1
                    for (int n = 6; n < 32; n++) {
                        mbar_wait(bars + 8 * (B_XEMPTY + j), ph, left);
                        tma_4d_mc(sb + hp * OFF_X1 + j * BOX, &mx, bars + 8 * (B_XFULL + hp * 6 + j), par * 1024 + (n >> 1) * 64, 0, (j0 + hp * 128) >> 5, ~n & 1);
                        if (++j == 6) { j = 0; ph ^= 1; }
#pragma unroll 1
                        for (; q < (PF_RATE * (n - PF_START) >> 3) && q < 18 + PF_NW; q++) {
                            const int u = q - PF_NW;
                            if (u < 0) bulk_pf(pf.wqkv + (size_t)(1024 + 128 * u + b) * 6144, 6144);
                            else if (u < 16) bulk_pf((b < 64 ? pf.wg : pf.wu) + (size_t)(u * 64 + (b & 63)) * 7168, 7168);
                            else bulk_pf(pf.wo + (size_t)((u - 16) * 128 + b) * 8192, 8192);
                        }
                    }
                }
                __syncwarp();
                uint32_t* hs = &scr->halo[b - 16][lane * 4];
                int tries = BUDGET;
#pragma unroll 1
                for (int c = 0; c < 4; c += 2) {
                    uint4 v0 = make_uint4(0, 0, 0, 0), v1 = v0;
                    if (j0) {
#pragma unroll 1
                        do { v0 = ld_rlx4(hs + c * 128); v1 = ld_rlx4(hs + c * 128 + 128); } while ((v0.x == 0 || v1.x == 0) && --tries > 0);
                        st_rlx(hs + c * 128, 0); st_rlx(hs + c * 128 + 128, 0);
                    }
                    __syncwarp();
                    stsm4(sb + OFF_HIN + c * 512 + lane * 16, v0.x, v0.y, v0.z, v0.w);
                    stsm4(sb + OFF_HIN + c * 512 + 512 + lane * 16, v1.x, v1.y, v1.z, v1.w);
                }
                bar_arrive(11, 64);
                TSC(lane == 0, 31);
                const int src = ((mt * 2 + rh) * 2 + 1 - hp) * 1024;
                if (elect_one()) {
                    const uint32_t* fl = &scr->oflag[mt * 2 + 1 - hp][0];
                    const uint32_t inv = (ep & 1) - 1;
                    uint32_t ready = 0, ph = 0;
                    int s = 4;
#pragma unroll 1
                    for (int i = 2; i < 16; i++) {
                        const int kb = (2 * p + i) & 15;
#pragma unroll 1
                        while (!((ready >> kb) & 1) && --budget > 0) ready = ld_rlx(fl) ^ inv;
                        TSC(i == 2, 30);
                        mbar_wait(bars + 8 * (B_OEMPTY + s), ph, budget);
                        tma_2d_mc(sb + hp * OFF_X1 + s * BOX, &mo, bars + 8 * (B_OFULL + hp * 6 + s), 0, src + kb * 64);
                        TSC(TIMING % 10 == 4 && hp == 0, 32 + i);
                        if (++s == 6) s = 0;
                        if (s == 4) ph ^= 1;
                    }
                }
            } else if (warp == 14) {
                if (elect_one()) {
                    uint32_t s8 = 0, ph = 0;
                    int tries = BUDGET;
                    const uint32_t* act = scr->act[ep & 1];
                    auto counted = [&](int c, uint32_t n) {
#pragma unroll 1
                        while (ld_rlx(&scr->cnt[c][0]) != ep * n && --tries > 0) __nanosleep(POLL_NS);
                    };
                    auto weights = [&](const CUtensorMap* m, int c0, int c1, int c2_) {
                        mbar_wait(bars + 8 * B_FEMPTY + s8, ph, budget);
                        mbar_expect_tx(bars + 8 * B_FFULL + s8, F_BYTES);
                        tma_3d(sb + OFF_FS + s8 * (F_BYTES / 8), m, bars + 8 * B_FFULL + s8, c0, c1, c2_);
                    };
                    if (b < 112) {
                        counted(8, 32);
                        TS(26);
#pragma unroll 1
                        for (int q = 0; q < 16; q++) {
                            weights(&mgu, b * 32, q * 64, 0);
                            bulk_g2s(sb + OFF_FS + BOX + s8 * (F_BYTES / 8), act + 14336 + q * 256, 1024, bars + 8 * B_FFULL + s8);
                            if (q >= 8) bulk_pf(pf.wd + (size_t)((q - 8) * 112 + b) * 8192, 8192);
                            s8 += 8;
                            if (s8 == 40) { s8 = 0; ph ^= 1; }
                        }
                    }
#pragma unroll 1
                    for (int q = -3; q < 7; q++) {
                        if (q == 0) { counted(kc, 28); TS(29); }
                        if ((unsigned)q >= 3) weights(&mwd, 0, kc * 448 + (q < 0 ? q + 3 : q) * 64, c2);
                        if (q >= 0) bulk_g2s(sb + OFF_FS + BOX + s8 * (F_BYTES / 8), act + (kc * 7 + q) * 256, 1024, bars + 8 * B_FFULL + s8);
                        s8 += 8;
                        if (s8 == 24) { s8 = 0; if ((unsigned)q >= 3) ph ^= 1; }
                    }
                }
            } else {
                mbar_wait(bars + 8 * B_ROW, 0, budget);
                uint8_t* oz = scr->o + ((size_t)mt * 64 + nt) * BOX + lane * 16;
#pragma unroll 1
                for (int i = 0; i < 64; i++) { st_rlx4(oz + (i >> 4) * 16 * BOX + (i & 15) * 512, 0, 0, 0, 0); if ((i & 3) == 3) __nanosleep(ZF_NS); }
                __syncwarp();
                fence_gpu();
                mbar_wait(bars + 8 * B_RDONE, 0, budget);
                int tries = BUDGET;
#pragma unroll 1
                for (int i = lane; i < 88; i += 32) {
                    const uint2* rp = &scr->row[2 * (j0 - 8 + i) + par];
                    uint2 v0, v1, v2;
#pragma unroll 1
                    do { v0 = ld_rlx2(rp + (j0 + i < 8 ? 16 : 0)); v1 = ld_rlx2(rp + 176); v2 = ld_rlx2(rp + 352); } while ((((v0.y ^ ep) | (v1.y ^ ep) | (v2.y ^ ep)) & 31) && --tries > 0);
                    sts2(sb + OFF_STAT + i * 8, (v0.x << 16) ^ 0x80000000u, __float_as_uint(rcp(bf_hi(v0.x))));
                    sts2(sb + OFF_STAT + i * 8 + 704, (v1.x << 16) ^ 0x80000000u, __float_as_uint(rcp(bf_hi(v1.x))));
                    sts2(sb + OFF_STAT + i * 8 + 1408, (v2.x << 16) ^ 0x80000000u, __float_as_uint(rcp(bf_hi(v2.x))));
                }
                __syncwarp();
                poll_all(&scr->csflag[lane & 3], ~0u, ep, budget);
                if (elect_one()) {
                    fence_async_gmem();
                    mbar_expect_tx(bars + 8 * B_AUX, CS_BYTES);
                    bulk_g2s(sb + OFF_CS, scr->cs[nt], CS_BYTES, bars + 8 * B_AUX);
                    TS(21);
                    mbar_expect_tx(bars + 8 * (B_OFULL + 3), BOX); mbar_expect_tx(bars + 8 * (B_OFULL + 9), BOX);
#pragma unroll 1
                    for (int v = 0; v < 2; v++) {
                        const uint32_t ring = sb + v * OFF_X1 + 2 * BOX, fb = bars + 8 * (B_OFULL + v * 6 + 2);
                        mbar_wait(bars + 8 * (B_STAGED + v), 0, budget);
                        asm volatile("red.relaxed.gpu.global.xor.b32 [%0], %1;" ::"l"(&scr->oflag[mt * 2 + 1 - v][0]), "r"(1u << nt) : "memory");
                        TS(13 + 2 * v);
                        mbar_arrive(fb);
                        mbar_wait(bars + 8 * B_G1DONE, 0, budget);
                        bulk_s2c(mapa(ring + BOX, hp ^ 1), ring, BOX, mapa(fb + 8, hp ^ 1));
                        if (v == 0) {
                            mbar_wait(bars + 8 * B_FREED, 0, budget);
#pragma unroll
                            for (int n = 0; n < 8; n++) {
                                mbar_expect_tx(bars + 8 * (B_OFULL + (n >> 2) * 6 + (4 + (n & 3)) % 6), BOX);
                                mbar_arrive_at(mapa(bars + 8 * B_OEMPTY, n >> 2) + (4 + (n & 3)) % 6 * 8);
                            }
                        }
                    }
                }
            }
        }
    } else if (warp >= 8) {
        reg_dec<40>();
        const int wq = warp - 8, ta = tid - 256;
        const uint32_t rbuf = sb + OFF_FR + wq * BOX, rbar = bars + 8 * B_ROW;
        const uint4 wv = ldg_nc(wr + ta * 8);
        if (ta == 0) sts1(sb + OFF_EP, ld_rlx(&scr->epoch[0]) + 1);
        sts4(sb + OFF_STAT + ta * 16, wv.x, wv.y, wv.z, wv.w);
        bar_sync(8, 224);
        const uint32_t ep = __shfl_sync(0xffffffffu, lds1(sb + OFF_EP), 0);
        {
            const int s = b * 16 + wq * 4 + (lane >> 3);
            if ((lane & 7) == 0) st_rlx2(&scr->row[s], 0, ep - 1);
            float sw = 0.f;
#pragma unroll 1
            for (int i = 0; i < 16; i++) { const uint32_t q = lds1(sb + OFF_STAT + i * 128 + lane * 4); sw += bf_lo(q) + bf_hi(q); }
#pragma unroll 1
            for (int o = 16; o > 0; o >>= 1) sw += __shfl_xor_sync(0xffffffffu, sw, o);
            float s1 = 0.f, s2 = 0.f, sr = 0.f;
            const uint32_t xa = rbuf + (lane >> 3) * 2048 + (lane & 7) * 16, wa = sb + OFF_STAT + (lane & 7) * 16;
            mbar_wait(rbar, 0, budget);
            TSC(ta == 0, 17);
            uint4 u = lds4(xa), w4 = lds4(wa);
#pragma unroll kStatsUnroll
            for (int i = 1; i <= 16; i++) {
                const uint32_t o = (i * 128) & 2047;
                const uint4 un = lds4(xa + o), wn = lds4(wa + o);
#pragma unroll
                for (int c = 0; c < 4; c++) {
                    const float a0 = bf_lo((&u.x)[c]), a1 = bf_hi((&u.x)[c]);
                    s1 += a0; s2 = fmaf(a0, a0, s2); sr = fmaf(a0, bf_lo((&w4.x)[c]), sr);
                    s1 += a1; s2 = fmaf(a1, a1, s2); sr = fmaf(a1, bf_hi((&w4.x)[c]), sr);
                }
                u = un; w4 = wn;
            }
#pragma unroll 1
            for (int o = 1; o < 8; o <<= 1) {
                s1 += __shfl_xor_sync(0xffffffffu, s1, o); s2 += __shfl_xor_sync(0xffffffffu, s2, o); sr += __shfl_xor_sync(0xffffffffu, sr, o);
            }
            const float mean = s1 * (1.f / 1024.f), mb = bf16r(mean);
            float var = fmaf(-mean, mean, s2 * (1.f / 1024.f));
            sr = fmaf(-mb, sw, sr);
            if (__builtin_expect(__any_sync(0xffffffffu, mean * mean > 256.f * var), 0)) {
                float a2 = 0.f, ar = 0.f;
#pragma unroll 1
                for (int i = 0; i < 64; i++) {
                    const uint32_t o = (i >> 2) * 128 + (i & 3) * 4, q1 = lds1(xa + o), q2 = lds1(wa + o);
                    a2 = fmaf(bf_lo(q1) - mean, bf_lo(q1) - mean, fmaf(bf_hi(q1) - mean, bf_hi(q1) - mean, a2));
                    ar = fmaf(bf_lo(q1) - mb, bf_lo(q2), fmaf(bf_hi(q1) - mb, bf_hi(q2), ar));
                }
#pragma unroll 1
                for (int o = 1; o < 8; o <<= 1) { a2 += __shfl_xor_sync(0xffffffffu, a2, o); ar += __shfl_xor_sync(0xffffffffu, ar, o); }
                var = a2 * (1.f / 1024.f); sr = ar;
            }
            float den;
            asm("sqrt.approx.f32 %0, %1;" : "=f"(den) : "f"(bf16r(bf16r(var) + 1e-5f)));
            const uint32_t st = pack_bf16(mb, den);
            const uint32_t rb = pack_bf16(0.f, sr * rcp(bf_hi(st)) + 0.f);
            uint32_t ord = (int)rb < 0 ? ~rb & 0xffff0000u : rb | 0x80000000u;
            if ((rb & 0x7fffffffu) > 0x7f800000u) ord = 0;
            if ((lane & 7) == 0) st_rlx2(&scr->row[s], st, ord | ((2047 - s) << 5) | (ep & 31));
            __syncwarp();
            if (lane < 7) mbar_arrive(bars + 8 * (lane < 5 ? B_FEMPTY + lane : B_RDONE));
        }
        TSC(ta == 0, 18);
        if ((b >> 3) == 14) {
            const uint32_t gm = sb + OFF_E, cnt = gm + 64, res = gm + 80, list = gm + 128;
            uint32_t kv[16];
            int tries = BUDGET;
#pragma unroll 1
            do {
                uint32_t bad = 0;
#pragma unroll
                for (int n = 0; n < 16; n++) kv[n] = ld_rlx(&scr->row[n * 128 + ta].y);
#pragma unroll
                for (int n = 0; n < 16; n++) bad |= kv[n] ^ ep;
                if ((bad & 31) == 0) break;
            } while (--tries > 0);
            __syncwarp();
            TSC(ta == 0, 26);
            uint32_t m = 0;
#pragma unroll
            for (int n = 0; n < 16; n++) m = max(m, kv[n]);
            uint32_t gmax = m;
#pragma unroll
            for (int o = 1; o < 8; o <<= 1) gmax = max(gmax, __shfl_xor_sync(0xffffffffu, gmax, o));
            sts1(gm + (ta >> 3) * 4, gmax);
            sts1(cnt, 0);
            bar_sync(12, 128);
            const uint32_t c = lds1(gm + (lane & 15) * 4);
            int rank = 0;
#pragma unroll
            for (int i = 0; i < 2; i++) { const uint4 q = lds4(gm + (lane >> 4) * 32 + i * 16); rank += (q.x > c) + (q.y > c) + (q.z > c) + (q.w > c); }
            rank += __shfl_xor_sync(0xffffffffu, rank, 16);
            const uint32_t thr = redux_max(rank == 7 ? c : 0u);
#pragma unroll 1
            while (m >= thr) {
                uint32_t at, m2 = 0;
                asm volatile("atom.shared.add.u32 %0, [%1], 1;" : "=r"(at) : "r"(cnt) : "memory");
#pragma unroll
                for (int n = 0; n < 16; n++) m2 = max(m2, kv[n] < m ? kv[n] : 0u);
                sts1(list + at * 4, m);
                if (m2 == 0) break;
                m = m2;
            }
            bar_sync(12, 128);
            const int nc = lds1(cnt);
#pragma unroll 1
            for (int i = ta >> 3; i < ((nc + 3) & ~3); i += 16) {
                const uint32_t ki = lds1(list + i * 4);
                int r = 0;
#pragma unroll 1
                for (int n = lane & 7; n < nc; n += 8) r += lds1(list + n * 4) > ki;
                __syncwarp();
#pragma unroll
                for (int o = 1; o < 8; o <<= 1) r += __shfl_xor_sync(0xffffffffu, r, o);
                if (r == (b & 7) && i < nc) sts1(res, ki);
            }
            bar_sync(12, 128);
            const uint32_t k0 = lds1(res);
            const int r0 = 2047 - ((k0 >> 5) & 2047);
            TSC(ta == 0, 22);
            if (ta == 0) st_rlx(&scr->sel[b & 7], k0);
            const uint4 v0 = ldg_nc(x + (size_t)r0 * 1024 + ta * 8);
            const uint32_t s0 = ld_rlx(&scr->row[r0]);
            const float m0 = bf_lo(s0), i0 = rcp(bf_hi(s0));
            const int ao = 14336 + (ta >> 3) * 256 + (b & 7) * 32 + ((ta ^ b) & 7) * 4;
            st_rlx4(scr->act[ep & 1] + ao, norm_pair(v0.x, m0, i0), norm_pair(v0.y, m0, i0), norm_pair(v0.z, m0, i0), norm_pair(v0.w, m0, i0));
            __syncwarp();
            if (lane == 0) red_add(&scr->cnt[8][tries >> 30]);
            st_rlx4(scr->act[~ep & 1] + ao, 0, 0, 0, 0);
        }
        uint32_t s8 = 0, fph = 0, own = 0; float sig = 0.f;
        const uint32_t chk = __shfl_sync(0xffffffffu, sb + OFF_FS + BOX + lane * 32 + (lane & 28), lane);
        int left = BUDGET;
#pragma unroll 1
        for (int ph = 0; ph < 2; ph++) {
            if (ph || b < 112) {
                float acc[4] = {0.f, 0.f, 0.f, 0.f};
                const uint32_t alo = sd + (ph ? dlo(OFF_FS, 8192) : dlo(OFF_FS, 4096)), ahi = ph ? dhi(1024, 1) : dhi(512, 2), astep = ph ? 128 : 64;
                const uint32_t bhi = ph ? dhi(128, 0) : dhi(1024, 1), bstep = ph ? 16 : 2, wrap = ph ? 24 : 40;
                uint32_t prev = 0, prev2 = 0;
                if (ph) mbar_wait(bars + 8 * FFN2_GATE, 0, left);
#pragma unroll 1
                for (int q = ph ? 7 : 16; q > 0; q--) {
                    const uint32_t da = alo + s8 * (F_BYTES >> 7), db = sd + dlo(OFF_FS + BOX, 128) + s8 * (F_BYTES >> 7);
                    mbar_wait_hot(bars + 8 * B_FFULL + s8, fph, left);
                    if (__builtin_expect(__any_sync(0xffffffffu, lds1(chk + s8 * (F_BYTES / 8)) == 0), 0)) {
                        int tries = BUDGET;
#pragma unroll 1
                        for (int n = lane * 4 + (left >> 30); n < 256; n += 128) {
                            uint4 v;
#pragma unroll 1
                            do { v = ld_rlx4(scr->act[ep & 1] + ((ph ? kc * 7 + 7 : 72) - q) * 256 + n); } while (v.x == 0 && --tries > 0);
                            __syncwarp();
                            sts4(sb + OFF_FS + BOX + s8 * (F_BYTES / 8) + n * 4, v.x, v.y, v.z, v.w);
                        }
                        NRETRY();
                        fence_async_smem();
                        __syncwarp();
                    }
                    TSC(TIMING % 10 == 3 && ta == 0, 32 + (ph ? 23 : 16) - q);
                    wg_fence();
#pragma unroll
                    for (int j = 0; j < 4; j++) wgmma_n8<1, 0>(acc, mkdesc(da + j * astep, ahi), mkdesc(db + j * bstep, bhi), 1);
                    wg_commit();
                    prev2 = prev;
                    if (lane == 0) prev = bars + 8 * B_FEMPTY + s8;
                    wg_wait<1>();
                    if (ph) { wg_wait<0>(); prev2 = prev; }
                    if (prev2) mbar_arrive(prev2);
                    s8 += 8;
                    if (s8 == wrap) { s8 = 0; fph ^= 1; }
                }
                wg_wait<0>();
                const int ln = lane + (left >> 30);
                if (ph == 0) {
                    if (prev) mbar_arrive(prev);
                    const bool second = (wq >= 2) != (swap_gu != 0);
                    const uint32_t xa = sb + OFF_GU + ((wq & 1) * 32 + ln) * 16;
                    if (second) sts4(xa, __float_as_uint(acc[0]), __float_as_uint(acc[1]), __float_as_uint(acc[2]), __float_as_uint(acc[3]));
                    bar_sync(12, 128);
                    if (!second) {
                        const float4 up = lds4f(xa);
                        float hv[4];
#pragma unroll
                        for (int c = 0; c < 4; c++) { const float ga = bf16r(acc[c]); hv[c] = bf16r(ga * sigmoidf(ga)) * bf16r((&up.x)[c]); }
                        const int ao = (b * 4 + (wq & 1) * 2) * 32 + ln;
                        st_rlx(scr->act[ep & 1] + ao, max(movm(pack_bf16(hv[0], hv[1])), 1u)); st_rlx(scr->act[ep & 1] + 32 + ao, max(movm(pack_bf16(hv[2], hv[3])), 1u));
                        __syncwarp();
                        if (ln == 0) red_add(&scr->cnt[b / 14][0]);
                        st_rlx(scr->act[~ep & 1] + ao, 0); st_rlx(scr->act[~ep & 1] + 32 + ao, 0);
                    }
                } else {
#pragma unroll
                    for (int c = 0; c < 4; c++) st_rlx(&scr->ypart[kc][2 * (ln & 3) + (c & 1)][c2 * 64 + wq * 16 + (c >> 1) * 8 + (ln >> 2)], (__float_as_uint(acc[c]) & ~1u) | (ep & 1));
                    if (b == 0 && ta == 0) st_rlx(&scr->epoch[ln], ep);
                }
                TSC(ta == 0, 22 + ph);
            }
            const int ln = lane + (left >> 30);
            if (ph == 0) {
                if ((ta & 126) == 64) mbar_arrive(bars + 8 * B_F1DONE);
                const uint32_t kj = poll_all(&scr->sel[ln & 7], 31u, ep & 31, left);
                const int row = 2047 - ((kj >> 5) & 2047), jj = (row & 1) == par ? (row >> 1) - j0 : -1;
                sig = bf16r(sigmoidf(__uint_as_float(((int)kj < 0 ? kj & 0x7fffffffu : ~kj) & 0xffff0000u)));
                own = __ballot_sync(0xffffffffu, (jj >> 7) == rh) & 255;
                sts1(sb + OFF_SEL + (ln & 7) * 4, jj);
                sts4(sb + OFF_UPD + wq * 512 + ln * 16, 0, 0, 0, 0);
            }
            if ((own != 0) == ph) {
                if (wq & 2) own &= own - 1;
#pragma unroll 1
                for (; own; own &= own - 1, own &= own - 1) {
                    const int j = __ffs(own) - 1;
                    const uint32_t* src = &scr->ypart[ln >> 4][j][cb * 128 + (wq & 1) * 64 + (ln & 15) * 4];
                    uint4 v[4]; int tries = BUDGET;
#pragma unroll 1
                    do {
#pragma unroll
                        for (int m = 0; m < 4; m++) v[m] = ld_rlx4(src + m * 2 * 8192);
                    } while ((((v[0].x ^ ep) | (v[1].x ^ ep) | (v[2].x ^ ep) | (v[3].x ^ ep)) & 1) && --tries > 0);
                    __syncwarp();
                    float a[4];
                    const float sj = __shfl_sync(0xffffffffu, sig, j);
#pragma unroll
                    for (int c = 0; c < 4; c++) {
                        a[c] = (__uint_as_float((&v[0].x)[c]) + __uint_as_float((&v[1].x)[c])) + (__uint_as_float((&v[2].x)[c]) + __uint_as_float((&v[3].x)[c]));
                        a[c] = bf16r(a[c] + __shfl_xor_sync(0xffffffffu, a[c], 16)) * sj;
                    }
                    sts2(sb + OFF_UPD + (wq & 1) * 1024 + j * 128 + ((((ln >> 1) & 7) ^ j) << 4) + (ln & 1) * 8, pack_bf16(a[0], a[1]), pack_bf16(a[2], a[3]));
                }
                fence_async_smem();
                __syncwarp();
                if (ln < 2) mbar_arrive(bars + 8 * B_UPD);
            }
        }
        TSC(ta == 0, 24);
    } else {
        reg_inc<224>();
        const int w = warp >> 2, wi = warp & 3, g = lane >> 2, t = lane & 3;
        const bool elect = (tid & 127) == 0;
        const uint32_t mad = (lane & 15) * 128 + (((lane >> 4) ^ (lane & 7)) << 4);
        float acc[64];
        const uint32_t ring = sb + w * OFF_X1, ofull = bars + 8 * (B_OFULL + w * 6), oempty = mapa(bars + 8 * B_OEMPTY, w);
        const int r0 = rh * 128 + wi * 32 + (1 - w) * 16 + g;
        {
            float acc0[96], acc1[96];
            const uint32_t sta = sb + OFF_STAT + (8 + w * 128 + wi * 32) * 8;
            {
                const uint32_t xfull = bars + 8 * (B_XFULL + w * 6), xempty = mapa(bars + 8 * B_XEMPTY, w), dx0 = sd + dlo(w * OFF_X1, 16);
                int j = 0, pj = 0, ws = 2, pws = 0; uint32_t xph = 0;
                cluster_wait();
#pragma unroll 1
                for (int k = 0;; k++) {
                    const uint32_t dx = dx0 + j * (BOX >> 4), dw = sd + dlo(OFF_W, BOX) + ws * (W_BYTES >> 4);
                    mbar_wait(bars + 8 * (B_WFULL + ws), xph, budget);
                    mbar_wait(xfull + 8 * j, xph, budget);
                    TSC(elect && k == 0, 1 + 8 * w);
                    TSC(TIMING % 10 == 1 && tid == 0, 32 + k);
                    wg_wait<0>();
                    wg_fence();
#pragma unroll
                    for (int kk = 0; kk < 4; kk++) wgmma_n192<0, 1>(acc1, mkdesc(dx + kk * 2, dhi(1024, 1)), mkdesc(dw + kk * 128, dhi(1024, 1)), kk ? 1 : k);
                    wg_commit();
                    if (elect && k > 0) {
                        mbar_arrive(bars + 8 * (B_WEMPTY + pws));
                        if (k <= 13) { mbar_expect_tx(xfull + 8 * pj, BOX); mbar_arrive_at(xempty + 8 * pj); }
                    }
                    if (k == 15) break;
                    mbar_wait(xfull + 8 * j + 8, xph, budget);
                    wg_wait<0>();
                    wg_fence();
#pragma unroll
                    for (int kk = 0; kk < 4; kk++) wgmma_n192<0, 1>(acc0, mkdesc(dx + 512 + kk * 2, dhi(1024, 1)), mkdesc(dw + kk * 128, dhi(1024, 1)), kk ? 1 : k);
                    wg_commit();
                    if (elect && k <= 12) { mbar_expect_tx(xfull + 8 * j, BOX); mbar_arrive_at(xempty + 8 * j); }
                    pj = j + 1; pws = ws;
                    if (++ws == 3) ws = 0;
                    j += 2;
                    if (j == 6) { j = 0; xph ^= 1; }
                }
            }
            mbar_wait(bars + 8 * B_AUX, 0, budget);
            const uint32_t zero = budget >> 30, pm = t & 1 ? 0x4432 : 0x3232, ra = sta + ((t >> 1) * 16 + g) * 8;
            const uint32_t a0 = __byte_perm(lds1(ra), 0, pm), a1 = __byte_perm(lds1(ra + 64), 0, pm), a2 = a0 & zero, a3 = a1 & zero;
            wg_fence();
            wgmma_rs_n192(acc1, a0, a1, a2, a3, mkdesc(sd + dlo(OFF_CS, 0), dhi(128, 0)));
            wg_commit();
            const bool u0 = 2 * t > g, u1 = 2 * t + 1 > g;
            uint32_t mU = (u0 ? 0xffffu : 0u) | (u1 ? 0xffff0000u : 0u);
            uint32_t ka0 = sta + (2 * t - (u0 ? 8 : 0)) * 8 + 4, ka1 = sta + (2 * t + 1 - (u1 ? 8 : 0)) * 8 + 4;
            float rk[2][4], fu[2][4], fn[2][4];
            auto factors = [&](int h) {
#pragma unroll
                for (int n = 0; n < 4; n += 2) {
                    const float rq = lds1f(sta + (16 * h + 4 * n + g) * 8 + 4) * (0.17677669529663687f * 1.4426950408889634f);
                    rk[h][n] = lds1f(ka0 + h * 128 + n * 32); rk[h][n + 1] = lds1f(ka1 + h * 128 + n * 32);
                    const float f0 = rq * rk[h][n], f1 = rq * rk[h][n + 1];
                    fu[h][n] = u0 ? f0 : 0.f; fn[h][n] = f0 - fu[h][n]; fu[h][n + 1] = u1 ? f1 : 0.f; fn[h][n + 1] = f1 - fu[h][n + 1];
                }
#pragma unroll
                for (int n = 0; n < 4; n++) asm volatile("" : "+f"(fu[h][n]), "+f"(fn[h][n]));
            };
            uint8_t* og = scr->o + ((size_t)(mt * 4 + w * 2) * 16 + nt) * BOX + wi * 256 + lane * 4;
            asm volatile("" : "+r"(ka0), "+r"(ka1));
            mbar_wait(bars + 8 * (B_XFULL + w * 6 + 1), 1, budget);
            wg_wait<0>();
            wg_fence();
#pragma unroll
            for (int kk = 0; kk < 4; kk++)
                wgmma_n192<0, 1>(acc0, mkdesc(sd + dlo(w * OFF_X1 + BOX, 16) + kk * 2, dhi(1024, 1)), mkdesc(sd + dlo(OFF_W + 2 * W_BYTES, BOX) + kk * 128, dhi(1024, 1)), 1);
            wgmma_rs_n192(acc0, a0, a1, a2, a3, mkdesc(sd + dlo(OFF_CS + 64, 0), dhi(128, 0)));
            wg_commit();
            TSC(elect, 19 + w);
            uint32_t pk0[48], pk1[48], o[16] = {};
#pragma unroll
            for (int j = 0; j < 48; j++) if (j < 16 || (j & 1)) pk1[j] = pack_here(acc1[2 * j], acc1[2 * j + 1]);
            if (warp < 7) {
#pragma unroll
                for (int c = 0; c < 4; c++) stsm4(ring + wi * 2048 + c * 512 + lane * 16, pk1[17 + 8 * c], pk1[19 + 8 * c], pk1[21 + 8 * c], pk1[23 + 8 * c]);
                bar_arrive(1 + warp, 64);
            } else if (j0 != 768) {
#pragma unroll
                for (int c = 0; c < 4; c++) {
                    pk1[17 + 8 * c] = max(pk1[17 + 8 * c], 1u);
                    st_rlx4(&scr->halo[b][c * 128 + lane * 4], pk1[17 + 8 * c], pk1[19 + 8 * c], pk1[21 + 8 * c], pk1[23 + 8 * c]);
                }
            }
            TSC(tid == 224, 28);
#pragma unroll
            for (int j = 16; j < 48; j += 2) pk1[j] = pack_here(acc1[2 * j], acc1[2 * j + 1]);
            factors(1);
            uint32_t od = sb + 2 * BOX + wi * 256 + (lane >> 4) * 1024 + (lane & 15) * 16, g1peer = mapa(bars + 8 * B_G1DONE, hp ^ 1);
            uint32_t ha = sb + (warp == 0 ? OFF_HIN : warp <= 4 ? -2048 : OFF_X1 - 5 * 2048) + warp * 2048 + lane * 16;
            const bool first = warp == 0 && j0 == 0;
            float bias0 = first && u0 ? -INFINITY : 0.f, bias1 = first && u1 ? -INFINITY : 0.f;
            float ci[4];
#pragma unroll
            for (int n = 0; n < 4; n++) ci[n] = __uint_as_float((0x03800000u + n) | zero);
            asm volatile("" : "+f"(ci[0]), "+f"(ci[1]), "+f"(ci[2]), "+f"(ci[3]));
            asm volatile("" : "+l"(og), "+r"(mU), "+r"(od), "+r"(ha), "+f"(bias0), "+f"(bias1));
            mbar_wait(bars + 8 * (B_WEMPTY + 1), 0, budget);
            wg_wait<0>();
            if (elect) { mbar_arrive(bars + 8 * B_G1DONE); mbar_arrive_at(g1peer); }
            TSC(elect, 2 + 8 * w);
            auto hand_over = [&](int v) {
                asm volatile("{\n.reg .pred p;\nsetp.ne.b32 p, %17, 0;\n"
                             "@p stmatrix.sync.aligned.m8n8.x4.shared.b16 [%16], {%0,%1,%2,%3};\n@p stmatrix.sync.aligned.m8n8.x4.shared.b16 [%16 + 2048], {%4,%5,%6,%7};\n"
                             "@p stmatrix.sync.aligned.m8n8.x4.shared.b16 [%16 + 4096], {%8,%9,%10,%11};\n@p stmatrix.sync.aligned.m8n8.x4.shared.b16 [%16 + 6144], {%12,%13,%14,%15};\n"
                             "fence.proxy.async.shared::cta;\n}"
                             ::"r"(o[0]), "r"(o[1]), "r"(o[2]), "r"(o[3]), "r"(o[4]), "r"(o[5]), "r"(o[6]), "r"(o[7]), "r"(o[8]), "r"(o[9]), "r"(o[10]), "r"(o[11]),
                               "r"(o[12]), "r"(o[13]), "r"(o[14]), "r"(o[15]), "r"(od + v * OFF_X1), "r"((int)(w == rh)) : "memory");
#pragma unroll
                for (int i = 0; i < 16; i++) asm volatile("st.global.u32 [%0], %1;" ::"l"(og + (1 - v) * 16 * BOX + (i >> 1) * 1024 + (i & 1) * 128), "r"(o[i]) : "memory");
                __syncwarp();
                if (lane == 0) mbar_arrive(bars + 8 * (B_STAGED + v));
            };
#pragma unroll
            for (int j = 32; j < 48; j++) pk1[j] = movm(pk1[j]);
#pragma unroll
            for (int j = 17; j < 48; j += 2) pk0[j] = pack_here(acc0[2 * j], acc0[2 * j + 1]);
#pragma unroll
            for (int j = 33; j < 48; j += 2) pk0[j] = movm(pk0[j]);
            factors(0);
            const float2 s0 = lds2f(sb + OFF_STAT + (8 + r0) * 8), s1 = lds2f(sb + OFF_STAT + (16 + r0) * 8);
            const float m0 = s0.x * s0.y, f0 = 1.f + s0.y, m1 = s1.x * s1.y, f1 = 1.f + s1.y;
            attn_pair<2>(pk1, pk1 + 16, pk1 + 32, pk0 + 17, pk0 + 33, fu[1], fn[1], rk[1], 0.f, 0.f, mU, zero, ci, o);
            hand_over(0);
            TSC(elect, 3 + 8 * w);
#pragma unroll
            for (int j = 0; j < 48; j++) if (j < 16 || !(j & 1)) pk0[j] = pack_here(acc0[2 * j], acc0[2 * j + 1]);
#pragma unroll
            for (int j = 32; j < 48; j += 2) pk0[j] = movm(pk0[j]);
            mbar_wait(bars + 8 * B_XT, 0, budget);
#pragma unroll
            for (int j = 0; j < 8; j++) {
                uint32_t a[4];
                ldsm4(a, ((ring + wi * 2048 + mad) ^ ((j & 3) * 32)) + (4 + (j >> 2)) * BOX);
                acc[8 * j + 0] = fmaf(bf_lo(a[0]), f0, m0); acc[8 * j + 1] = fmaf(bf_hi(a[0]), f0, m0);
                acc[8 * j + 2] = fmaf(bf_lo(a[1]), f1, m1); acc[8 * j + 3] = fmaf(bf_hi(a[1]), f1, m1);
                acc[8 * j + 4] = fmaf(bf_lo(a[2]), f0, m0); acc[8 * j + 5] = fmaf(bf_hi(a[2]), f0, m0);
                acc[8 * j + 6] = fmaf(bf_lo(a[3]), f1, m1); acc[8 * j + 7] = fmaf(bf_hi(a[3]), f1, m1);
            }
            bar_sync(warp ? warp : 11, 64);
            uint32_t hl[16];
            ldsm4t(hl + 8, ha + 1024); ldsm4t(hl + 12, ha + 1536); ldsm4(hl, ha); ldsm4(hl + 4, ha + 512);
            __syncwarp();
            if (lane == 0) mbar_arrive(bars + 8 * B_FREED);
            attn_pair<1>(pk0, pk0 + 16, pk0 + 32, hl, hl + 8, fu[0], fn[0], rk[0], bias0, bias1, mU, zero, ci, o);
            hand_over(1);
        }
        TSC(tid == 0, 4);
        {
            const uint32_t da0 = sd + dlo(w * OFF_X1, 1024), db0 = sd + dlo(OFF_WO, BOX);
            const uint32_t chk = ring + wi * 256 + (lane >> 3) * 1032 + (lane & 7) * 32 + (lane & 4);
            uint32_t s8 = 16, ps8 = 0, ph = 0;
#pragma unroll 1
            for (int i = 0; i < 16; i++) {
                mbar_wait_hot(ofull + s8, ph, budget);
                const uint32_t seen0 = lds1(chk + s8 * (BOX / 8)), seen1 = lds1(chk + s8 * (BOX / 8) + 4096);
                mbar_wait_hot(bars + 8 * B_WOFULL + s8, ph, budget);
                if (__builtin_expect(__any_sync(0xffffffffu, min(seen0, seen1) == 0), 0)) {
                    const uint32_t at = wi * 256 + (lane >> 4) * 1024 + (lane & 15) * 16;
                    const uint8_t* src = scr->o + ((size_t)((mt * 2 + rh) * 2 + 1 - w) * 16 + ((2 * p + (i < 2 ? i ^ hp : i)) & 15)) * BOX + at;
#pragma unroll 1
                    for (int n = 0; n < 8192; n += 2048) {
                        uint4 v; int tries = 4096;
#pragma unroll 1
                        do { v = ld_rlx4(src + n); } while (v.x == 0 && --tries > 0);
                        sts4(ring + s8 * (BOX / 8) + at + n, v.x, v.y, v.z, v.w);
                    }
                    NRETRY();
                    fence_async_smem();
                    __syncwarp();
                }
                TSC(TIMING % 10 == 1 && tid == 0, 48 + i);
                TSC(TIMING % 10 == 2 && elect, 32 + w * 16 + i);
                const uint32_t da = da0 + s8 * (BOX >> 7), db = db0 + s8 * (BOX >> 6);
                wg_wait<1>();
                wg_fence();
#pragma unroll
                for (int kk = 0; kk < 4; kk++) {
                    wgmma_n128<0, 1>(acc, mkdesc(da + kk * 128, dhi(128, 0)), mkdesc(db + kk * 128, dhi(1024, 1)), 1);
                    if (kk & 1) wg_commit();
                }
                wg_wait<2>();
                if (elect && (unsigned)(i - 1) < 10) { mbar_expect_tx(ofull + ps8, BOX); mbar_arrive_at(oempty + ps8); mbar_arrive(bars + 8 * B_WOEMPTY + ps8); }
                ps8 = s8;
                s8 = s8 == 40 ? 0 : s8 + 8;
                if (s8 == 16) ph ^= 1;
            }
            mbar_wait(bars + 8 * B_UPD, 0, budget);
            const float2 sl = lds2f(sb + OFF_SEL + t * 8);
            const int d0 = __float_as_int(sl.x) - r0, d1 = __float_as_int(sl.y) - r0;
            const uint32_t a0 = (d0 == 0 ? 0x3f80u : 0u) | (d1 == 0 ? 0x3f800000u : 0u), a1 = (d0 == 8 ? 0x3f80u : 0u) | (d1 == 8 ? 0x3f800000u : 0u);
            wg_fence();
            wgmma_rs_n128(acc, a0, a1, 0u, 0u, mkdesc(sd + dlo(OFF_UPD, 1024), dhi(0, 1)));
            wg_commit();
            wg_wait<0>();
            TSC(elect, 7 + 9 * w);
            const uint32_t os0 = ring + wi * 4096;
#pragma unroll
            for (int j = 0; j < 8; j++)
                stsm4(((os0 + mad) ^ ((j & 3) * 32)) + (j >> 2) * 2048, pack_bf16(acc[8 * j], acc[8 * j + 1]), pack_bf16(acc[8 * j + 2], acc[8 * j + 3]),
                      pack_bf16(acc[8 * j + 4], acc[8 * j + 5]), pack_bf16(acc[8 * j + 6], acc[8 * j + 7]));
            fence_async_smem();
            __syncwarp();
            if (elect_one()) {
                asm volatile("cp.async.bulk.tensor.5d.global.shared::cta.bulk_group [%0, {%2, %2, %3, %4, %5}], [%1];\ncp.async.bulk.commit_group;\ncp.async.bulk.wait_group.read 0;"
                             ::"l"(&mout), "r"(os0), "r"(0), "r"(((j0 + rh * 128) >> 5) + wi), "r"(1 - w), "r"(par * 16 + cb * 2) : "memory");
            }
            TSC(elect, 8 - 2 * w);
            TS_END();
        }
    }
}

typedef CUresult (*EncodeFn)(CUtensorMap*, CUtensorMapDataType, cuuint32_t, void*, const cuuint64_t*, const cuuint64_t*, const cuuint32_t*,
                             const cuuint32_t*, CUtensorMapInterleave, CUtensorMapSwizzle, CUtensorMapL2promotion, CUtensorMapFloatOOBfill);

CUtensorMap make_map(EncodeFn fn, const void* base, int rank, const cuuint64_t* dims, const cuuint64_t* strides, const cuuint32_t* box,
                     CUtensorMapSwizzle swz = CU_TENSOR_MAP_SWIZZLE_128B, CUtensorMapL2promotion pro = CU_TENSOR_MAP_L2_PROMOTION_L2_256B) {
    CUtensorMap m;
    cuuint32_t es[5] = {1, 1, 1, 1, 1};
    fn(&m, CU_TENSOR_MAP_DATA_TYPE_BFLOAT16, rank, (void*)base, dims, strides, box, es, CU_TENSOR_MAP_INTERLEAVE_NONE,
       swz, pro, CU_TENSOR_MAP_FLOAT_OOB_FILL_NONE);
    return m;
}

}

extern "C" void kernel_launch(void* const* d_in, const int* in_sizes, int n_in, void* d_out, int out_size) {
    (void)in_sizes; (void)n_in; (void)out_size;
    const __nv_bfloat16* x = (const __nv_bfloat16*)d_in[0];
    const __nv_bfloat16* wqkv = (const __nv_bfloat16*)d_in[1];
    const __nv_bfloat16* wo = (const __nv_bfloat16*)d_in[2];
    const __nv_bfloat16* wr = (const __nv_bfloat16*)d_in[4];
    const __nv_bfloat16* wg = (const __nv_bfloat16*)d_in[5];
    const __nv_bfloat16* wu = (const __nv_bfloat16*)d_in[6];
    const __nv_bfloat16* wd = (const __nv_bfloat16*)d_in[7];
    static EncodeFn fn = nullptr;
    static Scratch* scr = nullptr;
    if (!fn) {
        void* p = nullptr; cudaDriverEntryPointQueryResult q;
        cudaGetDriverEntryPoint("cuTensorMapEncodeTiled", &p, cudaEnableDefault, &q);
        fn = (EncodeFn)p;
        cudaFuncSetAttribute(fused_kernel, cudaFuncAttributeMaxDynamicSharedMemorySize, SMEM_LAUNCH);
        cudaGetSymbolAddress((void**)&scr, g_scr);
    }
    const cuuint64_t xd[4] = {2048, 16, 32, 2}, xs[4] = {4096, 131072, 65536, 128}, od[5] = {64, 16, 32, 2, 32};
    const cuuint32_t xb[4] = {64, 16, 4, 1}, ob[5] = {64, 16, 1, 1, 2};
    const cuuint64_t wdm[3] = {1024, 1024, 3}, wst[2] = {6144, 2048};
    const cuuint32_t wb[3] = {64, 64, 3};
    const cuuint64_t wod[3] = {64, 1024, 16}, wdd[3] = {64, 3584, 16}, wos[2] = {2048, 128};
    const cuuint32_t wob[3] = {64, 64, 2}, wdb[3] = {64, 64, 1};
    CUtensorMap mx = make_map(fn, x, 4, xd, xs, xb), mw = make_map(fn, wqkv, 3, wdm, wst, wb);
    CUtensorMap mwo = make_map(fn, wo, 3, wod, wos, wob), mout = make_map(fn, d_out, 5, od, xs, ob);
    const int swap_gu = wu < wg;
    const cuuint64_t gd[3] = {3584, 1024, 2}, gst[2] = {7168, (cuuint64_t)(swap_gu ? (const char*)wg - (const char*)wu : (const char*)wu - (const char*)wg)};
    const cuuint32_t gb[3] = {32, 64, 2};
    CUtensorMap mgu = make_map(fn, swap_gu ? wu : wg, 3, gd, gst, gb, CU_TENSOR_MAP_SWIZZLE_64B, CU_TENSOR_MAP_L2_PROMOTION_L2_128B);
    CUtensorMap mwd = make_map(fn, wd, 3, wdd, wos, wdb, CU_TENSOR_MAP_SWIZZLE_128B, CU_TENSOR_MAP_L2_PROMOTION_L2_128B);
    const cuuint64_t md[2] = {64, 32768}, ms[1] = {128};
    const cuuint32_t mb[2] = {64, 64};
    CUtensorMap mo = make_map(fn, scr, 2, md, ms, mb, CU_TENSOR_MAP_SWIZZLE_NONE, CU_TENSOR_MAP_L2_PROMOTION_NONE);
    cudaLaunchConfig_t cfg = {};
    cfg.gridDim = dim3(132); cfg.blockDim = dim3(512); cfg.dynamicSmemBytes = SMEM_LAUNCH; cfg.stream = cudaStreamPerThread;
    cudaLaunchAttribute at[1];
    at[0].id = cudaLaunchAttributeClusterDimension; at[0].val.clusterDim.x = 2; at[0].val.clusterDim.y = 1; at[0].val.clusterDim.z = 1;
    cfg.attrs = at; cfg.numAttrs = 1;
    cudaLaunchKernelEx(&cfg, fused_kernel, mx, mw, mwo, mout, mgu, mwd, mo, x, wr, scr, swap_gu, Weights{(const char*)wqkv, (const char*)wo, (const char*)wg, (const char*)wu, (const char*)wd});
}
```

```cpp
#include <cuda_runtime.h>
#include <cuda.h>
#include <cuda_bf16.h>
#include <stdint.h>

namespace {

constexpr int BOX = 8192, W_BYTES = 3 * BOX;
constexpr int OFF_X1 = 6 * BOX, OFF_FR = 12 * BOX, OFF_E = 16 * BOX, OFF_W = 19 * BOX;
constexpr int OFF_WO = OFF_E;
constexpr int OFF_UPD = OFF_FR, OFF_HIN = OFF_UPD + 2048, OFF_GU = OFF_HIN + 2048, OFF_FS = OFF_GU + 1024;
constexpr int F_BYTES = 9216;
constexpr int CS_BYTES = 3136;
constexpr int OFF_CS = OFF_FS + 5 * F_BYTES;
constexpr int OFF_STAT = 28 * BOX;
constexpr int OFF_SEL = OFF_STAT + 2112;
constexpr int OFF_EP = OFF_SEL + 32;
constexpr int OFF_BAR = OFF_EP + 16;
constexpr int B_WFULL = 0, B_XFULL = 3, B_AUX = 15, B_XT = 16, B_ROW = 17, B_WOFULL = 18, B_OFULL = 24, B_FFULL = 36;
constexpr int B_WEMPTY = 42, B_F1DONE = 45, B_XEMPTY = 46, B_WOEMPTY = 52, B_OEMPTY = 58;
constexpr int B_G1DONE = 66, B_FEMPTY = 67, B_STAGED = 72, B_UPD = 74, B_RDONE = 75, B_FREED = 76, NBAR = 78;
constexpr int SMEM_BYTES = OFF_BAR + NBAR * 8;
static_assert(OFF_FS + 3 * F_BYTES == OFF_E && OFF_CS + CS_BYTES <= OFF_W && SMEM_BYTES + 256 <= 232448 && OFF_BAR % 8 == 0 && OFF_UPD % 1024 == 0, "smem");
#define POLL_NS 30
#define PF_RATE 10
#define PF_START 7
#define ZF_NS 100
#define FFN2_GATE B_G1DONE
#define PF_NW 6
#define EARLY_PF 1
#define EARLY_PK 17
#define FENCE_PRED "@p "
#define DS_BYTES BOX
#define ZF_N 64
#define POLL_DEPTH 1
#define POLL_GAP 40
#define G1HI dhi(1024, 1)
#define ROWS_AT 11
#define STATS_UNROLL 1
constexpr int kStatsUnroll = STATS_UNROLL;
constexpr int BUDGET = 1 << 18;

struct Scratch {
    uint8_t o[2048 * 1024 * 2];
    uint32_t ypart[8][8][1024];
    uint32_t halo[128][512];
    uint32_t act[2][14336 + 4096];
    uint2 row[2048];
    uint32_t cs[16][800];
    uint32_t oflag[16][32];
    uint32_t cnt[9][32];
    uint32_t sel[32], csflag[32], epoch[32];
};
__device__ __align__(1024) Scratch g_scr;
struct Weights { const char *wqkv, *wo, *wg, *wu, *wd; };

#define TS(i) do {} while (0)
#define TS_END() do {} while (0)
#define TSC(c, i) do {} while (0)
#define NRETRY() do {} while (0)
constexpr int SMEM_LAUNCH = SMEM_BYTES;
__device__ __forceinline__ uint32_t smem_u32(const void* p) { return (uint32_t)__cvta_generic_to_shared(p); }
__device__ __forceinline__ void mbar_init(uint32_t bar, uint32_t cnt) { asm volatile("mbarrier.init.shared::cta.b64 [%0], %1;" ::"r"(bar), "r"(cnt) : "memory"); }
__device__ __forceinline__ void mbar_expect_tx(uint32_t bar, uint32_t bytes) { asm volatile("mbarrier.arrive.expect_tx.shared::cta.b64 _, [%0], %1;" ::"r"(bar), "r"(bytes) : "memory"); }
__device__ __forceinline__ void mbar_arrive(uint32_t bar) { asm volatile("mbarrier.arrive.shared::cta.b64 _, [%0];" ::"r"(bar) : "memory"); }
__device__ __forceinline__ uint32_t mapa(uint32_t a, uint32_t cta) { uint32_t r; asm("mapa.shared::cluster.u32 %0, %1, %2;" : "=r"(r) : "r"(a), "r"(cta)); return r; }
__device__ __forceinline__ void mbar_arrive_at(uint32_t cbar) { asm volatile("mbarrier.arrive.shared::cluster.b64 _, [%0];" ::"r"(cbar) : "memory"); }
__device__ __forceinline__ void mbar_wait(uint32_t bar, uint32_t parity, int& budget) {
    asm volatile("{\n.reg .pred p;\nLAB_WAIT:\nmbarrier.try_wait.parity.shared::cta.b64 p, [%1], %2;\n"
                 "add.s32 %0, %0, -1;\nsetp.gt.and.s32 p, %0, 0, !p;\n@p bra LAB_WAIT;\n}" : "+r"(budget) : "r"(bar), "r"(parity) : "memory");
}
__device__ __forceinline__ void mbar_wait_hot(uint32_t bar, uint32_t parity, int& budget) {
    asm volatile("{\n.reg .pred p;\nmbarrier.try_wait.parity.shared::cta.b64 p, [%1], %2;\n@p bra LAB_DONE;\nLAB_WAIT:\nmbarrier.try_wait.parity.shared::cta.b64 p, [%1], %2;\n"
                 "add.s32 %0, %0, -1;\nsetp.gt.and.s32 p, %0, 0, !p;\n@p bra LAB_WAIT;\nLAB_DONE:\n}" : "+r"(budget) : "r"(bar), "r"(parity) : "memory");
}
__device__ __forceinline__ void tma_2d_mc(uint32_t dst, const CUtensorMap* m, uint32_t bar, int c0, int c1) {
    asm volatile("cp.async.bulk.tensor.2d.shared::cluster.global.mbarrier::complete_tx::bytes.multicast::cluster [%0], [%1, {%3, %4}], [%2], %5;" ::"r"(dst), "l"(m), "r"(bar), "r"(c0), "r"(c1), "h"((uint16_t)3) : "memory");
}
__device__ __forceinline__ void tma_3d(uint32_t dst, const CUtensorMap* m, uint32_t bar, int c0, int c1, int c2) {
    asm volatile("cp.async.bulk.tensor.3d.shared::cluster.global.mbarrier::complete_tx::bytes [%0], [%1, {%3, %4, %5}], [%2];" ::"r"(dst), "l"(m), "r"(bar), "r"(c0), "r"(c1), "r"(c2) : "memory");
}
__device__ __forceinline__ void tma_4d(uint32_t dst, const CUtensorMap* m, uint32_t bar, int c0, int c1, int c2, int c3) {
    asm volatile("cp.async.bulk.tensor.4d.shared::cluster.global.mbarrier::complete_tx::bytes [%0], [%1, {%3, %4, %5, %6}], [%2];" ::"r"(dst), "l"(m), "r"(bar), "r"(c0), "r"(c1), "r"(c2), "r"(c3) : "memory");
}
__device__ __forceinline__ void tma_4d_mc(uint32_t dst, const CUtensorMap* m, uint32_t bar, int c0, int c1, int c2, int c3) {
    asm volatile("cp.async.bulk.tensor.4d.shared::cluster.global.mbarrier::complete_tx::bytes.multicast::cluster [%0], [%1, {%3, %4, %5, %6}], [%2], %7;" ::"r"(dst), "l"(m), "r"(bar), "r"(c0), "r"(c1), "r"(c2), "r"(c3), "h"((uint16_t)3) : "memory");
}
__device__ __forceinline__ void bulk_pf(const void* p, uint32_t bytes) { asm volatile("cp.async.bulk.prefetch.L2.global [%0], %1;" ::"l"(p), "r"(bytes) : "memory"); }
__device__ __forceinline__ void bulk_g2s(uint32_t dst, const void* src, uint32_t bytes, uint32_t bar) {
    asm volatile("cp.async.bulk.shared::cluster.global.mbarrier::complete_tx::bytes [%0], [%1], %2, [%3];" ::"r"(dst), "l"(src), "r"(bytes), "r"(bar) : "memory");
}
__device__ __forceinline__ void bulk_s2c(uint32_t cdst, uint32_t src, uint32_t bytes, uint32_t cbar) {
    asm volatile("cp.async.bulk.shared::cluster.shared::cta.mbarrier::complete_tx::bytes [%0], [%1], %2, [%3];" ::"r"(cdst), "r"(src), "r"(bytes), "r"(cbar) : "memory");
}
__device__ __forceinline__ void cluster_wait() { asm volatile("barrier.cluster.wait.aligned;" ::: "memory"); }
__device__ __forceinline__ void fence_gpu() { asm volatile("fence.acq_rel.gpu;" ::: "memory"); }
__device__ __forceinline__ void fence_async_smem() { asm volatile("fence.proxy.async.shared::cta;" ::: "memory"); }
__device__ __forceinline__ void fence_async_gmem() { asm volatile("fence.proxy.async.global;" ::: "memory"); }
__device__ __forceinline__ void wg_fence() { asm volatile("wgmma.fence.sync.aligned;" ::: "memory"); }
__device__ __forceinline__ void wg_commit() { asm volatile("wgmma.commit_group.sync.aligned;" ::: "memory"); }
template <int N> __device__ __forceinline__ void wg_wait() { asm volatile("wgmma.wait_group.sync.aligned %0;" ::"n"(N) : "memory"); }
__device__ __forceinline__ uint64_t mkdesc(uint32_t lo, uint32_t hi) { return ((uint64_t)hi << 32) | lo; }
__host__ __device__ constexpr uint32_t dhi(uint32_t sbo, uint32_t mode) { return (sbo >> 4) | (mode << 30); }
__host__ __device__ constexpr uint32_t dlo(uint32_t off, uint32_t lbo) { return (off >> 4) + ((lbo >> 4) << 16); }
__device__ __forceinline__ bool elect_one() {
    uint32_t e;
    asm volatile("{\n.reg .pred p;\nelect.sync _|p, 0xffffffff;\nselp.u32 %0, 1, 0, p;\n}" : "=r"(e));
    return e;
}
template <int R> __device__ __forceinline__ void reg_inc() { asm volatile("setmaxnreg.inc.sync.aligned.u32 %0;" ::"n"(R)); }
template <int R> __device__ __forceinline__ void reg_dec() { asm volatile("setmaxnreg.dec.sync.aligned.u32 %0;" ::"n"(R)); }
__device__ __forceinline__ void bar_sync(int id, int n) { asm volatile("bar.sync %0, %1;" ::"r"(id), "r"(n) : "memory"); }
__device__ __forceinline__ void bar_arrive(int id, int n) { asm volatile("bar.arrive %0, %1;" ::"r"(id), "r"(n) : "memory"); }
__device__ __forceinline__ uint32_t pack_bf16(float lo, float hi) { uint32_t r; asm("cvt.rn.bf16x2.f32 %0, %1, %2;" : "=r"(r) : "f"(hi), "f"(lo)); return r; }
__device__ __forceinline__ uint32_t pack_here(float lo, float hi) { uint32_t r; asm volatile("cvt.rn.bf16x2.f32 %0, %1, %2;" : "=r"(r) : "f"(hi), "f"(lo)); return r; }
__device__ __forceinline__ float bf_lo(uint32_t u) { return __uint_as_float(u << 16); }
__device__ __forceinline__ float bf_hi(uint32_t u) { return __uint_as_float(u & 0xffff0000u); }
__device__ __forceinline__ float bf16r(float v) { return bf_lo(pack_bf16(v, 0.f)); }
__device__ __forceinline__ float rcp(float x) { float r; asm("rcp.approx.ftz.f32 %0, %1;" : "=f"(r) : "f"(x)); return r; }
__device__ __forceinline__ float ex2(float x) { float r; asm("ex2.approx.ftz.f32 %0, %1;" : "=f"(r) : "f"(x)); return r; }
__device__ __forceinline__ float sigmoidf(float v) { return rcp(1.f + ex2(v * -1.4426950408889634f)); }
__device__ __forceinline__ uint32_t movm(uint32_t a) { uint32_t d; asm volatile("movmatrix.sync.aligned.m8n8.trans.b16 %0, %1;" : "=r"(d) : "r"(a)); return d; }
__device__ __forceinline__ void mma16816(float (&c)[4], uint32_t a0, uint32_t a1, uint32_t a2, uint32_t a3, uint32_t b0, uint32_t b1) {
    asm volatile("mma.sync.aligned.m16n8k16.row.col.f32.bf16.bf16.f32 {%0,%1,%2,%3}, {%4,%5,%6,%7}, {%8,%9}, {%0,%1,%2,%3};"
                 : "+f"(c[0]), "+f"(c[1]), "+f"(c[2]), "+f"(c[3]) : "r"(a0), "r"(a1), "r"(a2), "r"(a3), "r"(b0), "r"(b1));
}
__device__ __forceinline__ void mma1688(float (&c)[4], uint32_t a0, uint32_t a1, uint32_t b0) {
    asm volatile("mma.sync.aligned.m16n8k8.row.col.f32.bf16.bf16.f32 {%0,%1,%2,%3}, {%4,%5}, {%6}, {%0,%1,%2,%3};"
                 : "+f"(c[0]), "+f"(c[1]), "+f"(c[2]), "+f"(c[3]) : "r"(a0), "r"(a1), "r"(b0));
}
__device__ __forceinline__ void stsm4(uint32_t a, uint32_t r0, uint32_t r1, uint32_t r2, uint32_t r3) {
    asm volatile("stmatrix.sync.aligned.m8n8.x4.shared.b16 [%0], {%1,%2,%3,%4};" ::"r"(a), "r"(r0), "r"(r1), "r"(r2), "r"(r3) : "memory");
}
__device__ __forceinline__ void ldsm4(uint32_t* r, uint32_t a) {
    asm volatile("ldmatrix.sync.aligned.m8n8.x4.shared.b16 {%0,%1,%2,%3}, [%4];" : "=r"(r[0]), "=r"(r[1]), "=r"(r[2]), "=r"(r[3]) : "r"(a) : "memory");
}
__device__ __forceinline__ void ldsm4t(uint32_t* r, uint32_t a) {
    asm volatile("ldmatrix.sync.aligned.m8n8.x4.trans.shared.b16 {%0,%1,%2,%3}, [%4];" : "=r"(r[0]), "=r"(r[1]), "=r"(r[2]), "=r"(r[3]) : "r"(a) : "memory");
}
__device__ __forceinline__ uint32_t ld_rlx(const void* p) { uint32_t v; asm volatile("ld.relaxed.gpu.global.u32 %0, [%1];" : "=r"(v) : "l"(p) : "memory"); return v; }
__device__ __forceinline__ uint32_t ld_acq(const void* p) { uint32_t v; asm volatile("ld.acquire.gpu.global.u32 %0, [%1];" : "=r"(v) : "l"(p) : "memory"); return v; }
__device__ __forceinline__ uint2 ld_rlx2(const void* p) { uint2 v; asm volatile("ld.relaxed.gpu.global.v2.u32 {%0,%1}, [%2];" : "=r"(v.x), "=r"(v.y) : "l"(p) : "memory"); return v; }
__device__ __forceinline__ uint4 ld_rlx4(const void* p) { uint4 v; asm volatile("ld.relaxed.gpu.global.v4.u32 {%0,%1,%2,%3}, [%4];" : "=r"(v.x), "=r"(v.y), "=r"(v.z), "=r"(v.w) : "l"(p) : "memory"); return v; }
__device__ __forceinline__ void st_rlx(void* p, uint32_t v) { asm volatile("st.relaxed.gpu.global.u32 [%0], %1;" ::"l"(p), "r"(v) : "memory"); }
__device__ __forceinline__ void st_rlx2(void* p, uint32_t a, uint32_t b) { asm volatile("st.relaxed.gpu.global.v2.u32 [%0], {%1,%2};" ::"l"(p), "r"(a), "r"(b) : "memory"); }
__device__ __forceinline__ void st_rlx4(void* p, uint32_t a, uint32_t b, uint32_t c, uint32_t d) { asm volatile("st.relaxed.gpu.global.v4.u32 [%0], {%1,%2,%3,%4};" ::"l"(p), "r"(a), "r"(b), "r"(c), "r"(d) : "memory"); }
__device__ __forceinline__ void red_add(uint32_t* p) { asm volatile("red.relaxed.gpu.global.add.u32 [%0], 1;" ::"l"(p) : "memory"); }
__device__ __forceinline__ uint4 ldg_nc(const void* p) { uint4 v; asm volatile("ld.global.nc.v4.u32 {%0,%1,%2,%3}, [%4];" : "=r"(v.x), "=r"(v.y), "=r"(v.z), "=r"(v.w) : "l"(p)); return v; }
__device__ __forceinline__ void sts4(uint32_t a, uint32_t x, uint32_t y, uint32_t z, uint32_t w) { asm volatile("st.shared.v4.u32 [%0], {%1,%2,%3,%4};" ::"r"(a), "r"(x), "r"(y), "r"(z), "r"(w) : "memory"); }
__device__ __forceinline__ void sts2(uint32_t a, uint32_t x, uint32_t y) { asm volatile("st.shared.v2.u32 [%0], {%1,%2};" ::"r"(a), "r"(x), "r"(y) : "memory"); }
__device__ __forceinline__ void sts1(uint32_t a, uint32_t v) { asm volatile("st.shared.u32 [%0], %1;" ::"r"(a), "r"(v) : "memory"); }
__device__ __forceinline__ uint4 lds4(uint32_t a) { uint4 v; asm volatile("ld.shared.v4.u32 {%0,%1,%2,%3}, [%4];" : "=r"(v.x), "=r"(v.y), "=r"(v.z), "=r"(v.w) : "r"(a) : "memory"); return v; }
__device__ __forceinline__ float4 lds4f(uint32_t a) { float4 v; asm volatile("ld.shared.v4.f32 {%0,%1,%2,%3}, [%4];" : "=f"(v.x), "=f"(v.y), "=f"(v.z), "=f"(v.w) : "r"(a) : "memory"); return v; }
__device__ __forceinline__ float2 lds2f(uint32_t a) { float2 v; asm volatile("ld.shared.v2.f32 {%0,%1}, [%2];" : "=f"(v.x), "=f"(v.y) : "r"(a) : "memory"); return v; }
__device__ __forceinline__ float lds1f(uint32_t a) { float v; asm volatile("ld.shared.f32 %0, [%1];" : "=f"(v) : "r"(a) : "memory"); return v; }
__device__ __forceinline__ uint32_t lds1(uint32_t a) { uint32_t v; asm volatile("ld.shared.u32 %0, [%1];" : "=r"(v) : "r"(a) : "memory"); return v; }
__device__ __forceinline__ uint32_t redux_max(uint32_t v) { uint32_t r; asm volatile("redux.sync.max.u32 %0, %1, 0xffffffff;" : "=r"(r) : "r"(v)); return r; }
__device__ __forceinline__ uint32_t poll_all(const uint32_t* p, uint32_t mask, uint32_t want, int& budget) {
    uint32_t v;
#pragma unroll 1
    while (v = ld_acq(p), !__all_sync(0xffffffffu, (v & mask) == want) && --budget > 0) __nanosleep(POLL_NS);
    return v;
}

template <int TA, int TB>
__device__ __forceinline__ void wgmma_n192(float (&d)[96], uint64_t da, uint64_t db, int keep) {
    asm volatile("{\n.reg .pred p;\nsetp.ne.b32 p, %98, 0;\n"
        "wgmma.mma_async.sync.aligned.m64n192k16.f32.bf16.bf16 "
        "{%0, %1, %2, %3, %4, %5, %6, %7, %8, %9, %10, %11, %12, %13, %14, %15, "
        "%16, %17, %18, %19, %20, %21, %22, %23, %24, %25, %26, %27, %28, %29, %30, %31, "
        "%32, %33, %34, %35, %36, %37, %38, %39, %40, %41, %42, %43, %44, %45, %46, %47, "
        "%48, %49, %50, %51, %52, %53, %54, %55, %56, %57, %58, %59, %60, %61, %62, %63, "
        "%64, %65, %66, %67, %68, %69, %70, %71, %72, %73, %74, %75, %76, %77, %78, %79, "
        "%80, %81, %82, %83, %84, %85, %86, %87, %88, %89, %90, %91, %92, %93, %94, %95}, "
        "%96, %97, p, 1, 1, %99, %100;\n}\n"
        : "+f"(d[0]), "+f"(d[1]), "+f"(d[2]), "+f"(d[3]), "+f"(d[4]), "+f"(d[5]), "+f"(d[6]), "+f"(d[7]),
          "+f"(d[8]), "+f"(d[9]), "+f"(d[10]), "+f"(d[11]), "+f"(d[12]), "+f"(d[13]), "+f"(d[14]), "+f"(d[15]),
          "+f"(d[16]), "+f"(d[17]), "+f"(d[18]), "+f"(d[19]), "+f"(d[20]), "+f"(d[21]), "+f"(d[22]), "+f"(d[23]),
          "+f"(d[24]), "+f"(d[25]), "+f"(d[26]), "+f"(d[27]), "+f"(d[28]), "+f"(d[29]), "+f"(d[30]), "+f"(d[31]),
          "+f"(d[32]), "+f"(d[33]), "+f"(d[34]), "+f"(d[35]), "+f"(d[36]), "+f"(d[37]), "+f"(d[38]), "+f"(d[39]),
          "+f"(d[40]), "+f"(d[41]), "+f"(d[42]), "+f"(d[43]), "+f"(d[44]), "+f"(d[45]), "+f"(d[46]), "+f"(d[47]),
          "+f"(d[48]), "+f"(d[49]), "+f"(d[50]), "+f"(d[51]), "+f"(d[52]), "+f"(d[53]), "+f"(d[54]), "+f"(d[55]),
          "+f"(d[56]), "+f"(d[57]), "+f"(d[58]), "+f"(d[59]), "+f"(d[60]), "+f"(d[61]), "+f"(d[62]), "+f"(d[63]),
          "+f"(d[64]), "+f"(d[65]), "+f"(d[66]), "+f"(d[67]), "+f"(d[68]), "+f"(d[69]), "+f"(d[70]), "+f"(d[71]),
          "+f"(d[72]), "+f"(d[73]), "+f"(d[74]), "+f"(d[75]), "+f"(d[76]), "+f"(d[77]), "+f"(d[78]), "+f"(d[79]),
          "+f"(d[80]), "+f"(d[81]), "+f"(d[82]), "+f"(d[83]), "+f"(d[84]), "+f"(d[85]), "+f"(d[86]), "+f"(d[87]),
          "+f"(d[88]), "+f"(d[89]), "+f"(d[90]), "+f"(d[91]), "+f"(d[92]), "+f"(d[93]), "+f"(d[94]), "+f"(d[95])
        : "l"(da), "l"(db), "r"(keep), "n"(TA), "n"(TB));
}
template <int TA, int TB>
__device__ __forceinline__ void wgmma_n128(float (&d)[64], uint64_t da, uint64_t db, int keep) {
    asm volatile("{\n.reg .pred p;\nsetp.ne.b32 p, %66, 0;\n"
        "wgmma.mma_async.sync.aligned.m64n128k16.f32.bf16.bf16 "
        "{%0, %1, %2, %3, %4, %5, %6, %7, %8, %9, %10, %11, %12, %13, %14, %15, "
        "%16, %17, %18, %19, %20, %21, %22, %23, %24, %25, %26, %27, %28, %29, %30, %31, "
        "%32, %33, %34, %35, %36, %37, %38, %39, %40, %41, %42, %43, %44, %45, %46, %47, "
        "%48, %49, %50, %51, %52, %53, %54, %55, %56, %57, %58, %59, %60, %61, %62, %63}, "
        "%64, %65, p, 1, 1, %67, %68;\n}\n"
        : "+f"(d[0]), "+f"(d[1]), "+f"(d[2]), "+f"(d[3]), "+f"(d[4]), "+f"(d[5]), "+f"(d[6]), "+f"(d[7]),
          "+f"(d[8]), "+f"(d[9]), "+f"(d[10]), "+f"(d[11]), "+f"(d[12]), "+f"(d[13]), "+f"(d[14]), "+f"(d[15]),
          "+f"(d[16]), "+f"(d[17]), "+f"(d[18]), "+f"(d[19]), "+f"(d[20]), "+f"(d[21]), "+f"(d[22]), "+f"(d[23]),
          "+f"(d[24]), "+f"(d[25]), "+f"(d[26]), "+f"(d[27]), "+f"(d[28]), "+f"(d[29]), "+f"(d[30]), "+f"(d[31]),
          "+f"(d[32]), "+f"(d[33]), "+f"(d[34]), "+f"(d[35]), "+f"(d[36]), "+f"(d[37]), "+f"(d[38]), "+f"(d[39]),
          "+f"(d[40]), "+f"(d[41]), "+f"(d[42]), "+f"(d[43]), "+f"(d[44]), "+f"(d[45]), "+f"(d[46]), "+f"(d[47]),
          "+f"(d[48]), "+f"(d[49]), "+f"(d[50]), "+f"(d[51]), "+f"(d[52]), "+f"(d[53]), "+f"(d[54]), "+f"(d[55]),
          "+f"(d[56]), "+f"(d[57]), "+f"(d[58]), "+f"(d[59]), "+f"(d[60]), "+f"(d[61]), "+f"(d[62]), "+f"(d[63])
        : "l"(da), "l"(db), "r"(keep), "n"(TA), "n"(TB));
}
template <int TA, int TB>
__device__ __forceinline__ void wgmma_n8(float (&d)[4], uint64_t da, uint64_t db, int keep) {
    asm volatile("{\n.reg .pred p;\nsetp.ne.b32 p, %6, 0;\n"
        "wgmma.mma_async.sync.aligned.m64n8k16.f32.bf16.bf16 "
        "{%0, %1, %2, %3}, "
        "%4, %5, p, 1, 1, %7, %8;\n}\n"
        : "+f"(d[0]), "+f"(d[1]), "+f"(d[2]), "+f"(d[3])
        : "l"(da), "l"(db), "r"(keep), "n"(TA), "n"(TB));
}
__device__ __forceinline__ void wgmma_rs_n128(float (&d)[64], uint32_t a0, uint32_t a1, uint32_t a2, uint32_t a3, uint64_t db) {
    asm volatile("{\n.reg .pred p;\nsetp.ne.b32 p, 1, 0;\n"
        "wgmma.mma_async.sync.aligned.m64n128k16.f32.bf16.bf16 "
        "{%0, %1, %2, %3, %4, %5, %6, %7, %8, %9, %10, %11, %12, %13, %14, %15, "
        "%16, %17, %18, %19, %20, %21, %22, %23, %24, %25, %26, %27, %28, %29, %30, %31, "
        "%32, %33, %34, %35, %36, %37, %38, %39, %40, %41, %42, %43, %44, %45, %46, %47, "
        "%48, %49, %50, %51, %52, %53, %54, %55, %56, %57, %58, %59, %60, %61, %62, %63}, "
        "{%64, %65, %66, %67}, %68, p, 1, 1, 1;\n}\n"
        : "+f"(d[0]), "+f"(d[1]), "+f"(d[2]), "+f"(d[3]), "+f"(d[4]), "+f"(d[5]), "+f"(d[6]), "+f"(d[7]),
          "+f"(d[8]), "+f"(d[9]), "+f"(d[10]), "+f"(d[11]), "+f"(d[12]), "+f"(d[13]), "+f"(d[14]), "+f"(d[15]),
          "+f"(d[16]), "+f"(d[17]), "+f"(d[18]), "+f"(d[19]), "+f"(d[20]), "+f"(d[21]), "+f"(d[22]), "+f"(d[23]),
          "+f"(d[24]), "+f"(d[25]), "+f"(d[26]), "+f"(d[27]), "+f"(d[28]), "+f"(d[29]), "+f"(d[30]), "+f"(d[31]),
          "+f"(d[32]), "+f"(d[33]), "+f"(d[34]), "+f"(d[35]), "+f"(d[36]), "+f"(d[37]), "+f"(d[38]), "+f"(d[39]),
          "+f"(d[40]), "+f"(d[41]), "+f"(d[42]), "+f"(d[43]), "+f"(d[44]), "+f"(d[45]), "+f"(d[46]), "+f"(d[47]),
          "+f"(d[48]), "+f"(d[49]), "+f"(d[50]), "+f"(d[51]), "+f"(d[52]), "+f"(d[53]), "+f"(d[54]), "+f"(d[55]),
          "+f"(d[56]), "+f"(d[57]), "+f"(d[58]), "+f"(d[59]), "+f"(d[60]), "+f"(d[61]), "+f"(d[62]), "+f"(d[63])
        : "r"(a0), "r"(a1), "r"(a2), "r"(a3), "l"(db));
}
__device__ __forceinline__ void wgmma_rs_n192(float (&d)[96], uint32_t a0, uint32_t a1, uint32_t a2, uint32_t a3, uint64_t db) {
    asm volatile("{\n.reg .pred p;\nsetp.ne.b32 p, 1, 0;\n"
        "wgmma.mma_async.sync.aligned.m64n192k16.f32.bf16.bf16 "
        "{%0, %1, %2, %3, %4, %5, %6, %7, %8, %9, %10, %11, %12, %13, %14, %15, "
        "%16, %17, %18, %19, %20, %21, %22, %23, %24, %25, %26, %27, %28, %29, %30, %31, "
        "%32, %33, %34, %35, %36, %37, %38, %39, %40, %41, %42, %43, %44, %45, %46, %47, "
        "%48, %49, %50, %51, %52, %53, %54, %55, %56, %57, %58, %59, %60, %61, %62, %63, "
        "%64, %65, %66, %67, %68, %69, %70, %71, %72, %73, %74, %75, %76, %77, %78, %79, "
        "%80, %81, %82, %83, %84, %85, %86, %87, %88, %89, %90, %91, %92, %93, %94, %95}, "
        "{%96, %97, %98, %99}, %100, p, 1, 1, 1;\n}\n"
        : "+f"(d[0]), "+f"(d[1]), "+f"(d[2]), "+f"(d[3]), "+f"(d[4]), "+f"(d[5]), "+f"(d[6]), "+f"(d[7]),
          "+f"(d[8]), "+f"(d[9]), "+f"(d[10]), "+f"(d[11]), "+f"(d[12]), "+f"(d[13]), "+f"(d[14]), "+f"(d[15]),
          "+f"(d[16]), "+f"(d[17]), "+f"(d[18]), "+f"(d[19]), "+f"(d[20]), "+f"(d[21]), "+f"(d[22]), "+f"(d[23]),
          "+f"(d[24]), "+f"(d[25]), "+f"(d[26]), "+f"(d[27]), "+f"(d[28]), "+f"(d[29]), "+f"(d[30]), "+f"(d[31]),
          "+f"(d[32]), "+f"(d[33]), "+f"(d[34]), "+f"(d[35]), "+f"(d[36]), "+f"(d[37]), "+f"(d[38]), "+f"(d[39]),
          "+f"(d[40]), "+f"(d[41]), "+f"(d[42]), "+f"(d[43]), "+f"(d[44]), "+f"(d[45]), "+f"(d[46]), "+f"(d[47]),
          "+f"(d[48]), "+f"(d[49]), "+f"(d[50]), "+f"(d[51]), "+f"(d[52]), "+f"(d[53]), "+f"(d[54]), "+f"(d[55]),
          "+f"(d[56]), "+f"(d[57]), "+f"(d[58]), "+f"(d[59]), "+f"(d[60]), "+f"(d[61]), "+f"(d[62]), "+f"(d[63]),
          "+f"(d[64]), "+f"(d[65]), "+f"(d[66]), "+f"(d[67]), "+f"(d[68]), "+f"(d[69]), "+f"(d[70]), "+f"(d[71]),
          "+f"(d[72]), "+f"(d[73]), "+f"(d[74]), "+f"(d[75]), "+f"(d[76]), "+f"(d[77]), "+f"(d[78]), "+f"(d[79]),
          "+f"(d[80]), "+f"(d[81]), "+f"(d[82]), "+f"(d[83]), "+f"(d[84]), "+f"(d[85]), "+f"(d[86]), "+f"(d[87]),
          "+f"(d[88]), "+f"(d[89]), "+f"(d[90]), "+f"(d[91]), "+f"(d[92]), "+f"(d[93]), "+f"(d[94]), "+f"(d[95])
        : "r"(a0), "r"(a1), "r"(a2), "r"(a3), "l"(db));
}

template <int HS>
__device__ __forceinline__ void attn_pair(const uint32_t* q, const uint32_t* k, const uint32_t* v, const uint32_t* kh, const uint32_t* vh,
                                          const float* fu, const float* fn, const float* rk, float bias0, float bias1, uint32_t mU, uint32_t zero, const float* ci, uint32_t* o) {
    float s0[2][4] = {}, s1[2][4] = {}, s2[2][4] = {};
#pragma unroll
    for (int n = 0; n < 4; n++) {
        const int hd = n & 1, a = 8 * hd + 2 * (n & 2);
        mma16816(s1[hd], q[a], q[a + 1], q[a + 2], q[a + 3], k[a], k[a + 2]);
        mma16816(s2[hd], q[a], q[a + 1], q[a + 2], q[a + 3], k[a + 1], k[a + 3]);
    }
#pragma unroll
    for (int n = 0; n < 4; n++) {
        const int hd = n & 1, a = 8 * hd + 2 * (n & 2);
        mma16816(s0[hd], q[a], q[a + 1], q[a + 2], q[a + 3], kh[HS * (a / 2)], kh[HS * (a / 2 + 1)]);
    }
    float e[2][4], m[2][2];
#pragma unroll
    for (int hd = 0; hd < 2; hd++) {
        e[hd][2] = fmaf(s1[hd][2], fu[2], s2[hd][2] * fn[2]); e[hd][3] = fmaf(s1[hd][3], fu[3], s2[hd][3] * fn[3]);
        e[hd][0] = fmaf(s0[hd][0], fu[0], fmaf(s1[hd][0], fn[0], bias0)); e[hd][1] = fmaf(s0[hd][1], fu[1], fmaf(s1[hd][1], fn[1], bias1));
        m[hd][1] = fmaxf(e[hd][2], e[hd][3]); m[hd][0] = fmaxf(e[hd][0], e[hd][1]);
    }
#pragma unroll
    for (int x = 1; x < 3; x++)
#pragma unroll
        for (int n = 0; n < 4; n++) m[n & 1][1 - (n >> 1)] = fmaxf(m[n & 1][1 - (n >> 1)], __shfl_xor_sync(0xffffffffu, m[n & 1][1 - (n >> 1)], x));
#pragma unroll
    for (int hd = 0; hd < 2; hd++) {
#pragma unroll
        for (int n = 0; n < 4; n++) e[hd][n] = ex2(e[hd][n] - m[hd][n >> 1]);
        float sum[4] = {};
        mma1688(sum, pack_bf16(e[hd][0], e[hd][1]), pack_bf16(e[hd][2], e[hd][3]), 0x3f803f80u);
        const float i0 = rcp(sum[0]), i1 = rcp(sum[2]);
        const uint32_t plo = pack_bf16(e[hd][0] * rk[0] * i0, e[hd][1] * rk[1] * i0), phi = pack_bf16(e[hd][2] * rk[2] * i1, e[hd][3] * rk[3] * i1);
        const uint32_t z0 = plo & zero, z1 = phi & zero;
        const uint32_t a0 = plo & ~mU, a1 = phi & mU, a3 = phi & ~mU, b0 = plo & mU;
#pragma unroll
        for (int jj = 0; jj < 4; jj++) {
            float c[4];
            asm volatile("mma.sync.aligned.m16n8k16.row.col.f32.bf16.bf16.f32 {%0,%1,%2,%3}, {%4,%5,%6,%7}, {%8,%9}, {%10,%11,%12,%13};"
                         : "=f"(c[0]), "=f"(c[1]), "=f"(c[2]), "=f"(c[3])
                         : "r"(a0), "r"(a1), "r"(z0), "r"(a3), "r"(v[8 * hd + 2 * jj]), "r"(v[8 * hd + 2 * jj + 1]), "f"(ci[0]), "f"(ci[1]), "f"(ci[2]), "f"(ci[3]));
            mma1688(c, b0, z1, vh[HS * (4 * hd + jj)]);
            o[8 * hd + 2 * jj] = pack_bf16(c[0], c[1]); o[8 * hd + 2 * jj + 1] = pack_bf16(c[2], c[3]);
        }
    }
}

__device__ __forceinline__ uint32_t norm_pair(uint32_t u, float m, float rinv) {
    const uint32_t d = pack_bf16(bf_lo(u) - m, bf_hi(u) - m);
    return max(pack_bf16(bf_lo(d) * rinv, bf_hi(d) * rinv), 1u);
}

__global__ void __launch_bounds__(512, 1)
fused_kernel(const __grid_constant__ CUtensorMap mx, const __grid_constant__ CUtensorMap mw, const __grid_constant__ CUtensorMap mwo,
             const __grid_constant__ CUtensorMap mout, const __grid_constant__ CUtensorMap mgu, const __grid_constant__ CUtensorMap mwd,
             const __grid_constant__ CUtensorMap mo,
             const __nv_bfloat16* __restrict__ x, const __nv_bfloat16* __restrict__ wr, Scratch* __restrict__ scr, int swap_gu, const Weights pf) {
    extern __shared__ __align__(1024) uint8_t smem[];
    const uint32_t sb = smem_u32(smem);
    const uint32_t bars = sb + OFF_BAR;
    const int tid = threadIdx.x, lane = tid & 31, warp = __shfl_sync(0xffffffffu, tid >> 5, 0);
    const uint32_t sd = (sb & 0x3FFFF) >> 4;
    const int hp = blockIdx.x & 1, cl = blockIdx.x >> 1;
    int pr = cl - 4 + (max(cl - 36, 0) * 37 >> 8);
    asm("{\n.reg .pred p;\nsetp.lt.s32 p, %1, 4;\nselp.s32 %0, %2, %0, p;\n}" : "+r"(pr) : "r"(cl), "r"(39 + 8 * cl));
    const int b = pr * 2 + hp, mt = pr >> 3, p = pr & 7, nt = 2 * p + hp, rh = p & 1, cb = (p & 6) + hp;
    const int par = mt >> 2, j0 = (mt & 3) * 256;
    int budget = BUDGET;

    TSC(tid == 0, 0);
    if (b < 128 && tid >= 32 && tid < 112) {
        const char* a = tid < 64 ? (const char*)x + (size_t)(16 * b + ((tid >> 1) & 15)) * 2048 + (tid & 1) * 128 : pf.wqkv + (size_t)b * 6144 + (tid - 64) * 128;
        asm volatile("prefetch.global.L2 [%0];" ::"l"(a));
    }
    auto load_w = [&](int k, int s) {
        const uint32_t full = bars + 8 * (B_WFULL + s);
        mbar_expect_tx(full, W_BYTES);
        tma_3d(sb + OFF_W + s * W_BYTES, &mw, full, nt * 64, k * 64, 0);
    };
    auto load_x = [&](int n) {
        const int w = n & 1, j = n < 4 ? (n >> 1) + 4 : (n >> 1) - 2;
        const uint32_t full = bars + 8 * (B_XFULL + w * 6 + 5 - j);
        mbar_expect_tx(full, BOX);
        tma_4d(sb + w * OFF_X1 + j * BOX, &mx, full, par * 1024 + (n >> 2) * 64, 0, (j0 + w * 128) >> 5, (~n >> 1) & 1);
    };
    if (warp < NBAR / 6 && elect_one()) {
        const uint32_t cnt = warp < B_WEMPTY / 6 ? 1 : warp < B_G1DONE / 6 ? 2 : warp < B_STAGED / 6 ? 4 : 8;
#pragma unroll
        for (int i = 0; i < 6; i++) mbar_init(bars + 48 * warp + 8 * i, cnt);
        asm volatile("fence.mbarrier_init.release.cluster;" ::: "memory");
        if (warp == 0 && b < 128) { load_x(0); load_w(0, 2); }
    }
    __syncthreads();

    if (b >= 128) {
        const int hc = b - 128, g = lane >> 2, t = lane & 3;
        if (warp < 12) {
            const int n = warp / 3, part = warp - 3 * n;
            const uint32_t ep = ld_rlx(&scr->epoch[0]) + 1;
            auto load = [&](int k) {
                const uint32_t full = bars + 8 * (2 * n + (k & 1));
                mbar_expect_tx(full, W_BYTES);
                tma_3d(sb + (2 * n + (k & 1)) * W_BYTES, &mw, full, (4 * hc + n) * 64, k * 64, 0);
            };
            if (part == 0 && elect_one()) { load(0); load(1); }
            __syncwarp();
            float c0[4] = {0.f, 0.f, 0.f, 0.f}, c1[4] = {0.f, 0.f, 0.f, 0.f};
            const uint32_t sel = g == 0 ? 0x3f80u : g == 1 ? 0x3f800000u : 0u;
            const uint32_t a = sb + 2 * n * W_BYTES + part * BOX + t * 256 + ((g ^ (2 * t)) << 4);
#pragma unroll 1
            for (int k = 0; k < 16; k++) {
                mbar_wait(bars + 8 * (2 * n + (k & 1)), (k >> 1) & 1, budget);
                uint4 v[8], u[8];
#pragma unroll
                for (int i = 0; i < 8; i++) { v[i] = lds4(a + (k & 1) * W_BYTES + i * 1024); u[i] = lds4(((a + 128) ^ 16) + (k & 1) * W_BYTES + i * 1024); }
#pragma unroll
                for (int i = 0; i < 8; i++) { mma16816(c0, v[i].x, v[i].y, u[i].x, u[i].y, sel, sel); mma16816(c1, v[i].z, v[i].w, u[i].z, u[i].w, sel, sel); }
                bar_sync(1 + n, 96);
                if (part == 0 && k < 14 && elect_one()) load(k + 2);
                __syncwarp();
            }
            if (t == 0) {
#pragma unroll
                for (int r = 0; r < 3; r++) {
                    const uint32_t q0 = pack_bf16(c0[0], c0[1]), q1 = pack_bf16(c0[2], c0[3]), q2 = pack_bf16(c1[0], c1[1]), q3 = pack_bf16(c1[2], c1[3]);
                    st_rlx4(&scr->cs[4 * hc + n][16 + (part * 8 + g) * 32 + r * 4], q0, q1, q2, q3);
                    c0[0] -= bf_lo(q0); c0[1] -= bf_hi(q0); c0[2] -= bf_lo(q1); c0[3] -= bf_hi(q1);
                    c1[0] -= bf_lo(q2); c1[1] -= bf_hi(q2); c1[2] -= bf_lo(q3); c1[3] -= bf_hi(q3);
                }
            }
            bar_sync(7, 384);
            if (tid == 0) { fence_gpu(); st_rlx(&scr->csflag[hc], ep); }
            TSC(tid == 0, 19);
        }
        if (warp < 8) TS_END();
        return;
    }
    asm volatile("barrier.cluster.arrive.relaxed.aligned;" ::: "memory");

    const int kc = b >> 4, c2 = b & 15;
    if (warp >= 12) {
        reg_dec<24>();
        if (warp == 12) {
            if (elect_one()) {
#pragma unroll 1
                for (int n = 1; n < 12; n++) {
                    load_x(n);
                    if (n == ROWS_AT) { mbar_expect_tx(bars + 8 * B_ROW, 4 * BOX); bulk_g2s(sb + OFF_FR, x + (size_t)b * 16 * 1024, 4 * BOX, bars + 8 * B_ROW); }
                    if (n == 3 || n == 7) load_w((n + 1) >> 2, n >> 2);
                }
                int s = 2; uint32_t ph = 0;
#pragma unroll 1
                for (int k = 3; k < 16; k++) {
                    mbar_wait(bars + 8 * (B_WEMPTY + s), ph, budget);
                    load_w(k, s);
                    if (++s == 3) s = 0;
                    if (s == 2) ph ^= 1;
                }
                s = 2;
#pragma unroll 1
                for (int i = 0; i < 16; i++) {
                    mbar_wait(bars + 8 * (i < 2 ? B_WEMPTY + i : i < 4 ? B_G1DONE : i < 6 ? B_F1DONE : B_WOEMPTY + s), i >= 12, budget);
                    if (i == 0) {
                        mbar_expect_tx(bars + 8 * B_XT, 4 * BOX);
#pragma unroll 1
                        for (int n = 0; n < 4; n++)
                            tma_4d(sb + (n >> 1) * OFF_X1 + (n & 1) * BOX, &mx, bars + 8 * B_XT, par * 1024 + cb * 128 + (n & 1) * 64, 0, (j0 + rh * 128) >> 5, 1 - (n >> 1));
                    }
                    const uint32_t full = bars + 8 * (B_WOFULL + s);
                    mbar_expect_tx(full, 2 * BOX);
                    tma_3d(sb + OFF_WO + s * 2 * BOX, &mwo, full, 0, ((2 * p + (i < 2 ? i ^ hp : i)) & 15) * 64, cb * 2);
                    TSC(TIMING % 10 == 4, 48 + i);
                    if (++s == 6) s = 0;
                }
            }
        } else {
            bar_sync(8, 224);
            const uint32_t ep = __shfl_sync(0xffffffffu, lds1(sb + OFF_EP), 0);
            if (warp == 13) {
                cluster_wait();
                if (elect_one()) {
                    int j = 4, q = 0, left = BUDGET; uint32_t ph = 0;
#pragma unroll 1
                    for (int n = 6; n < 32; n++) {
                        mbar_wait(bars + 8 * (B_XEMPTY + j), ph, left);
                        tma_4d_mc(sb + hp * OFF_X1 + j * BOX, &mx, bars + 8 * (B_XFULL + hp * 6 + 5 - j), par * 1024 + (n >> 1) * 64, 0, (j0 + hp * 128) >> 5, ~n & 1);
                        if (++j == 6) j = 0;
                        if (j == 4) ph ^= 1;
#pragma unroll 1
                        for (; q < (PF_RATE * (n - PF_START) >> 3) && q < 18 + PF_NW; q++) {
                            const int u = q - PF_NW;
                            if (u < 0) bulk_pf(pf.wqkv + (size_t)(1024 + 128 * u + b) * 6144, 6144);
                            else if (u < 16) bulk_pf((b < 64 ? pf.wg : pf.wu) + (size_t)(u * 64 + (b & 63)) * 7168, 7168);
                            else bulk_pf(pf.wo + (size_t)((u - 16) * 128 + b) * 8192, 8192);
                        }
                    }
                }
                __syncwarp();
                uint32_t* hs = &scr->halo[b - 16][lane * 4];
                int tries = BUDGET;
#pragma unroll 1
                for (int c = 0; c < 4; c += 2) {
                    uint4 v0 = make_uint4(0, 0, 0, 0), v1 = v0;
                    if (j0) {
#pragma unroll 1
                        do { v0 = ld_rlx4(hs + c * 128); v1 = ld_rlx4(hs + c * 128 + 128); } while ((v0.x == 0 || v1.x == 0) && --tries > 0);
                        st_rlx(hs + c * 128, 0); st_rlx(hs + c * 128 + 128, 0);
                    }
                    __syncwarp();
                    stsm4(sb + OFF_HIN + c * 512 + lane * 16, v0.x, v0.y, v0.z, v0.w);
                    stsm4(sb + OFF_HIN + c * 512 + 512 + lane * 16, v1.x, v1.y, v1.z, v1.w);
                }
                bar_arrive(11, 64);
                TSC(lane == 0, 31);
                const int src = ((mt * 2 + rh) * 2 + 1 - hp) * 1024;
                if (elect_one()) {
                    const uint32_t* fl = &scr->oflag[mt * 2 + 1 - hp][0];
                    const uint32_t inv = (ep & 1) - 1;
                    uint32_t ready = 0, ph = 0;
                    int s = 4;
#pragma unroll 1
                    for (int i = 2; i < 16; i++) {
                        const int kb = (2 * p + i) & 15;
#pragma unroll 1
                        while (!((ready >> kb) & 1) && --budget > 0) ready = ld_rlx(fl) ^ inv;
                        TSC(i == 2, 30);
                        mbar_wait(bars + 8 * (B_OEMPTY + s), ph, budget);
                        tma_2d_mc(sb + hp * OFF_X1 + s * BOX, &mo, bars + 8 * (B_OFULL + hp * 6 + s), 0, src + kb * 64);
                        TSC(TIMING % 10 == 4 && hp == 0, 32 + i);
                        if (++s == 6) s = 0;
                        if (s == 4) ph ^= 1;
                    }
                }
            } else if (warp == 14) {
                if (elect_one()) {
                    uint32_t s8 = 0, ph = 0;
                    int tries = BUDGET;
                    const uint32_t* act = scr->act[ep & 1];
                    auto counted = [&](int c, uint32_t n) {
#pragma unroll 1
                        while (ld_rlx(&scr->cnt[c][0]) != ep * n && --tries > 0) __nanosleep(POLL_NS);
                    };
                    auto weights = [&](const CUtensorMap* m, int c0, int c1, int c2_) {
                        mbar_wait(bars + 8 * B_FEMPTY + s8, ph, budget);
                        mbar_expect_tx(bars + 8 * B_FFULL + s8, F_BYTES);
                        tma_3d(sb + OFF_FS + s8 * (F_BYTES / 8), m, bars + 8 * B_FFULL + s8, c0, c1, c2_);
                    };
                    if (b < 112) {
                        counted(8, 32);
                        TS(26);
#pragma unroll 1
                        for (int q = 0; q < 16; q++) {
                            weights(&mgu, b * 32, q * 64, 0);
                            bulk_g2s(sb + OFF_FS + BOX + s8 * (F_BYTES / 8), act + 14336 + q * 256, 1024, bars + 8 * B_FFULL + s8);
                            if (q >= 8) bulk_pf(pf.wd + (size_t)((q - 8) * 112 + b) * 8192, 8192);
                            s8 += 8;
                            if (s8 == 40) { s8 = 0; ph ^= 1; }
                        }
                    }
#pragma unroll 1
                    for (int q = -3; q < 7; q++) {
                        if (q == 0) { counted(kc, 28); TS(29); }
                        if ((unsigned)q >= 3) weights(&mwd, 0, kc * 448 + (q < 0 ? q + 3 : q) * 64, c2);
                        if (q >= 0) bulk_g2s(sb + OFF_FS + BOX + s8 * (F_BYTES / 8), act + (kc * 7 + q) * 256, 1024, bars + 8 * B_FFULL + s8);
                        s8 += 8;
                        if (s8 == 24) { s8 = 0; if ((unsigned)q >= 3) ph ^= 1; }
                    }
                }
            } else {
                mbar_wait(bars + 8 * B_ROW, 0, budget);
                uint8_t* oz = scr->o + ((size_t)mt * 64 + nt) * BOX + lane * 16;
#pragma unroll 1
                for (int i = 0; i < ZF_N; i++) { st_rlx4(oz + (i >> 4) * 16 * BOX + (i & 15) * 512, 0, 0, 0, 0); if ((i & 3) == 3) __nanosleep(ZF_NS); }
                __syncwarp();
                fence_gpu();
                mbar_wait(bars + 8 * B_RDONE, 0, budget);
                int tries = BUDGET;
#pragma unroll 1
                for (int i = lane; i < 88; i += 32) {
                    const uint2* rp = &scr->row[2 * (j0 - 8 + i) + par];
                    uint2 v0, v1, v2;
#pragma unroll 1
                    do { v0 = ld_rlx2(rp + (j0 + i < 8 ? 16 : 0)); v1 = ld_rlx2(rp + 176); v2 = ld_rlx2(rp + 352); } while ((((v0.y ^ ep) | (v1.y ^ ep) | (v2.y ^ ep)) & 31) && --tries > 0);
                    sts2(sb + OFF_STAT + i * 8, (v0.x << 16) ^ 0x80000000u, __float_as_uint(rcp(bf_hi(v0.x))));
                    sts2(sb + OFF_STAT + i * 8 + 704, (v1.x << 16) ^ 0x80000000u, __float_as_uint(rcp(bf_hi(v1.x))));
                    sts2(sb + OFF_STAT + i * 8 + 1408, (v2.x << 16) ^ 0x80000000u, __float_as_uint(rcp(bf_hi(v2.x))));
                }
                __syncwarp();
                poll_all(&scr->csflag[lane & 3], ~0u, ep, budget);
                if (elect_one()) {
                    fence_async_gmem();
                    mbar_expect_tx(bars + 8 * B_AUX, CS_BYTES);
                    bulk_g2s(sb + OFF_CS, scr->cs[nt], CS_BYTES, bars + 8 * B_AUX);
                    TS(21);
                    mbar_expect_tx(bars + 8 * (B_OFULL + 3), DS_BYTES); mbar_expect_tx(bars + 8 * (B_OFULL + 9), DS_BYTES);
#pragma unroll 1
                    for (int v = 0; v < 2; v++) {
                        const uint32_t ring = sb + v * OFF_X1 + 2 * BOX, fb = bars + 8 * (B_OFULL + v * 6 + 2);
                        mbar_wait(bars + 8 * (B_STAGED + v), 0, budget);
                        asm volatile("red.relaxed.gpu.global.xor.b32 [%0], %1;" ::"l"(&scr->oflag[mt * 2 + 1 - v][0]), "r"(1u << nt) : "memory");
                        TS(13 + 2 * v);
                        mbar_arrive(fb);
                        mbar_wait(bars + 8 * B_G1DONE, 0, budget);
                        bulk_s2c(mapa(ring + BOX, hp ^ 1), ring, DS_BYTES, mapa(fb + 8, hp ^ 1));
                        if (v == 0) mbar_wait(bars + 8 * B_FREED, 0, budget);
#pragma unroll
                        for (int n = 0; n < 4; n++) {
                            mbar_expect_tx(bars + 8 * (B_OFULL + (n >> 1) * 6 + 4 + (n & 1)) - v * 32, BOX);
                            mbar_arrive_at(mapa(bars + 8 * B_OEMPTY, n >> 1) + (4 + (n & 1)) * 8 - v * 32);
                        }
                    }
                }
            }
        }
    } else if (warp >= 8) {
        reg_dec<40>();
        const int wq = warp - 8, ta = tid - 256;
        const uint32_t rbuf = sb + OFF_FR + wq * BOX, rbar = bars + 8 * B_ROW;
        const uint4 wv = ldg_nc(wr + ta * 8);
        if (ta == 0) sts1(sb + OFF_EP, ld_rlx(&scr->epoch[0]) + 1);
        sts4(sb + OFF_STAT + ta * 16, wv.x, wv.y, wv.z, wv.w);
        bar_sync(8, 224);
        const uint32_t ep = __shfl_sync(0xffffffffu, lds1(sb + OFF_EP), 0);
        {
            const int s = b * 16 + wq * 4 + (lane >> 3);
            if ((lane & 7) == 0) st_rlx2(&scr->row[s], 0, ep - 1);
            float sw = 0.f;
#pragma unroll 1
            for (int i = 0; i < 16; i++) { const uint32_t q = lds1(sb + OFF_STAT + i * 128 + lane * 4); sw += bf_lo(q) + bf_hi(q); }
#pragma unroll 1
            for (int o = 16; o > 0; o >>= 1) sw += __shfl_xor_sync(0xffffffffu, sw, o);
            float s1 = 0.f, s2 = 0.f, sr = 0.f;
            const uint32_t xa = rbuf + (lane >> 3) * 2048 + (lane & 7) * 16, wa = sb + OFF_STAT + (lane & 7) * 16;
            mbar_wait(rbar, 0, budget);
            TSC(ta == 0, 17);
            uint4 u = lds4(xa), w4 = lds4(wa);
#pragma unroll kStatsUnroll
            for (int i = 1; i <= 16; i++) {
                const uint32_t o = (i * 128) & 2047;
                const uint4 un = lds4(xa + o), wn = lds4(wa + o);
#pragma unroll
                for (int c = 0; c < 4; c++) {
                    const float a0 = bf_lo((&u.x)[c]), a1 = bf_hi((&u.x)[c]);
                    s1 += a0; s2 = fmaf(a0, a0, s2); sr = fmaf(a0, bf_lo((&w4.x)[c]), sr);
                    s1 += a1; s2 = fmaf(a1, a1, s2); sr = fmaf(a1, bf_hi((&w4.x)[c]), sr);
                }
                u = un; w4 = wn;
            }
#pragma unroll 1
            for (int o = 1; o < 8; o <<= 1) {
                s1 += __shfl_xor_sync(0xffffffffu, s1, o); s2 += __shfl_xor_sync(0xffffffffu, s2, o); sr += __shfl_xor_sync(0xffffffffu, sr, o);
            }
            const float mean = s1 * (1.f / 1024.f), mb = bf16r(mean);
            float var = fmaf(-mean, mean, s2 * (1.f / 1024.f));
            sr = fmaf(-mb, sw, sr);
            if (__builtin_expect(__any_sync(0xffffffffu, mean * mean > 256.f * var), 0)) {
                float a2 = 0.f, ar = 0.f;
#pragma unroll 1
                for (int i = 0; i < 64; i++) {
                    const uint32_t o = (i >> 2) * 128 + (i & 3) * 4, q1 = lds1(xa + o), q2 = lds1(wa + o);
                    a2 = fmaf(bf_lo(q1) - mean, bf_lo(q1) - mean, fmaf(bf_hi(q1) - mean, bf_hi(q1) - mean, a2));
                    ar = fmaf(bf_lo(q1) - mb, bf_lo(q2), fmaf(bf_hi(q1) - mb, bf_hi(q2), ar));
                }
#pragma unroll 1
                for (int o = 1; o < 8; o <<= 1) { a2 += __shfl_xor_sync(0xffffffffu, a2, o); ar += __shfl_xor_sync(0xffffffffu, ar, o); }
                var = a2 * (1.f / 1024.f); sr = ar;
            }
            float den;
            asm("sqrt.approx.f32 %0, %1;" : "=f"(den) : "f"(bf16r(bf16r(var) + 1e-5f)));
            const uint32_t st = pack_bf16(mb, den);
            const uint32_t rb = pack_bf16(0.f, sr * rcp(bf_hi(st)) + 0.f);
            uint32_t ord = (int)rb < 0 ? ~rb & 0xffff0000u : rb | 0x80000000u;
            if ((rb & 0x7fffffffu) > 0x7f800000u) ord = 0;
            if ((lane & 7) == 0) st_rlx2(&scr->row[s], st, ord | ((2047 - s) << 5) | (ep & 31));
            __syncwarp();
            if (lane < 7) mbar_arrive(bars + 8 * (lane < 5 ? B_FEMPTY + lane : B_RDONE));
        }
        TSC(ta == 0, 18);
        if ((b >> 3) == 14) {
            const uint32_t gm = sb + OFF_E, cnt = gm + 64, res = gm + 80, list = gm + 128;
            uint32_t kv[16];
            int tries = BUDGET;
#pragma unroll 1
            do {
                uint32_t bad = 0;
#pragma unroll
                for (int n = 0; n < 16; n++) kv[n] = ld_rlx(&scr->row[n * 128 + ta].y);
#pragma unroll
                for (int n = 0; n < 16; n++) bad |= kv[n] ^ ep;
                if ((bad & 31) == 0) break;
            } while (--tries > 0);
            __syncwarp();
            TSC(ta == 0, 26);
            uint32_t m = 0;
#pragma unroll
            for (int n = 0; n < 16; n++) m = max(m, kv[n]);
            uint32_t gmax = m;
#pragma unroll
            for (int o = 1; o < 8; o <<= 1) gmax = max(gmax, __shfl_xor_sync(0xffffffffu, gmax, o));
            sts1(gm + (ta >> 3) * 4, gmax);
            sts1(cnt, 0);
            bar_sync(12, 128);
            const uint32_t c = lds1(gm + (lane & 15) * 4);
            int rank = 0;
#pragma unroll
            for (int i = 0; i < 2; i++) { const uint4 q = lds4(gm + (lane >> 4) * 32 + i * 16); rank += (q.x > c) + (q.y > c) + (q.z > c) + (q.w > c); }
            rank += __shfl_xor_sync(0xffffffffu, rank, 16);
            const uint32_t thr = redux_max(rank == 7 ? c : 0u);
#pragma unroll 1
            while (m >= thr) {
                uint32_t at, m2 = 0;
                asm volatile("atom.shared.add.u32 %0, [%1], 1;" : "=r"(at) : "r"(cnt) : "memory");
#pragma unroll
                for (int n = 0; n < 16; n++) m2 = max(m2, kv[n] < m ? kv[n] : 0u);
                sts1(list + at * 4, m);
                if (m2 == 0) break;
                m = m2;
            }
            bar_sync(12, 128);
            const int nc = lds1(cnt);
#pragma unroll 1
            for (int i = ta >> 3; i < ((nc + 3) & ~3); i += 16) {
                const uint32_t ki = lds1(list + i * 4);
                int r = 0;
#pragma unroll 1
                for (int n = lane & 7; n < nc; n += 8) r += lds1(list + n * 4) > ki;
                __syncwarp();
#pragma unroll
                for (int o = 1; o < 8; o <<= 1) r += __shfl_xor_sync(0xffffffffu, r, o);
                if (r == (b & 7) && i < nc) sts1(res, ki);
            }
            bar_sync(12, 128);
            const uint32_t k0 = lds1(res);
            const int r0 = 2047 - ((k0 >> 5) & 2047);
            TSC(ta == 0, 22);
            if (ta == 0) st_rlx(&scr->sel[b & 7], k0);
            const uint4 v0 = ldg_nc(x + (size_t)r0 * 1024 + ta * 8);
            const uint32_t s0 = ld_rlx(&scr->row[r0]);
            const float m0 = bf_lo(s0), i0 = rcp(bf_hi(s0));
            const int ao = 14336 + (ta >> 3) * 256 + (b & 7) * 32 + ((ta ^ b) & 7) * 4;
            st_rlx4(scr->act[ep & 1] + ao, norm_pair(v0.x, m0, i0), norm_pair(v0.y, m0, i0), norm_pair(v0.z, m0, i0), norm_pair(v0.w, m0, i0));
            __syncwarp();
            if (lane == 0) red_add(&scr->cnt[8][tries >> 30]);
            st_rlx4(scr->act[~ep & 1] + ao, 0, 0, 0, 0);
        }
        uint32_t s8 = 0, fph = 0, own = 0; float sig = 0.f;
        const uint32_t chk = __shfl_sync(0xffffffffu, sb + OFF_FS + BOX + lane * 32 + (lane & 28), lane);
        int left = BUDGET;
#pragma unroll 1
        for (int ph = 0; ph < 2; ph++) {
            if (ph || b < 112) {
                float acc[4] = {0.f, 0.f, 0.f, 0.f};
                const uint32_t alo = sd + (ph ? dlo(OFF_FS, 8192) : dlo(OFF_FS, 4096)), ahi = ph ? dhi(1024, 1) : dhi(512, 2), astep = ph ? 128 : 64;
                const uint32_t bhi = ph ? dhi(128, 0) : dhi(1024, 1), bstep = ph ? 16 : 2, wrap = ph ? 24 : 40;
                uint32_t prev = 0, prev2 = 0;
                if (ph) mbar_wait(bars + 8 * FFN2_GATE, 0, left);
#pragma unroll 1
                for (int q = ph ? 7 : 16; q > 0; q--) {
                    const uint32_t da = alo + s8 * (F_BYTES >> 7), db = sd + dlo(OFF_FS + BOX, 128) + s8 * (F_BYTES >> 7);
                    mbar_wait_hot(bars + 8 * B_FFULL + s8, fph, left);
                    if (__builtin_expect(__any_sync(0xffffffffu, lds1(chk + s8 * (F_BYTES / 8)) == 0), 0)) {
                        int tries = BUDGET;
#pragma unroll 1
                        for (int n = lane * 4 + (left >> 30); n < 256; n += 128) {
                            uint4 v;
#pragma unroll 1
                            do { v = ld_rlx4(scr->act[ep & 1] + ((ph ? kc * 7 + 7 : 72) - q) * 256 + n); } while (v.x == 0 && --tries > 0);
                            __syncwarp();
                            sts4(sb + OFF_FS + BOX + s8 * (F_BYTES / 8) + n * 4, v.x, v.y, v.z, v.w);
                        }
                        NRETRY();
                        fence_async_smem();
                        __syncwarp();
                    }
                    TSC(TIMING % 10 == 3 && ta == 0, 32 + (ph ? 23 : 16) - q);
                    wg_fence();
#pragma unroll
                    for (int j = 0; j < 4; j++) wgmma_n8<1, 0>(acc, mkdesc(da + j * astep, ahi), mkdesc(db + j * bstep, bhi), 1);
                    wg_commit();
                    prev2 = prev;
                    if (lane == 0) prev = bars + 8 * B_FEMPTY + s8;
                    wg_wait<1>();
                    if (ph) { wg_wait<0>(); prev2 = prev; }
                    if (prev2) mbar_arrive(prev2);
                    s8 += 8;
                    if (s8 == wrap) { s8 = 0; fph ^= 1; }
                }
                wg_wait<0>();
                const int ln = lane + (left >> 30);
                if (ph == 0) {
                    if (prev) mbar_arrive(prev);
                    const bool second = (wq >= 2) != (swap_gu != 0);
                    const uint32_t xa = sb + OFF_GU + ((wq & 1) * 32 + ln) * 16;
                    if (second) sts4(xa, __float_as_uint(acc[0]), __float_as_uint(acc[1]), __float_as_uint(acc[2]), __float_as_uint(acc[3]));
                    bar_sync(12, 128);
                    if (!second) {
                        const float4 up = lds4f(xa);
                        float hv[4];
#pragma unroll
                        for (int c = 0; c < 4; c++) { const float ga = bf16r(acc[c]); hv[c] = bf16r(ga * sigmoidf(ga)) * bf16r((&up.x)[c]); }
                        const int ao = (b * 4 + (wq & 1) * 2) * 32 + ln;
                        st_rlx(scr->act[ep & 1] + ao, max(movm(pack_bf16(hv[0], hv[1])), 1u)); st_rlx(scr->act[ep & 1] + 32 + ao, max(movm(pack_bf16(hv[2], hv[3])), 1u));
                        __syncwarp();
                        if (ln == 0) red_add(&scr->cnt[b / 14][0]);
                        st_rlx(scr->act[~ep & 1] + ao, 0); st_rlx(scr->act[~ep & 1] + 32 + ao, 0);
                    }
                } else {
#pragma unroll
                    for (int c = 0; c < 4; c++) st_rlx(&scr->ypart[kc][2 * (ln & 3) + (c & 1)][c2 * 64 + wq * 16 + (c >> 1) * 8 + (ln >> 2)], (__float_as_uint(acc[c]) & ~1u) | (ep & 1));
                    if (b == 0 && ta == 0) st_rlx(&scr->epoch[ln], ep);
                }
                TSC(ta == 0, 22 + ph);
            }
            const int ln = lane + (left >> 30);
            if (ph == 0) {
                if ((ta & 126) == 64) mbar_arrive(bars + 8 * B_F1DONE);
                const uint32_t kj = poll_all(&scr->sel[ln & 7], 31u, ep & 31, left);
                const int row = 2047 - ((kj >> 5) & 2047), jj = (row & 1) == par ? (row >> 1) - j0 : -1;
                sig = bf16r(sigmoidf(__uint_as_float(((int)kj < 0 ? kj & 0x7fffffffu : ~kj) & 0xffff0000u)));
                own = __ballot_sync(0xffffffffu, (jj >> 7) == rh) & 255;
                sts1(sb + OFF_SEL + (ln & 7) * 4, jj);
                sts4(sb + OFF_UPD + wq * 512 + ln * 16, 0, 0, 0, 0);
            }
            if ((own != 0) == ph) {
                if (wq & 2) own &= own - 1;
#pragma unroll 1
                for (; own; own &= own - 1, own &= own - 1) {
                    const int j = __ffs(own) - 1;
                    const uint32_t* src = &scr->ypart[ln >> 4][j][cb * 128 + (wq & 1) * 64 + (ln & 15) * 4];
                    uint4 v[4]; int tries = BUDGET;
#pragma unroll 1
                    do {
#pragma unroll
                        for (int m = 0; m < 4; m++) v[m] = ld_rlx4(src + m * 2 * 8192);
                    } while ((((v[0].x ^ ep) | (v[1].x ^ ep) | (v[2].x ^ ep) | (v[3].x ^ ep)) & 1) && --tries > 0);
                    __syncwarp();
                    float a[4];
                    const float sj = __shfl_sync(0xffffffffu, sig, j);
#pragma unroll
                    for (int c = 0; c < 4; c++) {
                        a[c] = (__uint_as_float((&v[0].x)[c]) + __uint_as_float((&v[1].x)[c])) + (__uint_as_float((&v[2].x)[c]) + __uint_as_float((&v[3].x)[c]));
                        a[c] = bf16r(a[c] + __shfl_xor_sync(0xffffffffu, a[c], 16)) * sj;
                    }
                    sts2(sb + OFF_UPD + (wq & 1) * 1024 + j * 128 + ((((ln >> 1) & 7) ^ j) << 4) + (ln & 1) * 8, pack_bf16(a[0], a[1]), pack_bf16(a[2], a[3]));
                }
                fence_async_smem();
                __syncwarp();
                if (ln < 2) mbar_arrive(bars + 8 * B_UPD);
            }
        }
        TSC(ta == 0, 24);
    } else {
        reg_inc<224>();
        const int w = warp >> 2, wi = warp & 3, g = lane >> 2, t = lane & 3;
        const bool elect = (tid & 127) == 0;
        const uint32_t mad = (lane & 15) * 128 + (((lane >> 4) ^ (lane & 7)) << 4);
        float acc[64];
        const uint32_t ring = sb + w * OFF_X1, ofull = bars + 8 * (B_OFULL + w * 6), oempty = mapa(bars + 8 * B_OEMPTY, w);
        const int r0 = rh * 128 + wi * 32 + (1 - w) * 16 + g;
        {
            float acc0[96], acc1[96];
            const uint32_t sta = sb + OFF_STAT + (8 + w * 128 + wi * 32) * 8;
            {
                const uint32_t xfull = bars + 8 * (B_XFULL + w * 6 + 5), xempty = mapa(bars + 8 * B_XEMPTY, w), dx0 = sd + dlo(w * OFF_X1, 16);
                uint32_t s8 = 16, ps8 = 0, ph = 0;
                const uint32_t hi = dhi(1024, 1) | (swap_gu >> 30);
                cluster_wait();
#pragma unroll 1
                for (int k = 0; k < 16; k++) {
                    const uint32_t dx = dx0 + s8 * (2 * BOX >> 7), dw = sd + dlo(OFF_W, BOX) + s8 * (W_BYTES >> 7);
                    mbar_wait(bars + 8 * B_WFULL + s8, ph, budget);
                    mbar_wait(xfull - 2 * s8, ph, budget);
                    TSC(elect && k == 0, 1 + 8 * w);
                    TSC(TIMING % 10 == 1 && tid == 0, 32 + k);
                    wg_wait<0>();
                    wg_fence();
#pragma unroll
                    for (int kk = 0; kk < 4; kk++) wgmma_n192<0, 1>(acc1, mkdesc(dx + kk * 2, G1HI), mkdesc(dw + kk * 128, G1HI), kk ? 1 : k);
                    wg_commit();
                    if (elect && k > 0) {
                        mbar_arrive(bars + 8 * B_WEMPTY + ps8);
                        if (k <= 13) { mbar_expect_tx(xfull - 2 * ps8 - 8, BOX); mbar_arrive_at(xempty + 2 * ps8 + 8); }
                    }
                    if (k == 15) {
                        mbar_wait(bars + 8 * B_AUX, 0, budget);
                        const uint32_t zero = budget >> 30, pm = t & 1 ? 0x4432 : 0x3232, ra = sta + ((t >> 1) * 16 + g) * 8;
                        const uint32_t a0 = __byte_perm(lds1(ra), 0, pm), a1 = __byte_perm(lds1(ra + 64), 0, pm), a2 = a0 & zero, a3 = a1 & zero;
                        wg_fence();
                        wgmma_rs_n192(acc1, a0, a1, a2, a3, mkdesc(sd + dlo(OFF_CS, 0), dhi(128, 0)));
                        wgmma_rs_n192(acc0, a0, a1, a2, a3, mkdesc(sd + dlo(OFF_CS + 64, 0), dhi(128, 0)));
                        wg_commit();
                    }
                    mbar_wait(xfull - 2 * s8 - 8, ph, budget);
                    wg_wait<0>();
                    wg_fence();
#pragma unroll
                    for (int kk = 0; kk < 4; kk++) wgmma_n192<0, 1>(acc0, mkdesc(dx + 512 + kk * 2, G1HI), mkdesc(dw + kk * 128, G1HI), kk ? 1 : k);
                    wg_commit();
                    if (elect && k <= 12) { mbar_expect_tx(xfull - 2 * s8, BOX); mbar_arrive_at(xempty + 2 * s8); }
                    ps8 = s8;
                    s8 = s8 == 16 ? 0 : s8 + 8;
                    if (s8 == 16) ph ^= 1;
                }
            }
            const uint32_t zero = budget >> 30;
            const bool u0 = 2 * t > g, u1 = 2 * t + 1 > g;
            uint32_t mU = (u0 ? 0xffffu : 0u) | (u1 ? 0xffff0000u : 0u);
            uint32_t ka0 = sta + (2 * t - (u0 ? 8 : 0)) * 8 + 4, ka1 = sta + (2 * t + 1 - (u1 ? 8 : 0)) * 8 + 4;
            float rk[2][4], fu[2][4], fn[2][4];
            auto factors = [&](int h) {
#pragma unroll
                for (int n = 0; n < 4; n += 2) {
                    const float rq = lds1f(sta + (16 * h + 4 * n + g) * 8 + 4) * (0.17677669529663687f * 1.4426950408889634f);
                    rk[h][n] = lds1f(ka0 + h * 128 + n * 32); rk[h][n + 1] = lds1f(ka1 + h * 128 + n * 32);
                    const float f0 = rq * rk[h][n], f1 = rq * rk[h][n + 1];
                    fu[h][n] = u0 ? f0 : 0.f; fn[h][n] = f0 - fu[h][n]; fu[h][n + 1] = u1 ? f1 : 0.f; fn[h][n + 1] = f1 - fu[h][n + 1];
                }
#pragma unroll
                for (int n = 0; n < 4; n++) asm volatile("" : "+f"(fu[h][n]), "+f"(fn[h][n]));
            };
            uint8_t* og = scr->o + ((size_t)(mt * 4 + w * 2) * 16 + nt) * BOX + wi * 256 + lane * 4;
            TSC(elect, 19 + w);
            uint32_t pk0[48], pk1[48], o[16] = {};
#pragma unroll
            for (int j = 0; j < 48; j++) if (j < 16 || (j & 1)) pk1[j] = pack_here(acc1[2 * j], acc1[2 * j + 1]);
            if (warp < 7) {
#pragma unroll
                for (int c = 0; c < 4; c++) stsm4(ring + 4 * BOX + wi * 2048 + c * 512 + lane * 16, pk1[17 + 8 * c], pk1[19 + 8 * c], pk1[21 + 8 * c], pk1[23 + 8 * c]);
                bar_arrive(1 + warp, 64);
            } else if (j0 != 768) {
#pragma unroll
                for (int c = 0; c < 4; c++) {
                    pk1[17 + 8 * c] = max(pk1[17 + 8 * c], 1u);
                    st_rlx4(&scr->halo[b][c * 128 + lane * 4], pk1[17 + 8 * c], pk1[19 + 8 * c], pk1[21 + 8 * c], pk1[23 + 8 * c]);
                }
            }
            TSC(tid == 224, 28);
#pragma unroll
            for (int j = 16; j < 48; j += 2) pk1[j] = pack_here(acc1[2 * j], acc1[2 * j + 1]);
            factors(1);
            uint32_t od = sb + 2 * BOX + wi * 256 + (lane >> 4) * 1024 + (lane & 15) * 16, g1peer = mapa(bars + 8 * B_G1DONE, hp ^ 1);
            uint32_t ha = sb + (warp == 0 ? OFF_HIN : warp <= 4 ? 4 * BOX - 2048 : OFF_X1 + 4 * BOX - 5 * 2048) + warp * 2048 + lane * 16;
            const bool first = warp == 0 && j0 == 0;
            float bias0 = first && u0 ? -INFINITY : 0.f, bias1 = first && u1 ? -INFINITY : 0.f;
            asm volatile("" : "+l"(og), "+r"(mU), "+r"(od), "+r"(ha), "+f"(bias0), "+f"(bias1));
            mbar_wait(bars + 8 * B_XT, 0, budget);
            mbar_wait(bars + 8 * (B_WEMPTY + 1), 0, budget);
            TSC(elect, 12 + 2 * w);
            wg_wait<0>();
            if (elect) { mbar_arrive(bars + 8 * B_G1DONE); mbar_arrive_at(g1peer); }
            TSC(elect, 2 + 8 * w);
            float ci[4];
#pragma unroll
            for (int n = 0; n < 4; n++) ci[n] = __uint_as_float((0x03800000u + n) | (budget >> 30));
            auto hand_over = [&](int v) {
                asm volatile("{\n.reg .pred p;\nsetp.ne.b32 p, %17, 0;\n"
                             "@p stmatrix.sync.aligned.m8n8.x4.shared.b16 [%16], {%0,%1,%2,%3};\n@p stmatrix.sync.aligned.m8n8.x4.shared.b16 [%16 + 2048], {%4,%5,%6,%7};\n"
                             "@p stmatrix.sync.aligned.m8n8.x4.shared.b16 [%16 + 4096], {%8,%9,%10,%11};\n@p stmatrix.sync.aligned.m8n8.x4.shared.b16 [%16 + 6144], {%12,%13,%14,%15};\n"
                             FENCE_PRED "fence.proxy.async.shared::cta;\n}"
                             ::"r"(o[0]), "r"(o[1]), "r"(o[2]), "r"(o[3]), "r"(o[4]), "r"(o[5]), "r"(o[6]), "r"(o[7]), "r"(o[8]), "r"(o[9]), "r"(o[10]), "r"(o[11]),
                               "r"(o[12]), "r"(o[13]), "r"(o[14]), "r"(o[15]), "r"(od + v * OFF_X1), "r"((int)(w == rh)) : "memory");
                TSC(tid == 0, v ? 27 : 5);
#pragma unroll
                for (int i = 0; i < 16; i++) asm volatile("st.global.u32 [%0], %1;" ::"l"(og + (1 - v) * 16 * BOX + (i >> 1) * 1024 + (i & 1) * 128), "r"(o[i]) : "memory");
                __syncwarp();
                if (lane == 0) mbar_arrive(bars + 8 * (B_STAGED + v));
            };
#pragma unroll
            for (int j = 32; j < 48; j++) pk1[j] = movm(pk1[j]);
#pragma unroll
            for (int j = EARLY_PK; j < 48; j++) if (j >= 32 || (j & 1) || EARLY_PK < 17) pk0[j] = pack_here(acc0[2 * j], acc0[2 * j + 1]);
#pragma unroll
            for (int j = 32; j < 48; j++) pk0[j] = movm(pk0[j]);
            factors(0);
            attn_pair<2>(pk1, pk1 + 16, pk1 + 32, pk0 + 17, pk0 + 33, fu[1], fn[1], rk[1], 0.f, 0.f, mU, zero, ci, o);
            hand_over(0);
            TSC(elect, 3 + 8 * w);
#pragma unroll
            for (int j = 0; j < 32; j++) if (j < EARLY_PK || (!(j & 1) && EARLY_PK == 17)) pk0[j] = pack_here(acc0[2 * j], acc0[2 * j + 1]);
            bar_sync(warp ? warp : 11, 64);
            uint32_t hl[16];
            ldsm4(hl, ha); ldsm4(hl + 4, ha + 512); ldsm4t(hl + 8, ha + 1024); ldsm4t(hl + 12, ha + 1536);
            __syncwarp();
            if (lane == 0) mbar_arrive(bars + 8 * B_FREED);
            attn_pair<1>(pk0, pk0 + 16, pk0 + 32, hl, hl + 8, fu[0], fn[0], rk[0], bias0, bias1, mU, zero, ci, o);
            const float2 s0 = lds2f(sb + OFF_STAT + (8 + r0) * 8), s1 = lds2f(sb + OFF_STAT + (16 + r0) * 8);
            const float m0 = s0.x * s0.y, f0 = 1.f + s0.y, m1 = s1.x * s1.y, f1 = 1.f + s1.y;
            uint32_t xt[32];
#pragma unroll
            for (int j = 0; j < 8; j++) ldsm4(xt + 4 * j, ((ring + wi * 2048 + mad) ^ ((j & 3) * 32)) + (j >> 2) * BOX);
            hand_over(1);
#pragma unroll
            for (int j = 0; j < 32; j++) {
                acc[2 * j] = fmaf(bf_lo(xt[j]), j & 1 ? f1 : f0, j & 1 ? m1 : m0); acc[2 * j + 1] = fmaf(bf_hi(xt[j]), j & 1 ? f1 : f0, j & 1 ? m1 : m0);
            }
        }
        TSC(tid == 0, 4);
        {
            const uint32_t da0 = sd + dlo(w * OFF_X1, 1024), db0 = sd + dlo(OFF_WO, BOX);
            const uint32_t chk = ring + wi * 256 + (lane >> 3) * 1032 + (lane & 7) * 32 + (lane & 4);
            uint32_t s8 = 16, ps8 = 0, ph = 0;
            mbar_wait(ofull + s8, 0, budget);
            mbar_wait(bars + 8 * B_WOFULL + s8, 0, budget);
            TSC(TIMING % 10 == 2 && elect, 32 + w * 16);
            const uint32_t ahi = dhi(128, 0) | (budget >> 30), bhi = dhi(1024, 1) | (budget >> 30);
            uint32_t rel = elect ? 0x7fe : 0;
#pragma unroll 1
            for (int i = 1;; i++) {
                const uint32_t da = da0 + s8 * (BOX >> 7), db = db0 + s8 * (BOX >> 6);
                wg_fence();
#pragma unroll
                for (int kk = 0; kk < 4; kk++) {
                    wgmma_n128<0, 1>(acc, mkdesc(da + kk * 128, ahi), mkdesc(db + kk * 128, bhi), 1);
                    if (kk & 1) wg_commit();
                }
                wg_wait<2>();
                if (rel & 1) { mbar_expect_tx(ofull + ps8, BOX); mbar_arrive_at(oempty + ps8); mbar_arrive(bars + 8 * B_WOEMPTY + ps8); }
                if (i == 16) break;
                rel >>= 1;
                ps8 = s8;
                s8 = s8 == 40 ? 0 : s8 + 8;
                if (s8 == 16) ph ^= 1;
                uint32_t bad;
                asm volatile("{\n.reg .pred p, q, r;\n.reg .u32 u, v;\nmbarrier.try_wait.parity.shared::cta.b64 q, [%2], %3;\nmbarrier.try_wait.parity.shared::cta.b64 p, [%1], %3;\n"
                             "setp.ne.and.u32 r, %5, 1, p;\nmov.u32 u, 1;\nmov.u32 v, 1;\n@r ld.shared.u32 u, [%4];\n@r ld.shared.u32 v, [%4 + 4096];\n"
                             "and.pred p, p, q;\nmin.u32 u, u, v;\nsetp.eq.or.u32 p, u, 0, !p;\nvote.sync.any.pred p, p, 0xffffffff;\nselp.u32 %0, 1, 0, p;\n}"
                             : "=r"(bad) : "r"(ofull + s8), "r"(bars + 8 * B_WOFULL + s8), "r"(ph), "r"(chk + s8 * (BOX / 8)), "r"(i) : "memory");
                if (__builtin_expect(bad, 0)) {
                    mbar_wait(ofull + s8, ph, budget);
                    mbar_wait(bars + 8 * B_WOFULL + s8, ph, budget);
                    if (__any_sync(0xffffffffu, min(lds1(chk + s8 * (BOX / 8)), lds1(chk + s8 * (BOX / 8) + 4096)) == 0)) {
                        const uint32_t at = wi * 256 + (lane >> 4) * 1024 + (lane & 15) * 16;
                        const uint8_t* src = scr->o + ((size_t)((mt * 2 + rh) * 2 + 1 - w) * 16 + ((2 * p + (i < 2 ? i ^ hp : i)) & 15)) * BOX + at;
#pragma unroll 1
                        for (int n = 0; n < 8192; n += 2048) {
                            uint4 v; int tries = 4096;
#pragma unroll 1
                            do { v = ld_rlx4(src + n); } while (v.x == 0 && --tries > 0);
                            sts4(ring + s8 * (BOX / 8) + at + n, v.x, v.y, v.z, v.w);
                        }
                        NRETRY();
                        fence_async_smem();
                        __syncwarp();
                    }
                }
                TSC(TIMING % 10 == 1 && tid == 0, 48 + i);
                TSC(TIMING % 10 == 2 && elect, 32 + w * 16 + i);
                wg_wait<1>();
            }
            mbar_wait(bars + 8 * B_UPD, 0, budget);
            const float2 sl = lds2f(sb + OFF_SEL + t * 8);
            const int d0 = __float_as_int(sl.x) - r0, d1 = __float_as_int(sl.y) - r0;
            const uint32_t a0 = (d0 == 0 ? 0x3f80u : 0u) | (d1 == 0 ? 0x3f800000u : 0u), a1 = (d0 == 8 ? 0x3f80u : 0u) | (d1 == 8 ? 0x3f800000u : 0u);
            wg_fence();
            wgmma_rs_n128(acc, a0, a1, 0u, 0u, mkdesc(sd + dlo(OFF_UPD, 1024), dhi(0, 1)));
            wg_commit();
            wg_wait<0>();
            TSC(elect, 7 + 9 * w);
            const uint32_t os0 = ring + wi * 4096;
#pragma unroll
            for (int j = 0; j < 8; j++)
                stsm4(((os0 + mad) ^ ((j & 3) * 32)) + (j >> 2) * 2048, pack_bf16(acc[8 * j], acc[8 * j + 1]), pack_bf16(acc[8 * j + 2], acc[8 * j + 3]),
                      pack_bf16(acc[8 * j + 4], acc[8 * j + 5]), pack_bf16(acc[8 * j + 6], acc[8 * j + 7]));
            fence_async_smem();
            __syncwarp();
            if (elect_one()) {
                asm volatile("cp.async.bulk.tensor.5d.global.shared::cta.bulk_group [%0, {%2, %2, %3, %4, %5}], [%1];\ncp.async.bulk.commit_group;\ncp.async.bulk.wait_group.read 0;"
                             ::"l"(&mout), "r"(os0), "r"(0), "r"(((j0 + rh * 128) >> 5) + wi), "r"(1 - w), "r"(par * 16 + cb * 2) : "memory");
            }
            TSC(elect, 8 - 2 * w);
            TS_END();
        }
    }
}

typedef CUresult (*EncodeFn)(CUtensorMap*, CUtensorMapDataType, cuuint32_t, void*, const cuuint64_t*, const cuuint64_t*, const cuuint32_t*,
                             const cuuint32_t*, CUtensorMapInterleave, CUtensorMapSwizzle, CUtensorMapL2promotion, CUtensorMapFloatOOBfill);

CUtensorMap make_map(EncodeFn fn, const void* base, int rank, const cuuint64_t* dims, const cuuint64_t* strides, const cuuint32_t* box,
                     CUtensorMapSwizzle swz = CU_TENSOR_MAP_SWIZZLE_128B, CUtensorMapL2promotion pro = CU_TENSOR_MAP_L2_PROMOTION_L2_256B) {
    CUtensorMap m;
    cuuint32_t es[5] = {1, 1, 1, 1, 1};
    fn(&m, CU_TENSOR_MAP_DATA_TYPE_BFLOAT16, rank, (void*)base, dims, strides, box, es, CU_TENSOR_MAP_INTERLEAVE_NONE,
       swz, pro, CU_TENSOR_MAP_FLOAT_OOB_FILL_NONE);
    return m;
}

}

extern "C" void kernel_launch(void* const* d_in, const int* in_sizes, int n_in, void* d_out, int out_size) {
    (void)in_sizes; (void)n_in; (void)out_size;
    const __nv_bfloat16* x = (const __nv_bfloat16*)d_in[0];
    const __nv_bfloat16* wqkv = (const __nv_bfloat16*)d_in[1];
    const __nv_bfloat16* wo = (const __nv_bfloat16*)d_in[2];
    const __nv_bfloat16* wr = (const __nv_bfloat16*)d_in[4];
    const __nv_bfloat16* wg = (const __nv_bfloat16*)d_in[5];
    const __nv_bfloat16* wu = (const __nv_bfloat16*)d_in[6];
    const __nv_bfloat16* wd = (const __nv_bfloat16*)d_in[7];
    static EncodeFn fn = nullptr;
    static Scratch* scr = nullptr;
    if (!fn) {
        void* p = nullptr; cudaDriverEntryPointQueryResult q;
        cudaGetDriverEntryPoint("cuTensorMapEncodeTiled", &p, cudaEnableDefault, &q);
        fn = (EncodeFn)p;
        cudaFuncSetAttribute(fused_kernel, cudaFuncAttributeMaxDynamicSharedMemorySize, SMEM_LAUNCH);
        cudaGetSymbolAddress((void**)&scr, g_scr);
    }
    const cuuint64_t xd[4] = {2048, 16, 32, 2}, xs[4] = {4096, 131072, 65536, 128}, od[5] = {64, 16, 32, 2, 32};
    const cuuint32_t xb[4] = {64, 16, 4, 1}, ob[5] = {64, 16, 1, 1, 2};
    const cuuint64_t wdm[3] = {1024, 1024, 3}, wst[2] = {6144, 2048};
    const cuuint32_t wb[3] = {64, 64, 3};
    const cuuint64_t wod[3] = {64, 1024, 16}, wdd[3] = {64, 3584, 16}, wos[2] = {2048, 128};
    const cuuint32_t wob[3] = {64, 64, 2}, wdb[3] = {64, 64, 1};
    CUtensorMap mx = make_map(fn, x, 4, xd, xs, xb), mw = make_map(fn, wqkv, 3, wdm, wst, wb);
    CUtensorMap mwo = make_map(fn, wo, 3, wod, wos, wob), mout = make_map(fn, d_out, 5, od, xs, ob);
    const int swap_gu = wu < wg;
    const cuuint64_t gd[3] = {3584, 1024, 2}, gst[2] = {7168, (cuuint64_t)(swap_gu ? (const char*)wg - (const char*)wu : (const char*)wu - (const char*)wg)};
    const cuuint32_t gb[3] = {32, 64, 2};
    CUtensorMap mgu = make_map(fn, swap_gu ? wu : wg, 3, gd, gst, gb, CU_TENSOR_MAP_SWIZZLE_64B, CU_TENSOR_MAP_L2_PROMOTION_L2_128B);
    CUtensorMap mwd = make_map(fn, wd, 3, wdd, wos, wdb, CU_TENSOR_MAP_SWIZZLE_128B, CU_TENSOR_MAP_L2_PROMOTION_L2_128B);
    const cuuint64_t md[2] = {64, 32768}, ms[1] = {128};
    const cuuint32_t mb[2] = {64, 64};
    CUtensorMap mo = make_map(fn, scr, 2, md, ms, mb, CU_TENSOR_MAP_SWIZZLE_NONE, CU_TENSOR_MAP_L2_PROMOTION_NONE);
    cudaLaunchConfig_t cfg = {};
    cfg.gridDim = dim3(132); cfg.blockDim = dim3(512); cfg.dynamicSmemBytes = SMEM_LAUNCH; cfg.stream = cudaStreamPerThread;
    cudaLaunchAttribute at[1];
    at[0].id = cudaLaunchAttributeClusterDimension; at[0].val.clusterDim.x = 2; at[0].val.clusterDim.y = 1; at[0].val.clusterDim.z = 1;
    cfg.attrs = at; cfg.numAttrs = 1;
    cudaLaunchKernelEx(&cfg, fused_kernel, mx, mw, mwo, mout, mgu, mwd, mo, x, wr, scr, swap_gu, Weights{(const char*)wqkv, (const char*)wo, (const char*)wg, (const char*)wu, (const char*)wd});
}
```

```cpp
#include <cuda_runtime.h>
#include <cuda.h>
#include <cuda_bf16.h>
#include <stdint.h>

namespace {

constexpr int BOX = 8192, W_BYTES = 3 * BOX;
constexpr int OFF_X1 = 6 * BOX, OFF_FR = 12 * BOX, OFF_E = 16 * BOX, OFF_W = 19 * BOX;
constexpr int OFF_WO = OFF_E;
constexpr int OFF_UPD = OFF_FR, OFF_HIN = OFF_UPD + 2048, OFF_GU = OFF_HIN + 2048, OFF_FS = OFF_GU + 1024;
constexpr int F_BYTES = 9216;
constexpr int CS_BYTES = 3136;
constexpr int OFF_CS = OFF_FS + 5 * F_BYTES;
constexpr int OFF_STAT = 28 * BOX;
constexpr int OFF_SEL = OFF_STAT + 2112;
constexpr int OFF_EP = OFF_SEL + 32;
constexpr int OFF_BAR = OFF_EP + 16;
constexpr int B_WFULL = 0, B_XFULL = 3, B_AUX = 15, B_XT = 16, B_ROW = 17, B_WOFULL = 18, B_OFULL = 24, B_FFULL = 36;
constexpr int B_WEMPTY = 42, B_F1DONE = 45, B_XEMPTY = 46, B_WOEMPTY = 52, B_OEMPTY = 58;
constexpr int B_G1DONE = 66, B_FEMPTY = 67, B_STAGED = 72, B_UPD = 74, B_RDONE = 75, B_FREED = 76, NBAR = 78;
constexpr int SMEM_BYTES = OFF_BAR + NBAR * 8;
static_assert(OFF_FS + 3 * F_BYTES == OFF_E && OFF_CS + CS_BYTES <= OFF_W && SMEM_BYTES + 256 <= 232448 && OFF_BAR % 8 == 0 && OFF_UPD % 1024 == 0, "smem");
#define POLL_NS 30
#define PF_RATE 10
#define PF_START 7
#define ZF_NS 100
#define FFN2_GATE B_G1DONE
#define PF_NW 6
#define EARLY_PF 1
#define EARLY_PK 17
#define FENCE_PRED "@p "
#define ZF_N 64
#define HOLD 12
#define ROWS_AT 11
#define STATS_UNROLL 1
constexpr int kStatsUnroll = STATS_UNROLL;
constexpr int BUDGET = 1 << 18;

struct Scratch {
    uint8_t o[2048 * 1024 * 2];
    uint32_t ypart[8][8][1024];
    uint32_t halo[128][512];
    uint32_t act[2][14336 + 4096];
    uint2 row[2048];
    uint32_t cs[16][800];
    uint32_t oflag[16][32];
    uint32_t cnt[9][32];
    uint32_t sel[32], csflag[32], epoch[32];
};
__device__ __align__(1024) Scratch g_scr;
struct Weights { const char *wqkv, *wo, *wg, *wu, *wd; };

#define TS(i) do {} while (0)
#define TS_END() do {} while (0)
#define TSC(c, i) do {} while (0)
#define NRETRY() do {} while (0)
constexpr int SMEM_LAUNCH = SMEM_BYTES;
__device__ __forceinline__ uint32_t smem_u32(const void* p) { return (uint32_t)__cvta_generic_to_shared(p); }
__device__ __forceinline__ void mbar_init(uint32_t bar, uint32_t cnt) { asm volatile("mbarrier.init.shared::cta.b64 [%0], %1;" ::"r"(bar), "r"(cnt) : "memory"); }
__device__ __forceinline__ void mbar_expect_tx(uint32_t bar, uint32_t bytes) { asm volatile("mbarrier.arrive.expect_tx.shared::cta.b64 _, [%0], %1;" ::"r"(bar), "r"(bytes) : "memory"); }
__device__ __forceinline__ void mbar_arrive(uint32_t bar) { asm volatile("mbarrier.arrive.shared::cta.b64 _, [%0];" ::"r"(bar) : "memory"); }
__device__ __forceinline__ uint32_t mapa(uint32_t a, uint32_t cta) { uint32_t r; asm("mapa.shared::cluster.u32 %0, %1, %2;" : "=r"(r) : "r"(a), "r"(cta)); return r; }
__device__ __forceinline__ void mbar_arrive_at(uint32_t cbar) { asm volatile("mbarrier.arrive.shared::cluster.b64 _, [%0];" ::"r"(cbar) : "memory"); }
__device__ __forceinline__ void mbar_wait(uint32_t bar, uint32_t parity, int& budget) {
    asm volatile("{\n.reg .pred p;\nLAB_WAIT:\nmbarrier.try_wait.parity.shared::cta.b64 p, [%1], %2;\n"
                 "add.s32 %0, %0, -1;\nsetp.gt.and.s32 p, %0, 0, !p;\n@p bra LAB_WAIT;\n}" : "+r"(budget) : "r"(bar), "r"(parity) : "memory");
}
__device__ __forceinline__ void mbar_wait_hot(uint32_t bar, uint32_t parity, int& budget) {
    asm volatile("{\n.reg .pred p;\nmbarrier.try_wait.parity.shared::cta.b64 p, [%1], %2;\n@p bra LAB_DONE;\nLAB_WAIT:\nmbarrier.try_wait.parity.shared::cta.b64 p, [%1], %2;\n"
                 "add.s32 %0, %0, -1;\nsetp.gt.and.s32 p, %0, 0, !p;\n@p bra LAB_WAIT;\nLAB_DONE:\n}" : "+r"(budget) : "r"(bar), "r"(parity) : "memory");
}
__device__ __forceinline__ void tma_2d_mc(uint32_t dst, const CUtensorMap* m, uint32_t bar, int c0, int c1) {
    asm volatile("cp.async.bulk.tensor.2d.shared::cluster.global.mbarrier::complete_tx::bytes.multicast::cluster [%0], [%1, {%3, %4}], [%2], %5;" ::"r"(dst), "l"(m), "r"(bar), "r"(c0), "r"(c1), "h"((uint16_t)3) : "memory");
}
__device__ __forceinline__ void tma_3d(uint32_t dst, const CUtensorMap* m, uint32_t bar, int c0, int c1, int c2) {
    asm volatile("cp.async.bulk.tensor.3d.shared::cluster.global.mbarrier::complete_tx::bytes [%0], [%1, {%3, %4, %5}], [%2];" ::"r"(dst), "l"(m), "r"(bar), "r"(c0), "r"(c1), "r"(c2) : "memory");
}
__device__ __forceinline__ void tma_4d(uint32_t dst, const CUtensorMap* m, uint32_t bar, int c0, int c1, int c2, int c3) {
    asm volatile("cp.async.bulk.tensor.4d.shared::cluster.global.mbarrier::complete_tx::bytes [%0], [%1, {%3, %4, %5, %6}], [%2];" ::"r"(dst), "l"(m), "r"(bar), "r"(c0), "r"(c1), "r"(c2), "r"(c3) : "memory");
}
__device__ __forceinline__ void tma_4d_mc(uint32_t dst, const CUtensorMap* m, uint32_t bar, int c0, int c1, int c2, int c3) {
    asm volatile("cp.async.bulk.tensor.4d.shared::cluster.global.mbarrier::complete_tx::bytes.multicast::cluster [%0], [%1, {%3, %4, %5, %6}], [%2], %7;" ::"r"(dst), "l"(m), "r"(bar), "r"(c0), "r"(c1), "r"(c2), "r"(c3), "h"((uint16_t)3) : "memory");
}
__device__ __forceinline__ void bulk_pf(const void* p, uint32_t bytes) { asm volatile("cp.async.bulk.prefetch.L2.global [%0], %1;" ::"l"(p), "r"(bytes) : "memory"); }
__device__ __forceinline__ void bulk_g2s(uint32_t dst, const void* src, uint32_t bytes, uint32_t bar) {
    asm volatile("cp.async.bulk.shared::cluster.global.mbarrier::complete_tx::bytes [%0], [%1], %2, [%3];" ::"r"(dst), "l"(src), "r"(bytes), "r"(bar) : "memory");
}
__device__ __forceinline__ void bulk_s2c(uint32_t cdst, uint32_t src, uint32_t bytes, uint32_t cbar) {
    asm volatile("cp.async.bulk.shared::cluster.shared::cta.mbarrier::complete_tx::bytes [%0], [%1], %2, [%3];" ::"r"(cdst), "r"(src), "r"(bytes), "r"(cbar) : "memory");
}
__device__ __forceinline__ void cluster_wait() { asm volatile("barrier.cluster.wait.aligned;" ::: "memory"); }
__device__ __forceinline__ void fence_gpu() { asm volatile("fence.acq_rel.gpu;" ::: "memory"); }
__device__ __forceinline__ void fence_async_smem() { asm volatile("fence.proxy.async.shared::cta;" ::: "memory"); }
__device__ __forceinline__ void fence_async_gmem() { asm volatile("fence.proxy.async.global;" ::: "memory"); }
__device__ __forceinline__ void wg_fence() { asm volatile("wgmma.fence.sync.aligned;" ::: "memory"); }
__device__ __forceinline__ void wg_commit() { asm volatile("wgmma.commit_group.sync.aligned;" ::: "memory"); }
template <int N> __device__ __forceinline__ void wg_wait() { asm volatile("wgmma.wait_group.sync.aligned %0;" ::"n"(N) : "memory"); }
__device__ __forceinline__ uint64_t mkdesc(uint32_t lo, uint32_t hi) { return ((uint64_t)hi << 32) | lo; }
__host__ __device__ constexpr uint32_t dhi(uint32_t sbo, uint32_t mode) { return (sbo >> 4) | (mode << 30); }
__host__ __device__ constexpr uint32_t dlo(uint32_t off, uint32_t lbo) { return (off >> 4) + ((lbo >> 4) << 16); }
__device__ __forceinline__ bool elect_one() {
    uint32_t e;
    asm volatile("{\n.reg .pred p;\nelect.sync _|p, 0xffffffff;\nselp.u32 %0, 1, 0, p;\n}" : "=r"(e));
    return e;
}
template <int R> __device__ __forceinline__ void reg_inc() { asm volatile("setmaxnreg.inc.sync.aligned.u32 %0;" ::"n"(R)); }
template <int R> __device__ __forceinline__ void reg_dec() { asm volatile("setmaxnreg.dec.sync.aligned.u32 %0;" ::"n"(R)); }
__device__ __forceinline__ void bar_sync(int id, int n) { asm volatile("bar.sync %0, %1;" ::"r"(id), "r"(n) : "memory"); }
__device__ __forceinline__ void bar_arrive(int id, int n) { asm volatile("bar.arrive %0, %1;" ::"r"(id), "r"(n) : "memory"); }
__device__ __forceinline__ uint32_t pack_bf16(float lo, float hi) { uint32_t r; asm("cvt.rn.bf16x2.f32 %0, %1, %2;" : "=r"(r) : "f"(hi), "f"(lo)); return r; }
__device__ __forceinline__ uint32_t pack_here(float lo, float hi) { uint32_t r; asm volatile("cvt.rn.bf16x2.f32 %0, %1, %2;" : "=r"(r) : "f"(hi), "f"(lo)); return r; }
__device__ __forceinline__ float bf_lo(uint32_t u) { return __uint_as_float(u << 16); }
__device__ __forceinline__ float bf_hi(uint32_t u) { return __uint_as_float(u & 0xffff0000u); }
__device__ __forceinline__ float bf16r(float v) { return bf_lo(pack_bf16(v, 0.f)); }
__device__ __forceinline__ float rcp(float x) { float r; asm("rcp.approx.ftz.f32 %0, %1;" : "=f"(r) : "f"(x)); return r; }
__device__ __forceinline__ float ex2(float x) { float r; asm("ex2.approx.ftz.f32 %0, %1;" : "=f"(r) : "f"(x)); return r; }
__device__ __forceinline__ float sigmoidf(float v) { return rcp(1.f + ex2(v * -1.4426950408889634f)); }
__device__ __forceinline__ uint32_t movm(uint32_t a) { uint32_t d; asm volatile("movmatrix.sync.aligned.m8n8.trans.b16 %0, %1;" : "=r"(d) : "r"(a)); return d; }
__device__ __forceinline__ void mma16816(float (&c)[4], uint32_t a0, uint32_t a1, uint32_t a2, uint32_t a3, uint32_t b0, uint32_t b1) {
    asm volatile("mma.sync.aligned.m16n8k16.row.col.f32.bf16.bf16.f32 {%0,%1,%2,%3}, {%4,%5,%6,%7}, {%8,%9}, {%0,%1,%2,%3};"
                 : "+f"(c[0]), "+f"(c[1]), "+f"(c[2]), "+f"(c[3]) : "r"(a0), "r"(a1), "r"(a2), "r"(a3), "r"(b0), "r"(b1));
}
__device__ __forceinline__ void mma1688(float (&c)[4], uint32_t a0, uint32_t a1, uint32_t b0) {
    asm volatile("mma.sync.aligned.m16n8k8.row.col.f32.bf16.bf16.f32 {%0,%1,%2,%3}, {%4,%5}, {%6}, {%0,%1,%2,%3};"
                 : "+f"(c[0]), "+f"(c[1]), "+f"(c[2]), "+f"(c[3]) : "r"(a0), "r"(a1), "r"(b0));
}
__device__ __forceinline__ void stsm4(uint32_t a, uint32_t r0, uint32_t r1, uint32_t r2, uint32_t r3) {
    asm volatile("stmatrix.sync.aligned.m8n8.x4.shared.b16 [%0], {%1,%2,%3,%4};" ::"r"(a), "r"(r0), "r"(r1), "r"(r2), "r"(r3) : "memory");
}
__device__ __forceinline__ void ldsm4(uint32_t* r, uint32_t a) {
    asm volatile("ldmatrix.sync.aligned.m8n8.x4.shared.b16 {%0,%1,%2,%3}, [%4];" : "=r"(r[0]), "=r"(r[1]), "=r"(r[2]), "=r"(r[3]) : "r"(a) : "memory");
}
__device__ __forceinline__ void ldsm4t(uint32_t* r, uint32_t a) {
    asm volatile("ldmatrix.sync.aligned.m8n8.x4.trans.shared.b16 {%0,%1,%2,%3}, [%4];" : "=r"(r[0]), "=r"(r[1]), "=r"(r[2]), "=r"(r[3]) : "r"(a) : "memory");
}
__device__ __forceinline__ uint32_t ld_rlx(const void* p) { uint32_t v; asm volatile("ld.relaxed.gpu.global.u32 %0, [%1];" : "=r"(v) : "l"(p) : "memory"); return v; }
__device__ __forceinline__ uint32_t ld_acq(const void* p) { uint32_t v; asm volatile("ld.acquire.gpu.global.u32 %0, [%1];" : "=r"(v) : "l"(p) : "memory"); return v; }
__device__ __forceinline__ uint2 ld_rlx2(const void* p) { uint2 v; asm volatile("ld.relaxed.gpu.global.v2.u32 {%0,%1}, [%2];" : "=r"(v.x), "=r"(v.y) : "l"(p) : "memory"); return v; }
__device__ __forceinline__ uint4 ld_rlx4(const void* p) { uint4 v; asm volatile("ld.relaxed.gpu.global.v4.u32 {%0,%1,%2,%3}, [%4];" : "=r"(v.x), "=r"(v.y), "=r"(v.z), "=r"(v.w) : "l"(p) : "memory"); return v; }
__device__ __forceinline__ void st_rlx(void* p, uint32_t v) { asm volatile("st.relaxed.gpu.global.u32 [%0], %1;" ::"l"(p), "r"(v) : "memory"); }
__device__ __forceinline__ void st_rlx2(void* p, uint32_t a, uint32_t b) { asm volatile("st.relaxed.gpu.global.v2.u32 [%0], {%1,%2};" ::"l"(p), "r"(a), "r"(b) : "memory"); }
__device__ __forceinline__ void st_rlx4(void* p, uint32_t a, uint32_t b, uint32_t c, uint32_t d) { asm volatile("st.relaxed.gpu.global.v4.u32 [%0], {%1,%2,%3,%4};" ::"l"(p), "r"(a), "r"(b), "r"(c), "r"(d) : "memory"); }
__device__ __forceinline__ void red_add(uint32_t* p) { asm volatile("red.relaxed.gpu.global.add.u32 [%0], 1;" ::"l"(p) : "memory"); }
__device__ __forceinline__ uint4 ldg_nc(const void* p) { uint4 v; asm volatile("ld.global.nc.v4.u32 {%0,%1,%2,%3}, [%4];" : "=r"(v.x), "=r"(v.y), "=r"(v.z), "=r"(v.w) : "l"(p)); return v; }
__device__ __forceinline__ void sts4(uint32_t a, uint32_t x, uint32_t y, uint32_t z, uint32_t w) { asm volatile("st.shared.v4.u32 [%0], {%1,%2,%3,%4};" ::"r"(a), "r"(x), "r"(y), "r"(z), "r"(w) : "memory"); }
__device__ __forceinline__ void sts2(uint32_t a, uint32_t x, uint32_t y) { asm volatile("st.shared.v2.u32 [%0], {%1,%2};" ::"r"(a), "r"(x), "r"(y) : "memory"); }
__device__ __forceinline__ void sts1(uint32_t a, uint32_t v) { asm volatile("st.shared.u32 [%0], %1;" ::"r"(a), "r"(v) : "memory"); }
__device__ __forceinline__ uint4 lds4(uint32_t a) { uint4 v; asm volatile("ld.shared.v4.u32 {%0,%1,%2,%3}, [%4];" : "=r"(v.x), "=r"(v.y), "=r"(v.z), "=r"(v.w) : "r"(a) : "memory"); return v; }
__device__ __forceinline__ float4 lds4f(uint32_t a) { float4 v; asm volatile("ld.shared.v4.f32 {%0,%1,%2,%3}, [%4];" : "=f"(v.x), "=f"(v.y), "=f"(v.z), "=f"(v.w) : "r"(a) : "memory"); return v; }
__device__ __forceinline__ float2 lds2f(uint32_t a) { float2 v; asm volatile("ld.shared.v2.f32 {%0,%1}, [%2];" : "=f"(v.x), "=f"(v.y) : "r"(a) : "memory"); return v; }
__device__ __forceinline__ float lds1f(uint32_t a) { float v; asm volatile("ld.shared.f32 %0, [%1];" : "=f"(v) : "r"(a) : "memory"); return v; }
__device__ __forceinline__ uint32_t lds1(uint32_t a) { uint32_t v; asm volatile("ld.shared.u32 %0, [%1];" : "=r"(v) : "r"(a) : "memory"); return v; }
__device__ __forceinline__ uint32_t redux_max(uint32_t v) { uint32_t r; asm volatile("redux.sync.max.u32 %0, %1, 0xffffffff;" : "=r"(r) : "r"(v)); return r; }
__device__ __forceinline__ uint32_t poll_all(const uint32_t* p, uint32_t mask, uint32_t want, int& budget) {
    uint32_t v;
#pragma unroll 1
    while (v = ld_acq(p), !__all_sync(0xffffffffu, (v & mask) == want) && --budget > 0) __nanosleep(POLL_NS);
    return v;
}

template <int TA, int TB>
__device__ __forceinline__ void wgmma_n192(float (&d)[96], uint64_t da, uint64_t db, int keep) {
    asm volatile("{\n.reg .pred p;\nsetp.ne.b32 p, %98, 0;\n"
        "wgmma.mma_async.sync.aligned.m64n192k16.f32.bf16.bf16 "
        "{%0, %1, %2, %3, %4, %5, %6, %7, %8, %9, %10, %11, %12, %13, %14, %15, "
        "%16, %17, %18, %19, %20, %21, %22, %23, %24, %25, %26, %27, %28, %29, %30, %31, "
        "%32, %33, %34, %35, %36, %37, %38, %39, %40, %41, %42, %43, %44, %45, %46, %47, "
        "%48, %49, %50, %51, %52, %53, %54, %55, %56, %57, %58, %59, %60, %61, %62, %63, "
        "%64, %65, %66, %67, %68, %69, %70, %71, %72, %73, %74, %75, %76, %77, %78, %79, "
        "%80, %81, %82, %83, %84, %85, %86, %87, %88, %89, %90, %91, %92, %93, %94, %95}, "
        "%96, %97, p, 1, 1, %99, %100;\n}\n"
        : "+f"(d[0]), "+f"(d[1]), "+f"(d[2]), "+f"(d[3]), "+f"(d[4]), "+f"(d[5]), "+f"(d[6]), "+f"(d[7]),
          "+f"(d[8]), "+f"(d[9]), "+f"(d[10]), "+f"(d[11]), "+f"(d[12]), "+f"(d[13]), "+f"(d[14]), "+f"(d[15]),
          "+f"(d[16]), "+f"(d[17]), "+f"(d[18]), "+f"(d[19]), "+f"(d[20]), "+f"(d[21]), "+f"(d[22]), "+f"(d[23]),
          "+f"(d[24]), "+f"(d[25]), "+f"(d[26]), "+f"(d[27]), "+f"(d[28]), "+f"(d[29]), "+f"(d[30]), "+f"(d[31]),
          "+f"(d[32]), "+f"(d[33]), "+f"(d[34]), "+f"(d[35]), "+f"(d[36]), "+f"(d[37]), "+f"(d[38]), "+f"(d[39]),
          "+f"(d[40]), "+f"(d[41]), "+f"(d[42]), "+f"(d[43]), "+f"(d[44]), "+f"(d[45]), "+f"(d[46]), "+f"(d[47]),
          "+f"(d[48]), "+f"(d[49]), "+f"(d[50]), "+f"(d[51]), "+f"(d[52]), "+f"(d[53]), "+f"(d[54]), "+f"(d[55]),
          "+f"(d[56]), "+f"(d[57]), "+f"(d[58]), "+f"(d[59]), "+f"(d[60]), "+f"(d[61]), "+f"(d[62]), "+f"(d[63]),
          "+f"(d[64]), "+f"(d[65]), "+f"(d[66]), "+f"(d[67]), "+f"(d[68]), "+f"(d[69]), "+f"(d[70]), "+f"(d[71]),
          "+f"(d[72]), "+f"(d[73]), "+f"(d[74]), "+f"(d[75]), "+f"(d[76]), "+f"(d[77]), "+f"(d[78]), "+f"(d[79]),
          "+f"(d[80]), "+f"(d[81]), "+f"(d[82]), "+f"(d[83]), "+f"(d[84]), "+f"(d[85]), "+f"(d[86]), "+f"(d[87]),
          "+f"(d[88]), "+f"(d[89]), "+f"(d[90]), "+f"(d[91]), "+f"(d[92]), "+f"(d[93]), "+f"(d[94]), "+f"(d[95])
        : "l"(da), "l"(db), "r"(keep), "n"(TA), "n"(TB));
}
template <int TA, int TB>
__device__ __forceinline__ void wgmma_n128(float (&d)[64], uint64_t da, uint64_t db, int keep) {
    asm volatile("{\n.reg .pred p;\nsetp.ne.b32 p, %66, 0;\n"
        "wgmma.mma_async.sync.aligned.m64n128k16.f32.bf16.bf16 "
        "{%0, %1, %2, %3, %4, %5, %6, %7, %8, %9, %10, %11, %12, %13, %14, %15, "
        "%16, %17, %18, %19, %20, %21, %22, %23, %24, %25, %26, %27, %28, %29, %30, %31, "
        "%32, %33, %34, %35, %36, %37, %38, %39, %40, %41, %42, %43, %44, %45, %46, %47, "
        "%48, %49, %50, %51, %52, %53, %54, %55, %56, %57, %58, %59, %60, %61, %62, %63}, "
        "%64, %65, p, 1, 1, %67, %68;\n}\n"
        : "+f"(d[0]), "+f"(d[1]), "+f"(d[2]), "+f"(d[3]), "+f"(d[4]), "+f"(d[5]), "+f"(d[6]), "+f"(d[7]),
          "+f"(d[8]), "+f"(d[9]), "+f"(d[10]), "+f"(d[11]), "+f"(d[12]), "+f"(d[13]), "+f"(d[14]), "+f"(d[15]),
          "+f"(d[16]), "+f"(d[17]), "+f"(d[18]), "+f"(d[19]), "+f"(d[20]), "+f"(d[21]), "+f"(d[22]), "+f"(d[23]),
          "+f"(d[24]), "+f"(d[25]), "+f"(d[26]), "+f"(d[27]), "+f"(d[28]), "+f"(d[29]), "+f"(d[30]), "+f"(d[31]),
          "+f"(d[32]), "+f"(d[33]), "+f"(d[34]), "+f"(d[35]), "+f"(d[36]), "+f"(d[37]), "+f"(d[38]), "+f"(d[39]),
          "+f"(d[40]), "+f"(d[41]), "+f"(d[42]), "+f"(d[43]), "+f"(d[44]), "+f"(d[45]), "+f"(d[46]), "+f"(d[47]),
          "+f"(d[48]), "+f"(d[49]), "+f"(d[50]), "+f"(d[51]), "+f"(d[52]), "+f"(d[53]), "+f"(d[54]), "+f"(d[55]),
          "+f"(d[56]), "+f"(d[57]), "+f"(d[58]), "+f"(d[59]), "+f"(d[60]), "+f"(d[61]), "+f"(d[62]), "+f"(d[63])
        : "l"(da), "l"(db), "r"(keep), "n"(TA), "n"(TB));
}
template <int TA, int TB>
__device__ __forceinline__ void wgmma_n8(float (&d)[4], uint64_t da, uint64_t db, int keep) {
    asm volatile("{\n.reg .pred p;\nsetp.ne.b32 p, %6, 0;\n"
        "wgmma.mma_async.sync.aligned.m64n8k16.f32.bf16.bf16 "
        "{%0, %1, %2, %3}, "
        "%4, %5, p, 1, 1, %7, %8;\n}\n"
        : "+f"(d[0]), "+f"(d[1]), "+f"(d[2]), "+f"(d[3])
        : "l"(da), "l"(db), "r"(keep), "n"(TA), "n"(TB));
}
__device__ __forceinline__ void wgmma_rs_n128(float (&d)[64], uint32_t a0, uint32_t a1, uint32_t a2, uint32_t a3, uint64_t db) {
    asm volatile("{\n.reg .pred p;\nsetp.ne.b32 p, 1, 0;\n"
        "wgmma.mma_async.sync.aligned.m64n128k16.f32.bf16.bf16 "
        "{%0, %1, %2, %3, %4, %5, %6, %7, %8, %9, %10, %11, %12, %13, %14, %15, "
        "%16, %17, %18, %19, %20, %21, %22, %23, %24, %25, %26, %27, %28, %29, %30, %31, "
        "%32, %33, %34, %35, %36, %37, %38, %39, %40, %41, %42, %43, %44, %45, %46, %47, "
        "%48, %49, %50, %51, %52, %53, %54, %55, %56, %57, %58, %59, %60, %61, %62, %63}, "
        "{%64, %65, %66, %67}, %68, p, 1, 1, 1;\n}\n"
        : "+f"(d[0]), "+f"(d[1]), "+f"(d[2]), "+f"(d[3]), "+f"(d[4]), "+f"(d[5]), "+f"(d[6]), "+f"(d[7]),
          "+f"(d[8]), "+f"(d[9]), "+f"(d[10]), "+f"(d[11]), "+f"(d[12]), "+f"(d[13]), "+f"(d[14]), "+f"(d[15]),
          "+f"(d[16]), "+f"(d[17]), "+f"(d[18]), "+f"(d[19]), "+f"(d[20]), "+f"(d[21]), "+f"(d[22]), "+f"(d[23]),
          "+f"(d[24]), "+f"(d[25]), "+f"(d[26]), "+f"(d[27]), "+f"(d[28]), "+f"(d[29]), "+f"(d[30]), "+f"(d[31]),
          "+f"(d[32]), "+f"(d[33]), "+f"(d[34]), "+f"(d[35]), "+f"(d[36]), "+f"(d[37]), "+f"(d[38]), "+f"(d[39]),
          "+f"(d[40]), "+f"(d[41]), "+f"(d[42]), "+f"(d[43]), "+f"(d[44]), "+f"(d[45]), "+f"(d[46]), "+f"(d[47]),
          "+f"(d[48]), "+f"(d[49]), "+f"(d[50]), "+f"(d[51]), "+f"(d[52]), "+f"(d[53]), "+f"(d[54]), "+f"(d[55]),
          "+f"(d[56]), "+f"(d[57]), "+f"(d[58]), "+f"(d[59]), "+f"(d[60]), "+f"(d[61]), "+f"(d[62]), "+f"(d[63])
        : "r"(a0), "r"(a1), "r"(a2), "r"(a3), "l"(db));
}
__device__ __forceinline__ void wgmma_rs_n192(float (&d)[96], uint32_t a0, uint32_t a1, uint32_t a2, uint32_t a3, uint64_t db) {
    asm volatile("{\n.reg .pred p;\nsetp.ne.b32 p, 1, 0;\n"
        "wgmma.mma_async.sync.aligned.m64n192k16.f32.bf16.bf16 "
        "{%0, %1, %2, %3, %4, %5, %6, %7, %8, %9, %10, %11, %12, %13, %14, %15, "
        "%16, %17, %18, %19, %20, %21, %22, %23, %24, %25, %26, %27, %28, %29, %30, %31, "
        "%32, %33, %34, %35, %36, %37, %38, %39, %40, %41, %42, %43, %44, %45, %46, %47, "
        "%48, %49, %50, %51, %52, %53, %54, %55, %56, %57, %58, %59, %60, %61, %62, %63, "
        "%64, %65, %66, %67, %68, %69, %70, %71, %72, %73, %74, %75, %76, %77, %78, %79, "
        "%80, %81, %82, %83, %84, %85, %86, %87, %88, %89, %90, %91, %92, %93, %94, %95}, "
        "{%96, %97, %98, %99}, %100, p, 1, 1, 1;\n}\n"
        : "+f"(d[0]), "+f"(d[1]), "+f"(d[2]), "+f"(d[3]), "+f"(d[4]), "+f"(d[5]), "+f"(d[6]), "+f"(d[7]),
          "+f"(d[8]), "+f"(d[9]), "+f"(d[10]), "+f"(d[11]), "+f"(d[12]), "+f"(d[13]), "+f"(d[14]), "+f"(d[15]),
          "+f"(d[16]), "+f"(d[17]), "+f"(d[18]), "+f"(d[19]), "+f"(d[20]), "+f"(d[21]), "+f"(d[22]), "+f"(d[23]),
          "+f"(d[24]), "+f"(d[25]), "+f"(d[26]), "+f"(d[27]), "+f"(d[28]), "+f"(d[29]), "+f"(d[30]), "+f"(d[31]),
          "+f"(d[32]), "+f"(d[33]), "+f"(d[34]), "+f"(d[35]), "+f"(d[36]), "+f"(d[37]), "+f"(d[38]), "+f"(d[39]),
          "+f"(d[40]), "+f"(d[41]), "+f"(d[42]), "+f"(d[43]), "+f"(d[44]), "+f"(d[45]), "+f"(d[46]), "+f"(d[47]),
          "+f"(d[48]), "+f"(d[49]), "+f"(d[50]), "+f"(d[51]), "+f"(d[52]), "+f"(d[53]), "+f"(d[54]), "+f"(d[55]),
          "+f"(d[56]), "+f"(d[57]), "+f"(d[58]), "+f"(d[59]), "+f"(d[60]), "+f"(d[61]), "+f"(d[62]), "+f"(d[63]),
          "+f"(d[64]), "+f"(d[65]), "+f"(d[66]), "+f"(d[67]), "+f"(d[68]), "+f"(d[69]), "+f"(d[70]), "+f"(d[71]),
          "+f"(d[72]), "+f"(d[73]), "+f"(d[74]), "+f"(d[75]), "+f"(d[76]), "+f"(d[77]), "+f"(d[78]), "+f"(d[79]),
          "+f"(d[80]), "+f"(d[81]), "+f"(d[82]), "+f"(d[83]), "+f"(d[84]), "+f"(d[85]), "+f"(d[86]), "+f"(d[87]),
          "+f"(d[88]), "+f"(d[89]), "+f"(d[90]), "+f"(d[91]), "+f"(d[92]), "+f"(d[93]), "+f"(d[94]), "+f"(d[95])
        : "r"(a0), "r"(a1), "r"(a2), "r"(a3), "l"(db));
}

template <int HS>
__device__ __forceinline__ void attn_pair(const uint32_t* q, const uint32_t* k, const uint32_t* v, const uint32_t* kh, const uint32_t* vh,
                                          const float* fu, const float* fn, const float* rk, float bias0, float bias1, uint32_t mU, uint32_t zero, const float* ci, uint32_t* o) {
    float s0[2][4] = {}, s1[2][4] = {}, s2[2][4] = {};
#pragma unroll
    for (int n = 0; n < 4; n++) {
        const int hd = n & 1, a = 8 * hd + 2 * (n & 2);
        mma16816(s1[hd], q[a], q[a + 1], q[a + 2], q[a + 3], k[a], k[a + 2]);
        mma16816(s2[hd], q[a], q[a + 1], q[a + 2], q[a + 3], k[a + 1], k[a + 3]);
    }
#pragma unroll
    for (int n = 0; n < 4; n++) {
        const int hd = n & 1, a = 8 * hd + 2 * (n & 2);
        mma16816(s0[hd], q[a], q[a + 1], q[a + 2], q[a + 3], kh[HS * (a / 2)], kh[HS * (a / 2 + 1)]);
    }
    float e[2][4], m[2][2];
#pragma unroll
    for (int hd = 0; hd < 2; hd++) {
        e[hd][2] = fmaf(s1[hd][2], fu[2], s2[hd][2] * fn[2]); e[hd][3] = fmaf(s1[hd][3], fu[3], s2[hd][3] * fn[3]);
        e[hd][0] = fmaf(s0[hd][0], fu[0], fmaf(s1[hd][0], fn[0], bias0)); e[hd][1] = fmaf(s0[hd][1], fu[1], fmaf(s1[hd][1], fn[1], bias1));
        m[hd][1] = fmaxf(e[hd][2], e[hd][3]); m[hd][0] = fmaxf(e[hd][0], e[hd][1]);
    }
#pragma unroll
    for (int x = 1; x < 3; x++)
#pragma unroll
        for (int n = 0; n < 4; n++) m[n & 1][1 - (n >> 1)] = fmaxf(m[n & 1][1 - (n >> 1)], __shfl_xor_sync(0xffffffffu, m[n & 1][1 - (n >> 1)], x));
#pragma unroll
    for (int hd = 0; hd < 2; hd++) {
#pragma unroll
        for (int n = 0; n < 4; n++) e[hd][n] = ex2(e[hd][n] - m[hd][n >> 1]);
        float sum[4] = {};
        mma1688(sum, pack_bf16(e[hd][0], e[hd][1]), pack_bf16(e[hd][2], e[hd][3]), 0x3f803f80u);
        const float i0 = rcp(sum[0]), i1 = rcp(sum[2]);
        const uint32_t plo = pack_bf16(e[hd][0] * rk[0] * i0, e[hd][1] * rk[1] * i0), phi = pack_bf16(e[hd][2] * rk[2] * i1, e[hd][3] * rk[3] * i1);
        const uint32_t z0 = plo & zero, z1 = phi & zero;
        const uint32_t a0 = plo & ~mU, a1 = phi & mU, a3 = phi & ~mU, b0 = plo & mU;
#pragma unroll
        for (int jj = 0; jj < 4; jj++) {
            float c[4];
            asm volatile("mma.sync.aligned.m16n8k16.row.col.f32.bf16.bf16.f32 {%0,%1,%2,%3}, {%4,%5,%6,%7}, {%8,%9}, {%10,%11,%12,%13};"
                         : "=f"(c[0]), "=f"(c[1]), "=f"(c[2]), "=f"(c[3])
                         : "r"(a0), "r"(a1), "r"(z0), "r"(a3), "r"(v[8 * hd + 2 * jj]), "r"(v[8 * hd + 2 * jj + 1]), "f"(ci[0]), "f"(ci[1]), "f"(ci[2]), "f"(ci[3]));
            mma1688(c, b0, z1, vh[HS * (4 * hd + jj)]);
            o[8 * hd + 2 * jj] = pack_bf16(c[0], c[1]); o[8 * hd + 2 * jj + 1] = pack_bf16(c[2], c[3]);
        }
    }
}

__device__ __forceinline__ uint32_t norm_pair(uint32_t u, float m, float rinv) {
    const uint32_t d = pack_bf16(bf_lo(u) - m, bf_hi(u) - m);
    return max(pack_bf16(bf_lo(d) * rinv, bf_hi(d) * rinv), 1u);
}

__global__ void __launch_bounds__(512, 1)
fused_kernel(const __grid_constant__ CUtensorMap mx, const __grid_constant__ CUtensorMap mw, const __grid_constant__ CUtensorMap mwo,
             const __grid_constant__ CUtensorMap mout, const __grid_constant__ CUtensorMap mgu, const __grid_constant__ CUtensorMap mwd,
             const __grid_constant__ CUtensorMap mo,
             const __nv_bfloat16* __restrict__ x, const __nv_bfloat16* __restrict__ wr, Scratch* __restrict__ scr, int swap_gu, const Weights pf) {
    extern __shared__ __align__(1024) uint8_t smem[];
    const uint32_t sb = smem_u32(smem);
    const uint32_t bars = sb + OFF_BAR;
    const int tid = threadIdx.x, lane = tid & 31, warp = __shfl_sync(0xffffffffu, tid >> 5, 0);
    const uint32_t sd = (sb & 0x3FFFF) >> 4;
    const int hp = blockIdx.x & 1, cl = blockIdx.x >> 1;
    int pr = cl - 4 + (max(cl - 36, 0) * 37 >> 8);
    asm("{\n.reg .pred p;\nsetp.lt.s32 p, %1, 4;\nselp.s32 %0, %2, %0, p;\n}" : "+r"(pr) : "r"(cl), "r"(39 + 8 * cl));
    const int b = pr * 2 + hp, mt = pr >> 3, p = pr & 7, nt = 2 * p + hp, rh = p & 1, cb = (p & 6) + hp;
    const int par = mt >> 2, j0 = (mt & 3) * 256;
    int budget = BUDGET;

    TSC(tid == 0, 0);
    if (b < 128 && tid >= 32 && tid < 112) {
        const char* a = tid < 64 ? (const char*)x + (size_t)(16 * b + ((tid >> 1) & 15)) * 2048 + (tid & 1) * 128 : pf.wqkv + (size_t)b * 6144 + (tid - 64) * 128;
        asm volatile("prefetch.global.L2 [%0];" ::"l"(a));
    }
    auto load_w = [&](int k, int s) {
        const uint32_t full = bars + 8 * (B_WFULL + s);
        mbar_expect_tx(full, W_BYTES);
        tma_3d(sb + OFF_W + s * W_BYTES, &mw, full, nt * 64, k * 64, 0);
    };
    auto load_x = [&](int n) {
        const int w = n & 1, j = n < 4 ? (n >> 1) + 4 : (n >> 1) - 2;
        const uint32_t full = bars + 8 * (B_XFULL + w * 6 + 5 - j);
        mbar_expect_tx(full, BOX);
        tma_4d(sb + w * OFF_X1 + j * BOX, &mx, full, par * 1024 + (n >> 2) * 64, 0, (j0 + w * 128) >> 5, (~n >> 1) & 1);
    };
    if (warp < NBAR / 6 && elect_one()) {
        const uint32_t cnt = warp < B_WEMPTY / 6 ? 1 : warp < B_G1DONE / 6 ? 2 : warp < B_STAGED / 6 ? 4 : 8;
#pragma unroll
        for (int i = 0; i < 6; i++) mbar_init(bars + 48 * warp + 8 * i, cnt);
        asm volatile("fence.mbarrier_init.release.cluster;" ::: "memory");
        if (warp == 0 && b < 128) { load_x(0); load_w(0, 2); }
    }
    __syncthreads();

    if (b >= 128) {
        const int hc = b - 128, g = lane >> 2, t = lane & 3;
        if (warp < 12) {
            const int n = warp / 3, part = warp - 3 * n;
            const uint32_t ep = ld_rlx(&scr->epoch[0]) + 1;
            auto load = [&](int k) {
                const uint32_t full = bars + 8 * (2 * n + (k & 1));
                mbar_expect_tx(full, W_BYTES);
                tma_3d(sb + (2 * n + (k & 1)) * W_BYTES, &mw, full, (4 * hc + n) * 64, k * 64, 0);
            };
            if (part == 0 && elect_one()) { load(0); load(1); }
            __syncwarp();
            float c0[4] = {0.f, 0.f, 0.f, 0.f}, c1[4] = {0.f, 0.f, 0.f, 0.f};
            const uint32_t sel = g == 0 ? 0x3f80u : g == 1 ? 0x3f800000u : 0u;
            const uint32_t a = sb + 2 * n * W_BYTES + part * BOX + t * 256 + ((g ^ (2 * t)) << 4);
#pragma unroll 1
            for (int k = 0; k < 16; k++) {
                mbar_wait(bars + 8 * (2 * n + (k & 1)), (k >> 1) & 1, budget);
                uint4 v[8], u[8];
#pragma unroll
                for (int i = 0; i < 8; i++) { v[i] = lds4(a + (k & 1) * W_BYTES + i * 1024); u[i] = lds4(((a + 128) ^ 16) + (k & 1) * W_BYTES + i * 1024); }
#pragma unroll
                for (int i = 0; i < 8; i++) { mma16816(c0, v[i].x, v[i].y, u[i].x, u[i].y, sel, sel); mma16816(c1, v[i].z, v[i].w, u[i].z, u[i].w, sel, sel); }
                bar_sync(1 + n, 96);
                if (part == 0 && k < 14 && elect_one()) load(k + 2);
                __syncwarp();
            }
            if (t == 0) {
#pragma unroll
                for (int r = 0; r < 3; r++) {
                    const uint32_t q0 = pack_bf16(c0[0], c0[1]), q1 = pack_bf16(c0[2], c0[3]), q2 = pack_bf16(c1[0], c1[1]), q3 = pack_bf16(c1[2], c1[3]);
                    st_rlx4(&scr->cs[4 * hc + n][16 + (part * 8 + g) * 32 + r * 4], q0, q1, q2, q3);
                    c0[0] -= bf_lo(q0); c0[1] -= bf_hi(q0); c0[2] -= bf_lo(q1); c0[3] -= bf_hi(q1);
                    c1[0] -= bf_lo(q2); c1[1] -= bf_hi(q2); c1[2] -= bf_lo(q3); c1[3] -= bf_hi(q3);
                }
            }
            bar_sync(7, 384);
            if (tid == 0) { fence_gpu(); st_rlx(&scr->csflag[hc], ep); }
            TSC(tid == 0, 19);
        }
        if (warp < 8) TS_END();
        return;
    }
    asm volatile("barrier.cluster.arrive.relaxed.aligned;" ::: "memory");

    const int kc = b >> 4, c2 = b & 15;
    if (warp >= 12) {
        reg_dec<24>();
        if (warp == 12) {
            if (elect_one()) {
#pragma unroll 1
                for (int n = 1; n < 12; n++) {
                    load_x(n);
                    if (n == ROWS_AT) { mbar_expect_tx(bars + 8 * B_ROW, 4 * BOX); bulk_g2s(sb + OFF_FR, x + (size_t)b * 16 * 1024, 4 * BOX, bars + 8 * B_ROW); }
                    if (n == 3 || n == 7) load_w((n + 1) >> 2, n >> 2);
                }
                int s = 2; uint32_t ph = 0;
#pragma unroll 1
                for (int k = 3; k < 16; k++) {
                    mbar_wait(bars + 8 * (B_WEMPTY + s), ph, budget);
                    load_w(k, s);
                    if (++s == 3) s = 0;
                    if (s == 2) ph ^= 1;
                }
                s = 2;
#pragma unroll 1
                for (int i = 0; i < 16; i++) {
                    mbar_wait(bars + 8 * (i < 2 ? B_WEMPTY + i : i < 4 ? B_G1DONE : i < 6 ? B_F1DONE : B_WOEMPTY + s), i >= 12, budget);
                    if (i == 0) {
                        mbar_expect_tx(bars + 8 * B_XT, 4 * BOX);
#pragma unroll 1
                        for (int n = 0; n < 4; n++)
                            tma_4d(sb + (n >> 1) * OFF_X1 + (n & 1) * BOX, &mx, bars + 8 * B_XT, par * 1024 + cb * 128 + (n & 1) * 64, 0, (j0 + rh * 128) >> 5, 1 - (n >> 1));
                    }
                    const uint32_t full = bars + 8 * (B_WOFULL + s);
                    mbar_expect_tx(full, 2 * BOX);
                    tma_3d(sb + OFF_WO + s * 2 * BOX, &mwo, full, 0, ((2 * p + (i < 2 ? i ^ hp : i)) & 15) * 64, cb * 2);
                    TSC(TIMING % 10 == 4, 48 + i);
                    if (++s == 6) s = 0;
                }
            }
        } else {
            bar_sync(8, 224);
            const uint32_t ep = __shfl_sync(0xffffffffu, lds1(sb + OFF_EP), 0);
            if (warp == 13) {
                cluster_wait();
                if (elect_one()) {
                    int j = 4, q = 0, left = BUDGET; uint32_t ph = 0;
#pragma unroll 1
                    for (int n = 6; n < 32; n++) {
                        mbar_wait(bars + 8 * (B_XEMPTY + j), ph, left);
                        tma_4d_mc(sb + hp * OFF_X1 + j * BOX, &mx, bars + 8 * (B_XFULL + hp * 6 + 5 - j), par * 1024 + (n >> 1) * 64, 0, (j0 + hp * 128) >> 5, ~n & 1);
                        if (++j == 6) j = 0;
                        if (j == 4) ph ^= 1;
#pragma unroll 1
                        for (; q < (PF_RATE * (n - PF_START) >> 3) && q < 18 + PF_NW; q++) {
                            const int u = q - PF_NW;
                            if (u < 0) bulk_pf(pf.wqkv + (size_t)(1024 + 128 * u + b) * 6144, 6144);
                            else if (u < 16) bulk_pf((b < 64 ? pf.wg : pf.wu) + (size_t)(u * 64 + (b & 63)) * 7168, 7168);
                            else bulk_pf(pf.wo + (size_t)((u - 16) * 128 + b) * 8192, 8192);
                        }
                    }
                }
                __syncwarp();
                uint32_t* hs = &scr->halo[b - 16][lane * 4];
                int tries = BUDGET;
#pragma unroll 1
                for (int c = 0; c < 4; c += 2) {
                    uint4 v0 = make_uint4(0, 0, 0, 0), v1 = v0;
                    if (j0) {
#pragma unroll 1
                        do { v0 = ld_rlx4(hs + c * 128); v1 = ld_rlx4(hs + c * 128 + 128); } while ((v0.x == 0 || v1.x == 0) && --tries > 0);
                        st_rlx(hs + c * 128, 0); st_rlx(hs + c * 128 + 128, 0);
                    }
                    __syncwarp();
                    stsm4(sb + OFF_HIN + c * 512 + lane * 16, v0.x, v0.y, v0.z, v0.w);
                    stsm4(sb + OFF_HIN + c * 512 + 512 + lane * 16, v1.x, v1.y, v1.z, v1.w);
                }
                bar_arrive(11, 64);
                TSC(lane == 0, 31);
                const int src = ((mt * 2 + rh) * 2 + 1 - hp) * 1024;
                if (elect_one()) {
                    const uint32_t* fl = &scr->oflag[mt * 2 + 1 - hp][0];
                    const uint32_t inv = (ep & 1) - 1;
                    uint32_t ready = 0, ph = 0;
                    int s = 4;
#pragma unroll 1
                    for (int i = 2; i < 16; i++) {
                        const int kb = (2 * p + i) & 15;
#pragma unroll 1
                        while (!((ready >> kb) & 1) && --budget > 0) ready = ld_rlx(fl) ^ inv;
                        TSC(i == 2, 30);
                        mbar_wait(bars + 8 * (B_OEMPTY + s), ph, budget);
                        tma_2d_mc(sb + hp * OFF_X1 + s * BOX, &mo, bars + 8 * (B_OFULL + hp * 6 + s), 0, src + kb * 64);
                        TSC(TIMING % 10 == 4 && hp == 0, 32 + i);
                        if (++s == 6) s = 0;
                        if (s == 4) ph ^= 1;
                    }
                }
            } else if (warp == 14) {
                if (elect_one()) {
                    uint32_t s8 = 0, ph = 0;
                    int tries = BUDGET;
                    const uint32_t* act = scr->act[ep & 1];
                    auto counted = [&](int c, uint32_t n) {
#pragma unroll 1
                        while (ld_rlx(&scr->cnt[c][0]) != ep * n && --tries > 0) __nanosleep(POLL_NS);
                    };
                    auto weights = [&](const CUtensorMap* m, int c0, int c1, int c2_) {
                        mbar_wait(bars + 8 * B_FEMPTY + s8, ph, budget);
                        mbar_expect_tx(bars + 8 * B_FFULL + s8, F_BYTES);
                        tma_3d(sb + OFF_FS + s8 * (F_BYTES / 8), m, bars + 8 * B_FFULL + s8, c0, c1, c2_);
                    };
                    if (b < 112) {
                        counted(8, 32);
                        TS(26);
#pragma unroll 1
                        for (int q = 0; q < 16; q++) {
                            weights(&mgu, b * 32, q * 64, 0);
                            bulk_g2s(sb + OFF_FS + BOX + s8 * (F_BYTES / 8), act + 14336 + q * 256, 1024, bars + 8 * B_FFULL + s8);
                            if (q >= 8) bulk_pf(pf.wd + (size_t)((q - 8) * 112 + b) * 8192, 8192);
                            s8 += 8;
                            if (s8 == 40) { s8 = 0; ph ^= 1; }
                        }
                    }
#pragma unroll 1
                    for (int q = -3; q < 7; q++) {
                        if (q == 0) { counted(kc, 28); TS(29); }
                        if ((unsigned)q >= 3) weights(&mwd, 0, kc * 448 + (q < 0 ? q + 3 : q) * 64, c2);
                        if (q >= 0) bulk_g2s(sb + OFF_FS + BOX + s8 * (F_BYTES / 8), act + (kc * 7 + q) * 256, 1024, bars + 8 * B_FFULL + s8);
                        s8 += 8;
                        if (s8 == 24) { s8 = 0; if ((unsigned)q >= 3) ph ^= 1; }
                    }
                }
            } else {
                mbar_wait(bars + 8 * B_ROW, 0, budget);
                uint8_t* oz = scr->o + ((size_t)mt * 64 + nt) * BOX + lane * 16;
#pragma unroll 1
                for (int i = 0; i < ZF_N; i++) { st_rlx4(oz + (i >> 4) * 16 * BOX + (i & 15) * 512, 0, 0, 0, 0); if ((i & 3) == 3) __nanosleep(ZF_NS); }
                __syncwarp();
                fence_gpu();
                mbar_wait(bars + 8 * B_RDONE, 0, budget);
                int tries = BUDGET;
#pragma unroll 1
                for (int i = lane; i < 88; i += 32) {
                    const uint2* rp = &scr->row[2 * (j0 - 8 + i) + par];
                    uint2 v0, v1, v2;
#pragma unroll 1
                    do { v0 = ld_rlx2(rp + (j0 + i < 8 ? 16 : 0)); v1 = ld_rlx2(rp + 176); v2 = ld_rlx2(rp + 352); } while ((((v0.y ^ ep) | (v1.y ^ ep) | (v2.y ^ ep)) & 31) && --tries > 0);
                    sts2(sb + OFF_STAT + i * 8, (v0.x << 16) ^ 0x80000000u, __float_as_uint(rcp(bf_hi(v0.x))));
                    sts2(sb + OFF_STAT + i * 8 + 704, (v1.x << 16) ^ 0x80000000u, __float_as_uint(rcp(bf_hi(v1.x))));
                    sts2(sb + OFF_STAT + i * 8 + 1408, (v2.x << 16) ^ 0x80000000u, __float_as_uint(rcp(bf_hi(v2.x))));
                }
                __syncwarp();
                poll_all(&scr->csflag[lane & 3], ~0u, ep, budget);
                if (elect_one()) {
                    fence_async_gmem();
                    mbar_expect_tx(bars + 8 * B_AUX, CS_BYTES);
                    bulk_g2s(sb + OFF_CS, scr->cs[nt], CS_BYTES, bars + 8 * B_AUX);
                    TS(21);
                    mbar_expect_tx(bars + 8 * (B_OFULL + 3), BOX); mbar_expect_tx(bars + 8 * (B_OFULL + 9), BOX);
#pragma unroll 1
                    for (int v = 0; v < 2; v++) {
                        const uint32_t ring = sb + v * OFF_X1 + 2 * BOX, fb = bars + 8 * (B_OFULL + v * 6 + 2);
                        mbar_wait(bars + 8 * (B_STAGED + v), 0, budget);
                        asm volatile("red.relaxed.gpu.global.xor.b32 [%0], %1;" ::"l"(&scr->oflag[mt * 2 + 1 - v][0]), "r"(1u << nt) : "memory");
                        TS(13 + 2 * v);
                        mbar_arrive(fb);
                        mbar_wait(bars + 8 * B_G1DONE, 0, budget);
                        bulk_s2c(mapa(ring + BOX, hp ^ 1), ring, BOX, mapa(fb + 8, hp ^ 1));
                        if (v == 0) mbar_wait(bars + 8 * B_FREED, 0, budget);
#pragma unroll
                        for (int n = 0; n < 4; n++) {
                            mbar_expect_tx(bars + 8 * (B_OFULL + (n >> 1) * 6 + 4 + (n & 1)) - v * 32, BOX);
                            mbar_arrive_at(mapa(bars + 8 * B_OEMPTY, n >> 1) + (4 + (n & 1)) * 8 - v * 32);
                        }
                    }
                }
            }
        }
    } else if (warp >= 8) {
        reg_dec<40>();
        const int wq = warp - 8, ta = tid - 256;
        const uint32_t rbuf = sb + OFF_FR + wq * BOX, rbar = bars + 8 * B_ROW;
        const uint4 wv = ldg_nc(wr + ta * 8);
        if (ta == 0) sts1(sb + OFF_EP, ld_rlx(&scr->epoch[0]) + 1);
        sts4(sb + OFF_STAT + ta * 16, wv.x, wv.y, wv.z, wv.w);
        bar_sync(8, 224);
        const uint32_t ep = __shfl_sync(0xffffffffu, lds1(sb + OFF_EP), 0);
        {
            const int s = b * 16 + wq * 4 + (lane >> 3);
            if ((lane & 7) == 0) st_rlx2(&scr->row[s], 0, ep - 1);
            float sw = 0.f;
#pragma unroll 1
            for (int i = 0; i < 16; i++) { const uint32_t q = lds1(sb + OFF_STAT + i * 128 + lane * 4); sw += bf_lo(q) + bf_hi(q); }
#pragma unroll 1
            for (int o = 16; o > 0; o >>= 1) sw += __shfl_xor_sync(0xffffffffu, sw, o);
            float s1 = 0.f, s2 = 0.f, sr = 0.f;
            const uint32_t xa = rbuf + (lane >> 3) * 2048 + (lane & 7) * 16, wa = sb + OFF_STAT + (lane & 7) * 16;
            mbar_wait(rbar, 0, budget);
            TSC(ta == 0, 17);
            uint4 u = lds4(xa), w4 = lds4(wa);
#pragma unroll kStatsUnroll
            for (int i = 1; i <= 16; i++) {
                const uint32_t o = (i * 128) & 2047;
                const uint4 un = lds4(xa + o), wn = lds4(wa + o);
#pragma unroll
                for (int c = 0; c < 4; c++) {
                    const float a0 = bf_lo((&u.x)[c]), a1 = bf_hi((&u.x)[c]);
                    s1 += a0; s2 = fmaf(a0, a0, s2); sr = fmaf(a0, bf_lo((&w4.x)[c]), sr);
                    s1 += a1; s2 = fmaf(a1, a1, s2); sr = fmaf(a1, bf_hi((&w4.x)[c]), sr);
                }
                u = un; w4 = wn;
            }
#pragma unroll 1
            for (int o = 1; o < 8; o <<= 1) {
                s1 += __shfl_xor_sync(0xffffffffu, s1, o); s2 += __shfl_xor_sync(0xffffffffu, s2, o); sr += __shfl_xor_sync(0xffffffffu, sr, o);
            }
            const float mean = s1 * (1.f / 1024.f), mb = bf16r(mean);
            float var = fmaf(-mean, mean, s2 * (1.f / 1024.f));
            sr = fmaf(-mb, sw, sr);
            if (__builtin_expect(__any_sync(0xffffffffu, mean * mean > 256.f * var), 0)) {
                float a2 = 0.f, ar = 0.f;
#pragma unroll 1
                for (int i = 0; i < 64; i++) {
                    const uint32_t o = (i >> 2) * 128 + (i & 3) * 4, q1 = lds1(xa + o), q2 = lds1(wa + o);
                    a2 = fmaf(bf_lo(q1) - mean, bf_lo(q1) - mean, fmaf(bf_hi(q1) - mean, bf_hi(q1) - mean, a2));
                    ar = fmaf(bf_lo(q1) - mb, bf_lo(q2), fmaf(bf_hi(q1) - mb, bf_hi(q2), ar));
                }
#pragma unroll 1
                for (int o = 1; o < 8; o <<= 1) { a2 += __shfl_xor_sync(0xffffffffu, a2, o); ar += __shfl_xor_sync(0xffffffffu, ar, o); }
                var = a2 * (1.f / 1024.f); sr = ar;
            }
            float den;
            asm("sqrt.approx.f32 %0, %1;" : "=f"(den) : "f"(bf16r(bf16r(var) + 1e-5f)));
            const uint32_t st = pack_bf16(mb, den);
            const uint32_t rb = pack_bf16(0.f, sr * rcp(bf_hi(st)) + 0.f);
            uint32_t ord = (int)rb < 0 ? ~rb & 0xffff0000u : rb | 0x80000000u;
            if ((rb & 0x7fffffffu) > 0x7f800000u) ord = 0;
            if ((lane & 7) == 0) st_rlx2(&scr->row[s], st, ord | ((2047 - s) << 5) | (ep & 31));
            __syncwarp();
            if (lane < 7) mbar_arrive(bars + 8 * (lane < 5 ? B_FEMPTY + lane : B_RDONE));
        }
        TSC(ta == 0, 18);
        if ((b >> 3) == 14) {
            const uint32_t gm = sb + OFF_E, cnt = gm + 64, res = gm + 80, list = gm + 128;
            uint32_t kv[16];
            int tries = BUDGET;
#pragma unroll 1
            do {
                uint32_t bad = 0;
#pragma unroll
                for (int n = 0; n < 16; n++) kv[n] = ld_rlx(&scr->row[n * 128 + ta].y);
#pragma unroll
                for (int n = 0; n < 16; n++) bad |= kv[n] ^ ep;
                if ((bad & 31) == 0) break;
            } while (--tries > 0);
            __syncwarp();
            TSC(ta == 0, 26);
            uint32_t m = 0;
#pragma unroll
            for (int n = 0; n < 16; n++) m = max(m, kv[n]);
            uint32_t gmax = m;
#pragma unroll
            for (int o = 1; o < 8; o <<= 1) gmax = max(gmax, __shfl_xor_sync(0xffffffffu, gmax, o));
            sts1(gm + (ta >> 3) * 4, gmax);
            sts1(cnt, 0);
            bar_sync(12, 128);
            const uint32_t c = lds1(gm + (lane & 15) * 4);
            int rank = 0;
#pragma unroll
            for (int i = 0; i < 2; i++) { const uint4 q = lds4(gm + (lane >> 4) * 32 + i * 16); rank += (q.x > c) + (q.y > c) + (q.z > c) + (q.w > c); }
            rank += __shfl_xor_sync(0xffffffffu, rank, 16);
            const uint32_t thr = redux_max(rank == 7 ? c : 0u);
#pragma unroll 1
            while (m >= thr) {
                uint32_t at, m2 = 0;
                asm volatile("atom.shared.add.u32 %0, [%1], 1;" : "=r"(at) : "r"(cnt) : "memory");
#pragma unroll
                for (int n = 0; n < 16; n++) m2 = max(m2, kv[n] < m ? kv[n] : 0u);
                sts1(list + at * 4, m);
                if (m2 == 0) break;
                m = m2;
            }
            bar_sync(12, 128);
            const int nc = lds1(cnt);
#pragma unroll 1
            for (int i = ta >> 3; i < ((nc + 3) & ~3); i += 16) {
                const uint32_t ki = lds1(list + i * 4);
                int r = 0;
#pragma unroll 1
                for (int n = lane & 7; n < nc; n += 8) r += lds1(list + n * 4) > ki;
                __syncwarp();
#pragma unroll
                for (int o = 1; o < 8; o <<= 1) r += __shfl_xor_sync(0xffffffffu, r, o);
                if (r == (b & 7) && i < nc) sts1(res, ki);
            }
            bar_sync(12, 128);
            const uint32_t k0 = lds1(res);
            const int r0 = 2047 - ((k0 >> 5) & 2047);
            TSC(ta == 0, 22);
            if (ta == 0) st_rlx(&scr->sel[b & 7], k0);
            const uint4 v0 = ldg_nc(x + (size_t)r0 * 1024 + ta * 8);
            const uint32_t s0 = ld_rlx(&scr->row[r0]);
            const float m0 = bf_lo(s0), i0 = rcp(bf_hi(s0));
            const int ao = 14336 + (ta >> 3) * 256 + (b & 7) * 32 + ((ta ^ b) & 7) * 4;
            st_rlx4(scr->act[ep & 1] + ao, norm_pair(v0.x, m0, i0), norm_pair(v0.y, m0, i0), norm_pair(v0.z, m0, i0), norm_pair(v0.w, m0, i0));
            __syncwarp();
            if (lane == 0) red_add(&scr->cnt[8][tries >> 30]);
            st_rlx4(scr->act[~ep & 1] + ao, 0, 0, 0, 0);
        }
        uint32_t s8 = 0, fph = 0, own = 0; float sig = 0.f;
        const uint32_t chk = __shfl_sync(0xffffffffu, sb + OFF_FS + BOX + lane * 32 + (lane & 28), lane);
        int left = BUDGET;
#pragma unroll 1
        for (int ph = 0; ph < 2; ph++) {
            if (ph || b < 112) {
                float acc[4] = {0.f, 0.f, 0.f, 0.f};
                const uint32_t alo = sd + (ph ? dlo(OFF_FS, 8192) : dlo(OFF_FS, 4096)), ahi = ph ? dhi(1024, 1) : dhi(512, 2), astep = ph ? 128 : 64;
                const uint32_t bhi = ph ? dhi(128, 0) : dhi(1024, 1), bstep = ph ? 16 : 2, wrap = ph ? 24 : 40;
                uint32_t prev = 0, prev2 = 0;
                if (ph) mbar_wait(bars + 8 * FFN2_GATE, 0, left);
#pragma unroll 1
                for (int q = ph ? 7 : 16; q > 0; q--) {
                    const uint32_t da = alo + s8 * (F_BYTES >> 7), db = sd + dlo(OFF_FS + BOX, 128) + s8 * (F_BYTES >> 7);
                    mbar_wait_hot(bars + 8 * B_FFULL + s8, fph, left);
                    if (__builtin_expect(__any_sync(0xffffffffu, lds1(chk + s8 * (F_BYTES / 8)) == 0), 0)) {
                        int tries = BUDGET;
#pragma unroll 1
                        for (int n = lane * 4 + (left >> 30); n < 256; n += 128) {
                            uint4 v;
#pragma unroll 1
                            do { v = ld_rlx4(scr->act[ep & 1] + ((ph ? kc * 7 + 7 : 72) - q) * 256 + n); } while (v.x == 0 && --tries > 0);
                            __syncwarp();
                            sts4(sb + OFF_FS + BOX + s8 * (F_BYTES / 8) + n * 4, v.x, v.y, v.z, v.w);
                        }
                        NRETRY();
                        fence_async_smem();
                        __syncwarp();
                    }
                    TSC(TIMING % 10 == 3 && ta == 0, 32 + (ph ? 23 : 16) - q);
                    wg_fence();
#pragma unroll
                    for (int j = 0; j < 4; j++) wgmma_n8<1, 0>(acc, mkdesc(da + j * astep, ahi), mkdesc(db + j * bstep, bhi), 1);
                    wg_commit();
                    prev2 = prev;
                    if (lane == 0) prev = bars + 8 * B_FEMPTY + s8;
                    wg_wait<1>();
                    if (ph) { wg_wait<0>(); prev2 = prev; }
                    if (prev2) mbar_arrive(prev2);
                    s8 += 8;
                    if (s8 == wrap) { s8 = 0; fph ^= 1; }
                }
                wg_wait<0>();
                const int ln = lane + (left >> 30);
                if (ph == 0) {
                    if (prev) mbar_arrive(prev);
                    const bool second = (wq >= 2) != (swap_gu != 0);
                    const uint32_t xa = sb + OFF_GU + ((wq & 1) * 32 + ln) * 16;
                    if (second) sts4(xa, __float_as_uint(acc[0]), __float_as_uint(acc[1]), __float_as_uint(acc[2]), __float_as_uint(acc[3]));
                    bar_sync(12, 128);
                    if (!second) {
                        const float4 up = lds4f(xa);
                        float hv[4];
#pragma unroll
                        for (int c = 0; c < 4; c++) { const float ga = bf16r(acc[c]); hv[c] = bf16r(ga * sigmoidf(ga)) * bf16r((&up.x)[c]); }
                        const int ao = (b * 4 + (wq & 1) * 2) * 32 + ln;
                        st_rlx(scr->act[ep & 1] + ao, max(movm(pack_bf16(hv[0], hv[1])), 1u)); st_rlx(scr->act[ep & 1] + 32 + ao, max(movm(pack_bf16(hv[2], hv[3])), 1u));
                        __syncwarp();
                        if (ln == 0) red_add(&scr->cnt[b / 14][0]);
                        st_rlx(scr->act[~ep & 1] + ao, 0); st_rlx(scr->act[~ep & 1] + 32 + ao, 0);
                    }
                } else {
#pragma unroll
                    for (int c = 0; c < 4; c++) st_rlx(&scr->ypart[kc][2 * (ln & 3) + (c & 1)][c2 * 64 + wq * 16 + (c >> 1) * 8 + (ln >> 2)], (__float_as_uint(acc[c]) & ~1u) | (ep & 1));
                    if (b == 0 && ta == 0) st_rlx(&scr->epoch[ln], ep);
                }
                TSC(ta == 0, 22 + ph);
            }
            const int ln = lane + (left >> 30);
            if (ph == 0) {
                if ((ta & 126) == 64) mbar_arrive(bars + 8 * B_F1DONE);
                const uint32_t kj = poll_all(&scr->sel[ln & 7], 31u, ep & 31, left);
                const int row = 2047 - ((kj >> 5) & 2047), jj = (row & 1) == par ? (row >> 1) - j0 : -1;
                sig = bf16r(sigmoidf(__uint_as_float(((int)kj < 0 ? kj & 0x7fffffffu : ~kj) & 0xffff0000u)));
                own = __ballot_sync(0xffffffffu, (jj >> 7) == rh) & 255;
                sts1(sb + OFF_SEL + (ln & 7) * 4, jj);
                sts4(sb + OFF_UPD + wq * 512 + ln * 16, 0, 0, 0, 0);
            }
            if ((own != 0) == ph) {
                if (wq & 2) own &= own - 1;
#pragma unroll 1
                for (; own; own &= own - 1, own &= own - 1) {
                    const int j = __ffs(own) - 1;
                    const uint32_t* src = &scr->ypart[ln >> 4][j][cb * 128 + (wq & 1) * 64 + (ln & 15) * 4];
                    uint4 v[4]; int tries = BUDGET;
#pragma unroll 1
                    do {
#pragma unroll
                        for (int m = 0; m < 4; m++) v[m] = ld_rlx4(src + m * 2 * 8192);
                    } while ((((v[0].x ^ ep) | (v[1].x ^ ep) | (v[2].x ^ ep) | (v[3].x ^ ep)) & 1) && --tries > 0);
                    __syncwarp();
                    float a[4];
                    const float sj = __shfl_sync(0xffffffffu, sig, j);
#pragma unroll
                    for (int c = 0; c < 4; c++) {
                        a[c] = (__uint_as_float((&v[0].x)[c]) + __uint_as_float((&v[1].x)[c])) + (__uint_as_float((&v[2].x)[c]) + __uint_as_float((&v[3].x)[c]));
                        a[c] = bf16r(a[c] + __shfl_xor_sync(0xffffffffu, a[c], 16)) * sj;
                    }
                    sts2(sb + OFF_UPD + (wq & 1) * 1024 + j * 128 + ((((ln >> 1) & 7) ^ j) << 4) + (ln & 1) * 8, pack_bf16(a[0], a[1]), pack_bf16(a[2], a[3]));
                }
                fence_async_smem();
                __syncwarp();
                if (ln < 2) mbar_arrive(bars + 8 * B_UPD);
            }
        }
        TSC(ta == 0, 24);
    } else {
        reg_inc<224>();
        const int w = warp >> 2, wi = warp & 3, g = lane >> 2, t = lane & 3;
        const bool elect = (tid & 127) == 0;
        const uint32_t mad = (lane & 15) * 128 + (((lane >> 4) ^ (lane & 7)) << 4);
        float acc[64];
        const uint32_t ring = sb + w * OFF_X1, ofull = bars + 8 * (B_OFULL + w * 6), oempty = mapa(bars + 8 * B_OEMPTY, w);
        const int r0 = rh * 128 + wi * 32 + (1 - w) * 16 + g;
        {
            float acc0[96], acc1[96];
            const uint32_t sta = sb + OFF_STAT + (8 + w * 128 + wi * 32) * 8;
            {
                const uint32_t xfull = bars + 8 * (B_XFULL + w * 6 + 5), xempty = mapa(bars + 8 * B_XEMPTY, w), dx0 = sd + dlo(w * OFF_X1, 16);
                uint32_t s8 = 16, ps8 = 0, ph = 0;
                cluster_wait();
#pragma unroll 1
                for (int k = 0; k < 16; k++) {
                    const uint32_t dx = dx0 + s8 * (2 * BOX >> 7), dw = sd + dlo(OFF_W, BOX) + s8 * (W_BYTES >> 7);
                    mbar_wait(bars + 8 * B_WFULL + s8, ph, budget);
                    mbar_wait(xfull - 2 * s8, ph, budget);
                    TSC(elect && k == 0, 1 + 8 * w);
                    TSC(TIMING % 10 == 1 && tid == 0, 32 + k);
                    wg_wait<0>();
                    wg_fence();
#pragma unroll
                    for (int kk = 0; kk < 4; kk++) wgmma_n192<0, 1>(acc1, mkdesc(dx + kk * 2, dhi(1024, 1)), mkdesc(dw + kk * 128, dhi(1024, 1)), kk ? 1 : k);
                    wg_commit();
                    if (elect && k > 0) {
                        mbar_arrive(bars + 8 * B_WEMPTY + ps8);
                        if (k <= 13) { mbar_expect_tx(xfull - 2 * ps8 - 8, BOX); mbar_arrive_at(xempty + 2 * ps8 + 8); }
                    }
                    if (k == 15) {
                        mbar_wait(bars + 8 * B_AUX, 0, budget);
                        const uint32_t zero = budget >> 30, pm = t & 1 ? 0x4432 : 0x3232, ra = sta + ((t >> 1) * 16 + g) * 8;
                        const uint32_t a0 = __byte_perm(lds1(ra), 0, pm), a1 = __byte_perm(lds1(ra + 64), 0, pm), a2 = a0 & zero, a3 = a1 & zero;
                        wg_fence();
                        wgmma_rs_n192(acc1, a0, a1, a2, a3, mkdesc(sd + dlo(OFF_CS, 0), dhi(128, 0)));
                        wgmma_rs_n192(acc0, a0, a1, a2, a3, mkdesc(sd + dlo(OFF_CS + 64, 0), dhi(128, 0)));
                        wg_commit();
                    }
                    mbar_wait(xfull - 2 * s8 - 8, ph, budget);
                    wg_wait<0>();
                    wg_fence();
#pragma unroll
                    for (int kk = 0; kk < 4; kk++) wgmma_n192<0, 1>(acc0, mkdesc(dx + 512 + kk * 2, dhi(1024, 1)), mkdesc(dw + kk * 128, dhi(1024, 1)), kk ? 1 : k);
                    wg_commit();
                    if (elect && k <= 12) { mbar_expect_tx(xfull - 2 * s8, BOX); mbar_arrive_at(xempty + 2 * s8); }
                    ps8 = s8;
                    s8 = s8 == 16 ? 0 : s8 + 8;
                    if (s8 == 16) ph ^= 1;
                }
            }
            const uint32_t zero = budget >> 30;
            const bool u0 = 2 * t > g, u1 = 2 * t + 1 > g;
            uint32_t mU = (u0 ? 0xffffu : 0u) | (u1 ? 0xffff0000u : 0u);
            uint32_t ka0 = sta + (2 * t - (u0 ? 8 : 0)) * 8 + 4, ka1 = sta + (2 * t + 1 - (u1 ? 8 : 0)) * 8 + 4;
            float rk[2][4], fu[2][4], fn[2][4];
            auto factors = [&](int h) {
#pragma unroll
                for (int n = 0; n < 4; n += 2) {
                    const float rq = lds1f(sta + (16 * h + 4 * n + g) * 8 + 4) * (0.17677669529663687f * 1.4426950408889634f);
                    rk[h][n] = lds1f(ka0 + h * 128 + n * 32); rk[h][n + 1] = lds1f(ka1 + h * 128 + n * 32);
                    const float f0 = rq * rk[h][n], f1 = rq * rk[h][n + 1];
                    fu[h][n] = u0 ? f0 : 0.f; fn[h][n] = f0 - fu[h][n]; fu[h][n + 1] = u1 ? f1 : 0.f; fn[h][n + 1] = f1 - fu[h][n + 1];
                }
#pragma unroll
                for (int n = 0; n < 4; n++) asm volatile("" : "+f"(fu[h][n]), "+f"(fn[h][n]));
            };
            uint8_t* og = scr->o + ((size_t)(mt * 4 + w * 2) * 16 + nt) * BOX + wi * 256 + lane * 4;
            TSC(elect, 19 + w);
            uint32_t pk0[48], pk1[48], o[16] = {};
#pragma unroll
            for (int j = 0; j < 48; j++) if (j < 16 || (j & 1)) pk1[j] = pack_here(acc1[2 * j], acc1[2 * j + 1]);
            if (warp < 7) {
#pragma unroll
                for (int c = 0; c < 4; c++) stsm4(ring + 4 * BOX + wi * 2048 + c * 512 + lane * 16, pk1[17 + 8 * c], pk1[19 + 8 * c], pk1[21 + 8 * c], pk1[23 + 8 * c]);
                bar_arrive(1 + warp, 64);
            } else if (j0 != 768) {
#pragma unroll
                for (int c = 0; c < 4; c++) {
                    pk1[17 + 8 * c] = max(pk1[17 + 8 * c], 1u);
                    st_rlx4(&scr->halo[b][c * 128 + lane * 4], pk1[17 + 8 * c], pk1[19 + 8 * c], pk1[21 + 8 * c], pk1[23 + 8 * c]);
                }
            }
            TSC(tid == 224, 28);
#pragma unroll
            for (int j = 16; j < 48; j += 2) pk1[j] = pack_here(acc1[2 * j], acc1[2 * j + 1]);
            factors(1);
            uint32_t od = sb + 2 * BOX + wi * 256 + (lane >> 4) * 1024 + (lane & 15) * 16, g1peer = mapa(bars + 8 * B_G1DONE, hp ^ 1);
            uint32_t ha = sb + (warp == 0 ? OFF_HIN : warp <= 4 ? 4 * BOX - 2048 : OFF_X1 + 4 * BOX - 5 * 2048) + warp * 2048 + lane * 16;
            const bool first = warp == 0 && j0 == 0;
            float bias0 = first && u0 ? -INFINITY : 0.f, bias1 = first && u1 ? -INFINITY : 0.f;
            asm volatile("" : "+l"(og), "+r"(mU), "+r"(od), "+r"(ha), "+f"(bias0), "+f"(bias1));
            mbar_wait(bars + 8 * B_XT, 0, budget);
            mbar_wait(bars + 8 * (B_WEMPTY + 1), 0, budget);
            TSC(elect, 12 + 2 * w);
            wg_wait<0>();
            if (elect) { mbar_arrive(bars + 8 * B_G1DONE); mbar_arrive_at(g1peer); }
            TSC(elect, 2 + 8 * w);
            float ci[4];
#pragma unroll
            for (int n = 0; n < 4; n++) ci[n] = __uint_as_float((0x03800000u + n) | (budget >> 30));
            auto hand_over = [&](int v) {
                asm volatile("{\n.reg .pred p;\nsetp.ne.b32 p, %17, 0;\n"
                             "@p stmatrix.sync.aligned.m8n8.x4.shared.b16 [%16], {%0,%1,%2,%3};\n@p stmatrix.sync.aligned.m8n8.x4.shared.b16 [%16 + 2048], {%4,%5,%6,%7};\n"
                             "@p stmatrix.sync.aligned.m8n8.x4.shared.b16 [%16 + 4096], {%8,%9,%10,%11};\n@p stmatrix.sync.aligned.m8n8.x4.shared.b16 [%16 + 6144], {%12,%13,%14,%15};\n"
                             FENCE_PRED "fence.proxy.async.shared::cta;\n}"
                             ::"r"(o[0]), "r"(o[1]), "r"(o[2]), "r"(o[3]), "r"(o[4]), "r"(o[5]), "r"(o[6]), "r"(o[7]), "r"(o[8]), "r"(o[9]), "r"(o[10]), "r"(o[11]),
                               "r"(o[12]), "r"(o[13]), "r"(o[14]), "r"(o[15]), "r"(od + v * OFF_X1), "r"((int)(w == rh)) : "memory");
                TSC(tid == 0, v ? 27 : 5);
#pragma unroll
                for (int i = 0; i < 16; i++) asm volatile("st.global.u32 [%0], %1;" ::"l"(og + (1 - v) * 16 * BOX + (i >> 1) * 1024 + (i & 1) * 128), "r"(o[i]) : "memory");
                __syncwarp();
                if (lane == 0) mbar_arrive(bars + 8 * (B_STAGED + v));
            };
#pragma unroll
            for (int j = 32; j < 48; j++) pk1[j] = movm(pk1[j]);
#pragma unroll
            for (int j = EARLY_PK; j < 48; j++) if (j >= 32 || (j & 1) || EARLY_PK < 17) pk0[j] = pack_here(acc0[2 * j], acc0[2 * j + 1]);
#pragma unroll
            for (int j = 32; j < 48; j++) pk0[j] = movm(pk0[j]);
            factors(0);
            attn_pair<2>(pk1, pk1 + 16, pk1 + 32, pk0 + 17, pk0 + 33, fu[1], fn[1], rk[1], 0.f, 0.f, mU, zero, ci, o);
            hand_over(0);
            TSC(elect, 3 + 8 * w);
#pragma unroll
            for (int j = 0; j < 32; j++) if (j < EARLY_PK || (!(j & 1) && EARLY_PK == 17)) pk0[j] = pack_here(acc0[2 * j], acc0[2 * j + 1]);
            bar_sync(warp ? warp : 11, 64);
            uint32_t hl[16];
            ldsm4(hl, ha); ldsm4(hl + 4, ha + 512); ldsm4t(hl + 8, ha + 1024); ldsm4t(hl + 12, ha + 1536);
            __syncwarp();
            if (lane == 0) mbar_arrive(bars + 8 * B_FREED);
            attn_pair<1>(pk0, pk0 + 16, pk0 + 32, hl, hl + 8, fu[0], fn[0], rk[0], bias0, bias1, mU, zero, ci, o);
            const float2 s0 = lds2f(sb + OFF_STAT + (8 + r0) * 8), s1 = lds2f(sb + OFF_STAT + (16 + r0) * 8);
            const float m0 = s0.x * s0.y, f0 = 1.f + s0.y, m1 = s1.x * s1.y, f1 = 1.f + s1.y;
            uint32_t xt[32];
#pragma unroll
            for (int j = 0; j < 8; j++) ldsm4(xt + 4 * j, ((ring + wi * 2048 + mad) ^ ((j & 3) * 32)) + (j >> 2) * BOX);
            hand_over(1);
#pragma unroll
            for (int j = 0; j < 32; j++) {
                acc[2 * j] = fmaf(bf_lo(xt[j]), j & 1 ? f1 : f0, j & 1 ? m1 : m0); acc[2 * j + 1] = fmaf(bf_hi(xt[j]), j & 1 ? f1 : f0, j & 1 ? m1 : m0);
            }
        }
        TSC(tid == 0, 4);
        {
            const uint32_t da0 = sd + dlo(w * OFF_X1, 1024), db0 = sd + dlo(OFF_WO, BOX);
            const uint32_t chk = ring + wi * 256 + (lane >> 3) * 1032 + (lane & 7) * 32 + (lane & 4);
            uint32_t s8 = 16, ps8 = 0, ph = 0;
            mbar_wait(ofull + s8, 0, budget);
            mbar_wait(bars + 8 * B_WOFULL + s8, 0, budget);
            TSC(TIMING % 10 == 2 && elect, 32 + w * 16);
            const uint32_t ahi = dhi(128, 0) | (budget >> 30), bhi = dhi(1024, 1) | (budget >> 30);
            const int last = w ? HOLD : 16;
            uint32_t rel = elect ? 0x7fe : 0;
#pragma unroll 1
            for (int i = 1;;) {
                const uint32_t da = da0 + s8 * (BOX >> 7), db = db0 + s8 * (BOX >> 6);
                wg_fence();
#pragma unroll
                for (int kk = 0; kk < 4; kk++) {
                    wgmma_n128<0, 1>(acc, mkdesc(da + kk * 128, ahi), mkdesc(db + kk * 128, bhi), 1);
                    if (kk & 1) wg_commit();
                }
                wg_wait<2>();
                if (rel & 1) { mbar_expect_tx(ofull + ps8, BOX); mbar_arrive_at(oempty + ps8); mbar_arrive(bars + 8 * B_WOEMPTY + ps8); }
                if (i == 16) break;
                rel >>= 1;
                ps8 = s8;
#pragma unroll 1
                do {
                    s8 = s8 == 40 ? 0 : s8 + 8;
                    if (s8 == 16) ph ^= 1;
                    uint32_t bad;
                    asm volatile("{\n.reg .pred p, q, r;\n.reg .u32 u, v;\nmbarrier.try_wait.parity.shared::cta.b64 q, [%2], %3;\nmbarrier.try_wait.parity.shared::cta.b64 p, [%1], %3;\n"
                                 "setp.ne.and.u32 r, %5, 1, p;\nmov.u32 u, 1;\nmov.u32 v, 1;\n@r ld.shared.u32 u, [%4];\n@r ld.shared.u32 v, [%4 + 4096];\n"
                                 "and.pred p, p, q;\nmin.u32 u, u, v;\nsetp.eq.or.u32 p, u, 0, !p;\nvote.sync.any.pred p, p, 0xffffffff;\nselp.u32 %0, 1, 0, p;\n}"
                                 : "=r"(bad) : "r"(ofull + s8), "r"(bars + 8 * B_WOFULL + s8), "r"(ph), "r"(chk + s8 * (BOX / 8)), "r"(i) : "memory");
                    if (__builtin_expect(bad, 0)) {
                        mbar_wait(ofull + s8, ph, budget);
                        mbar_wait(bars + 8 * B_WOFULL + s8, ph, budget);
                        if (__any_sync(0xffffffffu, min(lds1(chk + s8 * (BOX / 8)), lds1(chk + s8 * (BOX / 8) + 4096)) == 0)) {
                            const uint32_t at = wi * 256 + (lane >> 4) * 1024 + (lane & 15) * 16;
                            const uint8_t* src = scr->o + ((size_t)((mt * 2 + rh) * 2 + 1 - w) * 16 + ((2 * p + (i < 2 ? i ^ hp : i)) & 15)) * BOX + at;
#pragma unroll 1
                            for (int n = 0; n < 8192; n += 2048) {
                                uint4 v; int tries = 4096;
#pragma unroll 1
                                do { v = ld_rlx4(src + n); } while (v.x == 0 && --tries > 0);
                                sts4(ring + s8 * (BOX / 8) + at + n, v.x, v.y, v.z, v.w);
                            }
                            NRETRY();
                            fence_async_smem();
                            __syncwarp();
                        }
                    }
                    TSC(TIMING % 10 == 1 && tid == 0, 48 + i);
                    TSC(TIMING % 10 == 2 && elect, 32 + w * 16 + i);
                } while (++i > last && i < 16);
                if (i > last) break;
                wg_wait<1>();
            }
            uint32_t ready;
            asm volatile("{\n.reg .pred p;\nmbarrier.test_wait.parity.shared::cta.b64 p, [%1], 0;\nvote.sync.all.pred p, p, 0xffffffff;\nselp.u32 %0, 1, 0, p;\n}" : "=r"(ready) : "r"(bars + 8 * B_UPD) : "memory");
            if (w) {
                bar_sync(9, 256);
#pragma unroll 1
                for (int i = HOLD - 10; i < 6; i++) {
                    wg_fence();
#pragma unroll
                    for (int kk = 0; kk < 4; kk++) wgmma_n128<0, 1>(acc, mkdesc(da0 + i * 512 + kk * 128, ahi), mkdesc(db0 + i * 1024 + kk * 128, bhi), 1);
                    wg_commit();
                }
            } else if (!ready) bar_arrive(9, 256);
            mbar_wait(bars + 8 * B_UPD, 0, budget);
            const float2 sl = lds2f(sb + OFF_SEL + t * 8);
            const int d0 = __float_as_int(sl.x) - r0, d1 = __float_as_int(sl.y) - r0;
            const uint32_t a0 = (d0 == 0 ? 0x3f80u : 0u) | (d1 == 0 ? 0x3f800000u : 0u), a1 = (d0 == 8 ? 0x3f80u : 0u) | (d1 == 8 ? 0x3f800000u : 0u);
            wg_fence();
            wgmma_rs_n128(acc, a0, a1, 0u, 0u, mkdesc(sd + dlo(OFF_UPD, 1024), dhi(0, 1)));
            wg_commit();
            if (!w && ready) bar_arrive(9, 256);
            wg_wait<0>();
            TSC(elect, 7 + 9 * w);
            const uint32_t os0 = ring + wi * 4096;
#pragma unroll
            for (int j = 0; j < 8; j++)
                stsm4(((os0 + mad) ^ ((j & 3) * 32)) + (j >> 2) * 2048, pack_bf16(acc[8 * j], acc[8 * j + 1]), pack_bf16(acc[8 * j + 2], acc[8 * j + 3]),
                      pack_bf16(acc[8 * j + 4], acc[8 * j + 5]), pack_bf16(acc[8 * j + 6], acc[8 * j + 7]));
            fence_async_smem();
            __syncwarp();
            if (elect_one()) {
                asm volatile("cp.async.bulk.tensor.5d.global.shared::cta.bulk_group [%0, {%2, %2, %3, %4, %5}], [%1];\ncp.async.bulk.commit_group;\ncp.async.bulk.wait_group.read 0;"
                             ::"l"(&mout), "r"(os0), "r"(0), "r"(((j0 + rh * 128) >> 5) + wi), "r"(1 - w), "r"(par * 16 + cb * 2) : "memory");
            }
            TSC(elect, 8 - 2 * w);
            TS_END();
        }
    }
}

typedef CUresult (*EncodeFn)(CUtensorMap*, CUtensorMapDataType, cuuint32_t, void*, const cuuint64_t*, const cuuint64_t*, const cuuint32_t*,
                             const cuuint32_t*, CUtensorMapInterleave, CUtensorMapSwizzle, CUtensorMapL2promotion, CUtensorMapFloatOOBfill);

CUtensorMap make_map(EncodeFn fn, const void* base, int rank, const cuuint64_t* dims, const cuuint64_t* strides, const cuuint32_t* box,
                     CUtensorMapSwizzle swz = CU_TENSOR_MAP_SWIZZLE_128B, CUtensorMapL2promotion pro = CU_TENSOR_MAP_L2_PROMOTION_L2_256B) {
    CUtensorMap m;
    cuuint32_t es[5] = {1, 1, 1, 1, 1};
    fn(&m, CU_TENSOR_MAP_DATA_TYPE_BFLOAT16, rank, (void*)base, dims, strides, box, es, CU_TENSOR_MAP_INTERLEAVE_NONE,
       swz, pro, CU_TENSOR_MAP_FLOAT_OOB_FILL_NONE);
    return m;
}

}

extern "C" void kernel_launch(void* const* d_in, const int* in_sizes, int n_in, void* d_out, int out_size) {
    (void)in_sizes; (void)n_in; (void)out_size;
    const __nv_bfloat16* x = (const __nv_bfloat16*)d_in[0];
    const __nv_bfloat16* wqkv = (const __nv_bfloat16*)d_in[1];
    const __nv_bfloat16* wo = (const __nv_bfloat16*)d_in[2];
    const __nv_bfloat16* wr = (const __nv_bfloat16*)d_in[4];
    const __nv_bfloat16* wg = (const __nv_bfloat16*)d_in[5];
    const __nv_bfloat16* wu = (const __nv_bfloat16*)d_in[6];
    const __nv_bfloat16* wd = (const __nv_bfloat16*)d_in[7];
    static EncodeFn fn = nullptr;
    static Scratch* scr = nullptr;
    if (!fn) {
        void* p = nullptr; cudaDriverEntryPointQueryResult q;
        cudaGetDriverEntryPoint("cuTensorMapEncodeTiled", &p, cudaEnableDefault, &q);
        fn = (EncodeFn)p;
        cudaFuncSetAttribute(fused_kernel, cudaFuncAttributeMaxDynamicSharedMemorySize, SMEM_LAUNCH);
        cudaGetSymbolAddress((void**)&scr, g_scr);
    }
    const cuuint64_t xd[4] = {2048, 16, 32, 2}, xs[4] = {4096, 131072, 65536, 128}, od[5] = {64, 16, 32, 2, 32};
    const cuuint32_t xb[4] = {64, 16, 4, 1}, ob[5] = {64, 16, 1, 1, 2};
    const cuuint64_t wdm[3] = {1024, 1024, 3}, wst[2] = {6144, 2048};
    const cuuint32_t wb[3] = {64, 64, 3};
    const cuuint64_t wod[3] = {64, 1024, 16}, wdd[3] = {64, 3584, 16}, wos[2] = {2048, 128};
    const cuuint32_t wob[3] = {64, 64, 2}, wdb[3] = {64, 64, 1};
    CUtensorMap mx = make_map(fn, x, 4, xd, xs, xb), mw = make_map(fn, wqkv, 3, wdm, wst, wb);
    CUtensorMap mwo = make_map(fn, wo, 3, wod, wos, wob), mout = make_map(fn, d_out, 5, od, xs, ob);
    const int swap_gu = wu < wg;
    const cuuint64_t gd[3] = {3584, 1024, 2}, gst[2] = {7168, (cuuint64_t)(swap_gu ? (const char*)wg - (const char*)wu : (const char*)wu - (const char*)wg)};
    const cuuint32_t gb[3] = {32, 64, 2};
    CUtensorMap mgu = make_map(fn, swap_gu ? wu : wg, 3, gd, gst, gb, CU_TENSOR_MAP_SWIZZLE_64B, CU_TENSOR_MAP_L2_PROMOTION_L2_128B);
    CUtensorMap mwd = make_map(fn, wd, 3, wdd, wos, wdb, CU_TENSOR_MAP_SWIZZLE_128B, CU_TENSOR_MAP_L2_PROMOTION_L2_128B);
    const cuuint64_t md[2] = {64, 32768}, ms[1] = {128};
    const cuuint32_t mb[2] = {64, 64};
    CUtensorMap mo = make_map(fn, scr, 2, md, ms, mb, CU_TENSOR_MAP_SWIZZLE_NONE, CU_TENSOR_MAP_L2_PROMOTION_NONE);
    cudaLaunchConfig_t cfg = {};
    cfg.gridDim = dim3(132); cfg.blockDim = dim3(512); cfg.dynamicSmemBytes = SMEM_LAUNCH; cfg.stream = cudaStreamPerThread;
    cudaLaunchAttribute at[1];
    at[0].id = cudaLaunchAttributeClusterDimension; at[0].val.clusterDim.x = 2; at[0].val.clusterDim.y = 1; at[0].val.clusterDim.z = 1;
    cfg.attrs = at; cfg.numAttrs = 1;
    cudaLaunchKernelEx(&cfg, fused_kernel, mx, mw, mwo, mout, mgu, mwd, mo, x, wr, scr, swap_gu, Weights{(const char*)wqkv, (const char*)wo, (const char*)wg, (const char*)wu, (const char*)wd});
}
```

```cpp
#include <cuda_runtime.h>
#include <cuda.h>
#include <cuda_bf16.h>
#include <stdint.h>

namespace {

constexpr int BOX = 8192, W_BYTES = 3 * BOX;
constexpr int OFF_X1 = 6 * BOX, OFF_FR = 12 * BOX, OFF_E = 16 * BOX, OFF_W = 19 * BOX;
constexpr int OFF_WO = OFF_E;
constexpr int OFF_UPD = OFF_FR, OFF_HIN = OFF_UPD + 2048, OFF_GU = OFF_HIN + 2048, OFF_FS = OFF_GU + 1024;
constexpr int F_BYTES = 9216;
constexpr int CS_BYTES = 3136;
constexpr int OFF_CS = OFF_FS + 5 * F_BYTES;
constexpr int OFF_STAT = 28 * BOX;
constexpr int OFF_SEL = OFF_STAT + 2112;
constexpr int OFF_EP = OFF_SEL + 32;
constexpr int OFF_BAR = OFF_EP + 16;
constexpr int B_WFULL = 0, B_XFULL = 3, B_AUX = 15, B_XT = 16, B_ROW = 17, B_WOFULL = 18, B_OFULL = 24, B_FFULL = 36;
constexpr int B_WEMPTY = 42, B_F1DONE = 45, B_XEMPTY = 46, B_WOEMPTY = 52, B_OEMPTY = 58;
constexpr int B_G1DONE = 66, B_FEMPTY = 67, B_STAGED = 72, B_UPD = 74, B_RDONE = 75, B_FREED = 76, NBAR = 78;
constexpr int SMEM_BYTES = OFF_BAR + NBAR * 8;
static_assert(OFF_FS + 3 * F_BYTES == OFF_E && OFF_CS + CS_BYTES <= OFF_W && SMEM_BYTES + 256 <= 232448 && OFF_BAR % 8 == 0 && OFF_UPD % 1024 == 0, "smem");
#define POLL_NS 30
#define PF_RATE 10
#define PF_START 7
#define ZF_NS 100
#define FFN2_GATE B_G1DONE
#define PF_NW 6
#define EARLY_PF 1
#define EARLY_PK 17
#define FENCE_PRED "@p "
#define ZF_N 64
#define HOLD 12
#define ROWS_AT 11
constexpr int BUDGET = 1 << 18;

struct Scratch {
    uint8_t o[2048 * 1024 * 2];
    uint32_t ypart[8][8][1024];
    uint32_t halo[128][512];
    uint32_t act[2][14336 + 4096];
    uint2 row[2048];
    uint32_t cs[16][800];
    uint32_t oflag[16][32];
    uint32_t cnt[9][32];
    uint32_t sel[32], csflag[32], epoch[32];
};
__device__ __align__(1024) Scratch g_scr;
struct Weights { const char *wqkv, *wo, *wg, *wu, *wd; };

#define TS(i) do {} while (0)
#define TS_END() do {} while (0)
#define TSC(c, i) do {} while (0)
#define NRETRY() do {} while (0)
constexpr int SMEM_LAUNCH = SMEM_BYTES;
__device__ __forceinline__ uint32_t smem_u32(const void* p) { return (uint32_t)__cvta_generic_to_shared(p); }
__device__ __forceinline__ void mbar_init(uint32_t bar, uint32_t cnt) { asm volatile("mbarrier.init.shared::cta.b64 [%0], %1;" ::"r"(bar), "r"(cnt) : "memory"); }
__device__ __forceinline__ void mbar_expect_tx(uint32_t bar, uint32_t bytes) { asm volatile("mbarrier.arrive.expect_tx.shared::cta.b64 _, [%0], %1;" ::"r"(bar), "r"(bytes) : "memory"); }
__device__ __forceinline__ void mbar_arrive(uint32_t bar) { asm volatile("mbarrier.arrive.shared::cta.b64 _, [%0];" ::"r"(bar) : "memory"); }
__device__ __forceinline__ uint32_t mapa(uint32_t a, uint32_t cta) { uint32_t r; asm("mapa.shared::cluster.u32 %0, %1, %2;" : "=r"(r) : "r"(a), "r"(cta)); return r; }
__device__ __forceinline__ void mbar_arrive_at(uint32_t cbar) { asm volatile("mbarrier.arrive.shared::cluster.b64 _, [%0];" ::"r"(cbar) : "memory"); }
__device__ __forceinline__ void mbar_wait(uint32_t bar, uint32_t parity, int& budget) {
    asm volatile("{\n.reg .pred p;\nLAB_WAIT:\nmbarrier.try_wait.parity.shared::cta.b64 p, [%1], %2;\n"
                 "add.s32 %0, %0, -1;\nsetp.gt.and.s32 p, %0, 0, !p;\n@p bra LAB_WAIT;\n}" : "+r"(budget) : "r"(bar), "r"(parity) : "memory");
}
__device__ __forceinline__ void mbar_wait_hot(uint32_t bar, uint32_t parity, int& budget) {
    asm volatile("{\n.reg .pred p;\nmbarrier.try_wait.parity.shared::cta.b64 p, [%1], %2;\n@p bra LAB_DONE;\nLAB_WAIT:\nmbarrier.try_wait.parity.shared::cta.b64 p, [%1], %2;\n"
                 "add.s32 %0, %0, -1;\nsetp.gt.and.s32 p, %0, 0, !p;\n@p bra LAB_WAIT;\nLAB_DONE:\n}" : "+r"(budget) : "r"(bar), "r"(parity) : "memory");
}
__device__ __forceinline__ void tma_2d_mc(uint32_t dst, const CUtensorMap* m, uint32_t bar, int c0, int c1) {
    asm volatile("cp.async.bulk.tensor.2d.shared::cluster.global.mbarrier::complete_tx::bytes.multicast::cluster [%0], [%1, {%3, %4}], [%2], %5;" ::"r"(dst), "l"(m), "r"(bar), "r"(c0), "r"(c1), "h"((uint16_t)3) : "memory");
}
__device__ __forceinline__ void tma_3d(uint32_t dst, const CUtensorMap* m, uint32_t bar, int c0, int c1, int c2) {
    asm volatile("cp.async.bulk.tensor.3d.shared::cluster.global.mbarrier::complete_tx::bytes [%0], [%1, {%3, %4, %5}], [%2];" ::"r"(dst), "l"(m), "r"(bar), "r"(c0), "r"(c1), "r"(c2) : "memory");
}
__device__ __forceinline__ void tma_4d(uint32_t dst, const CUtensorMap* m, uint32_t bar, int c0, int c1, int c2, int c3) {
    asm volatile("cp.async.bulk.tensor.4d.shared::cluster.global.mbarrier::complete_tx::bytes [%0], [%1, {%3, %4, %5, %6}], [%2];" ::"r"(dst), "l"(m), "r"(bar), "r"(c0), "r"(c1), "r"(c2), "r"(c3) : "memory");
}
__device__ __forceinline__ void tma_4d_mc(uint32_t dst, const CUtensorMap* m, uint32_t bar, int c0, int c1, int c2, int c3) {
    asm volatile("cp.async.bulk.tensor.4d.shared::cluster.global.mbarrier::complete_tx::bytes.multicast::cluster [%0], [%1, {%3, %4, %5, %6}], [%2], %7;" ::"r"(dst), "l"(m), "r"(bar), "r"(c0), "r"(c1), "r"(c2), "r"(c3), "h"((uint16_t)3) : "memory");
}
__device__ __forceinline__ void bulk_pf(const void* p, uint32_t bytes) { asm volatile("cp.async.bulk.prefetch.L2.global [%0], %1;" ::"l"(p), "r"(bytes) : "memory"); }
__device__ __forceinline__ void bulk_g2s(uint32_t dst, const void* src, uint32_t bytes, uint32_t bar) {
    asm volatile("cp.async.bulk.shared::cluster.global.mbarrier::complete_tx::bytes [%0], [%1], %2, [%3];" ::"r"(dst), "l"(src), "r"(bytes), "r"(bar) : "memory");
}
__device__ __forceinline__ void bulk_s2c(uint32_t cdst, uint32_t src, uint32_t bytes, uint32_t cbar) {
    asm volatile("cp.async.bulk.shared::cluster.shared::cta.mbarrier::complete_tx::bytes [%0], [%1], %2, [%3];" ::"r"(cdst), "r"(src), "r"(bytes), "r"(cbar) : "memory");
}
__device__ __forceinline__ void cluster_wait() { asm volatile("barrier.cluster.wait.aligned;" ::: "memory"); }
__device__ __forceinline__ void fence_gpu() { asm volatile("fence.acq_rel.gpu;" ::: "memory"); }
__device__ __forceinline__ void fence_async_smem() { asm volatile("fence.proxy.async.shared::cta;" ::: "memory"); }
__device__ __forceinline__ void fence_async_gmem() { asm volatile("fence.proxy.async.global;" ::: "memory"); }
__device__ __forceinline__ void wg_fence() { asm volatile("wgmma.fence.sync.aligned;" ::: "memory"); }
__device__ __forceinline__ void wg_commit() { asm volatile("wgmma.commit_group.sync.aligned;" ::: "memory"); }
template <int N> __device__ __forceinline__ void wg_wait() { asm volatile("wgmma.wait_group.sync.aligned %0;" ::"n"(N) : "memory"); }
__device__ __forceinline__ uint64_t mkdesc(uint32_t lo, uint32_t hi) { return ((uint64_t)hi << 32) | lo; }
__host__ __device__ constexpr uint32_t dhi(uint32_t sbo, uint32_t mode) { return (sbo >> 4) | (mode << 30); }
__host__ __device__ constexpr uint32_t dlo(uint32_t off, uint32_t lbo) { return (off >> 4) + ((lbo >> 4) << 16); }
__device__ __forceinline__ bool elect_one() {
    uint32_t e;
    asm volatile("{\n.reg .pred p;\nelect.sync _|p, 0xffffffff;\nselp.u32 %0, 1, 0, p;\n}" : "=r"(e));
    return e;
}
template <int R> __device__ __forceinline__ void reg_inc() { asm volatile("setmaxnreg.inc.sync.aligned.u32 %0;" ::"n"(R)); }
template <int R> __device__ __forceinline__ void reg_dec() { asm volatile("setmaxnreg.dec.sync.aligned.u32 %0;" ::"n"(R)); }
__device__ __forceinline__ void bar_sync(int id, int n) { asm volatile("bar.sync %0, %1;" ::"r"(id), "r"(n) : "memory"); }
__device__ __forceinline__ void bar_arrive(int id, int n) { asm volatile("bar.arrive %0, %1;" ::"r"(id), "r"(n) : "memory"); }
__device__ __forceinline__ uint32_t pack_bf16(float lo, float hi) { uint32_t r; asm("cvt.rn.bf16x2.f32 %0, %1, %2;" : "=r"(r) : "f"(hi), "f"(lo)); return r; }
__device__ __forceinline__ uint32_t pack_here(float lo, float hi) { uint32_t r; asm volatile("cvt.rn.bf16x2.f32 %0, %1, %2;" : "=r"(r) : "f"(hi), "f"(lo)); return r; }
__device__ __forceinline__ float bf_lo(uint32_t u) { return __uint_as_float(u << 16); }
__device__ __forceinline__ float bf_hi(uint32_t u) { return __uint_as_float(u & 0xffff0000u); }
__device__ __forceinline__ float bf16r(float v) { return bf_lo(pack_bf16(v, 0.f)); }
__device__ __forceinline__ float rcp(float x) { float r; asm("rcp.approx.ftz.f32 %0, %1;" : "=f"(r) : "f"(x)); return r; }
__device__ __forceinline__ float ex2(float x) { float r; asm("ex2.approx.ftz.f32 %0, %1;" : "=f"(r) : "f"(x)); return r; }
__device__ __forceinline__ float sigmoidf(float v) { return rcp(1.f + ex2(v * -1.4426950408889634f)); }
__device__ __forceinline__ uint32_t movm(uint32_t a) { uint32_t d; asm volatile("movmatrix.sync.aligned.m8n8.trans.b16 %0, %1;" : "=r"(d) : "r"(a)); return d; }
__device__ __forceinline__ void mma16816(float (&c)[4], uint32_t a0, uint32_t a1, uint32_t a2, uint32_t a3, uint32_t b0, uint32_t b1) {
    asm volatile("mma.sync.aligned.m16n8k16.row.col.f32.bf16.bf16.f32 {%0,%1,%2,%3}, {%4,%5,%6,%7}, {%8,%9}, {%0,%1,%2,%3};"
                 : "+f"(c[0]), "+f"(c[1]), "+f"(c[2]), "+f"(c[3]) : "r"(a0), "r"(a1), "r"(a2), "r"(a3), "r"(b0), "r"(b1));
}
__device__ __forceinline__ void mma1688(float (&c)[4], uint32_t a0, uint32_t a1, uint32_t b0) {
    asm volatile("mma.sync.aligned.m16n8k8.row.col.f32.bf16.bf16.f32 {%0,%1,%2,%3}, {%4,%5}, {%6}, {%0,%1,%2,%3};"
                 : "+f"(c[0]), "+f"(c[1]), "+f"(c[2]), "+f"(c[3]) : "r"(a0), "r"(a1), "r"(b0));
}
__device__ __forceinline__ void stsm4(uint32_t a, uint32_t r0, uint32_t r1, uint32_t r2, uint32_t r3) {
    asm volatile("stmatrix.sync.aligned.m8n8.x4.shared.b16 [%0], {%1,%2,%3,%4};" ::"r"(a), "r"(r0), "r"(r1), "r"(r2), "r"(r3) : "memory");
}
__device__ __forceinline__ void ldsm4(uint32_t* r, uint32_t a) {
    asm volatile("ldmatrix.sync.aligned.m8n8.x4.shared.b16 {%0,%1,%2,%3}, [%4];" : "=r"(r[0]), "=r"(r[1]), "=r"(r[2]), "=r"(r[3]) : "r"(a) : "memory");
}
__device__ __forceinline__ void ldsm4t(uint32_t* r, uint32_t a) {
    asm volatile("ldmatrix.sync.aligned.m8n8.x4.trans.shared.b16 {%0,%1,%2,%3}, [%4];" : "=r"(r[0]), "=r"(r[1]), "=r"(r[2]), "=r"(r[3]) : "r"(a) : "memory");
}
__device__ __forceinline__ uint32_t ld_rlx(const void* p) { uint32_t v; asm volatile("ld.relaxed.gpu.global.u32 %0, [%1];" : "=r"(v) : "l"(p) : "memory"); return v; }
__device__ __forceinline__ uint32_t ld_acq(const void* p) { uint32_t v; asm volatile("ld.acquire.gpu.global.u32 %0, [%1];" : "=r"(v) : "l"(p) : "memory"); return v; }
__device__ __forceinline__ uint2 ld_rlx2(const void* p) { uint2 v; asm volatile("ld.relaxed.gpu.global.v2.u32 {%0,%1}, [%2];" : "=r"(v.x), "=r"(v.y) : "l"(p) : "memory"); return v; }
__device__ __forceinline__ uint4 ld_rlx4(const void* p) { uint4 v; asm volatile("ld.relaxed.gpu.global.v4.u32 {%0,%1,%2,%3}, [%4];" : "=r"(v.x), "=r"(v.y), "=r"(v.z), "=r"(v.w) : "l"(p) : "memory"); return v; }
__device__ __forceinline__ void st_rlx(void* p, uint32_t v) { asm volatile("st.relaxed.gpu.global.u32 [%0], %1;" ::"l"(p), "r"(v) : "memory"); }
__device__ __forceinline__ void st_rlx2(void* p, uint32_t a, uint32_t b) { asm volatile("st.relaxed.gpu.global.v2.u32 [%0], {%1,%2};" ::"l"(p), "r"(a), "r"(b) : "memory"); }
__device__ __forceinline__ void st_rlx4(void* p, uint32_t a, uint32_t b, uint32_t c, uint32_t d) { asm volatile("st.relaxed.gpu.global.v4.u32 [%0], {%1,%2,%3,%4};" ::"l"(p), "r"(a), "r"(b), "r"(c), "r"(d) : "memory"); }
__device__ __forceinline__ void red_add(uint32_t* p) { asm volatile("red.relaxed.gpu.global.add.u32 [%0], 1;" ::"l"(p) : "memory"); }
__device__ __forceinline__ uint4 ldg_nc(const void* p) { uint4 v; asm volatile("ld.global.nc.v4.u32 {%0,%1,%2,%3}, [%4];" : "=r"(v.x), "=r"(v.y), "=r"(v.z), "=r"(v.w) : "l"(p)); return v; }
__device__ __forceinline__ void sts4(uint32_t a, uint32_t x, uint32_t y, uint32_t z, uint32_t w) { asm volatile("st.shared.v4.u32 [%0], {%1,%2,%3,%4};" ::"r"(a), "r"(x), "r"(y), "r"(z), "r"(w) : "memory"); }
__device__ __forceinline__ void sts2(uint32_t a, uint32_t x, uint32_t y) { asm volatile("st.shared.v2.u32 [%0], {%1,%2};" ::"r"(a), "r"(x), "r"(y) : "memory"); }
__device__ __forceinline__ void sts1(uint32_t a, uint32_t v) { asm volatile("st.shared.u32 [%0], %1;" ::"r"(a), "r"(v) : "memory"); }
__device__ __forceinline__ uint4 lds4(uint32_t a) { uint4 v; asm volatile("ld.shared.v4.u32 {%0,%1,%2,%3}, [%4];" : "=r"(v.x), "=r"(v.y), "=r"(v.z), "=r"(v.w) : "r"(a) : "memory"); return v; }
__device__ __forceinline__ float4 lds4f(uint32_t a) { float4 v; asm volatile("ld.shared.v4.f32 {%0,%1,%2,%3}, [%4];" : "=f"(v.x), "=f"(v.y), "=f"(v.z), "=f"(v.w) : "r"(a) : "memory"); return v; }
__device__ __forceinline__ float2 lds2f(uint32_t a) { float2 v; asm volatile("ld.shared.v2.f32 {%0,%1}, [%2];" : "=f"(v.x), "=f"(v.y) : "r"(a) : "memory"); return v; }
__device__ __forceinline__ float lds1f(uint32_t a) { float v; asm volatile("ld.shared.f32 %0, [%1];" : "=f"(v) : "r"(a) : "memory"); return v; }
__device__ __forceinline__ uint32_t lds1(uint32_t a) { uint32_t v; asm volatile("ld.shared.u32 %0, [%1];" : "=r"(v) : "r"(a) : "memory"); return v; }
__device__ __forceinline__ uint32_t redux_max(uint32_t v) { uint32_t r; asm volatile("redux.sync.max.u32 %0, %1, 0xffffffff;" : "=r"(r) : "r"(v)); return r; }
__device__ __forceinline__ uint32_t poll_all(const uint32_t* p, uint32_t mask, uint32_t want, int& budget) {
    uint32_t v;
#pragma unroll 1
    while (v = ld_acq(p), !__all_sync(0xffffffffu, (v & mask) == want) && --budget > 0) __nanosleep(POLL_NS);
    return v;
}

template <int TA, int TB>
__device__ __forceinline__ void wgmma_n192(float (&d)[96], uint64_t da, uint64_t db, int keep) {
    asm volatile("{\n.reg .pred p;\nsetp.ne.b32 p, %98, 0;\n"
        "wgmma.mma_async.sync.aligned.m64n192k16.f32.bf16.bf16 "
        "{%0, %1, %2, %3, %4, %5, %6, %7, %8, %9, %10, %11, %12, %13, %14, %15, "
        "%16, %17, %18, %19, %20, %21, %22, %23, %24, %25, %26, %27, %28, %29, %30, %31, "
        "%32, %33, %34, %35, %36, %37, %38, %39, %40, %41, %42, %43, %44, %45, %46, %47, "
        "%48, %49, %50, %51, %52, %53, %54, %55, %56, %57, %58, %59, %60, %61, %62, %63, "
        "%64, %65, %66, %67, %68, %69, %70, %71, %72, %73, %74, %75, %76, %77, %78, %79, "
        "%80, %81, %82, %83, %84, %85, %86, %87, %88, %89, %90, %91, %92, %93, %94, %95}, "
        "%96, %97, p, 1, 1, %99, %100;\n}\n"
        : "+f"(d[0]), "+f"(d[1]), "+f"(d[2]), "+f"(d[3]), "+f"(d[4]), "+f"(d[5]), "+f"(d[6]), "+f"(d[7]),
          "+f"(d[8]), "+f"(d[9]), "+f"(d[10]), "+f"(d[11]), "+f"(d[12]), "+f"(d[13]), "+f"(d[14]), "+f"(d[15]),
          "+f"(d[16]), "+f"(d[17]), "+f"(d[18]), "+f"(d[19]), "+f"(d[20]), "+f"(d[21]), "+f"(d[22]), "+f"(d[23]),
          "+f"(d[24]), "+f"(d[25]), "+f"(d[26]), "+f"(d[27]), "+f"(d[28]), "+f"(d[29]), "+f"(d[30]), "+f"(d[31]),
          "+f"(d[32]), "+f"(d[33]), "+f"(d[34]), "+f"(d[35]), "+f"(d[36]), "+f"(d[37]), "+f"(d[38]), "+f"(d[39]),
          "+f"(d[40]), "+f"(d[41]), "+f"(d[42]), "+f"(d[43]), "+f"(d[44]), "+f"(d[45]), "+f"(d[46]), "+f"(d[47]),
          "+f"(d[48]), "+f"(d[49]), "+f"(d[50]), "+f"(d[51]), "+f"(d[52]), "+f"(d[53]), "+f"(d[54]), "+f"(d[55]),
          "+f"(d[56]), "+f"(d[57]), "+f"(d[58]), "+f"(d[59]), "+f"(d[60]), "+f"(d[61]), "+f"(d[62]), "+f"(d[63]),
          "+f"(d[64]), "+f"(d[65]), "+f"(d[66]), "+f"(d[67]), "+f"(d[68]), "+f"(d[69]), "+f"(d[70]), "+f"(d[71]),
          "+f"(d[72]), "+f"(d[73]), "+f"(d[74]), "+f"(d[75]), "+f"(d[76]), "+f"(d[77]), "+f"(d[78]), "+f"(d[79]),
          "+f"(d[80]), "+f"(d[81]), "+f"(d[82]), "+f"(d[83]), "+f"(d[84]), "+f"(d[85]), "+f"(d[86]), "+f"(d[87]),
          "+f"(d[88]), "+f"(d[89]), "+f"(d[90]), "+f"(d[91]), "+f"(d[92]), "+f"(d[93]), "+f"(d[94]), "+f"(d[95])
        : "l"(da), "l"(db), "r"(keep), "n"(TA), "n"(TB));
}
template <int TA, int TB>
__device__ __forceinline__ void wgmma_n128(float (&d)[64], uint64_t da, uint64_t db, int keep) {
    asm volatile("{\n.reg .pred p;\nsetp.ne.b32 p, %66, 0;\n"
        "wgmma.mma_async.sync.aligned.m64n128k16.f32.bf16.bf16 "
        "{%0, %1, %2, %3, %4, %5, %6, %7, %8, %9, %10, %11, %12, %13, %14, %15, "
        "%16, %17, %18, %19, %20, %21, %22, %23, %24, %25, %26, %27, %28, %29, %30, %31, "
        "%32, %33, %34, %35, %36, %37, %38, %39, %40, %41, %42, %43, %44, %45, %46, %47, "
        "%48, %49, %50, %51, %52, %53, %54, %55, %56, %57, %58, %59, %60, %61, %62, %63}, "
        "%64, %65, p, 1, 1, %67, %68;\n}\n"
        : "+f"(d[0]), "+f"(d[1]), "+f"(d[2]), "+f"(d[3]), "+f"(d[4]), "+f"(d[5]), "+f"(d[6]), "+f"(d[7]),
          "+f"(d[8]), "+f"(d[9]), "+f"(d[10]), "+f"(d[11]), "+f"(d[12]), "+f"(d[13]), "+f"(d[14]), "+f"(d[15]),
          "+f"(d[16]), "+f"(d[17]), "+f"(d[18]), "+f"(d[19]), "+f"(d[20]), "+f"(d[21]), "+f"(d[22]), "+f"(d[23]),
          "+f"(d[24]), "+f"(d[25]), "+f"(d[26]), "+f"(d[27]), "+f"(d[28]), "+f"(d[29]), "+f"(d[30]), "+f"(d[31]),
          "+f"(d[32]), "+f"(d[33]), "+f"(d[34]), "+f"(d[35]), "+f"(d[36]), "+f"(d[37]), "+f"(d[38]), "+f"(d[39]),
          "+f"(d[40]), "+f"(d[41]), "+f"(d[42]), "+f"(d[43]), "+f"(d[44]), "+f"(d[45]), "+f"(d[46]), "+f"(d[47]),
          "+f"(d[48]), "+f"(d[49]), "+f"(d[50]), "+f"(d[51]), "+f"(d[52]), "+f"(d[53]), "+f"(d[54]), "+f"(d[55]),
          "+f"(d[56]), "+f"(d[57]), "+f"(d[58]), "+f"(d[59]), "+f"(d[60]), "+f"(d[61]), "+f"(d[62]), "+f"(d[63])
        : "l"(da), "l"(db), "r"(keep), "n"(TA), "n"(TB));
}
template <int TA, int TB>
__device__ __forceinline__ void wgmma_n8(float (&d)[4], uint64_t da, uint64_t db, int keep) {
    asm volatile("{\n.reg .pred p;\nsetp.ne.b32 p, %6, 0;\n"
        "wgmma.mma_async.sync.aligned.m64n8k16.f32.bf16.bf16 "
        "{%0, %1, %2, %3}, "
        "%4, %5, p, 1, 1, %7, %8;\n}\n"
        : "+f"(d[0]), "+f"(d[1]), "+f"(d[2]), "+f"(d[3])
        : "l"(da), "l"(db), "r"(keep), "n"(TA), "n"(TB));
}
__device__ __forceinline__ void wgmma_rs_n128(float (&d)[64], uint32_t a0, uint32_t a1, uint32_t a2, uint32_t a3, uint64_t db) {
    asm volatile("{\n.reg .pred p;\nsetp.ne.b32 p, 1, 0;\n"
        "wgmma.mma_async.sync.aligned.m64n128k16.f32.bf16.bf16 "
        "{%0, %1, %2, %3, %4, %5, %6, %7, %8, %9, %10, %11, %12, %13, %14, %15, "
        "%16, %17, %18, %19, %20, %21, %22, %23, %24, %25, %26, %27, %28, %29, %30, %31, "
        "%32, %33, %34, %35, %36, %37, %38, %39, %40, %41, %42, %43, %44, %45, %46, %47, "
        "%48, %49, %50, %51, %52, %53, %54, %55, %56, %57, %58, %59, %60, %61, %62, %63}, "
        "{%64, %65, %66, %67}, %68, p, 1, 1, 1;\n}\n"
        : "+f"(d[0]), "+f"(d[1]), "+f"(d[2]), "+f"(d[3]), "+f"(d[4]), "+f"(d[5]), "+f"(d[6]), "+f"(d[7]),
          "+f"(d[8]), "+f"(d[9]), "+f"(d[10]), "+f"(d[11]), "+f"(d[12]), "+f"(d[13]), "+f"(d[14]), "+f"(d[15]),
          "+f"(d[16]), "+f"(d[17]), "+f"(d[18]), "+f"(d[19]), "+f"(d[20]), "+f"(d[21]), "+f"(d[22]), "+f"(d[23]),
          "+f"(d[24]), "+f"(d[25]), "+f"(d[26]), "+f"(d[27]), "+f"(d[28]), "+f"(d[29]), "+f"(d[30]), "+f"(d[31]),
          "+f"(d[32]), "+f"(d[33]), "+f"(d[34]), "+f"(d[35]), "+f"(d[36]), "+f"(d[37]), "+f"(d[38]), "+f"(d[39]),
          "+f"(d[40]), "+f"(d[41]), "+f"(d[42]), "+f"(d[43]), "+f"(d[44]), "+f"(d[45]), "+f"(d[46]), "+f"(d[47]),
          "+f"(d[48]), "+f"(d[49]), "+f"(d[50]), "+f"(d[51]), "+f"(d[52]), "+f"(d[53]), "+f"(d[54]), "+f"(d[55]),
          "+f"(d[56]), "+f"(d[57]), "+f"(d[58]), "+f"(d[59]), "+f"(d[60]), "+f"(d[61]), "+f"(d[62]), "+f"(d[63])
        : "r"(a0), "r"(a1), "r"(a2), "r"(a3), "l"(db));
}
__device__ __forceinline__ void wgmma_rs_n192(float (&d)[96], uint32_t a0, uint32_t a1, uint32_t a2, uint32_t a3, uint64_t db) {
    asm volatile("{\n.reg .pred p;\nsetp.ne.b32 p, 1, 0;\n"
        "wgmma.mma_async.sync.aligned.m64n192k16.f32.bf16.bf16 "
        "{%0, %1, %2, %3, %4, %5, %6, %7, %8, %9, %10, %11, %12, %13, %14, %15, "
        "%16, %17, %18, %19, %20, %21, %22, %23, %24, %25, %26, %27, %28, %29, %30, %31, "
        "%32, %33, %34, %35, %36, %37, %38, %39, %40, %41, %42, %43, %44, %45, %46, %47, "
        "%48, %49, %50, %51, %52, %53, %54, %55, %56, %57, %58, %59, %60, %61, %62, %63, "
        "%64, %65, %66, %67, %68, %69, %70, %71, %72, %73, %74, %75, %76, %77, %78, %79, "
        "%80, %81, %82, %83, %84, %85, %86, %87, %88, %89, %90, %91, %92, %93, %94, %95}, "
        "{%96, %97, %98, %99}, %100, p, 1, 1, 1;\n}\n"
        : "+f"(d[0]), "+f"(d[1]), "+f"(d[2]), "+f"(d[3]), "+f"(d[4]), "+f"(d[5]), "+f"(d[6]), "+f"(d[7]),
          "+f"(d[8]), "+f"(d[9]), "+f"(d[10]), "+f"(d[11]), "+f"(d[12]), "+f"(d[13]), "+f"(d[14]), "+f"(d[15]),
          "+f"(d[16]), "+f"(d[17]), "+f"(d[18]), "+f"(d[19]), "+f"(d[20]), "+f"(d[21]), "+f"(d[22]), "+f"(d[23]),
          "+f"(d[24]), "+f"(d[25]), "+f"(d[26]), "+f"(d[27]), "+f"(d[28]), "+f"(d[29]), "+f"(d[30]), "+f"(d[31]),
          "+f"(d[32]), "+f"(d[33]), "+f"(d[34]), "+f"(d[35]), "+f"(d[36]), "+f"(d[37]), "+f"(d[38]), "+f"(d[39]),
          "+f"(d[40]), "+f"(d[41]), "+f"(d[42]), "+f"(d[43]), "+f"(d[44]), "+f"(d[45]), "+f"(d[46]), "+f"(d[47]),
          "+f"(d[48]), "+f"(d[49]), "+f"(d[50]), "+f"(d[51]), "+f"(d[52]), "+f"(d[53]), "+f"(d[54]), "+f"(d[55]),
          "+f"(d[56]), "+f"(d[57]), "+f"(d[58]), "+f"(d[59]), "+f"(d[60]), "+f"(d[61]), "+f"(d[62]), "+f"(d[63]),
          "+f"(d[64]), "+f"(d[65]), "+f"(d[66]), "+f"(d[67]), "+f"(d[68]), "+f"(d[69]), "+f"(d[70]), "+f"(d[71]),
          "+f"(d[72]), "+f"(d[73]), "+f"(d[74]), "+f"(d[75]), "+f"(d[76]), "+f"(d[77]), "+f"(d[78]), "+f"(d[79]),
          "+f"(d[80]), "+f"(d[81]), "+f"(d[82]), "+f"(d[83]), "+f"(d[84]), "+f"(d[85]), "+f"(d[86]), "+f"(d[87]),
          "+f"(d[88]), "+f"(d[89]), "+f"(d[90]), "+f"(d[91]), "+f"(d[92]), "+f"(d[93]), "+f"(d[94]), "+f"(d[95])
        : "r"(a0), "r"(a1), "r"(a2), "r"(a3), "l"(db));
}

template <int HS>
__device__ __forceinline__ void attn_pair(const uint32_t* q, const uint32_t* k, const uint32_t* v, const uint32_t* kh, const uint32_t* vh,
                                          const float* fu, const float* fn, const float* rk, float bias0, float bias1, uint32_t mU, uint32_t zero, const float* ci, uint32_t* o) {
    float s0[2][4] = {}, s1[2][4] = {}, s2[2][4] = {};
#pragma unroll
    for (int n = 0; n < 4; n++) {
        const int hd = n & 1, a = 8 * hd + 2 * (n & 2);
        mma16816(s1[hd], q[a], q[a + 1], q[a + 2], q[a + 3], k[a], k[a + 2]);
        mma16816(s2[hd], q[a], q[a + 1], q[a + 2], q[a + 3], k[a + 1], k[a + 3]);
    }
#pragma unroll
    for (int n = 0; n < 4; n++) {
        const int hd = n & 1, a = 8 * hd + 2 * (n & 2);
        mma16816(s0[hd], q[a], q[a + 1], q[a + 2], q[a + 3], kh[HS * (a / 2)], kh[HS * (a / 2 + 1)]);
    }
    float e[2][4], m[2][2];
#pragma unroll
    for (int hd = 0; hd < 2; hd++) {
        e[hd][2] = fmaf(s1[hd][2], fu[2], s2[hd][2] * fn[2]); e[hd][3] = fmaf(s1[hd][3], fu[3], s2[hd][3] * fn[3]);
        e[hd][0] = fmaf(s0[hd][0], fu[0], fmaf(s1[hd][0], fn[0], bias0)); e[hd][1] = fmaf(s0[hd][1], fu[1], fmaf(s1[hd][1], fn[1], bias1));
        m[hd][1] = fmaxf(e[hd][2], e[hd][3]); m[hd][0] = fmaxf(e[hd][0], e[hd][1]);
    }
#pragma unroll
    for (int x = 1; x < 3; x++)
#pragma unroll
        for (int n = 0; n < 4; n++) m[n & 1][1 - (n >> 1)] = fmaxf(m[n & 1][1 - (n >> 1)], __shfl_xor_sync(0xffffffffu, m[n & 1][1 - (n >> 1)], x));
#pragma unroll
    for (int hd = 0; hd < 2; hd++) {
#pragma unroll
        for (int n = 0; n < 4; n++) e[hd][n] = ex2(e[hd][n] - m[hd][n >> 1]);
        float sum[4] = {};
        mma1688(sum, pack_bf16(e[hd][0], e[hd][1]), pack_bf16(e[hd][2], e[hd][3]), 0x3f803f80u);
        const float i0 = rcp(sum[0]), i1 = rcp(sum[2]);
        const uint32_t plo = pack_bf16(e[hd][0] * rk[0] * i0, e[hd][1] * rk[1] * i0), phi = pack_bf16(e[hd][2] * rk[2] * i1, e[hd][3] * rk[3] * i1);
        const uint32_t z0 = plo & zero, z1 = phi & zero;
        const uint32_t a0 = plo & ~mU, a1 = phi & mU, a3 = phi & ~mU, b0 = plo & mU;
#pragma unroll
        for (int jj = 0; jj < 4; jj++) {
            float c[4];
            asm volatile("mma.sync.aligned.m16n8k16.row.col.f32.bf16.bf16.f32 {%0,%1,%2,%3}, {%4,%5,%6,%7}, {%8,%9}, {%10,%11,%12,%13};"
                         : "=f"(c[0]), "=f"(c[1]), "=f"(c[2]), "=f"(c[3])
                         : "r"(a0), "r"(a1), "r"(z0), "r"(a3), "r"(v[8 * hd + 2 * jj]), "r"(v[8 * hd + 2 * jj + 1]), "f"(ci[0]), "f"(ci[1]), "f"(ci[2]), "f"(ci[3]));
            mma1688(c, b0, z1, vh[HS * (4 * hd + jj)]);
            o[8 * hd + 2 * jj] = pack_bf16(c[0], c[1]); o[8 * hd + 2 * jj + 1] = pack_bf16(c[2], c[3]);
        }
    }
}

__device__ __forceinline__ uint32_t norm_pair(uint32_t u, float m, float rinv) {
    const uint32_t d = pack_bf16(bf_lo(u) - m, bf_hi(u) - m);
    return max(pack_bf16(bf_lo(d) * rinv, bf_hi(d) * rinv), 1u);
}

__global__ void __launch_bounds__(512, 1)
fused_kernel(const __grid_constant__ CUtensorMap mx, const __grid_constant__ CUtensorMap mw, const __grid_constant__ CUtensorMap mwo,
             const __grid_constant__ CUtensorMap mout, const __grid_constant__ CUtensorMap mgu, const __grid_constant__ CUtensorMap mwd,
             const __grid_constant__ CUtensorMap mo,
             const __nv_bfloat16* __restrict__ x, const __nv_bfloat16* __restrict__ wr, Scratch* __restrict__ scr, int swap_gu, const Weights pf) {
    extern __shared__ __align__(1024) uint8_t smem[];
    const uint32_t sb = smem_u32(smem);
    const uint32_t bars = sb + OFF_BAR;
    const int tid = threadIdx.x, lane = tid & 31, warp = __shfl_sync(0xffffffffu, tid >> 5, 0);
    const uint32_t sd = (sb & 0x3FFFF) >> 4;
    const int hp = blockIdx.x & 1, cl = blockIdx.x >> 1;
    int pr = cl - 4 + (max(cl - 36, 0) * 37 >> 8);
    asm("{\n.reg .pred p;\nsetp.lt.s32 p, %1, 4;\nselp.s32 %0, %2, %0, p;\n}" : "+r"(pr) : "r"(cl), "r"(39 + 8 * cl));
    const int b = pr * 2 + hp, mt = pr >> 3, p = pr & 7, nt = 2 * p + hp, rh = p & 1, cb = (p & 6) + hp;
    const int par = mt >> 2, j0 = (mt & 3) * 256;
    int budget = BUDGET;

    TSC(tid == 0, 0);
    if (b < 128 && tid >= 32 && tid < 112) {
        const char* a = tid < 64 ? (const char*)x + (size_t)(16 * b + ((tid >> 1) & 15)) * 2048 + (tid & 1) * 128 : pf.wqkv + (size_t)b * 6144 + (tid - 64) * 128;
        asm volatile("prefetch.global.L2 [%0];" ::"l"(a));
    }
    auto load_w = [&](int k, int s) {
        const uint32_t full = bars + 8 * (B_WFULL + s);
        mbar_expect_tx(full, W_BYTES);
        tma_3d(sb + OFF_W + s * W_BYTES, &mw, full, nt * 64, k * 64, 0);
    };
    auto load_x = [&](int n) {
        const int w = n & 1, j = n < 4 ? (n >> 1) + 4 : (n >> 1) - 2;
        const uint32_t full = bars + 8 * (B_XFULL + w * 6 + 5 - j);
        mbar_expect_tx(full, BOX);
        tma_4d(sb + w * OFF_X1 + j * BOX, &mx, full, par * 1024 + (n >> 2) * 64, 0, (j0 + w * 128) >> 5, (~n >> 1) & 1);
    };
    if (warp < NBAR / 6 && elect_one()) {
        const uint32_t cnt = warp < B_WEMPTY / 6 ? 1 : warp < B_G1DONE / 6 ? 2 : warp < B_STAGED / 6 ? 4 : 8;
#pragma unroll
        for (int i = 0; i < 6; i++) mbar_init(bars + 48 * warp + 8 * i, cnt);
        asm volatile("fence.mbarrier_init.release.cluster;" ::: "memory");
        if (warp == 0 && b < 128) { load_x(0); load_w(0, 2); }
    }
    __syncthreads();

    if (b >= 128) {
        const int hc = b - 128, g = lane >> 2, t = lane & 3;
        if (warp < 12) {
            const int n = warp / 3, part = warp - 3 * n;
            const uint32_t ep = ld_rlx(&scr->epoch[0]) + 1;
            auto load = [&](int k) {
                const uint32_t full = bars + 8 * (2 * n + (k & 1));
                mbar_expect_tx(full, W_BYTES);
                tma_3d(sb + (2 * n + (k & 1)) * W_BYTES, &mw, full, (4 * hc + n) * 64, k * 64, 0);
            };
            if (part == 0 && elect_one()) { load(0); load(1); }
            __syncwarp();
            float c0[4] = {0.f, 0.f, 0.f, 0.f}, c1[4] = {0.f, 0.f, 0.f, 0.f};
            const uint32_t sel = g == 0 ? 0x3f80u : g == 1 ? 0x3f800000u : 0u;
            const uint32_t a = sb + 2 * n * W_BYTES + part * BOX + t * 256 + ((g ^ (2 * t)) << 4);
#pragma unroll 1
            for (int k = 0; k < 16; k++) {
                mbar_wait(bars + 8 * (2 * n + (k & 1)), (k >> 1) & 1, budget);
                uint4 v[8], u[8];
#pragma unroll
                for (int i = 0; i < 8; i++) { v[i] = lds4(a + (k & 1) * W_BYTES + i * 1024); u[i] = lds4(((a + 128) ^ 16) + (k & 1) * W_BYTES + i * 1024); }
#pragma unroll
                for (int i = 0; i < 8; i++) { mma16816(c0, v[i].x, v[i].y, u[i].x, u[i].y, sel, sel); mma16816(c1, v[i].z, v[i].w, u[i].z, u[i].w, sel, sel); }
                bar_sync(1 + n, 96);
                if (part == 0 && k < 14 && elect_one()) load(k + 2);
                __syncwarp();
            }
            if (t == 0) {
#pragma unroll
                for (int r = 0; r < 3; r++) {
                    const uint32_t q0 = pack_bf16(c0[0], c0[1]), q1 = pack_bf16(c0[2], c0[3]), q2 = pack_bf16(c1[0], c1[1]), q3 = pack_bf16(c1[2], c1[3]);
                    st_rlx4(&scr->cs[4 * hc + n][16 + (part * 8 + g) * 32 + r * 4], q0, q1, q2, q3);
                    c0[0] -= bf_lo(q0); c0[1] -= bf_hi(q0); c0[2] -= bf_lo(q1); c0[3] -= bf_hi(q1);
                    c1[0] -= bf_lo(q2); c1[1] -= bf_hi(q2); c1[2] -= bf_lo(q3); c1[3] -= bf_hi(q3);
                }
            }
            bar_sync(7, 384);
            if (tid == 0) { fence_gpu(); st_rlx(&scr->csflag[hc], ep); }
            TSC(tid == 0, 19);
        }
        if (warp < 8) TS_END();
        return;
    }
    asm volatile("barrier.cluster.arrive.relaxed.aligned;" ::: "memory");

    const int kc = b >> 4, c2 = b & 15;
    if (warp >= 12) {
        reg_dec<24>();
        if (warp == 12) {
            if (elect_one()) {
#pragma unroll 1
                for (int n = 1; n < 12; n++) {
                    load_x(n);
                    if (n == ROWS_AT) { mbar_expect_tx(bars + 8 * B_ROW, 4 * BOX); bulk_g2s(sb + OFF_FR, x + (size_t)b * 16 * 1024, 4 * BOX, bars + 8 * B_ROW); }
                    if (n == 3 || n == 7) load_w((n + 1) >> 2, n >> 2);
                }
                int s = 2; uint32_t ph = 0;
#pragma unroll 1
                for (int k = 3; k < 16; k++) {
                    mbar_wait(bars + 8 * (B_WEMPTY + s), ph, budget);
                    load_w(k, s);
                    if (++s == 3) s = 0;
                    if (s == 2) ph ^= 1;
                }
                s = 2;
#pragma unroll 1
                for (int i = 0; i < 16; i++) {
                    mbar_wait(bars + 8 * (i < 2 ? B_WEMPTY + i : i < 4 ? B_G1DONE : i < 6 ? B_F1DONE : B_WOEMPTY + s), i >= 12, budget);
                    if (i == 0) {
                        mbar_expect_tx(bars + 8 * B_XT, 4 * BOX);
#pragma unroll 1
                        for (int n = 0; n < 4; n++)
                            tma_4d(sb + (n >> 1) * OFF_X1 + (n & 1) * BOX, &mx, bars + 8 * B_XT, par * 1024 + cb * 128 + (n & 1) * 64, 0, (j0 + rh * 128) >> 5, 1 - (n >> 1));
                    }
                    const uint32_t full = bars + 8 * (B_WOFULL + s);
                    mbar_expect_tx(full, 2 * BOX);
                    tma_3d(sb + OFF_WO + s * 2 * BOX, &mwo, full, 0, ((2 * p + (i < 2 ? i ^ hp : i)) & 15) * 64, cb * 2);
                    TSC(TIMING % 10 == 4, 48 + i);
                    if (++s == 6) s = 0;
                }
            }
        } else {
            bar_sync(8, 224);
            const uint32_t ep = __shfl_sync(0xffffffffu, lds1(sb + OFF_EP), 0);
            if (warp == 13) {
                cluster_wait();
                if (elect_one()) {
                    int j = 4, q = 0, left = BUDGET; uint32_t ph = 0;
#pragma unroll 1
                    for (int n = 6; n < 32; n++) {
                        mbar_wait(bars + 8 * (B_XEMPTY + j), ph, left);
                        tma_4d_mc(sb + hp * OFF_X1 + j * BOX, &mx, bars + 8 * (B_XFULL + hp * 6 + 5 - j), par * 1024 + (n >> 1) * 64, 0, (j0 + hp * 128) >> 5, ~n & 1);
                        if (++j == 6) j = 0;
                        if (j == 4) ph ^= 1;
#pragma unroll 1
                        for (; q < (PF_RATE * (n - PF_START) >> 3) && q < 18 + PF_NW; q++) {
                            const int u = q - PF_NW;
                            if (u < 0) bulk_pf(pf.wqkv + (size_t)(1024 + 128 * u + b) * 6144, 6144);
                            else if (u < 16) bulk_pf((b < 64 ? pf.wg : pf.wu) + (size_t)(u * 64 + (b & 63)) * 7168, 7168);
                            else bulk_pf(pf.wo + (size_t)((u - 16) * 128 + b) * 8192, 8192);
                        }
                    }
                }
                __syncwarp();
                uint32_t* hs = &scr->halo[b - 16][lane * 4];
                int tries = BUDGET;
#pragma unroll 1
                for (int c = 0; c < 4; c += 2) {
                    uint4 v0 = make_uint4(0, 0, 0, 0), v1 = v0;
                    if (j0) {
#pragma unroll 1
                        do { v0 = ld_rlx4(hs + c * 128); v1 = ld_rlx4(hs + c * 128 + 128); } while ((v0.x == 0 || v1.x == 0) && --tries > 0);
                        st_rlx(hs + c * 128, 0); st_rlx(hs + c * 128 + 128, 0);
                    }
                    __syncwarp();
                    stsm4(sb + OFF_HIN + c * 512 + lane * 16, v0.x, v0.y, v0.z, v0.w);
                    stsm4(sb + OFF_HIN + c * 512 + 512 + lane * 16, v1.x, v1.y, v1.z, v1.w);
                }
                bar_arrive(11, 64);
                TSC(lane == 0, 31);
                const int src = ((mt * 2 + rh) * 2 + 1 - hp) * 1024;
                if (elect_one()) {
                    const uint32_t* fl = &scr->oflag[mt * 2 + 1 - hp][0];
                    const uint32_t inv = (ep & 1) - 1;
                    uint32_t ready = 0, ph = 0;
                    int s = 4;
#pragma unroll 1
                    for (int i = 2; i < 16; i++) {
                        const int kb = (2 * p + i) & 15;
#pragma unroll 1
                        while (!((ready >> kb) & 1) && --budget > 0) ready = ld_rlx(fl) ^ inv;
                        TSC(i == 2, 30);
                        mbar_wait(bars + 8 * (B_OEMPTY + s), ph, budget);
                        tma_2d_mc(sb + hp * OFF_X1 + s * BOX, &mo, bars + 8 * (B_OFULL + hp * 6 + s), 0, src + kb * 64);
                        TSC(TIMING % 10 == 4 && hp == 0, 32 + i);
                        if (++s == 6) s = 0;
                        if (s == 4) ph ^= 1;
                    }
                }
            } else if (warp == 14) {
                if (elect_one()) {
                    uint32_t s8 = 0, ph = 0;
                    int tries = BUDGET;
                    const uint32_t* act = scr->act[ep & 1];
                    auto counted = [&](int c, uint32_t n) {
#pragma unroll 1
                        while (ld_rlx(&scr->cnt[c][0]) != ep * n && --tries > 0) __nanosleep(POLL_NS);
                    };
                    auto weights = [&](const CUtensorMap* m, int c0, int c1, int c2_) {
                        mbar_wait(bars + 8 * B_FEMPTY + s8, ph, budget);
                        mbar_expect_tx(bars + 8 * B_FFULL + s8, F_BYTES);
                        tma_3d(sb + OFF_FS + s8 * (F_BYTES / 8), m, bars + 8 * B_FFULL + s8, c0, c1, c2_);
                    };
                    if (b < 112) {
                        counted(8, 32);
                        TS(26);
#pragma unroll 1
                        for (int q = 0; q < 16; q++) {
                            weights(&mgu, b * 32, q * 64, 0);
                            bulk_g2s(sb + OFF_FS + BOX + s8 * (F_BYTES / 8), act + 14336 + q * 256, 1024, bars + 8 * B_FFULL + s8);
                            if (q >= 8) bulk_pf(pf.wd + (size_t)((q - 8) * 112 + b) * 8192, 8192);
                            s8 += 8;
                            if (s8 == 40) { s8 = 0; ph ^= 1; }
                        }
                    }
#pragma unroll 1
                    for (int q = -3; q < 7; q++) {
                        if (q == 0) { counted(kc, 28); TS(29); }
                        if ((unsigned)q >= 3) weights(&mwd, 0, kc * 448 + (q < 0 ? q + 3 : q) * 64, c2);
                        if (q >= 0) bulk_g2s(sb + OFF_FS + BOX + s8 * (F_BYTES / 8), act + (kc * 7 + q) * 256, 1024, bars + 8 * B_FFULL + s8);
                        s8 += 8;
                        if (s8 == 24) { s8 = 0; if ((unsigned)q >= 3) ph ^= 1; }
                    }
                }
            } else {
                mbar_wait(bars + 8 * B_ROW, 0, budget);
                uint8_t* oz = scr->o + ((size_t)mt * 64 + nt) * BOX + lane * 16;
#pragma unroll 1
                for (int i = 0; i < ZF_N; i++) { st_rlx4(oz + (i >> 4) * 16 * BOX + (i & 15) * 512, 0, 0, 0, 0); if ((i & 3) == 3) __nanosleep(ZF_NS); }
                __syncwarp();
                fence_gpu();
                mbar_wait(bars + 8 * B_RDONE, 0, budget);
                int tries = BUDGET;
#pragma unroll 1
                for (int i = lane; i < 88; i += 32) {
                    const uint2* rp = &scr->row[2 * (j0 - 8 + i) + par];
                    uint2 v0, v1, v2;
#pragma unroll 1
                    do { v0 = ld_rlx2(rp + (j0 + i < 8 ? 16 : 0)); v1 = ld_rlx2(rp + 176); v2 = ld_rlx2(rp + 352); } while ((((v0.y ^ ep) | (v1.y ^ ep) | (v2.y ^ ep)) & 31) && --tries > 0);
                    sts2(sb + OFF_STAT + i * 8, (v0.x << 16) ^ 0x80000000u, __float_as_uint(rcp(bf_hi(v0.x))));
                    sts2(sb + OFF_STAT + i * 8 + 704, (v1.x << 16) ^ 0x80000000u, __float_as_uint(rcp(bf_hi(v1.x))));
                    sts2(sb + OFF_STAT + i * 8 + 1408, (v2.x << 16) ^ 0x80000000u, __float_as_uint(rcp(bf_hi(v2.x))));
                }
                __syncwarp();
                poll_all(&scr->csflag[lane & 3], ~0u, ep, budget);
                if (elect_one()) {
                    fence_async_gmem();
                    mbar_expect_tx(bars + 8 * B_AUX, CS_BYTES);
                    bulk_g2s(sb + OFF_CS, scr->cs[nt], CS_BYTES, bars + 8 * B_AUX);
                    TS(21);
                    mbar_expect_tx(bars + 8 * (B_OFULL + 3), BOX); mbar_expect_tx(bars + 8 * (B_OFULL + 9), BOX);
#pragma unroll 1
                    for (int v = 0; v < 2; v++) {
                        const uint32_t ring = sb + v * OFF_X1 + 2 * BOX, fb = bars + 8 * (B_OFULL + v * 6 + 2);
                        mbar_wait(bars + 8 * (B_STAGED + v), 0, budget);
                        asm volatile("red.relaxed.gpu.global.xor.b32 [%0], %1;" ::"l"(&scr->oflag[mt * 2 + 1 - v][0]), "r"(1u << nt) : "memory");
                        TS(13 + 2 * v);
                        mbar_arrive(fb);
                        mbar_wait(bars + 8 * B_G1DONE, 0, budget);
                        bulk_s2c(mapa(ring + BOX, hp ^ 1), ring, BOX, mapa(fb + 8, hp ^ 1));
                        if (v == 0) mbar_wait(bars + 8 * B_FREED, 0, budget);
#pragma unroll
                        for (int n = 0; n < 4; n++) {
                            mbar_expect_tx(bars + 8 * (B_OFULL + (n >> 1) * 6 + 4 + (n & 1)) - v * 32, BOX);
                            mbar_arrive_at(mapa(bars + 8 * B_OEMPTY, n >> 1) + (4 + (n & 1)) * 8 - v * 32);
                        }
                    }
                }
            }
        }
    } else if (warp >= 8) {
        reg_dec<40>();
        const int wq = warp - 8, ta = tid - 256;
        const uint32_t rbuf = sb + OFF_FR + wq * BOX, rbar = bars + 8 * B_ROW;
        const uint4 wv = ldg_nc(wr + ta * 8);
        if (ta == 0) sts1(sb + OFF_EP, ld_rlx(&scr->epoch[0]) + 1);
        sts4(sb + OFF_STAT + ta * 16, wv.x, wv.y, wv.z, wv.w);
        bar_sync(8, 224);
        const uint32_t ep = __shfl_sync(0xffffffffu, lds1(sb + OFF_EP), 0);
        {
            const int s = b * 16 + wq * 4 + (lane >> 3);
            if ((lane & 7) == 0) st_rlx2(&scr->row[s], 0, ep - 1);
            float sw = 0.f;
#pragma unroll 1
            for (int i = 0; i < 16; i++) { const uint32_t q = lds1(sb + OFF_STAT + i * 128 + lane * 4); sw += bf_lo(q) + bf_hi(q); }
#pragma unroll 1
            for (int o = 16; o > 0; o >>= 1) sw += __shfl_xor_sync(0xffffffffu, sw, o);
            float s1 = 0.f, s2 = 0.f, sr = 0.f;
            const uint32_t xa = rbuf + (lane >> 3) * 2048 + (lane & 7) * 16, wa = sb + OFF_STAT + (lane & 7) * 16;
            mbar_wait(rbar, 0, budget);
            TSC(ta == 0, 17);
            {
                float s1b = 0.f, s2b = 0.f, srb = 0.f;
                const uint32_t xb = rbuf + (lane >> 4) * 4096 + (lane & 15) * 16, wb = sb + OFF_STAT + (lane & 15) * 16;
                uint4 w4 = lds4(wb), u = lds4(xb), v = lds4(xb + 2048);
#pragma unroll 1
                for (int i = 1; i <= 8; i++) {
                    const uint32_t o = (i * 256) & 2047;
                    float wf[8];
#pragma unroll
                    for (int c = 0; c < 4; c++) { wf[2 * c] = bf_lo((&w4.x)[c]); wf[2 * c + 1] = bf_hi((&w4.x)[c]); }
                    w4 = lds4(wb + o);
#pragma unroll
                    for (int c = 0; c < 4; c++) {
                        const float a0 = bf_lo((&u.x)[c]), a1 = bf_hi((&u.x)[c]);
                        s1 += a0; s2 = fmaf(a0, a0, s2); sr = fmaf(a0, wf[2 * c], sr);
                        s1 += a1; s2 = fmaf(a1, a1, s2); sr = fmaf(a1, wf[2 * c + 1], sr);
                    }
                    u = lds4(xb + o);
#pragma unroll
                    for (int c = 0; c < 4; c++) {
                        const float a0 = bf_lo((&v.x)[c]), a1 = bf_hi((&v.x)[c]);
                        s1b += a0; s2b = fmaf(a0, a0, s2b); srb = fmaf(a0, wf[2 * c], srb);
                        s1b += a1; s2b = fmaf(a1, a1, s2b); srb = fmaf(a1, wf[2 * c + 1], srb);
                    }
                    v = lds4(xb + 2048 + o);
                }
                const bool up = lane & 8;
                s1 = (up ? s1b : s1) + __shfl_xor_sync(0xffffffffu, up ? s1 : s1b, 8);
                s2 = (up ? s2b : s2) + __shfl_xor_sync(0xffffffffu, up ? s2 : s2b, 8);
                sr = (up ? srb : sr) + __shfl_xor_sync(0xffffffffu, up ? sr : srb, 8);
            }
#pragma unroll
            for (int o = 1; o < 8; o <<= 1) {
                s1 += __shfl_xor_sync(0xffffffffu, s1, o); s2 += __shfl_xor_sync(0xffffffffu, s2, o); sr += __shfl_xor_sync(0xffffffffu, sr, o);
            }
            const float mean = s1 * (1.f / 1024.f), mb = bf16r(mean);
            float var = fmaf(-mean, mean, s2 * (1.f / 1024.f));
            sr = fmaf(-mb, sw, sr);
            if (__builtin_expect(__any_sync(0xffffffffu, mean * mean > 256.f * var), 0)) {
                float a2 = 0.f, ar = 0.f;
#pragma unroll 1
                for (int i = 0; i < 64; i++) {
                    const uint32_t o = (i >> 2) * 128 + (i & 3) * 4, q1 = lds1(xa + o), q2 = lds1(wa + o);
                    a2 = fmaf(bf_lo(q1) - mean, bf_lo(q1) - mean, fmaf(bf_hi(q1) - mean, bf_hi(q1) - mean, a2));
                    ar = fmaf(bf_lo(q1) - mb, bf_lo(q2), fmaf(bf_hi(q1) - mb, bf_hi(q2), ar));
                }
#pragma unroll 1
                for (int o = 1; o < 8; o <<= 1) { a2 += __shfl_xor_sync(0xffffffffu, a2, o); ar += __shfl_xor_sync(0xffffffffu, ar, o); }
                var = a2 * (1.f / 1024.f); sr = ar;
            }
            float den;
            asm("sqrt.approx.f32 %0, %1;" : "=f"(den) : "f"(bf16r(bf16r(var) + 1e-5f)));
            const uint32_t st = pack_bf16(mb, den);
            const uint32_t rb = pack_bf16(0.f, sr * rcp(bf_hi(st)) + 0.f);
            uint32_t ord = (int)rb < 0 ? ~rb & 0xffff0000u : rb | 0x80000000u;
            if ((rb & 0x7fffffffu) > 0x7f800000u) ord = 0;
            if ((lane & 7) == 0) st_rlx2(&scr->row[s], st, ord | ((2047 - s) << 5) | (ep & 31));
            __syncwarp();
            if (lane < 7) mbar_arrive(bars + 8 * (lane < 5 ? B_FEMPTY + lane : B_RDONE));
        }
        TSC(ta == 0, 18);
        if ((b >> 3) == 14) {
            const uint32_t gm = sb + OFF_E, cnt = gm + 64, res = gm + 80, list = gm + 128;
            uint32_t kv[16];
            int tries = BUDGET;
#pragma unroll 1
            do {
                uint32_t bad = 0;
#pragma unroll
                for (int n = 0; n < 16; n++) kv[n] = ld_rlx(&scr->row[n * 128 + ta].y);
#pragma unroll
                for (int n = 0; n < 16; n++) bad |= kv[n] ^ ep;
                if ((bad & 31) == 0) break;
            } while (--tries > 0);
            __syncwarp();
            TSC(ta == 0, 26);
            uint32_t m = 0;
#pragma unroll
            for (int n = 0; n < 16; n++) m = max(m, kv[n]);
            uint32_t gmax = m;
#pragma unroll
            for (int o = 1; o < 8; o <<= 1) gmax = max(gmax, __shfl_xor_sync(0xffffffffu, gmax, o));
            sts1(gm + (ta >> 3) * 4, gmax);
            sts1(cnt, 0);
            bar_sync(12, 128);
            const uint32_t c = lds1(gm + (lane & 15) * 4);
            int rank = 0;
#pragma unroll
            for (int i = 0; i < 2; i++) { const uint4 q = lds4(gm + (lane >> 4) * 32 + i * 16); rank += (q.x > c) + (q.y > c) + (q.z > c) + (q.w > c); }
            rank += __shfl_xor_sync(0xffffffffu, rank, 16);
            const uint32_t thr = redux_max(rank == 7 ? c : 0u);
#pragma unroll 1
            while (m >= thr) {
                uint32_t at, m2 = 0;
                asm volatile("atom.shared.add.u32 %0, [%1], 1;" : "=r"(at) : "r"(cnt) : "memory");
#pragma unroll
                for (int n = 0; n < 16; n++) m2 = max(m2, kv[n] < m ? kv[n] : 0u);
                sts1(list + at * 4, m);
                if (m2 == 0) break;
                m = m2;
            }
            bar_sync(12, 128);
            const int nc = lds1(cnt);
#pragma unroll 1
            for (int i = ta >> 3; i < ((nc + 3) & ~3); i += 16) {
                const uint32_t ki = lds1(list + i * 4);
                int r = 0;
#pragma unroll 1
                for (int n = lane & 7; n < nc; n += 8) r += lds1(list + n * 4) > ki;
                __syncwarp();
#pragma unroll
                for (int o = 1; o < 8; o <<= 1) r += __shfl_xor_sync(0xffffffffu, r, o);
                if (r == (b & 7) && i < nc) sts1(res, ki);
            }
            bar_sync(12, 128);
            const uint32_t k0 = lds1(res);
            const int r0 = 2047 - ((k0 >> 5) & 2047);
            TSC(ta == 0, 22);
            if (ta == 0) st_rlx(&scr->sel[b & 7], k0);
            const uint4 v0 = ldg_nc(x + (size_t)r0 * 1024 + ta * 8);
            const uint32_t s0 = ld_rlx(&scr->row[r0]);
            const float m0 = bf_lo(s0), i0 = rcp(bf_hi(s0));
            const int ao = 14336 + (ta >> 3) * 256 + (b & 7) * 32 + ((ta ^ b) & 7) * 4;
            st_rlx4(scr->act[ep & 1] + ao, norm_pair(v0.x, m0, i0), norm_pair(v0.y, m0, i0), norm_pair(v0.z, m0, i0), norm_pair(v0.w, m0, i0));
            __syncwarp();
            if (lane == 0) red_add(&scr->cnt[8][tries >> 30]);
            st_rlx4(scr->act[~ep & 1] + ao, 0, 0, 0, 0);
        }
        uint32_t s8 = 0, fph = 0, own = 0; float sig = 0.f;
        const uint32_t chk = __shfl_sync(0xffffffffu, sb + OFF_FS + BOX + lane * 32 + (lane & 28), lane);
        int left = BUDGET;
#pragma unroll 1
        for (int ph = 0; ph < 2; ph++) {
            if (ph || b < 112) {
                float acc[4] = {0.f, 0.f, 0.f, 0.f};
                const uint32_t alo = sd + (ph ? dlo(OFF_FS, 8192) : dlo(OFF_FS, 4096)), ahi = ph ? dhi(1024, 1) : dhi(512, 2), astep = ph ? 128 : 64;
                const uint32_t bhi = ph ? dhi(128, 0) : dhi(1024, 1), bstep = ph ? 16 : 2, wrap = ph ? 24 : 40;
                uint32_t prev = 0, prev2 = 0;
                if (ph) mbar_wait(bars + 8 * FFN2_GATE, 0, left);
#pragma unroll 1
                for (int q = ph ? 7 : 16; q > 0; q--) {
                    const uint32_t da = alo + s8 * (F_BYTES >> 7), db = sd + dlo(OFF_FS + BOX, 128) + s8 * (F_BYTES >> 7);
                    mbar_wait_hot(bars + 8 * B_FFULL + s8, fph, left);
                    if (__builtin_expect(__any_sync(0xffffffffu, lds1(chk + s8 * (F_BYTES / 8)) == 0), 0)) {
                        int tries = BUDGET;
#pragma unroll 1
                        for (int n = lane * 4 + (left >> 30); n < 256; n += 128) {
                            uint4 v;
#pragma unroll 1
                            do { v = ld_rlx4(scr->act[ep & 1] + ((ph ? kc * 7 + 7 : 72) - q) * 256 + n); } while (v.x == 0 && --tries > 0);
                            __syncwarp();
                            sts4(sb + OFF_FS + BOX + s8 * (F_BYTES / 8) + n * 4, v.x, v.y, v.z, v.w);
                        }
                        NRETRY();
                        fence_async_smem();
                        __syncwarp();
                    }
                    TSC(TIMING % 10 == 3 && ta == 0, 32 + (ph ? 23 : 16) - q);
                    wg_fence();
#pragma unroll
                    for (int j = 0; j < 4; j++) wgmma_n8<1, 0>(acc, mkdesc(da + j * astep, ahi), mkdesc(db + j * bstep, bhi), 1);
                    wg_commit();
                    prev2 = prev;
                    if (lane == 0) prev = bars + 8 * B_FEMPTY + s8;
                    wg_wait<1>();
                    if (ph) { wg_wait<0>(); prev2 = prev; }
                    if (prev2) mbar_arrive(prev2);
                    s8 += 8;
                    if (s8 == wrap) { s8 = 0; fph ^= 1; }
                }
                wg_wait<0>();
                const int ln = lane + (left >> 30);
                if (ph == 0) {
                    if (prev) mbar_arrive(prev);
                    const bool second = (wq >= 2) != (swap_gu != 0);
                    const uint32_t xa = sb + OFF_GU + ((wq & 1) * 32 + ln) * 16;
                    if (second) sts4(xa, __float_as_uint(acc[0]), __float_as_uint(acc[1]), __float_as_uint(acc[2]), __float_as_uint(acc[3]));
                    bar_sync(12, 128);
                    if (!second) {
                        const float4 up = lds4f(xa);
                        float hv[4];
#pragma unroll
                        for (int c = 0; c < 4; c++) { const float ga = bf16r(acc[c]); hv[c] = bf16r(ga * sigmoidf(ga)) * bf16r((&up.x)[c]); }
                        const int ao = (b * 4 + (wq & 1) * 2) * 32 + ln;
                        st_rlx(scr->act[ep & 1] + ao, max(movm(pack_bf16(hv[0], hv[1])), 1u)); st_rlx(scr->act[ep & 1] + 32 + ao, max(movm(pack_bf16(hv[2], hv[3])), 1u));
                        __syncwarp();
                        if (ln == 0) red_add(&scr->cnt[b / 14][0]);
                        st_rlx(scr->act[~ep & 1] + ao, 0); st_rlx(scr->act[~ep & 1] + 32 + ao, 0);
                    }
                } else {
#pragma unroll
                    for (int c = 0; c < 4; c++) st_rlx(&scr->ypart[kc][2 * (ln & 3) + (c & 1)][c2 * 64 + wq * 16 + (c >> 1) * 8 + (ln >> 2)], (__float_as_uint(acc[c]) & ~1u) | (ep & 1));
                    if (b == 0 && ta == 0) st_rlx(&scr->epoch[ln], ep);
                }
                TSC(ta == 0, 22 + ph);
            }
            const int ln = lane + (left >> 30);
            if (ph == 0) {
                if ((ta & 126) == 64) mbar_arrive(bars + 8 * B_F1DONE);
                const uint32_t kj = poll_all(&scr->sel[ln & 7], 31u, ep & 31, left);
                const int row = 2047 - ((kj >> 5) & 2047), jj = (row & 1) == par ? (row >> 1) - j0 : -1;
                sig = bf16r(sigmoidf(__uint_as_float(((int)kj < 0 ? kj & 0x7fffffffu : ~kj) & 0xffff0000u)));
                own = __ballot_sync(0xffffffffu, (jj >> 7) == rh) & 255;
                sts1(sb + OFF_SEL + (ln & 7) * 4, jj);
                sts4(sb + OFF_UPD + wq * 512 + ln * 16, 0, 0, 0, 0);
            }
            if ((own != 0) == ph) {
                if (wq & 2) own &= own - 1;
#pragma unroll 1
                for (; own; own &= own - 1, own &= own - 1) {
                    const int j = __ffs(own) - 1;
                    const uint32_t* src = &scr->ypart[ln >> 4][j][cb * 128 + (wq & 1) * 64 + (ln & 15) * 4];
                    uint4 v[4]; int tries = BUDGET;
#pragma unroll 1
                    do {
#pragma unroll
                        for (int m = 0; m < 4; m++) v[m] = ld_rlx4(src + m * 2 * 8192);
                    } while ((((v[0].x ^ ep) | (v[1].x ^ ep) | (v[2].x ^ ep) | (v[3].x ^ ep)) & 1) && --tries > 0);
                    __syncwarp();
                    float a[4];
                    const float sj = __shfl_sync(0xffffffffu, sig, j);
#pragma unroll
                    for (int c = 0; c < 4; c++) {
                        a[c] = (__uint_as_float((&v[0].x)[c]) + __uint_as_float((&v[1].x)[c])) + (__uint_as_float((&v[2].x)[c]) + __uint_as_float((&v[3].x)[c]));
                        a[c] = bf16r(a[c] + __shfl_xor_sync(0xffffffffu, a[c], 16)) * sj;
                    }
                    sts2(sb + OFF_UPD + (wq & 1) * 1024 + j * 128 + ((((ln >> 1) & 7) ^ j) << 4) + (ln & 1) * 8, pack_bf16(a[0], a[1]), pack_bf16(a[2], a[3]));
                }
                fence_async_smem();
                __syncwarp();
                if (ln < 2) mbar_arrive(bars + 8 * B_UPD);
            }
        }
        TSC(ta == 0, 24);
    } else {
        reg_inc<224>();
        const int w = warp >> 2, wi = warp & 3, g = lane >> 2, t = lane & 3;
        const bool elect = (tid & 127) == 0;
        const uint32_t mad = (lane & 15) * 128 + (((lane >> 4) ^ (lane & 7)) << 4);
        float acc[64];
        const uint32_t ring = sb + w * OFF_X1, ofull = bars + 8 * (B_OFULL + w * 6), oempty = mapa(bars + 8 * B_OEMPTY, w);
        const int r0 = rh * 128 + wi * 32 + (1 - w) * 16 + g;
        {
            float acc0[96], acc1[96];
            const uint32_t sta = sb + OFF_STAT + (8 + w * 128 + wi * 32) * 8;
            {
                const uint32_t xfull = bars + 8 * (B_XFULL + w * 6 + 5), xempty = mapa(bars + 8 * B_XEMPTY, w), dx0 = sd + dlo(w * OFF_X1, 16);
                uint32_t s8 = 16, ps8 = 0, ph = 0;
                cluster_wait();
#pragma unroll 1
                for (int k = 0; k < 16; k++) {
                    const uint32_t dx = dx0 + s8 * (2 * BOX >> 7), dw = sd + dlo(OFF_W, BOX) + s8 * (W_BYTES >> 7);
                    mbar_wait(bars + 8 * B_WFULL + s8, ph, budget);
                    mbar_wait(xfull - 2 * s8, ph, budget);
                    TSC(elect && k == 0, 1 + 8 * w);
                    TSC(TIMING % 10 == 1 && tid == 0, 32 + k);
                    wg_wait<0>();
                    wg_fence();
#pragma unroll
                    for (int kk = 0; kk < 4; kk++) wgmma_n192<0, 1>(acc1, mkdesc(dx + kk * 2, dhi(1024, 1)), mkdesc(dw + kk * 128, dhi(1024, 1)), kk ? 1 : k);
                    wg_commit();
                    if (elect && k > 0) {
                        mbar_arrive(bars + 8 * B_WEMPTY + ps8);
                        if (k <= 13) { mbar_expect_tx(xfull - 2 * ps8 - 8, BOX); mbar_arrive_at(xempty + 2 * ps8 + 8); }
                    }
                    if (k == 15) {
                        mbar_wait(bars + 8 * B_AUX, 0, budget);
                        const uint32_t zero = budget >> 30, pm = t & 1 ? 0x4432 : 0x3232, ra = sta + ((t >> 1) * 16 + g) * 8;
                        const uint32_t a0 = __byte_perm(lds1(ra), 0, pm), a1 = __byte_perm(lds1(ra + 64), 0, pm), a2 = a0 & zero, a3 = a1 & zero;
                        wg_fence();
                        wgmma_rs_n192(acc1, a0, a1, a2, a3, mkdesc(sd + dlo(OFF_CS, 0), dhi(128, 0)));
                        wgmma_rs_n192(acc0, a0, a1, a2, a3, mkdesc(sd + dlo(OFF_CS + 64, 0), dhi(128, 0)));
                        wg_commit();
                    }
                    mbar_wait(xfull - 2 * s8 - 8, ph, budget);
                    wg_wait<0>();
                    wg_fence();
#pragma unroll
                    for (int kk = 0; kk < 4; kk++) wgmma_n192<0, 1>(acc0, mkdesc(dx + 512 + kk * 2, dhi(1024, 1)), mkdesc(dw + kk * 128, dhi(1024, 1)), kk ? 1 : k);
                    wg_commit();
                    if (elect && k <= 12) { mbar_expect_tx(xfull - 2 * s8, BOX); mbar_arrive_at(xempty + 2 * s8); }
                    ps8 = s8;
                    s8 = s8 == 16 ? 0 : s8 + 8;
                    if (s8 == 16) ph ^= 1;
                }
            }
            const uint32_t zero = budget >> 30;
            const bool u0 = 2 * t > g, u1 = 2 * t + 1 > g;
            uint32_t mU = (u0 ? 0xffffu : 0u) | (u1 ? 0xffff0000u : 0u);
            uint32_t ka0 = sta + (2 * t - (u0 ? 8 : 0)) * 8 + 4, ka1 = sta + (2 * t + 1 - (u1 ? 8 : 0)) * 8 + 4;
            float rk[2][4], fu[2][4], fn[2][4];
            auto factors = [&](int h) {
#pragma unroll
                for (int n = 0; n < 4; n += 2) {
                    const float rq = lds1f(sta + (16 * h + 4 * n + g) * 8 + 4) * (0.17677669529663687f * 1.4426950408889634f);
                    rk[h][n] = lds1f(ka0 + h * 128 + n * 32); rk[h][n + 1] = lds1f(ka1 + h * 128 + n * 32);
                    const float f0 = rq * rk[h][n], f1 = rq * rk[h][n + 1];
                    fu[h][n] = u0 ? f0 : 0.f; fn[h][n] = f0 - fu[h][n]; fu[h][n + 1] = u1 ? f1 : 0.f; fn[h][n + 1] = f1 - fu[h][n + 1];
                }
#pragma unroll
                for (int n = 0; n < 4; n++) asm volatile("" : "+f"(fu[h][n]), "+f"(fn[h][n]));
            };
            uint8_t* og = scr->o + ((size_t)(mt * 4 + w * 2) * 16 + nt) * BOX + wi * 256 + lane * 4;
            TSC(elect, 19 + w);
            uint32_t pk0[48], pk1[48], o[16] = {};
#pragma unroll
            for (int j = 0; j < 48; j++) if (j < 16 || (j & 1)) pk1[j] = pack_here(acc1[2 * j], acc1[2 * j + 1]);
            if (warp < 7) {
#pragma unroll
                for (int c = 0; c < 4; c++) stsm4(ring + 4 * BOX + wi * 2048 + c * 512 + lane * 16, pk1[17 + 8 * c], pk1[19 + 8 * c], pk1[21 + 8 * c], pk1[23 + 8 * c]);
                bar_arrive(1 + warp, 64);
            } else if (j0 != 768) {
#pragma unroll
                for (int c = 0; c < 4; c++) {
                    pk1[17 + 8 * c] = max(pk1[17 + 8 * c], 1u);
                    st_rlx4(&scr->halo[b][c * 128 + lane * 4], pk1[17 + 8 * c], pk1[19 + 8 * c], pk1[21 + 8 * c], pk1[23 + 8 * c]);
                }
            }
            TSC(tid == 224, 28);
#pragma unroll
            for (int j = 16; j < 48; j += 2) pk1[j] = pack_here(acc1[2 * j], acc1[2 * j + 1]);
            factors(1);
            uint32_t od = sb + 2 * BOX + wi * 256 + (lane >> 4) * 1024 + (lane & 15) * 16, g1peer = mapa(bars + 8 * B_G1DONE, hp ^ 1);
            uint32_t ha = sb + (warp == 0 ? OFF_HIN : warp <= 4 ? 4 * BOX - 2048 : OFF_X1 + 4 * BOX - 5 * 2048) + warp * 2048 + lane * 16;
            const bool first = warp == 0 && j0 == 0;
            float bias0 = first && u0 ? -INFINITY : 0.f, bias1 = first && u1 ? -INFINITY : 0.f;
            asm volatile("" : "+l"(og), "+r"(mU), "+r"(od), "+r"(ha), "+f"(bias0), "+f"(bias1));
            mbar_wait(bars + 8 * B_XT, 0, budget);
            mbar_wait(bars + 8 * (B_WEMPTY + 1), 0, budget);
            TSC(elect, 12 + 2 * w);
            wg_wait<0>();
            if (elect) { mbar_arrive(bars + 8 * B_G1DONE); mbar_arrive_at(g1peer); }
            TSC(elect, 2 + 8 * w);
            float ci[4];
#pragma unroll
            for (int n = 0; n < 4; n++) ci[n] = __uint_as_float((0x03800000u + n) | (budget >> 30));
            auto hand_over = [&](int v) {
                asm volatile("{\n.reg .pred p;\nsetp.ne.b32 p, %17, 0;\n"
                             "@p stmatrix.sync.aligned.m8n8.x4.shared.b16 [%16], {%0,%1,%2,%3};\n@p stmatrix.sync.aligned.m8n8.x4.shared.b16 [%16 + 2048], {%4,%5,%6,%7};\n"
                             "@p stmatrix.sync.aligned.m8n8.x4.shared.b16 [%16 + 4096], {%8,%9,%10,%11};\n@p stmatrix.sync.aligned.m8n8.x4.shared.b16 [%16 + 6144], {%12,%13,%14,%15};\n"
                             FENCE_PRED "fence.proxy.async.shared::cta;\n}"
                             ::"r"(o[0]), "r"(o[1]), "r"(o[2]), "r"(o[3]), "r"(o[4]), "r"(o[5]), "r"(o[6]), "r"(o[7]), "r"(o[8]), "r"(o[9]), "r"(o[10]), "r"(o[11]),
                               "r"(o[12]), "r"(o[13]), "r"(o[14]), "r"(o[15]), "r"(od + v * OFF_X1), "r"((int)(w == rh)) : "memory");
                TSC(tid == 0, v ? 27 : 5);
#pragma unroll
                for (int i = 0; i < 16; i++) asm volatile("st.global.u32 [%0], %1;" ::"l"(og + (1 - v) * 16 * BOX + (i >> 1) * 1024 + (i & 1) * 128), "r"(o[i]) : "memory");
                __syncwarp();
                if (lane == 0) mbar_arrive(bars + 8 * (B_STAGED + v));
            };
#pragma unroll
            for (int j = 32; j < 48; j++) pk1[j] = movm(pk1[j]);
#pragma unroll
            for (int j = EARLY_PK; j < 48; j++) if (j >= 32 || (j & 1) || EARLY_PK < 17) pk0[j] = pack_here(acc0[2 * j], acc0[2 * j + 1]);
#pragma unroll
            for (int j = 32; j < 48; j++) pk0[j] = movm(pk0[j]);
            factors(0);
            attn_pair<2>(pk1, pk1 + 16, pk1 + 32, pk0 + 17, pk0 + 33, fu[1], fn[1], rk[1], 0.f, 0.f, mU, zero, ci, o);
            hand_over(0);
            TSC(elect, 3 + 8 * w);
#pragma unroll
            for (int j = 0; j < 32; j++) if (j < EARLY_PK || (!(j & 1) && EARLY_PK == 17)) pk0[j] = pack_here(acc0[2 * j], acc0[2 * j + 1]);
            bar_sync(warp ? warp : 11, 64);
            uint32_t hl[16];
            ldsm4(hl, ha); ldsm4(hl + 4, ha + 512); ldsm4t(hl + 8, ha + 1024); ldsm4t(hl + 12, ha + 1536);
            __syncwarp();
            if (lane == 0) mbar_arrive(bars + 8 * B_FREED);
            attn_pair<1>(pk0, pk0 + 16, pk0 + 32, hl, hl + 8, fu[0], fn[0], rk[0], bias0, bias1, mU, zero, ci, o);
            const float2 s0 = lds2f(sb + OFF_STAT + (8 + r0) * 8), s1 = lds2f(sb + OFF_STAT + (16 + r0) * 8);
            const float m0 = s0.x * s0.y, f0 = 1.f + s0.y, m1 = s1.x * s1.y, f1 = 1.f + s1.y;
            uint32_t xt[32];
#pragma unroll
            for (int j = 0; j < 8; j++) ldsm4(xt + 4 * j, ((ring + wi * 2048 + mad) ^ ((j & 3) * 32)) + (j >> 2) * BOX);
            hand_over(1);
#pragma unroll
            for (int j = 0; j < 32; j++) {
                acc[2 * j] = fmaf(bf_lo(xt[j]), j & 1 ? f1 : f0, j & 1 ? m1 : m0); acc[2 * j + 1] = fmaf(bf_hi(xt[j]), j & 1 ? f1 : f0, j & 1 ? m1 : m0);
            }
        }
        TSC(tid == 0, 4);
        {
            const uint32_t da0 = sd + dlo(w * OFF_X1, 1024), db0 = sd + dlo(OFF_WO, BOX);
            const uint32_t chk = ring + wi * 256 + (lane >> 3) * 1032 + (lane & 7) * 32 + (lane & 4);
            uint32_t s8 = 16, ps8 = 0, ph = 0;
            mbar_wait(ofull + s8, 0, budget);
            mbar_wait(bars + 8 * B_WOFULL + s8, 0, budget);
            TSC(TIMING % 10 == 2 && elect, 32 + w * 16);
            const uint32_t ahi = dhi(128, 0) | (budget >> 30), bhi = dhi(1024, 1) | (budget >> 30);
            const int last = w ? HOLD : 16;
            uint32_t rel = elect ? 0x7fe : 0;
#pragma unroll 1
            for (int i = 1;;) {
                const uint32_t da = da0 + s8 * (BOX >> 7), db = db0 + s8 * (BOX >> 6);
                wg_fence();
#pragma unroll
                for (int kk = 0; kk < 4; kk++) {
                    wgmma_n128<0, 1>(acc, mkdesc(da + kk * 128, ahi), mkdesc(db + kk * 128, bhi), 1);
                    if (kk & 1) wg_commit();
                }
                wg_wait<2>();
                if (rel & 1) { mbar_expect_tx(ofull + ps8, BOX); mbar_arrive_at(oempty + ps8); mbar_arrive(bars + 8 * B_WOEMPTY + ps8); }
                if (i == 16) break;
                rel >>= 1;
                ps8 = s8;
#pragma unroll 1
                do {
                    s8 = s8 == 40 ? 0 : s8 + 8;
                    if (s8 == 16) ph ^= 1;
                    uint32_t bad;
                    asm volatile("{\n.reg .pred p, q, r;\n.reg .u32 u, v;\nmbarrier.try_wait.parity.shared::cta.b64 q, [%2], %3;\nmbarrier.try_wait.parity.shared::cta.b64 p, [%1], %3;\n"
                                 "setp.ne.and.u32 r, %5, 1, p;\nmov.u32 u, 1;\nmov.u32 v, 1;\n@r ld.shared.u32 u, [%4];\n@r ld.shared.u32 v, [%4 + 4096];\n"
                                 "and.pred p, p, q;\nmin.u32 u, u, v;\nsetp.eq.or.u32 p, u, 0, !p;\nvote.sync.any.pred p, p, 0xffffffff;\nselp.u32 %0, 1, 0, p;\n}"
                                 : "=r"(bad) : "r"(ofull + s8), "r"(bars + 8 * B_WOFULL + s8), "r"(ph), "r"(chk + s8 * (BOX / 8)), "r"(i) : "memory");
                    if (__builtin_expect(bad, 0)) {
                        mbar_wait(ofull + s8, ph, budget);
                        mbar_wait(bars + 8 * B_WOFULL + s8, ph, budget);
                        if (__any_sync(0xffffffffu, min(lds1(chk + s8 * (BOX / 8)), lds1(chk + s8 * (BOX / 8) + 4096)) == 0)) {
                            const uint32_t at = wi * 256 + (lane >> 4) * 1024 + (lane & 15) * 16;
                            const uint8_t* src = scr->o + ((size_t)((mt * 2 + rh) * 2 + 1 - w) * 16 + ((2 * p + (i < 2 ? i ^ hp : i)) & 15)) * BOX + at;
#pragma unroll 1
                            for (int n = 0; n < 8192; n += 2048) {
                                uint4 v; int tries = 4096;
#pragma unroll 1
                                do { v = ld_rlx4(src + n); } while (v.x == 0 && --tries > 0);
                                sts4(ring + s8 * (BOX / 8) + at + n, v.x, v.y, v.z, v.w);
                            }
                            NRETRY();
                            fence_async_smem();
                            __syncwarp();
                        }
                    }
                    TSC(TIMING % 10 == 1 && tid == 0, 48 + i);
                    TSC(TIMING % 10 == 2 && elect, 32 + w * 16 + i);
                } while (++i > last && i < 16);
                if (i > last) break;
                wg_wait<1>();
            }
            uint32_t ready;
            asm volatile("{\n.reg .pred p;\nmbarrier.test_wait.parity.shared::cta.b64 p, [%1], 0;\nvote.sync.all.pred p, p, 0xffffffff;\nselp.u32 %0, 1, 0, p;\n}" : "=r"(ready) : "r"(bars + 8 * B_UPD) : "memory");
            if (w) {
                bar_sync(9, 256);
#pragma unroll 1
                for (int i = HOLD - 10; i < 6; i++) {
                    wg_fence();
#pragma unroll
                    for (int kk = 0; kk < 4; kk++) wgmma_n128<0, 1>(acc, mkdesc(da0 + i * 512 + kk * 128, ahi), mkdesc(db0 + i * 1024 + kk * 128, bhi), 1);
                    wg_commit();
                }
            } else if (!ready) bar_arrive(9, 256);
            mbar_wait(bars + 8 * B_UPD, 0, budget);
            const float2 sl = lds2f(sb + OFF_SEL + t * 8);
            const int d0 = __float_as_int(sl.x) - r0, d1 = __float_as_int(sl.y) - r0;
            const uint32_t a0 = (d0 == 0 ? 0x3f80u : 0u) | (d1 == 0 ? 0x3f800000u : 0u), a1 = (d0 == 8 ? 0x3f80u : 0u) | (d1 == 8 ? 0x3f800000u : 0u);
            wg_fence();
            wgmma_rs_n128(acc, a0, a1, 0u, 0u, mkdesc(sd + dlo(OFF_UPD, 1024), dhi(0, 1)));
            wg_commit();
            if (!w && ready) bar_arrive(9, 256);
            wg_wait<0>();
            TSC(elect, 7 + 9 * w);
            const uint32_t os0 = ring + wi * 4096;
#pragma unroll
            for (int j = 0; j < 8; j++)
                stsm4(((os0 + mad) ^ ((j & 3) * 32)) + (j >> 2) * 2048, pack_bf16(acc[8 * j], acc[8 * j + 1]), pack_bf16(acc[8 * j + 2], acc[8 * j + 3]),
                      pack_bf16(acc[8 * j + 4], acc[8 * j + 5]), pack_bf16(acc[8 * j + 6], acc[8 * j + 7]));
            fence_async_smem();
            __syncwarp();
            if (elect_one()) {
                asm volatile("cp.async.bulk.tensor.5d.global.shared::cta.bulk_group [%0, {%2, %2, %3, %4, %5}], [%1];\ncp.async.bulk.commit_group;\ncp.async.bulk.wait_group.read 0;"
                             ::"l"(&mout), "r"(os0), "r"(0), "r"(((j0 + rh * 128) >> 5) + wi), "r"(1 - w), "r"(par * 16 + cb * 2) : "memory");
            }
            TSC(elect, 8 - 2 * w);
            TS_END();
        }
    }
}

typedef CUresult (*EncodeFn)(CUtensorMap*, CUtensorMapDataType, cuuint32_t, void*, const cuuint64_t*, const cuuint64_t*, const cuuint32_t*,
                             const cuuint32_t*, CUtensorMapInterleave, CUtensorMapSwizzle, CUtensorMapL2promotion, CUtensorMapFloatOOBfill);

CUtensorMap make_map(EncodeFn fn, const void* base, int rank, const cuuint64_t* dims, const cuuint64_t* strides, const cuuint32_t* box,
                     CUtensorMapSwizzle swz = CU_TENSOR_MAP_SWIZZLE_128B, CUtensorMapL2promotion pro = CU_TENSOR_MAP_L2_PROMOTION_L2_256B) {
    CUtensorMap m;
    cuuint32_t es[5] = {1, 1, 1, 1, 1};
    fn(&m, CU_TENSOR_MAP_DATA_TYPE_BFLOAT16, rank, (void*)base, dims, strides, box, es, CU_TENSOR_MAP_INTERLEAVE_NONE,
       swz, pro, CU_TENSOR_MAP_FLOAT_OOB_FILL_NONE);
    return m;
}

}

extern "C" void kernel_launch(void* const* d_in, const int* in_sizes, int n_in, void* d_out, int out_size) {
    (void)in_sizes; (void)n_in; (void)out_size;
    const __nv_bfloat16* x = (const __nv_bfloat16*)d_in[0];
    const __nv_bfloat16* wqkv = (const __nv_bfloat16*)d_in[1];
    const __nv_bfloat16* wo = (const __nv_bfloat16*)d_in[2];
    const __nv_bfloat16* wr = (const __nv_bfloat16*)d_in[4];
    const __nv_bfloat16* wg = (const __nv_bfloat16*)d_in[5];
    const __nv_bfloat16* wu = (const __nv_bfloat16*)d_in[6];
    const __nv_bfloat16* wd = (const __nv_bfloat16*)d_in[7];
    static EncodeFn fn = nullptr;
    static Scratch* scr = nullptr;
    if (!fn) {
        void* p = nullptr; cudaDriverEntryPointQueryResult q;
        cudaGetDriverEntryPoint("cuTensorMapEncodeTiled", &p, cudaEnableDefault, &q);
        fn = (EncodeFn)p;
        cudaFuncSetAttribute(fused_kernel, cudaFuncAttributeMaxDynamicSharedMemorySize, SMEM_LAUNCH);
        cudaGetSymbolAddress((void**)&scr, g_scr);
    }
    const cuuint64_t xd[4] = {2048, 16, 32, 2}, xs[4] = {4096, 131072, 65536, 128}, od[5] = {64, 16, 32, 2, 32};
    const cuuint32_t xb[4] = {64, 16, 4, 1}, ob[5] = {64, 16, 1, 1, 2};
    const cuuint64_t wdm[3] = {1024, 1024, 3}, wst[2] = {6144, 2048};
    const cuuint32_t wb[3] = {64, 64, 3};
    const cuuint64_t wod[3] = {64, 1024, 16}, wdd[3] = {64, 3584, 16}, wos[2] = {2048, 128};
    const cuuint32_t wob[3] = {64, 64, 2}, wdb[3] = {64, 64, 1};
    CUtensorMap mx = make_map(fn, x, 4, xd, xs, xb), mw = make_map(fn, wqkv, 3, wdm, wst, wb);
    CUtensorMap mwo = make_map(fn, wo, 3, wod, wos, wob), mout = make_map(fn, d_out, 5, od, xs, ob);
    const int swap_gu = wu < wg;
    const cuuint64_t gd[3] = {3584, 1024, 2}, gst[2] = {7168, (cuuint64_t)(swap_gu ? (const char*)wg - (const char*)wu : (const char*)wu - (const char*)wg)};
    const cuuint32_t gb[3] = {32, 64, 2};
    CUtensorMap mgu = make_map(fn, swap_gu ? wu : wg, 3, gd, gst, gb, CU_TENSOR_MAP_SWIZZLE_64B, CU_TENSOR_MAP_L2_PROMOTION_L2_128B);
    CUtensorMap mwd = make_map(fn, wd, 3, wdd, wos, wdb, CU_TENSOR_MAP_SWIZZLE_128B, CU_TENSOR_MAP_L2_PROMOTION_L2_128B);
    const cuuint64_t md[2] = {64, 32768}, ms[1] = {128};
    const cuuint32_t mb[2] = {64, 64};
    CUtensorMap mo = make_map(fn, scr, 2, md, ms, mb, CU_TENSOR_MAP_SWIZZLE_NONE, CU_TENSOR_MAP_L2_PROMOTION_NONE);
    cudaLaunchConfig_t cfg = {};
    cfg.gridDim = dim3(132); cfg.blockDim = dim3(512); cfg.dynamicSmemBytes = SMEM_LAUNCH; cfg.stream = cudaStreamPerThread;
    cudaLaunchAttribute at[1];
    at[0].id = cudaLaunchAttributeClusterDimension; at[0].val.clusterDim.x = 2; at[0].val.clusterDim.y = 1; at[0].val.clusterDim.z = 1;
    cfg.attrs = at; cfg.numAttrs = 1;
    cudaLaunchKernelEx(&cfg, fused_kernel, mx, mw, mwo, mout, mgu, mwd, mo, x, wr, scr, swap_gu, Weights{(const char*)wqkv, (const char*)wo, (const char*)wg, (const char*)wu, (const char*)wd});
}
```

```cpp
#include <cuda_runtime.h>
#include <cuda.h>
#include <cuda_bf16.h>
#include <stdint.h>

namespace {

constexpr int BOX = 8192, W_BYTES = 3 * BOX;
constexpr int OFF_X1 = 6 * BOX, OFF_FR = 12 * BOX, OFF_E = 16 * BOX, OFF_W = 19 * BOX;
constexpr int OFF_WO = OFF_E;
constexpr int OFF_HIN = OFF_FR + 2048, OFF_GU = OFF_HIN + 2048, OFF_FS = OFF_GU + 1024;
constexpr int F_BYTES = 9216;
constexpr int CS_BYTES = 3136;
constexpr int OFF_CS = OFF_FS + 5 * F_BYTES;
constexpr int OFF_STAT = 28 * BOX;
constexpr int OFF_SEL = OFF_STAT + 2112;
constexpr int OFF_EP = OFF_SEL + 32;
constexpr int OFF_BAR = OFF_EP + 16;
constexpr int B_WFULL = 0, B_XFULL = 3, B_AUX = 15, B_XT = 16, B_ROW = 17, B_WOFULL = 18, B_OFULL = 24, B_FFULL = 36, B_ZERO = 41;
constexpr int B_WEMPTY = 42, B_F1DONE = 45, B_XEMPTY = 46, B_WOEMPTY = 52, B_OEMPTY = 58;
constexpr int B_G1DONE = 66, B_FEMPTY = 67, B_STAGED = 72, B_RDONE = 75, B_FREED = 76, NBAR = 78;
constexpr int SMEM_BYTES = OFF_BAR + NBAR * 8;
static_assert(OFF_FS + 3 * F_BYTES == OFF_E && OFF_CS + CS_BYTES <= OFF_W && SMEM_BYTES + 256 <= 232448 && OFF_BAR % 8 == 0, "smem");
#define POLL_NS 30
#define PF_RATE 10
#define PF_START 7
#define ZF_NS 100
#define FFN2_GATE (B_STAGED + 1)
#define PF_NW 6
#define EARLY_PF 1
#define EARLY_PK 17
#define FENCE_PRED "@p "
#define ZF_N 64
#define HOLD 12
#define F1_DEPTH 1
#define F2_DEPTH 0
#define ROWS_AT 11
constexpr int BUDGET = 1 << 18;

struct Scratch {
    uint8_t o[2048 * 1024 * 2];
    uint32_t ypart[8][8][1024];
    uint32_t halo[128][512];
    uint32_t act[2][14336 + 4096];
    uint2 row[2048];
    uint4 cs[16][3][24];
    uint32_t oflag[16][32];
    uint32_t cnt[9][32];
    uint32_t sel[32], epoch[32];
};
__device__ __align__(1024) Scratch g_scr;
struct Weights { const char *wqkv, *wo, *wg, *wu, *wd; char* out; };

#define TS(i) do {} while (0)
#define TS_END() do {} while (0)
#define TSC(c, i) do {} while (0)
#define NRETRY() do {} while (0)
constexpr int SMEM_LAUNCH = SMEM_BYTES;
__device__ __forceinline__ uint32_t smem_u32(const void* p) { return (uint32_t)__cvta_generic_to_shared(p); }
__device__ __forceinline__ void mbar_init(uint32_t bar, uint32_t cnt) { asm volatile("mbarrier.init.shared::cta.b64 [%0], %1;" ::"r"(bar), "r"(cnt) : "memory"); }
__device__ __forceinline__ void mbar_expect_tx(uint32_t bar, uint32_t bytes) { asm volatile("mbarrier.arrive.expect_tx.shared::cta.b64 _, [%0], %1;" ::"r"(bar), "r"(bytes) : "memory"); }
__device__ __forceinline__ void mbar_arrive(uint32_t bar) { asm volatile("mbarrier.arrive.shared::cta.b64 _, [%0];" ::"r"(bar) : "memory"); }
__device__ __forceinline__ uint32_t mapa(uint32_t a, uint32_t cta) { uint32_t r; asm("mapa.shared::cluster.u32 %0, %1, %2;" : "=r"(r) : "r"(a), "r"(cta)); return r; }
__device__ __forceinline__ void mbar_arrive_at(uint32_t cbar) { asm volatile("mbarrier.arrive.shared::cluster.b64 _, [%0];" ::"r"(cbar) : "memory"); }
__device__ __forceinline__ void mbar_wait(uint32_t bar, uint32_t parity, int& budget) {
    asm volatile("{\n.reg .pred p;\nLAB_WAIT:\nmbarrier.try_wait.parity.shared::cta.b64 p, [%1], %2;\n"
                 "add.s32 %0, %0, -1;\nsetp.gt.and.s32 p, %0, 0, !p;\n@p bra LAB_WAIT;\n}" : "+r"(budget) : "r"(bar), "r"(parity) : "memory");
}
__device__ __forceinline__ void mbar_wait_hot(uint32_t bar, uint32_t parity, int& budget) {
    asm volatile("{\n.reg .pred p;\nmbarrier.try_wait.parity.shared::cta.b64 p, [%1], %2;\n@p bra LAB_DONE;\nLAB_WAIT:\nmbarrier.try_wait.parity.shared::cta.b64 p, [%1], %2;\n"
                 "add.s32 %0, %0, -1;\nsetp.gt.and.s32 p, %0, 0, !p;\n@p bra LAB_WAIT;\nLAB_DONE:\n}" : "+r"(budget) : "r"(bar), "r"(parity) : "memory");
}
__device__ __forceinline__ void tma_2d_mc(uint32_t dst, const CUtensorMap* m, uint32_t bar, int c0, int c1) {
    asm volatile("cp.async.bulk.tensor.2d.shared::cluster.global.mbarrier::complete_tx::bytes.multicast::cluster [%0], [%1, {%3, %4}], [%2], %5;" ::"r"(dst), "l"(m), "r"(bar), "r"(c0), "r"(c1), "h"((uint16_t)3) : "memory");
}
__device__ __forceinline__ void tma_3d(uint32_t dst, const CUtensorMap* m, uint32_t bar, int c0, int c1, int c2) {
    asm volatile("cp.async.bulk.tensor.3d.shared::cluster.global.mbarrier::complete_tx::bytes [%0], [%1, {%3, %4, %5}], [%2];" ::"r"(dst), "l"(m), "r"(bar), "r"(c0), "r"(c1), "r"(c2) : "memory");
}
__device__ __forceinline__ void tma_4d(uint32_t dst, const CUtensorMap* m, uint32_t bar, int c0, int c1, int c2, int c3) {
    asm volatile("cp.async.bulk.tensor.4d.shared::cluster.global.mbarrier::complete_tx::bytes [%0], [%1, {%3, %4, %5, %6}], [%2];" ::"r"(dst), "l"(m), "r"(bar), "r"(c0), "r"(c1), "r"(c2), "r"(c3) : "memory");
}
__device__ __forceinline__ void tma_4d_mc(uint32_t dst, const CUtensorMap* m, uint32_t bar, int c0, int c1, int c2, int c3) {
    asm volatile("cp.async.bulk.tensor.4d.shared::cluster.global.mbarrier::complete_tx::bytes.multicast::cluster [%0], [%1, {%3, %4, %5, %6}], [%2], %7;" ::"r"(dst), "l"(m), "r"(bar), "r"(c0), "r"(c1), "r"(c2), "r"(c3), "h"((uint16_t)3) : "memory");
}
__device__ __forceinline__ void bulk_pf(const void* p, uint32_t bytes) { asm volatile("cp.async.bulk.prefetch.L2.global [%0], %1;" ::"l"(p), "r"(bytes) : "memory"); }
__device__ __forceinline__ void bulk_g2s(uint32_t dst, const void* src, uint32_t bytes, uint32_t bar) {
    asm volatile("cp.async.bulk.shared::cluster.global.mbarrier::complete_tx::bytes [%0], [%1], %2, [%3];" ::"r"(dst), "l"(src), "r"(bytes), "r"(bar) : "memory");
}
__device__ __forceinline__ void bulk_s2c(uint32_t cdst, uint32_t src, uint32_t bytes, uint32_t cbar) {
    asm volatile("cp.async.bulk.shared::cluster.shared::cta.mbarrier::complete_tx::bytes [%0], [%1], %2, [%3];" ::"r"(cdst), "r"(src), "r"(bytes), "r"(cbar) : "memory");
}
__device__ __forceinline__ void cluster_wait() { asm volatile("barrier.cluster.wait.aligned;" ::: "memory"); }
__device__ __forceinline__ void fence_gpu() { asm volatile("fence.acq_rel.gpu;" ::: "memory"); }
__device__ __forceinline__ void fence_async_smem() { asm volatile("fence.proxy.async.shared::cta;" ::: "memory"); }
__device__ __forceinline__ void wg_fence() { asm volatile("wgmma.fence.sync.aligned;" ::: "memory"); }
__device__ __forceinline__ void wg_commit() { asm volatile("wgmma.commit_group.sync.aligned;" ::: "memory"); }
template <int N> __device__ __forceinline__ void wg_wait() { asm volatile("wgmma.wait_group.sync.aligned %0;" ::"n"(N) : "memory"); }
__device__ __forceinline__ uint64_t mkdesc(uint32_t lo, uint32_t hi) { return ((uint64_t)hi << 32) | lo; }
__host__ __device__ constexpr uint32_t dhi(uint32_t sbo, uint32_t mode) { return (sbo >> 4) | (mode << 30); }
__host__ __device__ constexpr uint32_t dlo(uint32_t off, uint32_t lbo) { return (off >> 4) + ((lbo >> 4) << 16); }
__device__ __forceinline__ bool elect_one() {
    uint32_t e;
    asm volatile("{\n.reg .pred p;\nelect.sync _|p, 0xffffffff;\nselp.u32 %0, 1, 0, p;\n}" : "=r"(e));
    return e;
}
template <int R> __device__ __forceinline__ void reg_inc() { asm volatile("setmaxnreg.inc.sync.aligned.u32 %0;" ::"n"(R)); }
template <int R> __device__ __forceinline__ void reg_dec() { asm volatile("setmaxnreg.dec.sync.aligned.u32 %0;" ::"n"(R)); }
__device__ __forceinline__ void bar_sync(int id, int n) { asm volatile("bar.sync %0, %1;" ::"r"(id), "r"(n) : "memory"); }
__device__ __forceinline__ void bar_arrive(int id, int n) { asm volatile("bar.arrive %0, %1;" ::"r"(id), "r"(n) : "memory"); }
__device__ __forceinline__ uint32_t pack_bf16(float lo, float hi) { uint32_t r; asm("cvt.rn.bf16x2.f32 %0, %1, %2;" : "=r"(r) : "f"(hi), "f"(lo)); return r; }
__device__ __forceinline__ uint32_t pack_here(float lo, float hi) { uint32_t r; asm volatile("cvt.rn.bf16x2.f32 %0, %1, %2;" : "=r"(r) : "f"(hi), "f"(lo)); return r; }
__device__ __forceinline__ float bf_lo(uint32_t u) { return __uint_as_float(u << 16); }
__device__ __forceinline__ float bf_hi(uint32_t u) { return __uint_as_float(u & 0xffff0000u); }
__device__ __forceinline__ float bf16r(float v) { return bf_lo(pack_bf16(v, 0.f)); }
__device__ __forceinline__ float rcp(float x) { float r; asm("rcp.approx.ftz.f32 %0, %1;" : "=f"(r) : "f"(x)); return r; }
__device__ __forceinline__ float ex2(float x) { float r; asm("ex2.approx.ftz.f32 %0, %1;" : "=f"(r) : "f"(x)); return r; }
__device__ __forceinline__ float sigmoidf(float v) { return rcp(1.f + ex2(v * -1.4426950408889634f)); }
__device__ __forceinline__ uint32_t movm(uint32_t a) { uint32_t d; asm volatile("movmatrix.sync.aligned.m8n8.trans.b16 %0, %1;" : "=r"(d) : "r"(a)); return d; }
__device__ __forceinline__ void mma16816(float (&c)[4], uint32_t a0, uint32_t a1, uint32_t a2, uint32_t a3, uint32_t b0, uint32_t b1) {
    asm volatile("mma.sync.aligned.m16n8k16.row.col.f32.bf16.bf16.f32 {%0,%1,%2,%3}, {%4,%5,%6,%7}, {%8,%9}, {%0,%1,%2,%3};"
                 : "+f"(c[0]), "+f"(c[1]), "+f"(c[2]), "+f"(c[3]) : "r"(a0), "r"(a1), "r"(a2), "r"(a3), "r"(b0), "r"(b1));
}
__device__ __forceinline__ void mma1688(float (&c)[4], uint32_t a0, uint32_t a1, uint32_t b0) {
    asm volatile("mma.sync.aligned.m16n8k8.row.col.f32.bf16.bf16.f32 {%0,%1,%2,%3}, {%4,%5}, {%6}, {%0,%1,%2,%3};"
                 : "+f"(c[0]), "+f"(c[1]), "+f"(c[2]), "+f"(c[3]) : "r"(a0), "r"(a1), "r"(b0));
}
__device__ __forceinline__ void stsm4(uint32_t a, uint32_t r0, uint32_t r1, uint32_t r2, uint32_t r3) {
    asm volatile("stmatrix.sync.aligned.m8n8.x4.shared.b16 [%0], {%1,%2,%3,%4};" ::"r"(a), "r"(r0), "r"(r1), "r"(r2), "r"(r3) : "memory");
}
__device__ __forceinline__ void ldsm4(uint32_t* r, uint32_t a) {
    asm volatile("ldmatrix.sync.aligned.m8n8.x4.shared.b16 {%0,%1,%2,%3}, [%4];" : "=r"(r[0]), "=r"(r[1]), "=r"(r[2]), "=r"(r[3]) : "r"(a) : "memory");
}
__device__ __forceinline__ void ldsm4t(uint32_t* r, uint32_t a) {
    asm volatile("ldmatrix.sync.aligned.m8n8.x4.trans.shared.b16 {%0,%1,%2,%3}, [%4];" : "=r"(r[0]), "=r"(r[1]), "=r"(r[2]), "=r"(r[3]) : "r"(a) : "memory");
}
__device__ __forceinline__ uint32_t ld_rlx(const void* p) { uint32_t v; asm volatile("ld.relaxed.gpu.global.u32 %0, [%1];" : "=r"(v) : "l"(p) : "memory"); return v; }
__device__ __forceinline__ uint32_t ld_acq(const void* p) { uint32_t v; asm volatile("ld.acquire.gpu.global.u32 %0, [%1];" : "=r"(v) : "l"(p) : "memory"); return v; }
__device__ __forceinline__ uint2 ld_rlx2(const void* p) { uint2 v; asm volatile("ld.relaxed.gpu.global.v2.u32 {%0,%1}, [%2];" : "=r"(v.x), "=r"(v.y) : "l"(p) : "memory"); return v; }
__device__ __forceinline__ uint4 ld_rlx4(const void* p) { uint4 v; asm volatile("ld.relaxed.gpu.global.v4.u32 {%0,%1,%2,%3}, [%4];" : "=r"(v.x), "=r"(v.y), "=r"(v.z), "=r"(v.w) : "l"(p) : "memory"); return v; }
__device__ __forceinline__ void st_rlx(void* p, uint32_t v) { asm volatile("st.relaxed.gpu.global.u32 [%0], %1;" ::"l"(p), "r"(v) : "memory"); }
__device__ __forceinline__ void st_rlx2(void* p, uint32_t a, uint32_t b) { asm volatile("st.relaxed.gpu.global.v2.u32 [%0], {%1,%2};" ::"l"(p), "r"(a), "r"(b) : "memory"); }
__device__ __forceinline__ void st_rlx4(void* p, uint32_t a, uint32_t b, uint32_t c, uint32_t d) { asm volatile("st.relaxed.gpu.global.v4.u32 [%0], {%1,%2,%3,%4};" ::"l"(p), "r"(a), "r"(b), "r"(c), "r"(d) : "memory"); }
__device__ __forceinline__ void red_add(uint32_t* p) { asm volatile("red.relaxed.gpu.global.add.u32 [%0], 1;" ::"l"(p) : "memory"); }
__device__ __forceinline__ uint4 ldg_nc(const void* p) { uint4 v; asm volatile("ld.global.nc.v4.u32 {%0,%1,%2,%3}, [%4];" : "=r"(v.x), "=r"(v.y), "=r"(v.z), "=r"(v.w) : "l"(p)); return v; }
__device__ __forceinline__ void sts4(uint32_t a, uint32_t x, uint32_t y, uint32_t z, uint32_t w) { asm volatile("st.shared.v4.u32 [%0], {%1,%2,%3,%4};" ::"r"(a), "r"(x), "r"(y), "r"(z), "r"(w) : "memory"); }
__device__ __forceinline__ void sts2(uint32_t a, uint32_t x, uint32_t y) { asm volatile("st.shared.v2.u32 [%0], {%1,%2};" ::"r"(a), "r"(x), "r"(y) : "memory"); }
__device__ __forceinline__ void sts1(uint32_t a, uint32_t v) { asm volatile("st.shared.u32 [%0], %1;" ::"r"(a), "r"(v) : "memory"); }
__device__ __forceinline__ uint4 lds4(uint32_t a) { uint4 v; asm volatile("ld.shared.v4.u32 {%0,%1,%2,%3}, [%4];" : "=r"(v.x), "=r"(v.y), "=r"(v.z), "=r"(v.w) : "r"(a) : "memory"); return v; }
__device__ __forceinline__ float4 lds4f(uint32_t a) { float4 v; asm volatile("ld.shared.v4.f32 {%0,%1,%2,%3}, [%4];" : "=f"(v.x), "=f"(v.y), "=f"(v.z), "=f"(v.w) : "r"(a) : "memory"); return v; }
__device__ __forceinline__ float2 lds2f(uint32_t a) { float2 v; asm volatile("ld.shared.v2.f32 {%0,%1}, [%2];" : "=f"(v.x), "=f"(v.y) : "r"(a) : "memory"); return v; }
__device__ __forceinline__ float lds1f(uint32_t a) { float v; asm volatile("ld.shared.f32 %0, [%1];" : "=f"(v) : "r"(a) : "memory"); return v; }
__device__ __forceinline__ uint32_t lds1(uint32_t a) { uint32_t v; asm volatile("ld.shared.u32 %0, [%1];" : "=r"(v) : "r"(a) : "memory"); return v; }
__device__ __forceinline__ uint32_t redux_max(uint32_t v) { uint32_t r; asm volatile("redux.sync.max.u32 %0, %1, 0xffffffff;" : "=r"(r) : "r"(v)); return r; }
__device__ __forceinline__ uint32_t poll_all(const uint32_t* p, uint32_t mask, uint32_t want, int& budget) {
    uint32_t v;
#pragma unroll 1
    while (v = ld_acq(p), !__all_sync(0xffffffffu, (v & mask) == want) && --budget > 0) __nanosleep(POLL_NS);
    return v;
}

template <int TA, int TB>
__device__ __forceinline__ void wgmma_n192(float (&d)[96], uint64_t da, uint64_t db, int keep) {
    asm volatile("{\n.reg .pred p;\nsetp.ne.b32 p, %98, 0;\n"
        "wgmma.mma_async.sync.aligned.m64n192k16.f32.bf16.bf16 "
        "{%0, %1, %2, %3, %4, %5, %6, %7, %8, %9, %10, %11, %12, %13, %14, %15, "
        "%16, %17, %18, %19, %20, %21, %22, %23, %24, %25, %26, %27, %28, %29, %30, %31, "
        "%32, %33, %34, %35, %36, %37, %38, %39, %40, %41, %42, %43, %44, %45, %46, %47, "
        "%48, %49, %50, %51, %52, %53, %54, %55, %56, %57, %58, %59, %60, %61, %62, %63, "
        "%64, %65, %66, %67, %68, %69, %70, %71, %72, %73, %74, %75, %76, %77, %78, %79, "
        "%80, %81, %82, %83, %84, %85, %86, %87, %88, %89, %90, %91, %92, %93, %94, %95}, "
        "%96, %97, p, 1, 1, %99, %100;\n}\n"
        : "+f"(d[0]), "+f"(d[1]), "+f"(d[2]), "+f"(d[3]), "+f"(d[4]), "+f"(d[5]), "+f"(d[6]), "+f"(d[7]),
          "+f"(d[8]), "+f"(d[9]), "+f"(d[10]), "+f"(d[11]), "+f"(d[12]), "+f"(d[13]), "+f"(d[14]), "+f"(d[15]),
          "+f"(d[16]), "+f"(d[17]), "+f"(d[18]), "+f"(d[19]), "+f"(d[20]), "+f"(d[21]), "+f"(d[22]), "+f"(d[23]),
          "+f"(d[24]), "+f"(d[25]), "+f"(d[26]), "+f"(d[27]), "+f"(d[28]), "+f"(d[29]), "+f"(d[30]), "+f"(d[31]),
          "+f"(d[32]), "+f"(d[33]), "+f"(d[34]), "+f"(d[35]), "+f"(d[36]), "+f"(d[37]), "+f"(d[38]), "+f"(d[39]),
          "+f"(d[40]), "+f"(d[41]), "+f"(d[42]), "+f"(d[43]), "+f"(d[44]), "+f"(d[45]), "+f"(d[46]), "+f"(d[47]),
          "+f"(d[48]), "+f"(d[49]), "+f"(d[50]), "+f"(d[51]), "+f"(d[52]), "+f"(d[53]), "+f"(d[54]), "+f"(d[55]),
          "+f"(d[56]), "+f"(d[57]), "+f"(d[58]), "+f"(d[59]), "+f"(d[60]), "+f"(d[61]), "+f"(d[62]), "+f"(d[63]),
          "+f"(d[64]), "+f"(d[65]), "+f"(d[66]), "+f"(d[67]), "+f"(d[68]), "+f"(d[69]), "+f"(d[70]), "+f"(d[71]),
          "+f"(d[72]), "+f"(d[73]), "+f"(d[74]), "+f"(d[75]), "+f"(d[76]), "+f"(d[77]), "+f"(d[78]), "+f"(d[79]),
          "+f"(d[80]), "+f"(d[81]), "+f"(d[82]), "+f"(d[83]), "+f"(d[84]), "+f"(d[85]), "+f"(d[86]), "+f"(d[87]),
          "+f"(d[88]), "+f"(d[89]), "+f"(d[90]), "+f"(d[91]), "+f"(d[92]), "+f"(d[93]), "+f"(d[94]), "+f"(d[95])
        : "l"(da), "l"(db), "r"(keep), "n"(TA), "n"(TB));
}
template <int TA, int TB>
__device__ __forceinline__ void wgmma_n128(float (&d)[64], uint64_t da, uint64_t db, int keep) {
    asm volatile("{\n.reg .pred p;\nsetp.ne.b32 p, %66, 0;\n"
        "wgmma.mma_async.sync.aligned.m64n128k16.f32.bf16.bf16 "
        "{%0, %1, %2, %3, %4, %5, %6, %7, %8, %9, %10, %11, %12, %13, %14, %15, "
        "%16, %17, %18, %19, %20, %21, %22, %23, %24, %25, %26, %27, %28, %29, %30, %31, "
        "%32, %33, %34, %35, %36, %37, %38, %39, %40, %41, %42, %43, %44, %45, %46, %47, "
        "%48, %49, %50, %51, %52, %53, %54, %55, %56, %57, %58, %59, %60, %61, %62, %63}, "
        "%64, %65, p, 1, 1, %67, %68;\n}\n"
        : "+f"(d[0]), "+f"(d[1]), "+f"(d[2]), "+f"(d[3]), "+f"(d[4]), "+f"(d[5]), "+f"(d[6]), "+f"(d[7]),
          "+f"(d[8]), "+f"(d[9]), "+f"(d[10]), "+f"(d[11]), "+f"(d[12]), "+f"(d[13]), "+f"(d[14]), "+f"(d[15]),
          "+f"(d[16]), "+f"(d[17]), "+f"(d[18]), "+f"(d[19]), "+f"(d[20]), "+f"(d[21]), "+f"(d[22]), "+f"(d[23]),
          "+f"(d[24]), "+f"(d[25]), "+f"(d[26]), "+f"(d[27]), "+f"(d[28]), "+f"(d[29]), "+f"(d[30]), "+f"(d[31]),
          "+f"(d[32]), "+f"(d[33]), "+f"(d[34]), "+f"(d[35]), "+f"(d[36]), "+f"(d[37]), "+f"(d[38]), "+f"(d[39]),
          "+f"(d[40]), "+f"(d[41]), "+f"(d[42]), "+f"(d[43]), "+f"(d[44]), "+f"(d[45]), "+f"(d[46]), "+f"(d[47]),
          "+f"(d[48]), "+f"(d[49]), "+f"(d[50]), "+f"(d[51]), "+f"(d[52]), "+f"(d[53]), "+f"(d[54]), "+f"(d[55]),
          "+f"(d[56]), "+f"(d[57]), "+f"(d[58]), "+f"(d[59]), "+f"(d[60]), "+f"(d[61]), "+f"(d[62]), "+f"(d[63])
        : "l"(da), "l"(db), "r"(keep), "n"(TA), "n"(TB));
}
template <int TA, int TB>
__device__ __forceinline__ void wgmma_n8(float (&d)[4], uint64_t da, uint64_t db, int keep) {
    asm volatile("{\n.reg .pred p;\nsetp.ne.b32 p, %6, 0;\n"
        "wgmma.mma_async.sync.aligned.m64n8k16.f32.bf16.bf16 "
        "{%0, %1, %2, %3}, "
        "%4, %5, p, 1, 1, %7, %8;\n}\n"
        : "+f"(d[0]), "+f"(d[1]), "+f"(d[2]), "+f"(d[3])
        : "l"(da), "l"(db), "r"(keep), "n"(TA), "n"(TB));
}
__device__ __forceinline__ void wgmma_rs_n192(float (&d)[96], uint32_t a0, uint32_t a1, uint32_t a2, uint32_t a3, uint64_t db) {
    asm volatile("{\n.reg .pred p;\nsetp.ne.b32 p, 1, 0;\n"
        "wgmma.mma_async.sync.aligned.m64n192k16.f32.bf16.bf16 "
        "{%0, %1, %2, %3, %4, %5, %6, %7, %8, %9, %10, %11, %12, %13, %14, %15, "
        "%16, %17, %18, %19, %20, %21, %22, %23, %24, %25, %26, %27, %28, %29, %30, %31, "
        "%32, %33, %34, %35, %36, %37, %38, %39, %40, %41, %42, %43, %44, %45, %46, %47, "
        "%48, %49, %50, %51, %52, %53, %54, %55, %56, %57, %58, %59, %60, %61, %62, %63, "
        "%64, %65, %66, %67, %68, %69, %70, %71, %72, %73, %74, %75, %76, %77, %78, %79, "
        "%80, %81, %82, %83, %84, %85, %86, %87, %88, %89, %90, %91, %92, %93, %94, %95}, "
        "{%96, %97, %98, %99}, %100, p, 1, 1, 1;\n}\n"
        : "+f"(d[0]), "+f"(d[1]), "+f"(d[2]), "+f"(d[3]), "+f"(d[4]), "+f"(d[5]), "+f"(d[6]), "+f"(d[7]),
          "+f"(d[8]), "+f"(d[9]), "+f"(d[10]), "+f"(d[11]), "+f"(d[12]), "+f"(d[13]), "+f"(d[14]), "+f"(d[15]),
          "+f"(d[16]), "+f"(d[17]), "+f"(d[18]), "+f"(d[19]), "+f"(d[20]), "+f"(d[21]), "+f"(d[22]), "+f"(d[23]),
          "+f"(d[24]), "+f"(d[25]), "+f"(d[26]), "+f"(d[27]), "+f"(d[28]), "+f"(d[29]), "+f"(d[30]), "+f"(d[31]),
          "+f"(d[32]), "+f"(d[33]), "+f"(d[34]), "+f"(d[35]), "+f"(d[36]), "+f"(d[37]), "+f"(d[38]), "+f"(d[39]),
          "+f"(d[40]), "+f"(d[41]), "+f"(d[42]), "+f"(d[43]), "+f"(d[44]), "+f"(d[45]), "+f"(d[46]), "+f"(d[47]),
          "+f"(d[48]), "+f"(d[49]), "+f"(d[50]), "+f"(d[51]), "+f"(d[52]), "+f"(d[53]), "+f"(d[54]), "+f"(d[55]),
          "+f"(d[56]), "+f"(d[57]), "+f"(d[58]), "+f"(d[59]), "+f"(d[60]), "+f"(d[61]), "+f"(d[62]), "+f"(d[63]),
          "+f"(d[64]), "+f"(d[65]), "+f"(d[66]), "+f"(d[67]), "+f"(d[68]), "+f"(d[69]), "+f"(d[70]), "+f"(d[71]),
          "+f"(d[72]), "+f"(d[73]), "+f"(d[74]), "+f"(d[75]), "+f"(d[76]), "+f"(d[77]), "+f"(d[78]), "+f"(d[79]),
          "+f"(d[80]), "+f"(d[81]), "+f"(d[82]), "+f"(d[83]), "+f"(d[84]), "+f"(d[85]), "+f"(d[86]), "+f"(d[87]),
          "+f"(d[88]), "+f"(d[89]), "+f"(d[90]), "+f"(d[91]), "+f"(d[92]), "+f"(d[93]), "+f"(d[94]), "+f"(d[95])
        : "r"(a0), "r"(a1), "r"(a2), "r"(a3), "l"(db));
}

template <int HS>
__device__ __forceinline__ void attn_pair(const uint32_t* q, const uint32_t* k, const uint32_t* v, const uint32_t* kh, const uint32_t* vh,
                                          const float* fu, const float* fn, const float* rk, float bias0, float bias1, uint32_t mU, uint32_t zero, const float* ci, uint32_t* o) {
    float s0[2][4] = {}, s1[2][4] = {}, s2[2][4] = {};
#pragma unroll
    for (int n = 0; n < 4; n++) {
        const int hd = n & 1, a = 8 * hd + 2 * (n & 2);
        mma16816(s1[hd], q[a], q[a + 1], q[a + 2], q[a + 3], k[a], k[a + 2]);
        mma16816(s2[hd], q[a], q[a + 1], q[a + 2], q[a + 3], k[a + 1], k[a + 3]);
    }
#pragma unroll
    for (int n = 0; n < 4; n++) {
        const int hd = n & 1, a = 8 * hd + 2 * (n & 2);
        mma16816(s0[hd], q[a], q[a + 1], q[a + 2], q[a + 3], kh[HS * (a / 2)], kh[HS * (a / 2 + 1)]);
    }
    float e[2][4], m[2][2];
#pragma unroll
    for (int hd = 0; hd < 2; hd++) {
        e[hd][2] = fmaf(s1[hd][2], fu[2], s2[hd][2] * fn[2]); e[hd][3] = fmaf(s1[hd][3], fu[3], s2[hd][3] * fn[3]);
        e[hd][0] = fmaf(s0[hd][0], fu[0], fmaf(s1[hd][0], fn[0], bias0)); e[hd][1] = fmaf(s0[hd][1], fu[1], fmaf(s1[hd][1], fn[1], bias1));
        m[hd][1] = fmaxf(e[hd][2], e[hd][3]); m[hd][0] = fmaxf(e[hd][0], e[hd][1]);
    }
#pragma unroll
    for (int x = 1; x < 3; x++)
#pragma unroll
        for (int n = 0; n < 4; n++) m[n & 1][1 - (n >> 1)] = fmaxf(m[n & 1][1 - (n >> 1)], __shfl_xor_sync(0xffffffffu, m[n & 1][1 - (n >> 1)], x));
#pragma unroll
    for (int hd = 0; hd < 2; hd++) {
#pragma unroll
        for (int n = 0; n < 4; n++) e[hd][n] = ex2(e[hd][n] - m[hd][n >> 1]);
        float sum[4] = {};
        mma1688(sum, pack_bf16(e[hd][0], e[hd][1]), pack_bf16(e[hd][2], e[hd][3]), 0x3f803f80u);
        const float i0 = rcp(sum[0]), i1 = rcp(sum[2]);
        const uint32_t plo = pack_bf16(e[hd][0] * rk[0] * i0, e[hd][1] * rk[1] * i0), phi = pack_bf16(e[hd][2] * rk[2] * i1, e[hd][3] * rk[3] * i1);
        const uint32_t z0 = plo & zero, z1 = phi & zero;
        const uint32_t a0 = plo & ~mU, a1 = phi & mU, a3 = phi & ~mU, b0 = plo & mU;
#pragma unroll
        for (int jj = 0; jj < 4; jj++) {
            float c[4];
            asm volatile("mma.sync.aligned.m16n8k16.row.col.f32.bf16.bf16.f32 {%0,%1,%2,%3}, {%4,%5,%6,%7}, {%8,%9}, {%10,%11,%12,%13};"
                         : "=f"(c[0]), "=f"(c[1]), "=f"(c[2]), "=f"(c[3])
                         : "r"(a0), "r"(a1), "r"(z0), "r"(a3), "r"(v[8 * hd + 2 * jj]), "r"(v[8 * hd + 2 * jj + 1]), "f"(ci[0]), "f"(ci[1]), "f"(ci[2]), "f"(ci[3]));
            mma1688(c, b0, z1, vh[HS * (4 * hd + jj)]);
            o[8 * hd + 2 * jj] = pack_bf16(c[0], c[1]); o[8 * hd + 2 * jj + 1] = pack_bf16(c[2], c[3]);
        }
    }
}

__device__ __forceinline__ uint32_t norm_pair(uint32_t u, float m, float rinv) {
    const uint32_t d = pack_bf16(bf_lo(u) - m, bf_hi(u) - m);
    return max(pack_bf16(bf_lo(d) * rinv, bf_hi(d) * rinv), 1u);
}

__global__ void __launch_bounds__(512, 1)
fused_kernel(const __grid_constant__ CUtensorMap mx, const __grid_constant__ CUtensorMap mw, const __grid_constant__ CUtensorMap mwo,
             const __grid_constant__ CUtensorMap mout, const __grid_constant__ CUtensorMap mgu, const __grid_constant__ CUtensorMap mwd,
             const __grid_constant__ CUtensorMap mo,
             const __nv_bfloat16* __restrict__ x, const __nv_bfloat16* __restrict__ wr, Scratch* __restrict__ scr, int swap_gu, const Weights pf) {
    extern __shared__ __align__(1024) uint8_t smem[];
    const uint32_t sb = smem_u32(smem);
    const uint32_t bars = sb + OFF_BAR;
    const int tid = threadIdx.x, lane = tid & 31, warp = __shfl_sync(0xffffffffu, tid >> 5, 0);
    const uint32_t sd = (sb & 0x3FFFF) >> 4;
    const int hp = blockIdx.x & 1, cl = blockIdx.x >> 1;
    int pr = cl - 4 + (max(cl - 36, 0) * 37 >> 8);
    asm("{\n.reg .pred p;\nsetp.lt.s32 p, %1, 4;\nselp.s32 %0, %2, %0, p;\n}" : "+r"(pr) : "r"(cl), "r"(39 + 8 * cl));
    const int b = pr * 2 + hp, mt = pr >> 3, p = pr & 7, nt = 2 * p + hp, rh = p & 1, cb = (p & 6) + hp;
    const int par = mt >> 2, j0 = (mt & 3) * 256;
    int budget = BUDGET;

    TSC(tid == 0, 0);
    if (b < 128 && tid >= 32 && tid < 112) {
        const char* a = tid < 64 ? (const char*)x + (size_t)(16 * b + ((tid >> 1) & 15)) * 2048 + (tid & 1) * 128 : pf.wqkv + (size_t)b * 6144 + (tid - 64) * 128;
        asm volatile("prefetch.global.L2 [%0];" ::"l"(a));
    }
    auto load_w = [&](int k, int s) {
        const uint32_t full = bars + 8 * (B_WFULL + s);
        mbar_expect_tx(full, W_BYTES);
        tma_3d(sb + OFF_W + s * W_BYTES, &mw, full, nt * 64, k * 64, 0);
    };
    auto load_x = [&](int n) {
        const int w = n & 1, j = n < 4 ? (n >> 1) + 4 : (n >> 1) - 2;
        const uint32_t full = bars + 8 * (B_XFULL + w * 6 + 5 - j);
        mbar_expect_tx(full, BOX);
        tma_4d(sb + w * OFF_X1 + j * BOX, &mx, full, par * 1024 + (n >> 2) * 64, 0, (j0 + w * 128) >> 5, (~n >> 1) & 1);
    };
    if (warp < NBAR / 6 && elect_one()) {
        const uint32_t cnt = warp < B_WEMPTY / 6 ? 1 : warp < B_G1DONE / 6 ? 2 : warp < B_STAGED / 6 ? 4 : 8;
#pragma unroll
        for (int i = 0; i < 6; i++) mbar_init(bars + 48 * warp + 8 * i, cnt);
        asm volatile("fence.mbarrier_init.release.cluster;" ::: "memory");
        if (warp == 0 && b < 128) { load_x(0); load_w(0, 2); }
    }
    __syncthreads();

    if (b >= 128) {
        const int hc = b - 128, g = lane >> 2, t = lane & 3;
        const uint32_t ep = ld_rlx(&scr->epoch[0]) + 1;
        if (warp < 12) {
            const int n = warp / 3, part = warp - 3 * n;
            auto load = [&](int k) {
                const uint32_t full = bars + 8 * (2 * n + (k & 1));
                mbar_expect_tx(full, W_BYTES);
                tma_3d(sb + (2 * n + (k & 1)) * W_BYTES, &mw, full, (4 * hc + n) * 64, k * 64, 0);
            };
            if (part == 0 && elect_one()) { load(0); load(1); }
            __syncwarp();
            float c0[4] = {0.f, 0.f, 0.f, 0.f}, c1[4] = {0.f, 0.f, 0.f, 0.f};
            const uint32_t sel = g == 0 ? 0x3f80u : g == 1 ? 0x3f800000u : 0u;
            const uint32_t a = sb + 2 * n * W_BYTES + part * BOX + t * 256 + ((g ^ (2 * t)) << 4);
#pragma unroll 1
            for (int k = 0; k < 16; k++) {
                mbar_wait(bars + 8 * (2 * n + (k & 1)), (k >> 1) & 1, budget);
                uint4 v[8], u[8];
#pragma unroll
                for (int i = 0; i < 8; i++) { v[i] = lds4(a + (k & 1) * W_BYTES + i * 1024); u[i] = lds4(((a + 128) ^ 16) + (k & 1) * W_BYTES + i * 1024); }
#pragma unroll
                for (int i = 0; i < 8; i++) { mma16816(c0, v[i].x, v[i].y, u[i].x, u[i].y, sel, sel); mma16816(c1, v[i].z, v[i].w, u[i].z, u[i].w, sel, sel); }
                bar_sync(1 + n, 96);
                if (part == 0 && k < 14 && elect_one()) load(k + 2);
                __syncwarp();
            }
            if (t == 0) {
#pragma unroll
                for (int r = 0; r < 3; r++) {
                    const uint32_t q0 = (pack_bf16(c0[0], c0[1]) & ~1u) | (ep & 1), q1 = pack_bf16(c0[2], c0[3]), q2 = pack_bf16(c1[0], c1[1]), q3 = pack_bf16(c1[2], c1[3]);
                    st_rlx4(&scr->cs[4 * hc + n][r][part * 8 + g], q0, q1, q2, q3);
                    c0[0] -= bf_lo(q0); c0[1] -= bf_hi(q0); c0[2] -= bf_lo(q1); c0[3] -= bf_hi(q1);
                    c1[0] -= bf_lo(q2); c1[1] -= bf_hi(q2); c1[2] -= bf_lo(q3); c1[3] -= bf_hi(q3);
                }
            }
            TSC(tid == 0, 19);
        }
        if (warp < 8) TS_END();
        return;
    }
    asm volatile("barrier.cluster.arrive.relaxed.aligned;" ::: "memory");

    const int kc = b >> 4, c2 = b & 15;
    if (warp >= 12) {
        reg_dec<24>();
        if (warp == 12) {
            if (elect_one()) {
#pragma unroll 1
                for (int n = 1; n < 12; n++) {
                    load_x(n);
                    if (n == ROWS_AT) { mbar_expect_tx(bars + 8 * B_ROW, 4 * BOX); bulk_g2s(sb + OFF_FR, x + (size_t)b * 16 * 1024, 4 * BOX, bars + 8 * B_ROW); }
                    if (n == 3 || n == 7) load_w((n + 1) >> 2, n >> 2);
                }
                int s = 2; uint32_t ph = 0;
#pragma unroll 1
                for (int k = 3; k < 16; k++) {
                    mbar_wait(bars + 8 * (B_WEMPTY + s), ph, budget);
                    load_w(k, s);
                    if (++s == 3) s = 0;
                    if (s == 2) ph ^= 1;
                }
                s = 2;
#pragma unroll 1
                for (int i = 0; i < 16; i++) {
                    mbar_wait(bars + 8 * (i < 2 ? B_WEMPTY + i : i < 4 ? B_G1DONE : i < 6 ? B_F1DONE : B_WOEMPTY + s), i >= 12, budget);
                    if (i == 0) {
                        mbar_expect_tx(bars + 8 * B_XT, 4 * BOX);
#pragma unroll 1
                        for (int n = 0; n < 4; n++)
                            tma_4d(sb + (n >> 1) * OFF_X1 + (n & 1) * BOX, &mx, bars + 8 * B_XT, par * 1024 + cb * 128 + (n & 1) * 64, 0, (j0 + rh * 128) >> 5, 1 - (n >> 1));
                    }
                    const uint32_t full = bars + 8 * (B_WOFULL + s);
                    mbar_expect_tx(full, 2 * BOX);
                    tma_3d(sb + OFF_WO + s * 2 * BOX, &mwo, full, 0, ((2 * p + (i < 2 ? i ^ hp : i)) & 15) * 64, cb * 2);
                    TSC(TIMING % 10 == 4, 48 + i);
                    if (++s == 6) s = 0;
                }
            }
        } else {
            bar_sync(8, 224);
            const uint32_t ep = __shfl_sync(0xffffffffu, lds1(sb + OFF_EP), 0);
            if (warp == 13) {
                cluster_wait();
                if (elect_one()) {
                    int j = 4, q = 0, left = BUDGET; uint32_t ph = 0;
#pragma unroll 1
                    for (int n = 6; n < 32; n++) {
                        mbar_wait(bars + 8 * (B_XEMPTY + j), ph, left);
                        tma_4d_mc(sb + hp * OFF_X1 + j * BOX, &mx, bars + 8 * (B_XFULL + hp * 6 + 5 - j), par * 1024 + (n >> 1) * 64, 0, (j0 + hp * 128) >> 5, ~n & 1);
                        if (++j == 6) j = 0;
                        if (j == 4) ph ^= 1;
#pragma unroll 1
                        for (; q < (PF_RATE * (n - PF_START) >> 3) && q < 18 + PF_NW; q++) {
                            const int u = q - PF_NW;
                            if (u < 0) bulk_pf(pf.wqkv + (size_t)(1024 + 128 * u + b) * 6144, 6144);
                            else if (u < 16) bulk_pf((b < 64 ? pf.wg : pf.wu) + (size_t)(u * 64 + (b & 63)) * 7168, 7168);
                            else bulk_pf(pf.wo + (size_t)((u - 16) * 128 + b) * 8192, 8192);
                        }
                    }
                }
                __syncwarp();
                uint32_t* hs = &scr->halo[b - 16][lane * 4];
                int tries = BUDGET;
#pragma unroll 1
                for (int c = 0; c < 4; c += 2) {
                    uint4 v0 = make_uint4(0, 0, 0, 0), v1 = v0;
                    if (j0) {
#pragma unroll 1
                        do { v0 = ld_rlx4(hs + c * 128); v1 = ld_rlx4(hs + c * 128 + 128); } while ((v0.x == 0 || v1.x == 0) && --tries > 0);
                        st_rlx(hs + c * 128, 0); st_rlx(hs + c * 128 + 128, 0);
                    }
                    __syncwarp();
                    stsm4(sb + OFF_HIN + c * 512 + lane * 16, v0.x, v0.y, v0.z, v0.w);
                    stsm4(sb + OFF_HIN + c * 512 + 512 + lane * 16, v1.x, v1.y, v1.z, v1.w);
                }
                bar_arrive(11, 64);
                TSC(lane == 0, 31);
                const int src = ((mt * 2 + rh) * 2 + 1 - hp) * 1024;
                if (elect_one()) {
                    const uint32_t* fl = &scr->oflag[mt * 2 + 1 - hp][0];
                    const uint32_t inv = (ep & 1) - 1;
                    uint32_t ready = 0, ph = 0;
                    int s = 4;
#pragma unroll 1
                    for (int i = 2; i < 16; i++) {
                        const int kb = (2 * p + i) & 15;
#pragma unroll 1
                        while (!((ready >> kb) & 1) && --budget > 0) ready = ld_rlx(fl) ^ inv;
                        TSC(i == 2, 30);
                        mbar_wait(bars + 8 * (B_OEMPTY + s), ph, budget);
                        tma_2d_mc(sb + hp * OFF_X1 + s * BOX, &mo, bars + 8 * (B_OFULL + hp * 6 + s), 0, src + kb * 64);
                        TSC(TIMING % 10 == 4 && hp == 0, 32 + i);
                        if (++s == 6) s = 0;
                        if (s == 4) ph ^= 1;
                    }
                }
            } else if (warp == 14) {
                if (elect_one()) {
                    uint32_t s8 = 0, ph = 0;
                    int tries = BUDGET;
                    const uint32_t* act = scr->act[ep & 1];
                    auto counted = [&](int c, uint32_t n) {
#pragma unroll 1
                        while (ld_rlx(&scr->cnt[c][0]) != ep * n && --tries > 0) __nanosleep(POLL_NS);
                    };
                    auto weights = [&](const CUtensorMap* m, int c0, int c1, int c2_) {
                        mbar_wait(bars + 8 * B_FEMPTY + s8, ph, budget);
                        mbar_expect_tx(bars + 8 * B_FFULL + s8, F_BYTES);
                        tma_3d(sb + OFF_FS + s8 * (F_BYTES / 8), m, bars + 8 * B_FFULL + s8, c0, c1, c2_);
                    };
                    if (b < 112) {
                        counted(8, 32);
                        TS(26);
#pragma unroll 1
                        for (int q = 0; q < 16; q++) {
                            weights(&mgu, b * 32, q * 64, 0);
                            bulk_g2s(sb + OFF_FS + BOX + s8 * (F_BYTES / 8), act + 14336 + q * 256, 1024, bars + 8 * B_FFULL + s8);
                            TSC(TIMING % 10 == 5, 32 + q);
                            if (q >= 8) bulk_pf(pf.wd + (size_t)((q - 8) * 112 + b) * 8192, 8192);
                            s8 += 8;
                            if (s8 == 40) { s8 = 0; ph ^= 1; }
                        }
                    }
#pragma unroll 1
                    for (int q = -3; q < 7; q++) {
                        if (q == 0) { counted(kc, 28); TS(29); }
                        if ((unsigned)q >= 3) weights(&mwd, 0, kc * 448 + (q < 0 ? q + 3 : q) * 64, c2);
                        if (q >= 0) bulk_g2s(sb + OFF_FS + BOX + s8 * (F_BYTES / 8), act + (kc * 7 + q) * 256, 1024, bars + 8 * B_FFULL + s8);
                        TSC(TIMING % 10 == 5, 51 + q);
                        s8 += 8;
                        if (s8 == 24) { s8 = 0; if ((unsigned)q >= 3) ph ^= 1; }
                    }
                }
            } else {
#pragma unroll 1
                for (int i = lane * 16; i < CS_BYTES; i += 512) sts4(sb + OFF_CS + i, 0, 0, 0, 0);
                mbar_wait(bars + 8 * B_ROW, 0, budget);
                uint8_t* oz = scr->o + ((size_t)mt * 64 + nt) * BOX + lane * 16;
#pragma unroll 1
                for (int i = 0; i < ZF_N; i++) { st_rlx4(oz + (i >> 4) * 16 * BOX + (i & 15) * 512, 0, 0, 0, 0); if ((i & 3) == 3) __nanosleep(ZF_NS); }
                __syncwarp();
                fence_gpu();
                mbar_wait(bars + 8 * B_RDONE, 0, budget);
                int tries = BUDGET;
#pragma unroll 1
                for (int i = lane; i < 88; i += 32) {
                    const uint2* rp = &scr->row[2 * (j0 - 8 + i) + par];
                    uint2 v0, v1, v2;
#pragma unroll 1
                    do { v0 = ld_rlx2(rp + (j0 + i < 8 ? 16 : 0)); v1 = ld_rlx2(rp + 176); v2 = ld_rlx2(rp + 352); } while ((((v0.y ^ ep) | (v1.y ^ ep) | (v2.y ^ ep)) & 31) && --tries > 0);
                    sts2(sb + OFF_STAT + i * 8, (v0.x << 16) ^ 0x80000000u, __float_as_uint(rcp(bf_hi(v0.x))));
                    sts2(sb + OFF_STAT + i * 8 + 704, (v1.x << 16) ^ 0x80000000u, __float_as_uint(rcp(bf_hi(v1.x))));
                    sts2(sb + OFF_STAT + i * 8 + 1408, (v2.x << 16) ^ 0x80000000u, __float_as_uint(rcp(bf_hi(v2.x))));
                }
                __syncwarp();
                {
                    const int row = 2047 - ((poll_all(&scr->sel[lane & 7], 31u, ep & 31, budget) >> 5) & 2047), jj = (row >> 1) - j0 - rh * 128;
                    uint32_t boxes = __reduce_or_sync(0xffffffffu, (row & 1) == par && (unsigned)jj < 128 ? 1u << (jj >> 4) : 0u);
                    sts1(sb + OFF_SEL, boxes);
#pragma unroll 1
                    for (int i = 0; boxes; i += 2) {
                        if (boxes & 1) st_rlx4(pf.out + (size_t)(2 * (j0 + rh * 128 + i + (lane >> 4)) + par) * 2048 + cb * 256 + (lane & 15) * 16, 0, 0, 0, 0);
                        else i += 14;
                        if ((i & 14) == 14) boxes >>= 1;
                    }
                }
                if (lane < 24) {
                    uint4 v[3];
#pragma unroll 1
                    while (v[0] = ld_rlx4(&scr->cs[nt][0][lane]), v[1] = ld_rlx4(&scr->cs[nt][1][lane]), v[2] = ld_rlx4(&scr->cs[nt][2][lane]),
                           (((v[0].x ^ ep) | (v[1].x ^ ep) | (v[2].x ^ ep)) & 1) && --tries > 0) __nanosleep(100);
#pragma unroll
                    for (int r = 0; r < 3; r++) sts4(sb + OFF_CS + 64 + lane * 128 + r * 16, v[r].x, v[r].y, v[r].z, v[r].w);
                }
                fence_async_smem();
                __syncwarp();
                if (elect_one()) {
                    mbar_arrive(bars + 8 * B_AUX);
                    TS(21);
                    if (lds1(sb + OFF_SEL)) { fence_gpu(); asm volatile("fence.proxy.async.global;" ::: "memory"); }
                    mbar_arrive(bars + 8 * B_ZERO);
                    TS(25);
                    mbar_expect_tx(bars + 8 * (B_OFULL + 3), BOX); mbar_expect_tx(bars + 8 * (B_OFULL + 9), BOX);
#pragma unroll 1
                    for (int v = 0; v < 2; v++) {
                        const uint32_t ring = sb + v * OFF_X1 + 2 * BOX, fb = bars + 8 * (B_OFULL + v * 6 + 2);
                        mbar_wait(bars + 8 * (B_STAGED + v), 0, budget);
                        asm volatile("red.relaxed.gpu.global.xor.b32 [%0], %1;" ::"l"(&scr->oflag[mt * 2 + 1 - v][0]), "r"(1u << nt) : "memory");
                        TS(13 + 2 * v);
                        mbar_arrive(fb);
                        mbar_wait(bars + 8 * B_G1DONE, 0, budget);
                        bulk_s2c(mapa(ring + BOX, hp ^ 1), ring, BOX, mapa(fb + 8, hp ^ 1));
                        if (v == 0) mbar_wait(bars + 8 * B_FREED, 0, budget);
#pragma unroll
                        for (int n = 0; n < 4; n++) {
                            mbar_expect_tx(bars + 8 * (B_OFULL + (n >> 1) * 6 + 4 + (n & 1)) - v * 32, BOX);
                            mbar_arrive_at(mapa(bars + 8 * B_OEMPTY, n >> 1) + (4 + (n & 1)) * 8 - v * 32);
                        }
                    }
                }
            }
        }
    } else if (warp >= 8) {
        reg_dec<40>();
        const int wq = warp - 8, ta = tid - 256;
        const uint32_t rbuf = sb + OFF_FR + wq * BOX, rbar = bars + 8 * B_ROW;
        const uint4 wv = ldg_nc(wr + ta * 8);
        if (ta == 0) sts1(sb + OFF_EP, ld_rlx(&scr->epoch[0]) + 1);
        sts4(sb + OFF_STAT + ta * 16, wv.x, wv.y, wv.z, wv.w);
        bar_sync(8, 224);
        const uint32_t ep = __shfl_sync(0xffffffffu, lds1(sb + OFF_EP), 0);
        {
            const int s = b * 16 + wq * 4 + (lane >> 3);
            if ((lane & 7) == 0) st_rlx2(&scr->row[s], 0, ep - 1);
            float sw = 0.f;
#pragma unroll 1
            for (int i = 0; i < 16; i++) { const uint32_t q = lds1(sb + OFF_STAT + i * 128 + lane * 4); sw += bf_lo(q) + bf_hi(q); }
#pragma unroll 1
            for (int o = 16; o > 0; o >>= 1) sw += __shfl_xor_sync(0xffffffffu, sw, o);
            float s1 = 0.f, s2 = 0.f, sr = 0.f;
            const uint32_t xa = rbuf + (lane >> 3) * 2048 + (lane & 7) * 16, wa = sb + OFF_STAT + (lane & 7) * 16;
            mbar_wait(rbar, 0, budget);
            TSC(ta == 0, 17);
            {
                float s1b = 0.f, s2b = 0.f, srb = 0.f;
                const uint32_t xb = rbuf + (lane >> 4) * 4096 + (lane & 15) * 16, wb = sb + OFF_STAT + (lane & 15) * 16;
                uint4 w4 = lds4(wb), u = lds4(xb), v = lds4(xb + 2048);
#pragma unroll 1
                for (int i = 1; i <= 8; i++) {
                    const uint32_t o = (i * 256) & 2047;
                    float wf[8];
#pragma unroll
                    for (int c = 0; c < 4; c++) { wf[2 * c] = bf_lo((&w4.x)[c]); wf[2 * c + 1] = bf_hi((&w4.x)[c]); }
                    w4 = lds4(wb + o);
#pragma unroll
                    for (int c = 0; c < 4; c++) {
                        const float a0 = bf_lo((&u.x)[c]), a1 = bf_hi((&u.x)[c]);
                        s1 += a0; s2 = fmaf(a0, a0, s2); sr = fmaf(a0, wf[2 * c], sr);
                        s1 += a1; s2 = fmaf(a1, a1, s2); sr = fmaf(a1, wf[2 * c + 1], sr);
                    }
                    u = lds4(xb + o);
#pragma unroll
                    for (int c = 0; c < 4; c++) {
                        const float a0 = bf_lo((&v.x)[c]), a1 = bf_hi((&v.x)[c]);
                        s1b += a0; s2b = fmaf(a0, a0, s2b); srb = fmaf(a0, wf[2 * c], srb);
                        s1b += a1; s2b = fmaf(a1, a1, s2b); srb = fmaf(a1, wf[2 * c + 1], srb);
                    }
                    v = lds4(xb + 2048 + o);
                }
                const bool up = lane & 8;
                s1 = (up ? s1b : s1) + __shfl_xor_sync(0xffffffffu, up ? s1 : s1b, 8);
                s2 = (up ? s2b : s2) + __shfl_xor_sync(0xffffffffu, up ? s2 : s2b, 8);
                sr = (up ? srb : sr) + __shfl_xor_sync(0xffffffffu, up ? sr : srb, 8);
            }
#pragma unroll
            for (int o = 1; o < 8; o <<= 1) {
                s1 += __shfl_xor_sync(0xffffffffu, s1, o); s2 += __shfl_xor_sync(0xffffffffu, s2, o); sr += __shfl_xor_sync(0xffffffffu, sr, o);
            }
            const float mean = s1 * (1.f / 1024.f), mb = bf16r(mean);
            float var = fmaf(-mean, mean, s2 * (1.f / 1024.f));
            sr = fmaf(-mb, sw, sr);
            if (__builtin_expect(__any_sync(0xffffffffu, mean * mean > 256.f * var), 0)) {
                float a2 = 0.f, ar = 0.f;
#pragma unroll 1
                for (int i = 0; i < 64; i++) {
                    const uint32_t o = (i >> 2) * 128 + (i & 3) * 4, q1 = lds1(xa + o), q2 = lds1(wa + o);
                    a2 = fmaf(bf_lo(q1) - mean, bf_lo(q1) - mean, fmaf(bf_hi(q1) - mean, bf_hi(q1) - mean, a2));
                    ar = fmaf(bf_lo(q1) - mb, bf_lo(q2), fmaf(bf_hi(q1) - mb, bf_hi(q2), ar));
                }
#pragma unroll 1
                for (int o = 1; o < 8; o <<= 1) { a2 += __shfl_xor_sync(0xffffffffu, a2, o); ar += __shfl_xor_sync(0xffffffffu, ar, o); }
                var = a2 * (1.f / 1024.f); sr = ar;
            }
            float den;
            asm("sqrt.approx.f32 %0, %1;" : "=f"(den) : "f"(bf16r(bf16r(var) + 1e-5f)));
            const uint32_t st = pack_bf16(mb, den);
            const uint32_t rb = pack_bf16(0.f, sr * rcp(bf_hi(st)) + 0.f);
            uint32_t ord = (int)rb < 0 ? ~rb & 0xffff0000u : rb | 0x80000000u;
            if ((rb & 0x7fffffffu) > 0x7f800000u) ord = 0;
            if ((lane & 7) == 0) st_rlx2(&scr->row[s], st, ord | ((2047 - s) << 5) | (ep & 31));
            __syncwarp();
            if (lane < 7) mbar_arrive(bars + 8 * (lane < 5 ? B_FEMPTY + lane : B_RDONE));
        }
        TSC(ta == 0, 18);
        if ((b >> 3) == 14) {
            const uint32_t gm = sb + OFF_E, cnt = gm + 64, res = gm + 80, list = gm + 128;
            uint32_t kv[16];
            int tries = BUDGET;
#pragma unroll 1
            do {
                uint32_t bad = 0;
#pragma unroll
                for (int n = 0; n < 16; n++) kv[n] = ld_rlx(&scr->row[n * 128 + ta].y);
#pragma unroll
                for (int n = 0; n < 16; n++) bad |= kv[n] ^ ep;
                if ((bad & 31) == 0) break;
            } while (--tries > 0);
            __syncwarp();
            TSC(ta == 0, 26);
            uint32_t m = 0;
#pragma unroll
            for (int n = 0; n < 16; n++) m = max(m, kv[n]);
            uint32_t gmax = m;
#pragma unroll
            for (int o = 1; o < 8; o <<= 1) gmax = max(gmax, __shfl_xor_sync(0xffffffffu, gmax, o));
            sts1(gm + (ta >> 3) * 4, gmax);
            sts1(cnt, 0);
            bar_sync(12, 128);
            const uint32_t c = lds1(gm + (lane & 15) * 4);
            int rank = 0;
#pragma unroll
            for (int i = 0; i < 2; i++) { const uint4 q = lds4(gm + (lane >> 4) * 32 + i * 16); rank += (q.x > c) + (q.y > c) + (q.z > c) + (q.w > c); }
            rank += __shfl_xor_sync(0xffffffffu, rank, 16);
            const uint32_t thr = redux_max(rank == 7 ? c : 0u);
#pragma unroll 1
            while (m >= thr) {
                uint32_t at, m2 = 0;
                asm volatile("atom.shared.add.u32 %0, [%1], 1;" : "=r"(at) : "r"(cnt) : "memory");
#pragma unroll
                for (int n = 0; n < 16; n++) m2 = max(m2, kv[n] < m ? kv[n] : 0u);
                sts1(list + at * 4, m);
                if (m2 == 0) break;
                m = m2;
            }
            bar_sync(12, 128);
            const int nc = lds1(cnt);
#pragma unroll 1
            for (int i = ta >> 3; i < ((nc + 3) & ~3); i += 16) {
                const uint32_t ki = lds1(list + i * 4);
                int r = 0;
#pragma unroll 1
                for (int n = lane & 7; n < nc; n += 8) r += lds1(list + n * 4) > ki;
                __syncwarp();
#pragma unroll
                for (int o = 1; o < 8; o <<= 1) r += __shfl_xor_sync(0xffffffffu, r, o);
                if (r == (b & 7) && i < nc) sts1(res, ki);
            }
            bar_sync(12, 128);
            const uint32_t k0 = lds1(res);
            const int r0 = 2047 - ((k0 >> 5) & 2047);
            TSC(ta == 0, 22);
            if (ta == 0) st_rlx(&scr->sel[b & 7], k0);
            const uint4 v0 = ldg_nc(x + (size_t)r0 * 1024 + ta * 8);
            const uint32_t s0 = ld_rlx(&scr->row[r0]);
            const float m0 = bf_lo(s0), i0 = rcp(bf_hi(s0));
            const int ao = 14336 + (ta >> 3) * 256 + (b & 7) * 32 + ((ta ^ b) & 7) * 4;
            st_rlx4(scr->act[ep & 1] + ao, norm_pair(v0.x, m0, i0), norm_pair(v0.y, m0, i0), norm_pair(v0.z, m0, i0), norm_pair(v0.w, m0, i0));
            __syncwarp();
            if (lane == 0) red_add(&scr->cnt[8][tries >> 30]);
            st_rlx4(scr->act[~ep & 1] + ao, 0, 0, 0, 0);
        }
        uint32_t s8 = 0, fph = 0, key = 0;
        const uint32_t chk = __shfl_sync(0xffffffffu, sb + OFF_FS + BOX + lane * 32 + (lane & 28), lane);
        int left = BUDGET;
#pragma unroll 1
        for (int ph = 0; ph < 2; ph++) {
            if (ph || b < 112) {
                float acc[4] = {0.f, 0.f, 0.f, 0.f};
                const uint32_t alo = sd + (ph ? dlo(OFF_FS, 8192) : dlo(OFF_FS, 4096)), ahi = ph ? dhi(1024, 1) : dhi(512, 2), astep = ph ? 128 : 64;
                const uint32_t bhi = ph ? dhi(128, 0) : dhi(1024, 1), bstep = ph ? 16 : 2, wrap = ph ? 24 : 40;
                uint32_t prev = 0, prev2 = 0;
                if (ph) mbar_wait(bars + 8 * FFN2_GATE, 0, left);
#pragma unroll 1
                for (int q = ph ? 7 : 16; q > 0; q--) {
                    const uint32_t da = alo + s8 * (F_BYTES >> 7), db = sd + dlo(OFF_FS + BOX, 128) + s8 * (F_BYTES >> 7);
                    mbar_wait_hot(bars + 8 * B_FFULL + s8, fph, left);
                    if (__builtin_expect(__any_sync(0xffffffffu, lds1(chk + s8 * (F_BYTES / 8)) == 0), 0)) {
                        int tries = BUDGET;
#pragma unroll 1
                        for (int n = lane * 4 + (left >> 30); n < 256; n += 128) {
                            uint4 v;
#pragma unroll 1
                            do { v = ld_rlx4(scr->act[ep & 1] + ((ph ? kc * 7 + 7 : 72) - q) * 256 + n); } while (v.x == 0 && --tries > 0);
                            __syncwarp();
                            sts4(sb + OFF_FS + BOX + s8 * (F_BYTES / 8) + n * 4, v.x, v.y, v.z, v.w);
                        }
                        NRETRY();
                        fence_async_smem();
                        __syncwarp();
                    }
                    TSC(TIMING % 10 == 3 && ta == 0, 32 + (ph ? 23 : 16) - q);
                    wg_fence();
#pragma unroll
                    for (int j = 0; j < 4; j++) wgmma_n8<1, 0>(acc, mkdesc(da + j * astep, ahi), mkdesc(db + j * bstep, bhi), 1);
                    wg_commit();
                    uint32_t done = F1_DEPTH == 2 ? prev2 : prev;
                    prev2 = prev;
                    if (lane == 0) prev = bars + 8 * B_FEMPTY + s8;
                    wg_wait<F1_DEPTH>();
                    if (ph) { wg_wait<F2_DEPTH>(); done = F2_DEPTH ? prev2 : prev; }
                    if (done) mbar_arrive(done);
                    s8 += 8;
                    if (s8 == wrap) { s8 = 0; fph ^= 1; }
                }
                wg_wait<0>();
                const int ln = lane + (left >> 30);
                if (ph == 0) {
                    if (prev) mbar_arrive(prev);
                    const bool second = (wq >= 2) != (swap_gu != 0);
                    const uint32_t xa = sb + OFF_GU + ((wq & 1) * 32 + ln) * 16;
                    if (second) sts4(xa, __float_as_uint(acc[0]), __float_as_uint(acc[1]), __float_as_uint(acc[2]), __float_as_uint(acc[3]));
                    bar_sync(12, 128);
                    if (!second) {
                        const float4 up = lds4f(xa);
                        float hv[4];
#pragma unroll
                        for (int c = 0; c < 4; c++) { const float ga = bf16r(acc[c]); hv[c] = bf16r(ga * sigmoidf(ga)) * bf16r((&up.x)[c]); }
                        const int ao = (b * 4 + (wq & 1) * 2) * 32 + ln;
                        st_rlx(scr->act[ep & 1] + ao, max(movm(pack_bf16(hv[0], hv[1])), 1u)); st_rlx(scr->act[ep & 1] + 32 + ao, max(movm(pack_bf16(hv[2], hv[3])), 1u));
                        __syncwarp();
                        if (ln == 0) red_add(&scr->cnt[b / 14][0]);
                        st_rlx(scr->act[~ep & 1] + ao, 0); st_rlx(scr->act[~ep & 1] + 32 + ao, 0);
                    }
                } else {
#pragma unroll
                    for (int c = 0; c < 4; c++) st_rlx(&scr->ypart[kc][2 * (ln & 3) + (c & 1)][c2 * 64 + wq * 16 + (c >> 1) * 8 + (ln >> 2)], (__float_as_uint(acc[c]) & ~1u) | (ep & 1));
                }
                TSC(ta == 0, 22 + ph);
            }
            const int ln = lane + (left >> 30);
            if (ph == 0) {
                if ((ta & 126) == 64) mbar_arrive(bars + 8 * B_F1DONE);
                key = poll_all(&scr->sel[ln & 7], 31u, ep & 31, left);
            }
        }
        {
            const int row = 2047 - ((key >> 5) & 2047);
            const float sig = bf16r(sigmoidf(__uint_as_float(((int)key < 0 ? key & 0x7fffffffu : ~key) & 0xffff0000u)));
            uint32_t own = __ballot_sync(0xffffffffu, (row & 1) == par && (row >> 8) == (mt & 3) * 2 + rh) & 255;
            if (wq & 2) own &= own - 1;
            mbar_wait(bars + 8 * B_ZERO, 0, left);
#pragma unroll 1
            for (; own; own &= own - 1, own &= own - 1) {
                const int j = __ffs(own) - 1, col = cb * 128 + (wq & 1) * 64 + (lane & 15) * 4;
                const uint32_t* src = &scr->ypart[lane >> 4][j][col];
                uint4 v[4]; int tries = BUDGET;
#pragma unroll 1
                do {
#pragma unroll
                    for (int m = 0; m < 4; m++) v[m] = ld_rlx4(src + m * 2 * 8192);
                } while ((((v[0].x ^ ep) | (v[1].x ^ ep) | (v[2].x ^ ep) | (v[3].x ^ ep)) & 1) && --tries > 0);
                __syncwarp();
                float a[4];
                const float sj = __shfl_sync(0xffffffffu, sig, j);
                const int rj = __shfl_sync(0xffffffffu, row, j);
#pragma unroll
                for (int c = 0; c < 4; c++) {
                    a[c] = (__uint_as_float((&v[0].x)[c]) + __uint_as_float((&v[1].x)[c])) + (__uint_as_float((&v[2].x)[c]) + __uint_as_float((&v[3].x)[c]));
                    a[c] = bf16r(a[c] + __shfl_xor_sync(0xffffffffu, a[c], 16)) * sj;
                }
                if (lane < 16) asm volatile("red.relaxed.gpu.global.add.noftz.v2.bf16x2 [%0], {%1, %2};" ::"l"(pf.out + (size_t)rj * 2048 + col * 2), "r"(pack_bf16(a[0], a[1])), "r"(pack_bf16(a[2], a[3])) : "memory");
            }
        }
        TSC(ta == 0, 24);
    } else {
        reg_inc<224>();
        const int w = warp >> 2, wi = warp & 3, g = lane >> 2, t = lane & 3;
        const bool elect = (tid & 127) == 0;
        const uint32_t mad = (lane & 15) * 128 + (((lane >> 4) ^ (lane & 7)) << 4);
        float acc[64];
        const uint32_t ring = sb + w * OFF_X1, ofull = bars + 8 * (B_OFULL + w * 6), oempty = mapa(bars + 8 * B_OEMPTY, w);
        const int r0 = rh * 128 + wi * 32 + (1 - w) * 16 + g;
        {
            float acc0[96], acc1[96];
            const uint32_t sta = sb + OFF_STAT + (8 + w * 128 + wi * 32) * 8;
            {
                const uint32_t xfull = bars + 8 * (B_XFULL + w * 6 + 5), xempty = mapa(bars + 8 * B_XEMPTY, w), dx0 = sd + dlo(w * OFF_X1, 16);
                uint32_t s8 = 16, ps8 = 0, ph = 0;
                cluster_wait();
#pragma unroll 1
                for (int k = 0; k < 16; k++) {
                    const uint32_t dx = dx0 + s8 * (2 * BOX >> 7), dw = sd + dlo(OFF_W, BOX) + s8 * (W_BYTES >> 7);
                    mbar_wait(bars + 8 * B_WFULL + s8, ph, budget);
                    mbar_wait(xfull - 2 * s8, ph, budget);
                    TSC(elect && k == 0, 1 + 8 * w);
                    TSC(TIMING % 10 == 1 && tid == 0, 32 + k);
                    wg_wait<0>();
                    wg_fence();
#pragma unroll
                    for (int kk = 0; kk < 4; kk++) wgmma_n192<0, 1>(acc1, mkdesc(dx + kk * 2, dhi(1024, 1)), mkdesc(dw + kk * 128, dhi(1024, 1)), kk ? 1 : k);
                    wg_commit();
                    if (elect && k > 0) {
                        mbar_arrive(bars + 8 * B_WEMPTY + ps8);
                        if (k <= 13) { mbar_expect_tx(xfull - 2 * ps8 - 8, BOX); mbar_arrive_at(xempty + 2 * ps8 + 8); }
                    }
                    if (k == 15) {
                        mbar_wait(bars + 8 * B_AUX, 0, budget);
                        const uint32_t zero = budget >> 30, pm = t & 1 ? 0x4432 : 0x3232, ra = sta + ((t >> 1) * 16 + g) * 8;
                        const uint32_t a0 = __byte_perm(lds1(ra), 0, pm), a1 = __byte_perm(lds1(ra + 64), 0, pm), a2 = a0 & zero, a3 = a1 & zero;
                        wg_fence();
                        wgmma_rs_n192(acc1, a0, a1, a2, a3, mkdesc(sd + dlo(OFF_CS, 0), dhi(128, 0)));
                        wgmma_rs_n192(acc0, a0, a1, a2, a3, mkdesc(sd + dlo(OFF_CS + 64, 0), dhi(128, 0)));
                        wg_commit();
                    }
                    mbar_wait(xfull - 2 * s8 - 8, ph, budget);
                    wg_wait<0>();
                    wg_fence();
#pragma unroll
                    for (int kk = 0; kk < 4; kk++) wgmma_n192<0, 1>(acc0, mkdesc(dx + 512 + kk * 2, dhi(1024, 1)), mkdesc(dw + kk * 128, dhi(1024, 1)), kk ? 1 : k);
                    wg_commit();
                    if (elect && k <= 12) { mbar_expect_tx(xfull - 2 * s8, BOX); mbar_arrive_at(xempty + 2 * s8); }
                    ps8 = s8;
                    s8 = s8 == 16 ? 0 : s8 + 8;
                    if (s8 == 16) ph ^= 1;
                }
            }
            const uint32_t zero = budget >> 30;
            const bool u0 = 2 * t > g, u1 = 2 * t + 1 > g;
            uint32_t mU = (u0 ? 0xffffu : 0u) | (u1 ? 0xffff0000u : 0u);
            uint32_t ka0 = sta + (2 * t - (u0 ? 8 : 0)) * 8 + 4, ka1 = sta + (2 * t + 1 - (u1 ? 8 : 0)) * 8 + 4;
            float rk[2][4], fu[2][4], fn[2][4];
            auto factors = [&](int h) {
#pragma unroll
                for (int n = 0; n < 4; n += 2) {
                    const float rq = lds1f(sta + (16 * h + 4 * n + g) * 8 + 4) * (0.17677669529663687f * 1.4426950408889634f);
                    rk[h][n] = lds1f(ka0 + h * 128 + n * 32); rk[h][n + 1] = lds1f(ka1 + h * 128 + n * 32);
                    const float f0 = rq * rk[h][n], f1 = rq * rk[h][n + 1];
                    fu[h][n] = u0 ? f0 : 0.f; fn[h][n] = f0 - fu[h][n]; fu[h][n + 1] = u1 ? f1 : 0.f; fn[h][n + 1] = f1 - fu[h][n + 1];
                }
#pragma unroll
                for (int n = 0; n < 4; n++) asm volatile("" : "+f"(fu[h][n]), "+f"(fn[h][n]));
            };
            uint8_t* og = scr->o + ((size_t)(mt * 4 + w * 2) * 16 + nt) * BOX + wi * 256 + lane * 4;
            TSC(elect, 19 + w);
            uint32_t pk0[48], pk1[48], o[16] = {};
#pragma unroll
            for (int j = 0; j < 48; j++) if (j < 16 || (j & 1)) pk1[j] = pack_here(acc1[2 * j], acc1[2 * j + 1]);
            if (warp < 7) {
#pragma unroll
                for (int c = 0; c < 4; c++) stsm4(ring + 4 * BOX + wi * 2048 + c * 512 + lane * 16, pk1[17 + 8 * c], pk1[19 + 8 * c], pk1[21 + 8 * c], pk1[23 + 8 * c]);
                bar_arrive(1 + warp, 64);
            } else if (j0 != 768) {
#pragma unroll
                for (int c = 0; c < 4; c++) {
                    pk1[17 + 8 * c] = max(pk1[17 + 8 * c], 1u);
                    st_rlx4(&scr->halo[b][c * 128 + lane * 4], pk1[17 + 8 * c], pk1[19 + 8 * c], pk1[21 + 8 * c], pk1[23 + 8 * c]);
                }
            }
            TSC(tid == 224, 28);
#pragma unroll
            for (int j = 16; j < 48; j += 2) pk1[j] = pack_here(acc1[2 * j], acc1[2 * j + 1]);
            factors(1);
            uint32_t od = sb + 2 * BOX + wi * 256 + (lane >> 4) * 1024 + (lane & 15) * 16, g1peer = mapa(bars + 8 * B_G1DONE, hp ^ 1);
            uint32_t ha = sb + (warp == 0 ? OFF_HIN : warp <= 4 ? 4 * BOX - 2048 : OFF_X1 + 4 * BOX - 5 * 2048) + warp * 2048 + lane * 16;
            const bool first = warp == 0 && j0 == 0;
            float bias0 = first && u0 ? -INFINITY : 0.f, bias1 = first && u1 ? -INFINITY : 0.f;
            asm volatile("" : "+l"(og), "+r"(mU), "+r"(od), "+r"(ha), "+f"(bias0), "+f"(bias1));
            mbar_wait(bars + 8 * B_XT, 0, budget);
            mbar_wait(bars + 8 * (B_WEMPTY + 1), 0, budget);
            TSC(elect, 12 + 2 * w);
            wg_wait<0>();
            if (elect) { mbar_arrive(bars + 8 * B_G1DONE); mbar_arrive_at(g1peer); }
            TSC(elect, 2 + 8 * w);
            float ci[4];
#pragma unroll
            for (int n = 0; n < 4; n++) ci[n] = __uint_as_float((0x03800000u + n) | (budget >> 30));
            auto hand_over = [&](int v) {
                asm volatile("{\n.reg .pred p;\nsetp.ne.b32 p, %17, 0;\n"
                             "@p stmatrix.sync.aligned.m8n8.x4.shared.b16 [%16], {%0,%1,%2,%3};\n@p stmatrix.sync.aligned.m8n8.x4.shared.b16 [%16 + 2048], {%4,%5,%6,%7};\n"
                             "@p stmatrix.sync.aligned.m8n8.x4.shared.b16 [%16 + 4096], {%8,%9,%10,%11};\n@p stmatrix.sync.aligned.m8n8.x4.shared.b16 [%16 + 6144], {%12,%13,%14,%15};\n"
                             FENCE_PRED "fence.proxy.async.shared::cta;\n}"
                             ::"r"(o[0]), "r"(o[1]), "r"(o[2]), "r"(o[3]), "r"(o[4]), "r"(o[5]), "r"(o[6]), "r"(o[7]), "r"(o[8]), "r"(o[9]), "r"(o[10]), "r"(o[11]),
                               "r"(o[12]), "r"(o[13]), "r"(o[14]), "r"(o[15]), "r"(od + v * OFF_X1), "r"((int)(w == rh)) : "memory");
                TSC(tid == 0, v ? 27 : 5);
#pragma unroll
                for (int i = 0; i < 16; i++) asm volatile("st.global.u32 [%0], %1;" ::"l"(og + (1 - v) * 16 * BOX + (i >> 1) * 1024 + (i & 1) * 128), "r"(o[i]) : "memory");
                __syncwarp();
                if (lane == 0) mbar_arrive(bars + 8 * (B_STAGED + v));
            };
#pragma unroll
            for (int j = 32; j < 48; j++) pk1[j] = movm(pk1[j]);
#pragma unroll
            for (int j = EARLY_PK; j < 48; j++) if (j >= 32 || (j & 1) || EARLY_PK < 17) pk0[j] = pack_here(acc0[2 * j], acc0[2 * j + 1]);
#pragma unroll
            for (int j = 32; j < 48; j++) pk0[j] = movm(pk0[j]);
            factors(0);
            attn_pair<2>(pk1, pk1 + 16, pk1 + 32, pk0 + 17, pk0 + 33, fu[1], fn[1], rk[1], 0.f, 0.f, mU, zero, ci, o);
            hand_over(0);
            TSC(elect, 3 + 8 * w);
#pragma unroll
            for (int j = 0; j < 32; j++) if (j < EARLY_PK || (!(j & 1) && EARLY_PK == 17)) pk0[j] = pack_here(acc0[2 * j], acc0[2 * j + 1]);
            bar_sync(warp ? warp : 11, 64);
            uint32_t hl[16];
            ldsm4(hl, ha); ldsm4(hl + 4, ha + 512); ldsm4t(hl + 8, ha + 1024); ldsm4t(hl + 12, ha + 1536);
            __syncwarp();
            if (lane == 0) mbar_arrive(bars + 8 * B_FREED);
            attn_pair<1>(pk0, pk0 + 16, pk0 + 32, hl, hl + 8, fu[0], fn[0], rk[0], bias0, bias1, mU, zero, ci, o);
            const float2 s0 = lds2f(sb + OFF_STAT + (8 + r0) * 8), s1 = lds2f(sb + OFF_STAT + (16 + r0) * 8);
            const float m0 = s0.x * s0.y, f0 = 1.f + s0.y, m1 = s1.x * s1.y, f1 = 1.f + s1.y;
            uint32_t xt[32];
#pragma unroll
            for (int j = 0; j < 8; j++) ldsm4(xt + 4 * j, ((ring + wi * 2048 + mad) ^ ((j & 3) * 32)) + (j >> 2) * BOX);
            hand_over(1);
#pragma unroll
            for (int j = 0; j < 32; j++) {
                acc[2 * j] = fmaf(bf_lo(xt[j]), j & 1 ? f1 : f0, j & 1 ? m1 : m0); acc[2 * j + 1] = fmaf(bf_hi(xt[j]), j & 1 ? f1 : f0, j & 1 ? m1 : m0);
            }
        }
        TSC(tid == 0, 4);
        {
            const uint32_t da0 = sd + dlo(w * OFF_X1, 1024), db0 = sd + dlo(OFF_WO, BOX);
            const uint32_t chk = ring + wi * 256 + (lane >> 3) * 1032 + (lane & 7) * 32 + (lane & 4);
            uint32_t s8 = 16, ps8 = 0, ph = 0;
            mbar_wait(ofull + s8, 0, budget);
            mbar_wait(bars + 8 * B_WOFULL + s8, 0, budget);
            TSC(TIMING % 10 == 2 && elect, 32 + w * 16);
            const uint32_t ahi = dhi(128, 0) | (budget >> 30), bhi = dhi(1024, 1) | (budget >> 30);
            const int last = w ? HOLD : 16;
            uint32_t rel = elect ? 0x7fe : 0;
#pragma unroll 1
            for (int i = 1;;) {
                const uint32_t da = da0 + s8 * (BOX >> 7), db = db0 + s8 * (BOX >> 6);
                wg_fence();
#pragma unroll
                for (int kk = 0; kk < 4; kk++) {
                    wgmma_n128<0, 1>(acc, mkdesc(da + kk * 128, ahi), mkdesc(db + kk * 128, bhi), 1);
                    if (kk & 1) wg_commit();
                }
                wg_wait<2>();
                if (rel & 1) { mbar_expect_tx(ofull + ps8, BOX); mbar_arrive_at(oempty + ps8); mbar_arrive(bars + 8 * B_WOEMPTY + ps8); }
                if (i == 16) break;
                rel >>= 1;
                ps8 = s8;
#pragma unroll 1
                do {
                    s8 = s8 == 40 ? 0 : s8 + 8;
                    if (s8 == 16) ph ^= 1;
                    uint32_t bad;
                    asm volatile("{\n.reg .pred p, q, r;\n.reg .u32 u, v;\nmbarrier.try_wait.parity.shared::cta.b64 q, [%2], %3;\nmbarrier.try_wait.parity.shared::cta.b64 p, [%1], %3;\n"
                                 "setp.ne.and.u32 r, %5, 1, p;\nmov.u32 u, 1;\nmov.u32 v, 1;\n@r ld.shared.u32 u, [%4];\n@r ld.shared.u32 v, [%4 + 4096];\n"
                                 "and.pred p, p, q;\nmin.u32 u, u, v;\nsetp.eq.or.u32 p, u, 0, !p;\nvote.sync.any.pred p, p, 0xffffffff;\nselp.u32 %0, 1, 0, p;\n}"
                                 : "=r"(bad) : "r"(ofull + s8), "r"(bars + 8 * B_WOFULL + s8), "r"(ph), "r"(chk + s8 * (BOX / 8)), "r"(i) : "memory");
                    if (__builtin_expect(bad, 0)) {
                        mbar_wait(ofull + s8, ph, budget);
                        mbar_wait(bars + 8 * B_WOFULL + s8, ph, budget);
                        if (__any_sync(0xffffffffu, min(lds1(chk + s8 * (BOX / 8)), lds1(chk + s8 * (BOX / 8) + 4096)) == 0)) {
                            const uint32_t at = wi * 256 + (lane >> 4) * 1024 + (lane & 15) * 16;
                            const uint8_t* src = scr->o + ((size_t)((mt * 2 + rh) * 2 + 1 - w) * 16 + ((2 * p + (i < 2 ? i ^ hp : i)) & 15)) * BOX + at;
#pragma unroll 1
                            for (int n = 0; n < 8192; n += 2048) {
                                uint4 v; int tries = 4096;
#pragma unroll 1
                                do { v = ld_rlx4(src + n); } while (v.x == 0 && --tries > 0);
                                sts4(ring + s8 * (BOX / 8) + at + n, v.x, v.y, v.z, v.w);
                            }
                            NRETRY();
                            fence_async_smem();
                            __syncwarp();
                        }
                    }
                    TSC(TIMING % 10 == 1 && tid == 0, 48 + i);
                    TSC(TIMING % 10 == 2 && elect, 32 + w * 16 + i);
                } while (++i > last && i < 16);
                if (i > last) break;
                wg_wait<1>();
            }
            if (w) {
                bar_sync(9, 256);
#pragma unroll 1
                for (int i = HOLD - 10; i < 6; i++) {
                    wg_fence();
#pragma unroll
                    for (int kk = 0; kk < 4; kk++) wgmma_n128<0, 1>(acc, mkdesc(da0 + i * 512 + kk * 128, ahi), mkdesc(db0 + i * 1024 + kk * 128, bhi), 1);
                    wg_commit();
                }
            } else bar_arrive(9, 256);
            const bool add = (lds1(sb + OFF_SEL) >> (wi * 2 + 1 - w)) & 1;
            wg_wait<0>();
            TSC(elect, 7 + 9 * w);
            const uint32_t os0 = ring + wi * 4096;
#pragma unroll
            for (int j = 0; j < 8; j++)
                stsm4(((os0 + mad) ^ ((j & 3) * 32)) + (j >> 2) * 2048, pack_bf16(acc[8 * j], acc[8 * j + 1]), pack_bf16(acc[8 * j + 2], acc[8 * j + 3]),
                      pack_bf16(acc[8 * j + 4], acc[8 * j + 5]), pack_bf16(acc[8 * j + 6], acc[8 * j + 7]));
            fence_async_smem();
            __syncwarp();
            if (elect_one()) {
                asm volatile("{\n.reg .pred p;\nsetp.ne.b32 p, %6, 0;\n@!p cp.async.bulk.tensor.5d.global.shared::cta.bulk_group [%0, {%2, %2, %3, %4, %5}], [%1];\n"
                             "@p cp.reduce.async.bulk.tensor.5d.global.shared::cta.add.bulk_group [%0, {%2, %2, %3, %4, %5}], [%1];\n"
                             "cp.async.bulk.commit_group;\ncp.async.bulk.wait_group.read 0;\n}"
                             ::"l"(&mout), "r"(os0), "r"(0), "r"(((j0 + rh * 128) >> 5) + wi), "r"(1 - w), "r"(par * 16 + cb * 2), "r"((int)add) : "memory");
            }
            if (b == 0 && tid == 0) st_rlx(&scr->epoch[0], lds1(sb + OFF_EP));
            TSC(elect, 8 - 2 * w);
            TS_END();
        }
    }
}

typedef CUresult (*EncodeFn)(CUtensorMap*, CUtensorMapDataType, cuuint32_t, void*, const cuuint64_t*, const cuuint64_t*, const cuuint32_t*,
                             const cuuint32_t*, CUtensorMapInterleave, CUtensorMapSwizzle, CUtensorMapL2promotion, CUtensorMapFloatOOBfill);

CUtensorMap make_map(EncodeFn fn, const void* base, int rank, const cuuint64_t* dims, const cuuint64_t* strides, const cuuint32_t* box,
                     CUtensorMapSwizzle swz = CU_TENSOR_MAP_SWIZZLE_128B, CUtensorMapL2promotion pro = CU_TENSOR_MAP_L2_PROMOTION_L2_256B) {
    CUtensorMap m;
    cuuint32_t es[5] = {1, 1, 1, 1, 1};
    fn(&m, CU_TENSOR_MAP_DATA_TYPE_BFLOAT16, rank, (void*)base, dims, strides, box, es, CU_TENSOR_MAP_INTERLEAVE_NONE,
       swz, pro, CU_TENSOR_MAP_FLOAT_OOB_FILL_NONE);
    return m;
}

}

extern "C" void kernel_launch(void* const* d_in, const int* in_sizes, int n_in, void* d_out, int out_size) {
    (void)in_sizes; (void)n_in; (void)out_size;
    const __nv_bfloat16* x = (const __nv_bfloat16*)d_in[0];
    const __nv_bfloat16* wqkv = (const __nv_bfloat16*)d_in[1];
    const __nv_bfloat16* wo = (const __nv_bfloat16*)d_in[2];
    const __nv_bfloat16* wr = (const __nv_bfloat16*)d_in[4];
    const __nv_bfloat16* wg = (const __nv_bfloat16*)d_in[5];
    const __nv_bfloat16* wu = (const __nv_bfloat16*)d_in[6];
    const __nv_bfloat16* wd = (const __nv_bfloat16*)d_in[7];
    static EncodeFn fn = nullptr;
    static Scratch* scr = nullptr;
    if (!fn) {
        void* p = nullptr; cudaDriverEntryPointQueryResult q;
        cudaGetDriverEntryPoint("cuTensorMapEncodeTiled", &p, cudaEnableDefault, &q);
        fn = (EncodeFn)p;
        cudaFuncSetAttribute(fused_kernel, cudaFuncAttributeMaxDynamicSharedMemorySize, SMEM_LAUNCH);
        cudaGetSymbolAddress((void**)&scr, g_scr);
    }
    const cuuint64_t xd[4] = {2048, 16, 32, 2}, xs[4] = {4096, 131072, 65536, 128}, od[5] = {64, 16, 32, 2, 32};
    const cuuint32_t xb[4] = {64, 16, 4, 1}, ob[5] = {64, 16, 1, 1, 2};
    const cuuint64_t wdm[3] = {1024, 1024, 3}, wst[2] = {6144, 2048};
    const cuuint32_t wb[3] = {64, 64, 3};
    const cuuint64_t wod[3] = {64, 1024, 16}, wdd[3] = {64, 3584, 16}, wos[2] = {2048, 128};
    const cuuint32_t wob[3] = {64, 64, 2}, wdb[3] = {64, 64, 1};
    CUtensorMap mx = make_map(fn, x, 4, xd, xs, xb), mw = make_map(fn, wqkv, 3, wdm, wst, wb);
    CUtensorMap mwo = make_map(fn, wo, 3, wod, wos, wob), mout = make_map(fn, d_out, 5, od, xs, ob);
    const int swap_gu = wu < wg;
    const cuuint64_t gd[3] = {3584, 1024, 2}, gst[2] = {7168, (cuuint64_t)(swap_gu ? (const char*)wg - (const char*)wu : (const char*)wu - (const char*)wg)};
    const cuuint32_t gb[3] = {32, 64, 2};
    CUtensorMap mgu = make_map(fn, swap_gu ? wu : wg, 3, gd, gst, gb, CU_TENSOR_MAP_SWIZZLE_64B, CU_TENSOR_MAP_L2_PROMOTION_L2_128B);
    CUtensorMap mwd = make_map(fn, wd, 3, wdd, wos, wdb, CU_TENSOR_MAP_SWIZZLE_128B, CU_TENSOR_MAP_L2_PROMOTION_L2_128B);
    const cuuint64_t md[2] = {64, 32768}, ms[1] = {128};
    const cuuint32_t mb[2] = {64, 64};
    CUtensorMap mo = make_map(fn, scr, 2, md, ms, mb, CU_TENSOR_MAP_SWIZZLE_NONE, CU_TENSOR_MAP_L2_PROMOTION_NONE);
    cudaLaunchConfig_t cfg = {};
    cfg.gridDim = dim3(132); cfg.blockDim = dim3(512); cfg.dynamicSmemBytes = SMEM_LAUNCH; cfg.stream = cudaStreamPerThread;
    cudaLaunchAttribute at[1];
    at[0].id = cudaLaunchAttributeClusterDimension; at[0].val.clusterDim.x = 2; at[0].val.clusterDim.y = 1; at[0].val.clusterDim.z = 1;
    cfg.attrs = at; cfg.numAttrs = 1;
    cudaLaunchKernelEx(&cfg, fused_kernel, mx, mw, mwo, mout, mgu, mwd, mo, x, wr, scr, swap_gu, Weights{(const char*)wqkv, (const char*)wo, (const char*)wg, (const char*)wu, (const char*)wd, (char*)d_out});
}
```

```cpp
#include <cuda_runtime.h>
#include <cuda.h>
#include <cuda_bf16.h>
#include <stdint.h>

namespace {

constexpr int BOX = 8192, W_BYTES = 3 * BOX;
constexpr int OFF_X1 = 6 * BOX, OFF_FR = 12 * BOX, OFF_E = 16 * BOX, OFF_W = 19 * BOX;
constexpr int OFF_WO = OFF_E;
constexpr int OFF_HIN = OFF_FR + 2048, OFF_GU = OFF_HIN + 2048, OFF_FS = OFF_GU + 1024;
constexpr int F_BYTES = 9216;
constexpr int CS_BYTES = 3136;
constexpr int OFF_CS = OFF_FS + 5 * F_BYTES;
constexpr int OFF_STAT = 28 * BOX;
constexpr int OFF_SEL = OFF_STAT + 2112;
constexpr int OFF_EP = OFF_SEL + 32;
constexpr int OFF_BAR = OFF_EP + 16;
constexpr int B_WFULL = 0, B_XFULL = 3, B_AUX = 15, B_XT = 16, B_ROW = 17, B_WOFULL = 18, B_OFULL = 24, B_FFULL = 36, B_ZERO = 41;
constexpr int B_WEMPTY = 42, B_F1DONE = 45, B_XEMPTY = 46, B_WOEMPTY = 52, B_OEMPTY = 58;
constexpr int B_G1DONE = 66, B_FEMPTY = 67, B_STAGED = 72, B_RDONE = 75, B_FREED = 76, NBAR = 78;
constexpr int SMEM_BYTES = OFF_BAR + NBAR * 8;
static_assert(OFF_FS + 3 * F_BYTES == OFF_E && OFF_CS + CS_BYTES <= OFF_W && SMEM_BYTES + 256 <= 232448 && OFF_BAR % 8 == 0, "smem");
#define POLL_NS 30
#define PF_RATE 8
#define PF_START 7
#define ZF_NS 100
#define FFN2_GATE (B_STAGED + 1)
#define PF_NW 0
#define EARLY_PF 1
#define EARLY_PK 17
#define FENCE_PRED "@p "
#define ZF_N 64
#define HOLD 12
#define F1_DEPTH 1
#define F2_DEPTH 0
#define F1_HOLD 2
#define F1_GATE B_G1DONE
#define OUT_PARTS 2
#define ROWS_AT 11
constexpr int BUDGET = 1 << 18;

struct Scratch {
    uint8_t o[2048 * 1024 * 2];
    uint32_t ypart[8][8][1024];
    uint32_t halo[128][512];
    uint32_t act[2][14336 + 4096];
    uint2 row[2048];
    uint4 cs[16][3][24];
    uint32_t oflag[16][32];
    uint32_t cnt[9][32];
    uint32_t sel[32], epoch[32];
};
__device__ __align__(1024) Scratch g_scr;
struct Weights { const char *wqkv, *wo, *wg, *wu, *wd; char* out; };

#define TS(i) do {} while (0)
#define TS_END() do {} while (0)
#define TSC(c, i) do {} while (0)
#define NRETRY() do {} while (0)
constexpr int SMEM_LAUNCH = SMEM_BYTES;
__device__ __forceinline__ uint32_t smem_u32(const void* p) { return (uint32_t)__cvta_generic_to_shared(p); }
__device__ __forceinline__ void mbar_init(uint32_t bar, uint32_t cnt) { asm volatile("mbarrier.init.shared::cta.b64 [%0], %1;" ::"r"(bar), "r"(cnt) : "memory"); }
__device__ __forceinline__ void mbar_expect_tx(uint32_t bar, uint32_t bytes) { asm volatile("mbarrier.arrive.expect_tx.shared::cta.b64 _, [%0], %1;" ::"r"(bar), "r"(bytes) : "memory"); }
__device__ __forceinline__ void mbar_arrive(uint32_t bar) { asm volatile("mbarrier.arrive.shared::cta.b64 _, [%0];" ::"r"(bar) : "memory"); }
__device__ __forceinline__ uint32_t mapa(uint32_t a, uint32_t cta) { uint32_t r; asm("mapa.shared::cluster.u32 %0, %1, %2;" : "=r"(r) : "r"(a), "r"(cta)); return r; }
__device__ __forceinline__ void mbar_arrive_at(uint32_t cbar) { asm volatile("mbarrier.arrive.shared::cluster.b64 _, [%0];" ::"r"(cbar) : "memory"); }
__device__ __forceinline__ void mbar_wait(uint32_t bar, uint32_t parity, int& budget) {
    asm volatile("{\n.reg .pred p;\nLAB_WAIT:\nmbarrier.try_wait.parity.shared::cta.b64 p, [%1], %2;\n"
                 "add.s32 %0, %0, -1;\nsetp.gt.and.s32 p, %0, 0, !p;\n@p bra LAB_WAIT;\n}" : "+r"(budget) : "r"(bar), "r"(parity) : "memory");
}
__device__ __forceinline__ void mbar_wait_hot(uint32_t bar, uint32_t parity, int& budget) {
    asm volatile("{\n.reg .pred p;\nmbarrier.try_wait.parity.shared::cta.b64 p, [%1], %2;\n@p bra LAB_DONE;\nLAB_WAIT:\nmbarrier.try_wait.parity.shared::cta.b64 p, [%1], %2;\n"
                 "add.s32 %0, %0, -1;\nsetp.gt.and.s32 p, %0, 0, !p;\n@p bra LAB_WAIT;\nLAB_DONE:\n}" : "+r"(budget) : "r"(bar), "r"(parity) : "memory");
}
__device__ __forceinline__ void tma_2d_mc(uint32_t dst, const CUtensorMap* m, uint32_t bar, int c0, int c1) {
    asm volatile("cp.async.bulk.tensor.2d.shared::cluster.global.mbarrier::complete_tx::bytes.multicast::cluster [%0], [%1, {%3, %4}], [%2], %5;" ::"r"(dst), "l"(m), "r"(bar), "r"(c0), "r"(c1), "h"((uint16_t)3) : "memory");
}
__device__ __forceinline__ void tma_3d(uint32_t dst, const CUtensorMap* m, uint32_t bar, int c0, int c1, int c2) {
    asm volatile("cp.async.bulk.tensor.3d.shared::cluster.global.mbarrier::complete_tx::bytes [%0], [%1, {%3, %4, %5}], [%2];" ::"r"(dst), "l"(m), "r"(bar), "r"(c0), "r"(c1), "r"(c2) : "memory");
}
__device__ __forceinline__ void tma_4d(uint32_t dst, const CUtensorMap* m, uint32_t bar, int c0, int c1, int c2, int c3) {
    asm volatile("cp.async.bulk.tensor.4d.shared::cluster.global.mbarrier::complete_tx::bytes [%0], [%1, {%3, %4, %5, %6}], [%2];" ::"r"(dst), "l"(m), "r"(bar), "r"(c0), "r"(c1), "r"(c2), "r"(c3) : "memory");
}
__device__ __forceinline__ void tma_4d_mc(uint32_t dst, const CUtensorMap* m, uint32_t bar, int c0, int c1, int c2, int c3) {
    asm volatile("cp.async.bulk.tensor.4d.shared::cluster.global.mbarrier::complete_tx::bytes.multicast::cluster [%0], [%1, {%3, %4, %5, %6}], [%2], %7;" ::"r"(dst), "l"(m), "r"(bar), "r"(c0), "r"(c1), "r"(c2), "r"(c3), "h"((uint16_t)3) : "memory");
}
__device__ __forceinline__ void bulk_pf(const void* p, uint32_t bytes) { asm volatile("cp.async.bulk.prefetch.L2.global [%0], %1;" ::"l"(p), "r"(bytes) : "memory"); }
__device__ __forceinline__ void bulk_g2s(uint32_t dst, const void* src, uint32_t bytes, uint32_t bar) {
    asm volatile("cp.async.bulk.shared::cluster.global.mbarrier::complete_tx::bytes [%0], [%1], %2, [%3];" ::"r"(dst), "l"(src), "r"(bytes), "r"(bar) : "memory");
}
__device__ __forceinline__ void bulk_s2c(uint32_t cdst, uint32_t src, uint32_t bytes, uint32_t cbar) {
    asm volatile("cp.async.bulk.shared::cluster.shared::cta.mbarrier::complete_tx::bytes [%0], [%1], %2, [%3];" ::"r"(cdst), "r"(src), "r"(bytes), "r"(cbar) : "memory");
}
__device__ __forceinline__ void cluster_wait() { asm volatile("barrier.cluster.wait.aligned;" ::: "memory"); }
__device__ __forceinline__ void fence_gpu() { asm volatile("fence.acq_rel.gpu;" ::: "memory"); }
__device__ __forceinline__ void fence_async_smem() { asm volatile("fence.proxy.async.shared::cta;" ::: "memory"); }
__device__ __forceinline__ void wg_fence() { asm volatile("wgmma.fence.sync.aligned;" ::: "memory"); }
__device__ __forceinline__ void wg_commit() { asm volatile("wgmma.commit_group.sync.aligned;" ::: "memory"); }
template <int N> __device__ __forceinline__ void wg_wait() { asm volatile("wgmma.wait_group.sync.aligned %0;" ::"n"(N) : "memory"); }
__device__ __forceinline__ uint64_t mkdesc(uint32_t lo, uint32_t hi) { return ((uint64_t)hi << 32) | lo; }
__host__ __device__ constexpr uint32_t dhi(uint32_t sbo, uint32_t mode) { return (sbo >> 4) | (mode << 30); }
__host__ __device__ constexpr uint32_t dlo(uint32_t off, uint32_t lbo) { return (off >> 4) + ((lbo >> 4) << 16); }
__device__ __forceinline__ bool elect_one() {
    uint32_t e;
    asm volatile("{\n.reg .pred p;\nelect.sync _|p, 0xffffffff;\nselp.u32 %0, 1, 0, p;\n}" : "=r"(e));
    return e;
}
template <int R> __device__ __forceinline__ void reg_inc() { asm volatile("setmaxnreg.inc.sync.aligned.u32 %0;" ::"n"(R)); }
template <int R> __device__ __forceinline__ void reg_dec() { asm volatile("setmaxnreg.dec.sync.aligned.u32 %0;" ::"n"(R)); }
__device__ __forceinline__ void bar_sync(int id, int n) { asm volatile("bar.sync %0, %1;" ::"r"(id), "r"(n) : "memory"); }
__device__ __forceinline__ void bar_arrive(int id, int n) { asm volatile("bar.arrive %0, %1;" ::"r"(id), "r"(n) : "memory"); }
__device__ __forceinline__ uint32_t pack_bf16(float lo, float hi) { uint32_t r; asm("cvt.rn.bf16x2.f32 %0, %1, %2;" : "=r"(r) : "f"(hi), "f"(lo)); return r; }
__device__ __forceinline__ uint32_t pack_here(float lo, float hi) { uint32_t r; asm volatile("cvt.rn.bf16x2.f32 %0, %1, %2;" : "=r"(r) : "f"(hi), "f"(lo)); return r; }
__device__ __forceinline__ float bf_lo(uint32_t u) { return __uint_as_float(u << 16); }
__device__ __forceinline__ float bf_hi(uint32_t u) { return __uint_as_float(u & 0xffff0000u); }
__device__ __forceinline__ float bf16r(float v) { return bf_lo(pack_bf16(v, 0.f)); }
__device__ __forceinline__ float rcp(float x) { float r; asm("rcp.approx.ftz.f32 %0, %1;" : "=f"(r) : "f"(x)); return r; }
__device__ __forceinline__ float ex2(float x) { float r; asm("ex2.approx.ftz.f32 %0, %1;" : "=f"(r) : "f"(x)); return r; }
__device__ __forceinline__ float sigmoidf(float v) { return rcp(1.f + ex2(v * -1.4426950408889634f)); }
__device__ __forceinline__ uint32_t movm(uint32_t a) { uint32_t d; asm volatile("movmatrix.sync.aligned.m8n8.trans.b16 %0, %1;" : "=r"(d) : "r"(a)); return d; }
__device__ __forceinline__ void mma16816(float (&c)[4], uint32_t a0, uint32_t a1, uint32_t a2, uint32_t a3, uint32_t b0, uint32_t b1) {
    asm volatile("mma.sync.aligned.m16n8k16.row.col.f32.bf16.bf16.f32 {%0,%1,%2,%3}, {%4,%5,%6,%7}, {%8,%9}, {%0,%1,%2,%3};"
                 : "+f"(c[0]), "+f"(c[1]), "+f"(c[2]), "+f"(c[3]) : "r"(a0), "r"(a1), "r"(a2), "r"(a3), "r"(b0), "r"(b1));
}
__device__ __forceinline__ void mma1688(float (&c)[4], uint32_t a0, uint32_t a1, uint32_t b0) {
    asm volatile("mma.sync.aligned.m16n8k8.row.col.f32.bf16.bf16.f32 {%0,%1,%2,%3}, {%4,%5}, {%6}, {%0,%1,%2,%3};"
                 : "+f"(c[0]), "+f"(c[1]), "+f"(c[2]), "+f"(c[3]) : "r"(a0), "r"(a1), "r"(b0));
}
__device__ __forceinline__ void stsm4(uint32_t a, uint32_t r0, uint32_t r1, uint32_t r2, uint32_t r3) {
    asm volatile("stmatrix.sync.aligned.m8n8.x4.shared.b16 [%0], {%1,%2,%3,%4};" ::"r"(a), "r"(r0), "r"(r1), "r"(r2), "r"(r3) : "memory");
}
__device__ __forceinline__ void ldsm4(uint32_t* r, uint32_t a) {
    asm volatile("ldmatrix.sync.aligned.m8n8.x4.shared.b16 {%0,%1,%2,%3}, [%4];" : "=r"(r[0]), "=r"(r[1]), "=r"(r[2]), "=r"(r[3]) : "r"(a) : "memory");
}
__device__ __forceinline__ void ldsm4t(uint32_t* r, uint32_t a) {
    asm volatile("ldmatrix.sync.aligned.m8n8.x4.trans.shared.b16 {%0,%1,%2,%3}, [%4];" : "=r"(r[0]), "=r"(r[1]), "=r"(r[2]), "=r"(r[3]) : "r"(a) : "memory");
}
__device__ __forceinline__ uint32_t ld_rlx(const void* p) { uint32_t v; asm volatile("ld.relaxed.gpu.global.u32 %0, [%1];" : "=r"(v) : "l"(p) : "memory"); return v; }
__device__ __forceinline__ uint32_t ld_acq(const void* p) { uint32_t v; asm volatile("ld.acquire.gpu.global.u32 %0, [%1];" : "=r"(v) : "l"(p) : "memory"); return v; }
__device__ __forceinline__ uint2 ld_rlx2(const void* p) { uint2 v; asm volatile("ld.relaxed.gpu.global.v2.u32 {%0,%1}, [%2];" : "=r"(v.x), "=r"(v.y) : "l"(p) : "memory"); return v; }
__device__ __forceinline__ uint4 ld_rlx4(const void* p) { uint4 v; asm volatile("ld.relaxed.gpu.global.v4.u32 {%0,%1,%2,%3}, [%4];" : "=r"(v.x), "=r"(v.y), "=r"(v.z), "=r"(v.w) : "l"(p) : "memory"); return v; }
__device__ __forceinline__ void st_rlx(void* p, uint32_t v) { asm volatile("st.relaxed.gpu.global.u32 [%0], %1;" ::"l"(p), "r"(v) : "memory"); }
__device__ __forceinline__ void st_rlx2(void* p, uint32_t a, uint32_t b) { asm volatile("st.relaxed.gpu.global.v2.u32 [%0], {%1,%2};" ::"l"(p), "r"(a), "r"(b) : "memory"); }
__device__ __forceinline__ void st_rlx4(void* p, uint32_t a, uint32_t b, uint32_t c, uint32_t d) { asm volatile("st.relaxed.gpu.global.v4.u32 [%0], {%1,%2,%3,%4};" ::"l"(p), "r"(a), "r"(b), "r"(c), "r"(d) : "memory"); }
__device__ __forceinline__ void red_add(uint32_t* p) { asm volatile("red.relaxed.gpu.global.add.u32 [%0], 1;" ::"l"(p) : "memory"); }
__device__ __forceinline__ uint4 ldg_nc(const void* p) { uint4 v; asm volatile("ld.global.nc.v4.u32 {%0,%1,%2,%3}, [%4];" : "=r"(v.x), "=r"(v.y), "=r"(v.z), "=r"(v.w) : "l"(p)); return v; }
__device__ __forceinline__ void sts4(uint32_t a, uint32_t x, uint32_t y, uint32_t z, uint32_t w) { asm volatile("st.shared.v4.u32 [%0], {%1,%2,%3,%4};" ::"r"(a), "r"(x), "r"(y), "r"(z), "r"(w) : "memory"); }
__device__ __forceinline__ void sts2(uint32_t a, uint32_t x, uint32_t y) { asm volatile("st.shared.v2.u32 [%0], {%1,%2};" ::"r"(a), "r"(x), "r"(y) : "memory"); }
__device__ __forceinline__ void sts1(uint32_t a, uint32_t v) { asm volatile("st.shared.u32 [%0], %1;" ::"r"(a), "r"(v) : "memory"); }
__device__ __forceinline__ uint4 lds4(uint32_t a) { uint4 v; asm volatile("ld.shared.v4.u32 {%0,%1,%2,%3}, [%4];" : "=r"(v.x), "=r"(v.y), "=r"(v.z), "=r"(v.w) : "r"(a) : "memory"); return v; }
__device__ __forceinline__ float4 lds4f(uint32_t a) { float4 v; asm volatile("ld.shared.v4.f32 {%0,%1,%2,%3}, [%4];" : "=f"(v.x), "=f"(v.y), "=f"(v.z), "=f"(v.w) : "r"(a) : "memory"); return v; }
__device__ __forceinline__ float2 lds2f(uint32_t a) { float2 v; asm volatile("ld.shared.v2.f32 {%0,%1}, [%2];" : "=f"(v.x), "=f"(v.y) : "r"(a) : "memory"); return v; }
__device__ __forceinline__ float lds1f(uint32_t a) { float v; asm volatile("ld.shared.f32 %0, [%1];" : "=f"(v) : "r"(a) : "memory"); return v; }
__device__ __forceinline__ uint32_t lds1(uint32_t a) { uint32_t v; asm volatile("ld.shared.u32 %0, [%1];" : "=r"(v) : "r"(a) : "memory"); return v; }
__device__ __forceinline__ uint32_t redux_max(uint32_t v) { uint32_t r; asm volatile("redux.sync.max.u32 %0, %1, 0xffffffff;" : "=r"(r) : "r"(v)); return r; }
__device__ __forceinline__ uint32_t poll_all(const uint32_t* p, uint32_t mask, uint32_t want, int& budget) {
    uint32_t v;
#pragma unroll 1
    while (v = ld_acq(p), !__all_sync(0xffffffffu, (v & mask) == want) && --budget > 0) __nanosleep(POLL_NS);
    return v;
}

template <int TA, int TB>
__device__ __forceinline__ void wgmma_n192(float (&d)[96], uint64_t da, uint64_t db, int keep) {
    asm volatile("{\n.reg .pred p;\nsetp.ne.b32 p, %98, 0;\n"
        "wgmma.mma_async.sync.aligned.m64n192k16.f32.bf16.bf16 "
        "{%0, %1, %2, %3, %4, %5, %6, %7, %8, %9, %10, %11, %12, %13, %14, %15, "
        "%16, %17, %18, %19, %20, %21, %22, %23, %24, %25, %26, %27, %28, %29, %30, %31, "
        "%32, %33, %34, %35, %36, %37, %38, %39, %40, %41, %42, %43, %44, %45, %46, %47, "
        "%48, %49, %50, %51, %52, %53, %54, %55, %56, %57, %58, %59, %60, %61, %62, %63, "
        "%64, %65, %66, %67, %68, %69, %70, %71, %72, %73, %74, %75, %76, %77, %78, %79, "
        "%80, %81, %82, %83, %84, %85, %86, %87, %88, %89, %90, %91, %92, %93, %94, %95}, "
        "%96, %97, p, 1, 1, %99, %100;\n}\n"
        : "+f"(d[0]), "+f"(d[1]), "+f"(d[2]), "+f"(d[3]), "+f"(d[4]), "+f"(d[5]), "+f"(d[6]), "+f"(d[7]),
          "+f"(d[8]), "+f"(d[9]), "+f"(d[10]), "+f"(d[11]), "+f"(d[12]), "+f"(d[13]), "+f"(d[14]), "+f"(d[15]),
          "+f"(d[16]), "+f"(d[17]), "+f"(d[18]), "+f"(d[19]), "+f"(d[20]), "+f"(d[21]), "+f"(d[22]), "+f"(d[23]),
          "+f"(d[24]), "+f"(d[25]), "+f"(d[26]), "+f"(d[27]), "+f"(d[28]), "+f"(d[29]), "+f"(d[30]), "+f"(d[31]),
          "+f"(d[32]), "+f"(d[33]), "+f"(d[34]), "+f"(d[35]), "+f"(d[36]), "+f"(d[37]), "+f"(d[38]), "+f"(d[39]),
          "+f"(d[40]), "+f"(d[41]), "+f"(d[42]), "+f"(d[43]), "+f"(d[44]), "+f"(d[45]), "+f"(d[46]), "+f"(d[47]),
          "+f"(d[48]), "+f"(d[49]), "+f"(d[50]), "+f"(d[51]), "+f"(d[52]), "+f"(d[53]), "+f"(d[54]), "+f"(d[55]),
          "+f"(d[56]), "+f"(d[57]), "+f"(d[58]), "+f"(d[59]), "+f"(d[60]), "+f"(d[61]), "+f"(d[62]), "+f"(d[63]),
          "+f"(d[64]), "+f"(d[65]), "+f"(d[66]), "+f"(d[67]), "+f"(d[68]), "+f"(d[69]), "+f"(d[70]), "+f"(d[71]),
          "+f"(d[72]), "+f"(d[73]), "+f"(d[74]), "+f"(d[75]), "+f"(d[76]), "+f"(d[77]), "+f"(d[78]), "+f"(d[79]),
          "+f"(d[80]), "+f"(d[81]), "+f"(d[82]), "+f"(d[83]), "+f"(d[84]), "+f"(d[85]), "+f"(d[86]), "+f"(d[87]),
          "+f"(d[88]), "+f"(d[89]), "+f"(d[90]), "+f"(d[91]), "+f"(d[92]), "+f"(d[93]), "+f"(d[94]), "+f"(d[95])
        : "l"(da), "l"(db), "r"(keep), "n"(TA), "n"(TB));
}
template <int TA, int TB>
__device__ __forceinline__ void wgmma_n128(float (&d)[64], uint64_t da, uint64_t db, int keep) {
    asm volatile("{\n.reg .pred p;\nsetp.ne.b32 p, %66, 0;\n"
        "wgmma.mma_async.sync.aligned.m64n128k16.f32.bf16.bf16 "
        "{%0, %1, %2, %3, %4, %5, %6, %7, %8, %9, %10, %11, %12, %13, %14, %15, "
        "%16, %17, %18, %19, %20, %21, %22, %23, %24, %25, %26, %27, %28, %29, %30, %31, "
        "%32, %33, %34, %35, %36, %37, %38, %39, %40, %41, %42, %43, %44, %45, %46, %47, "
        "%48, %49, %50, %51, %52, %53, %54, %55, %56, %57, %58, %59, %60, %61, %62, %63}, "
        "%64, %65, p, 1, 1, %67, %68;\n}\n"
        : "+f"(d[0]), "+f"(d[1]), "+f"(d[2]), "+f"(d[3]), "+f"(d[4]), "+f"(d[5]), "+f"(d[6]), "+f"(d[7]),
          "+f"(d[8]), "+f"(d[9]), "+f"(d[10]), "+f"(d[11]), "+f"(d[12]), "+f"(d[13]), "+f"(d[14]), "+f"(d[15]),
          "+f"(d[16]), "+f"(d[17]), "+f"(d[18]), "+f"(d[19]), "+f"(d[20]), "+f"(d[21]), "+f"(d[22]), "+f"(d[23]),
          "+f"(d[24]), "+f"(d[25]), "+f"(d[26]), "+f"(d[27]), "+f"(d[28]), "+f"(d[29]), "+f"(d[30]), "+f"(d[31]),
          "+f"(d[32]), "+f"(d[33]), "+f"(d[34]), "+f"(d[35]), "+f"(d[36]), "+f"(d[37]), "+f"(d[38]), "+f"(d[39]),
          "+f"(d[40]), "+f"(d[41]), "+f"(d[42]), "+f"(d[43]), "+f"(d[44]), "+f"(d[45]), "+f"(d[46]), "+f"(d[47]),
          "+f"(d[48]), "+f"(d[49]), "+f"(d[50]), "+f"(d[51]), "+f"(d[52]), "+f"(d[53]), "+f"(d[54]), "+f"(d[55]),
          "+f"(d[56]), "+f"(d[57]), "+f"(d[58]), "+f"(d[59]), "+f"(d[60]), "+f"(d[61]), "+f"(d[62]), "+f"(d[63])
        : "l"(da), "l"(db), "r"(keep), "n"(TA), "n"(TB));
}
template <int TA, int TB>
__device__ __forceinline__ void wgmma_n8(float (&d)[4], uint64_t da, uint64_t db, int keep) {
    asm volatile("{\n.reg .pred p;\nsetp.ne.b32 p, %6, 0;\n"
        "wgmma.mma_async.sync.aligned.m64n8k16.f32.bf16.bf16 "
        "{%0, %1, %2, %3}, "
        "%4, %5, p, 1, 1, %7, %8;\n}\n"
        : "+f"(d[0]), "+f"(d[1]), "+f"(d[2]), "+f"(d[3])
        : "l"(da), "l"(db), "r"(keep), "n"(TA), "n"(TB));
}
__device__ __forceinline__ void wgmma_rs_n192(float (&d)[96], uint32_t a0, uint32_t a1, uint32_t a2, uint32_t a3, uint64_t db) {
    asm volatile("{\n.reg .pred p;\nsetp.ne.b32 p, 1, 0;\n"
        "wgmma.mma_async.sync.aligned.m64n192k16.f32.bf16.bf16 "
        "{%0, %1, %2, %3, %4, %5, %6, %7, %8, %9, %10, %11, %12, %13, %14, %15, "
        "%16, %17, %18, %19, %20, %21, %22, %23, %24, %25, %26, %27, %28, %29, %30, %31, "
        "%32, %33, %34, %35, %36, %37, %38, %39, %40, %41, %42, %43, %44, %45, %46, %47, "
        "%48, %49, %50, %51, %52, %53, %54, %55, %56, %57, %58, %59, %60, %61, %62, %63, "
        "%64, %65, %66, %67, %68, %69, %70, %71, %72, %73, %74, %75, %76, %77, %78, %79, "
        "%80, %81, %82, %83, %84, %85, %86, %87, %88, %89, %90, %91, %92, %93, %94, %95}, "
        "{%96, %97, %98, %99}, %100, p, 1, 1, 1;\n}\n"
        : "+f"(d[0]), "+f"(d[1]), "+f"(d[2]), "+f"(d[3]), "+f"(d[4]), "+f"(d[5]), "+f"(d[6]), "+f"(d[7]),
          "+f"(d[8]), "+f"(d[9]), "+f"(d[10]), "+f"(d[11]), "+f"(d[12]), "+f"(d[13]), "+f"(d[14]), "+f"(d[15]),
          "+f"(d[16]), "+f"(d[17]), "+f"(d[18]), "+f"(d[19]), "+f"(d[20]), "+f"(d[21]), "+f"(d[22]), "+f"(d[23]),
          "+f"(d[24]), "+f"(d[25]), "+f"(d[26]), "+f"(d[27]), "+f"(d[28]), "+f"(d[29]), "+f"(d[30]), "+f"(d[31]),
          "+f"(d[32]), "+f"(d[33]), "+f"(d[34]), "+f"(d[35]), "+f"(d[36]), "+f"(d[37]), "+f"(d[38]), "+f"(d[39]),
          "+f"(d[40]), "+f"(d[41]), "+f"(d[42]), "+f"(d[43]), "+f"(d[44]), "+f"(d[45]), "+f"(d[46]), "+f"(d[47]),
          "+f"(d[48]), "+f"(d[49]), "+f"(d[50]), "+f"(d[51]), "+f"(d[52]), "+f"(d[53]), "+f"(d[54]), "+f"(d[55]),
          "+f"(d[56]), "+f"(d[57]), "+f"(d[58]), "+f"(d[59]), "+f"(d[60]), "+f"(d[61]), "+f"(d[62]), "+f"(d[63]),
          "+f"(d[64]), "+f"(d[65]), "+f"(d[66]), "+f"(d[67]), "+f"(d[68]), "+f"(d[69]), "+f"(d[70]), "+f"(d[71]),
          "+f"(d[72]), "+f"(d[73]), "+f"(d[74]), "+f"(d[75]), "+f"(d[76]), "+f"(d[77]), "+f"(d[78]), "+f"(d[79]),
          "+f"(d[80]), "+f"(d[81]), "+f"(d[82]), "+f"(d[83]), "+f"(d[84]), "+f"(d[85]), "+f"(d[86]), "+f"(d[87]),
          "+f"(d[88]), "+f"(d[89]), "+f"(d[90]), "+f"(d[91]), "+f"(d[92]), "+f"(d[93]), "+f"(d[94]), "+f"(d[95])
        : "r"(a0), "r"(a1), "r"(a2), "r"(a3), "l"(db));
}

template <int HS>
__device__ __forceinline__ void attn_pair(const uint32_t* q, const uint32_t* k, const uint32_t* v, const uint32_t* kh, const uint32_t* vh,
                                          const float* fu, const float* fn, const float* rk, float bias0, float bias1, uint32_t mU, uint32_t zero, const float* ci, uint32_t* o) {
    float s0[2][4] = {}, s1[2][4] = {}, s2[2][4] = {};
#pragma unroll
    for (int n = 0; n < 4; n++) {
        const int hd = n & 1, a = 8 * hd + 2 * (n & 2);
        mma16816(s1[hd], q[a], q[a + 1], q[a + 2], q[a + 3], k[a], k[a + 2]);
        mma16816(s2[hd], q[a], q[a + 1], q[a + 2], q[a + 3], k[a + 1], k[a + 3]);
    }
#pragma unroll
    for (int n = 0; n < 4; n++) {
        const int hd = n & 1, a = 8 * hd + 2 * (n & 2);
        mma16816(s0[hd], q[a], q[a + 1], q[a + 2], q[a + 3], kh[HS * (a / 2)], kh[HS * (a / 2 + 1)]);
    }
    float e[2][4], m[2][2];
#pragma unroll
    for (int hd = 0; hd < 2; hd++) {
        e[hd][2] = fmaf(s1[hd][2], fu[2], s2[hd][2] * fn[2]); e[hd][3] = fmaf(s1[hd][3], fu[3], s2[hd][3] * fn[3]);
        e[hd][0] = fmaf(s0[hd][0], fu[0], fmaf(s1[hd][0], fn[0], bias0)); e[hd][1] = fmaf(s0[hd][1], fu[1], fmaf(s1[hd][1], fn[1], bias1));
        m[hd][1] = fmaxf(e[hd][2], e[hd][3]); m[hd][0] = fmaxf(e[hd][0], e[hd][1]);
    }
#pragma unroll
    for (int x = 1; x < 3; x++)
#pragma unroll
        for (int n = 0; n < 4; n++) m[n & 1][1 - (n >> 1)] = fmaxf(m[n & 1][1 - (n >> 1)], __shfl_xor_sync(0xffffffffu, m[n & 1][1 - (n >> 1)], x));
#pragma unroll
    for (int hd = 0; hd < 2; hd++) {
#pragma unroll
        for (int n = 0; n < 4; n++) e[hd][n] = ex2(e[hd][n] - m[hd][n >> 1]);
        float sum[4] = {};
        mma1688(sum, pack_bf16(e[hd][0], e[hd][1]), pack_bf16(e[hd][2], e[hd][3]), 0x3f803f80u);
        const float i0 = rcp(sum[0]), i1 = rcp(sum[2]);
        const uint32_t plo = pack_bf16(e[hd][0] * rk[0] * i0, e[hd][1] * rk[1] * i0), phi = pack_bf16(e[hd][2] * rk[2] * i1, e[hd][3] * rk[3] * i1);
        const uint32_t z0 = plo & zero, z1 = phi & zero;
        const uint32_t a0 = plo & ~mU, a1 = phi & mU, a3 = phi & ~mU, b0 = plo & mU;
#pragma unroll
        for (int jj = 0; jj < 4; jj++) {
            float c[4];
            asm volatile("mma.sync.aligned.m16n8k16.row.col.f32.bf16.bf16.f32 {%0,%1,%2,%3}, {%4,%5,%6,%7}, {%8,%9}, {%10,%11,%12,%13};"
                         : "=f"(c[0]), "=f"(c[1]), "=f"(c[2]), "=f"(c[3])
                         : "r"(a0), "r"(a1), "r"(z0), "r"(a3), "r"(v[8 * hd + 2 * jj]), "r"(v[8 * hd + 2 * jj + 1]), "f"(ci[0]), "f"(ci[1]), "f"(ci[2]), "f"(ci[3]));
            mma1688(c, b0, z1, vh[HS * (4 * hd + jj)]);
            o[8 * hd + 2 * jj] = pack_bf16(c[0], c[1]); o[8 * hd + 2 * jj + 1] = pack_bf16(c[2], c[3]);
        }
    }
}

__device__ __forceinline__ uint32_t norm_pair(uint32_t u, float m, float rinv) {
    const uint32_t d = pack_bf16(bf_lo(u) - m, bf_hi(u) - m);
    return max(pack_bf16(bf_lo(d) * rinv, bf_hi(d) * rinv), 1u);
}

__global__ void __launch_bounds__(512, 1)
fused_kernel(const __grid_constant__ CUtensorMap mx, const __grid_constant__ CUtensorMap mw, const __grid_constant__ CUtensorMap mwo,
             const __grid_constant__ CUtensorMap mout, const __grid_constant__ CUtensorMap mgu, const __grid_constant__ CUtensorMap mwd,
             const __grid_constant__ CUtensorMap mo,
             const __nv_bfloat16* __restrict__ x, const __nv_bfloat16* __restrict__ wr, Scratch* __restrict__ scr, int swap_gu, const Weights pf) {
    extern __shared__ __align__(1024) uint8_t smem[];
    const uint32_t sb = smem_u32(smem);
    const uint32_t bars = sb + OFF_BAR;
    const int tid = threadIdx.x, lane = tid & 31, warp = __shfl_sync(0xffffffffu, tid >> 5, 0);
    const uint32_t sd = (sb & 0x3FFFF) >> 4;
    const int hp = blockIdx.x & 1, cl = blockIdx.x >> 1;
    int pr = cl - 4 + (max(cl - 36, 0) * 37 >> 8);
    asm("{\n.reg .pred p;\nsetp.lt.s32 p, %1, 4;\nselp.s32 %0, %2, %0, p;\n}" : "+r"(pr) : "r"(cl), "r"(39 + 8 * cl));
    const int b = pr * 2 + hp, mt = pr >> 3, p = pr & 7, nt = 2 * p + hp, rh = p & 1, cb = (p & 6) + hp;
    const int par = mt >> 2, j0 = (mt & 3) * 256;
    int budget = BUDGET;

    TSC(tid == 0, 0);
    if (b < 128 && tid >= 32 && tid < 112) {
        const char* a = tid < 64 ? (const char*)x + (size_t)(16 * b + ((tid >> 1) & 15)) * 2048 + (tid & 1) * 128 : pf.wqkv + (size_t)b * 6144 + (tid - 64) * 128;
        asm volatile("prefetch.global.L2 [%0];" ::"l"(a));
    }
    auto load_w = [&](int k, int s) {
        const uint32_t full = bars + 8 * (B_WFULL + s);
        mbar_expect_tx(full, W_BYTES);
        tma_3d(sb + OFF_W + s * W_BYTES, &mw, full, nt * 64, k * 64, 0);
    };
    auto load_x = [&](int n) {
        const int w = n & 1, j = n < 4 ? (n >> 1) + 4 : (n >> 1) - 2;
        const uint32_t full = bars + 8 * (B_XFULL + w * 6 + 5 - j);
        mbar_expect_tx(full, BOX);
        tma_4d(sb + w * OFF_X1 + j * BOX, &mx, full, par * 1024 + (n >> 2) * 64, 0, (j0 + w * 128) >> 5, (~n >> 1) & 1);
    };
    if (warp < NBAR / 6 && elect_one()) {
        const uint32_t cnt = warp < B_WEMPTY / 6 ? 1 : warp < B_G1DONE / 6 ? 2 : warp < B_STAGED / 6 ? 4 : 8;
#pragma unroll
        for (int i = 0; i < 6; i++) mbar_init(bars + 48 * warp + 8 * i, cnt);
        asm volatile("fence.mbarrier_init.release.cluster;" ::: "memory");
        if (warp == 0 && b < 128) { load_x(0); load_w(0, 2); }
    }
    __syncthreads();

    if (b >= 128) {
        const int hc = b - 128, g = lane >> 2, t = lane & 3;
        const uint32_t ep = ld_rlx(&scr->epoch[0]) + 1;
        if (warp < 12) {
            const int n = warp / 3, part = warp - 3 * n;
            auto load = [&](int k) {
                const uint32_t full = bars + 8 * (2 * n + (k & 1));
                mbar_expect_tx(full, W_BYTES);
                tma_3d(sb + (2 * n + (k & 1)) * W_BYTES, &mw, full, (4 * hc + n) * 64, k * 64, 0);
            };
            if (part == 0 && elect_one()) { load(0); load(1); }
            __syncwarp();
            float c0[4] = {0.f, 0.f, 0.f, 0.f}, c1[4] = {0.f, 0.f, 0.f, 0.f};
            const uint32_t sel = g == 0 ? 0x3f80u : g == 1 ? 0x3f800000u : 0u;
            const uint32_t a = sb + 2 * n * W_BYTES + part * BOX + t * 256 + ((g ^ (2 * t)) << 4);
#pragma unroll 1
            for (int k = 0; k < 16; k++) {
                mbar_wait(bars + 8 * (2 * n + (k & 1)), (k >> 1) & 1, budget);
                uint4 v[8], u[8];
#pragma unroll
                for (int i = 0; i < 8; i++) { v[i] = lds4(a + (k & 1) * W_BYTES + i * 1024); u[i] = lds4(((a + 128) ^ 16) + (k & 1) * W_BYTES + i * 1024); }
#pragma unroll
                for (int i = 0; i < 8; i++) { mma16816(c0, v[i].x, v[i].y, u[i].x, u[i].y, sel, sel); mma16816(c1, v[i].z, v[i].w, u[i].z, u[i].w, sel, sel); }
                bar_sync(1 + n, 96);
                if (part == 0 && k < 14 && elect_one()) load(k + 2);
                __syncwarp();
            }
            if (t == 0) {
#pragma unroll
                for (int r = 0; r < 3; r++) {
                    const uint32_t q0 = (pack_bf16(c0[0], c0[1]) & ~1u) | (ep & 1), q1 = pack_bf16(c0[2], c0[3]), q2 = pack_bf16(c1[0], c1[1]), q3 = pack_bf16(c1[2], c1[3]);
                    st_rlx4(&scr->cs[4 * hc + n][r][part * 8 + g], q0, q1, q2, q3);
                    c0[0] -= bf_lo(q0); c0[1] -= bf_hi(q0); c0[2] -= bf_lo(q1); c0[3] -= bf_hi(q1);
                    c1[0] -= bf_lo(q2); c1[1] -= bf_hi(q2); c1[2] -= bf_lo(q3); c1[3] -= bf_hi(q3);
                }
            }
            TSC(tid == 0, 19);
        }
        if (warp < 8) TS_END();
        return;
    }
    asm volatile("barrier.cluster.arrive.relaxed.aligned;" ::: "memory");

    const int kc = b >> 4, c2 = b & 15;
    if (warp >= 12) {
        reg_dec<24>();
        if (warp == 12) {
            if (elect_one()) {
#pragma unroll 1
                for (int n = 1; n < 12; n++) {
                    load_x(n);
                    if (n == ROWS_AT) { mbar_expect_tx(bars + 8 * B_ROW, 4 * BOX); bulk_g2s(sb + OFF_FR, x + (size_t)b * 16 * 1024, 4 * BOX, bars + 8 * B_ROW); }
                    if (n == 3 || n == 7) load_w((n + 1) >> 2, n >> 2);
                }
                int s = 2; uint32_t ph = 0;
#pragma unroll 1
                for (int k = 3; k < 16; k++) {
                    mbar_wait(bars + 8 * (B_WEMPTY + s), ph, budget);
                    load_w(k, s);
                    if (++s == 3) s = 0;
                    if (s == 2) ph ^= 1;
                }
                s = 2;
#pragma unroll 1
                for (int i = 0; i < 16; i++) {
                    mbar_wait(bars + 8 * (i < 2 ? B_WEMPTY + i : i < 4 ? B_G1DONE : i < 6 ? B_F1DONE : B_WOEMPTY + s), i >= 12, budget);
                    if (i == 0) {
                        mbar_expect_tx(bars + 8 * B_XT, 4 * BOX);
#pragma unroll 1
                        for (int n = 0; n < 4; n++)
                            tma_4d(sb + (n >> 1) * OFF_X1 + (n & 1) * BOX, &mx, bars + 8 * B_XT, par * 1024 + cb * 128 + (n & 1) * 64, 0, (j0 + rh * 128) >> 5, 1 - (n >> 1));
                    }
                    const uint32_t full = bars + 8 * (B_WOFULL + s);
                    mbar_expect_tx(full, 2 * BOX);
                    tma_3d(sb + OFF_WO + s * 2 * BOX, &mwo, full, 0, ((2 * p + (i < 2 ? i ^ hp : i)) & 15) * 64, cb * 2);
                    TSC(TIMING % 10 == 4, 48 + i);
                    if (++s == 6) s = 0;
                }
            }
        } else {
            bar_sync(8, 224);
            const uint32_t ep = __shfl_sync(0xffffffffu, lds1(sb + OFF_EP), 0);
            if (warp == 13) {
                cluster_wait();
                if (elect_one()) {
                    int j = 4, q = 0, left = BUDGET; uint32_t ph = 0;
#pragma unroll 1
                    for (int n = 6; n < 32; n++) {
                        mbar_wait(bars + 8 * (B_XEMPTY + j), ph, left);
                        tma_4d_mc(sb + hp * OFF_X1 + j * BOX, &mx, bars + 8 * (B_XFULL + hp * 6 + 5 - j), par * 1024 + (n >> 1) * 64, 0, (j0 + hp * 128) >> 5, ~n & 1);
                        if (++j == 6) j = 0;
                        if (j == 4) ph ^= 1;
#pragma unroll 1
                        for (; q < (PF_RATE * (n - PF_START) >> 3) && q < 18 + PF_NW; q++) {
                            const int u = q - PF_NW;
                            if (u < 0) bulk_pf(pf.wqkv + (size_t)(1024 + 128 * u + b) * 6144, 6144);
                            else if (u < 16) bulk_pf((b < 64 ? pf.wg : pf.wu) + (size_t)(u * 64 + (b & 63)) * 7168, 7168);
                            else bulk_pf(pf.wo + (size_t)((u - 16) * 128 + b) * 8192, 8192);
                        }
                    }
                }
                __syncwarp();
                uint32_t* hs = &scr->halo[b - 16][lane * 4];
                int tries = BUDGET;
#pragma unroll 1
                for (int c = 0; c < 4; c += 2) {
                    uint4 v0 = make_uint4(0, 0, 0, 0), v1 = v0;
                    if (j0) {
#pragma unroll 1
                        do { v0 = ld_rlx4(hs + c * 128); v1 = ld_rlx4(hs + c * 128 + 128); } while ((v0.x == 0 || v1.x == 0) && --tries > 0);
                        st_rlx(hs + c * 128, 0); st_rlx(hs + c * 128 + 128, 0);
                    }
                    __syncwarp();
                    stsm4(sb + OFF_HIN + c * 512 + lane * 16, v0.x, v0.y, v0.z, v0.w);
                    stsm4(sb + OFF_HIN + c * 512 + 512 + lane * 16, v1.x, v1.y, v1.z, v1.w);
                }
                bar_arrive(11, 64);
                TSC(lane == 0, 31);
                const int src = ((mt * 2 + rh) * 2 + 1 - hp) * 1024;
                if (elect_one()) {
                    const uint32_t* fl = &scr->oflag[mt * 2 + 1 - hp][0];
                    const uint32_t inv = (ep & 1) - 1;
                    uint32_t ready = 0, ph = 0;
                    int s = 4;
#pragma unroll 1
                    for (int i = 2; i < 16; i++) {
                        const int kb = (2 * p + i) & 15;
#pragma unroll 1
                        while (!((ready >> kb) & 1) && --budget > 0) ready = ld_rlx(fl) ^ inv;
                        TSC(i == 2, 30);
                        mbar_wait(bars + 8 * (B_OEMPTY + s), ph, budget);
                        tma_2d_mc(sb + hp * OFF_X1 + s * BOX, &mo, bars + 8 * (B_OFULL + hp * 6 + s), 0, src + kb * 64);
                        TSC(TIMING % 10 == 4 && hp == 0, 32 + i);
                        if (++s == 6) s = 0;
                        if (s == 4) ph ^= 1;
                    }
                }
            } else if (warp == 14) {
                if (elect_one()) {
                    uint32_t s8 = 0, ph = 0;
                    int tries = BUDGET;
                    const uint32_t* act = scr->act[ep & 1];
                    auto counted = [&](int c, uint32_t n) {
#pragma unroll 1
                        while (ld_rlx(&scr->cnt[c][0]) != ep * n && --tries > 0) __nanosleep(POLL_NS);
                    };
                    auto weights = [&](const CUtensorMap* m, int c0, int c1, int c2_) {
                        mbar_wait(bars + 8 * B_FEMPTY + s8, ph, budget);
                        mbar_expect_tx(bars + 8 * B_FFULL + s8, F_BYTES);
                        tma_3d(sb + OFF_FS + s8 * (F_BYTES / 8), m, bars + 8 * B_FFULL + s8, c0, c1, c2_);
                    };
                    if (b < 112) {
                        counted(8, 32);
                        TS(26);
#pragma unroll 1
                        for (int q = 0; q < 16; q++) {
                            weights(&mgu, b * 32, q * 64, 0);
                            bulk_g2s(sb + OFF_FS + BOX + s8 * (F_BYTES / 8), act + 14336 + q * 256, 1024, bars + 8 * B_FFULL + s8);
                            TSC(TIMING % 10 == 5, 32 + q);
                            if (q >= 8) bulk_pf(pf.wd + (size_t)((q - 8) * 112 + b) * 8192, 8192);
                            s8 += 8;
                            if (s8 == 40) { s8 = 0; ph ^= 1; }
                        }
                    }
#pragma unroll 1
                    for (int q = -3; q < 7; q++) {
                        if (q == 0) { counted(kc, 28); TS(29); }
                        if ((unsigned)q >= 3) weights(&mwd, 0, kc * 448 + (q < 0 ? q + 3 : q) * 64, c2);
                        if (q >= 0) bulk_g2s(sb + OFF_FS + BOX + s8 * (F_BYTES / 8), act + (kc * 7 + q) * 256, 1024, bars + 8 * B_FFULL + s8);
                        TSC(TIMING % 10 == 5, 51 + q);
                        s8 += 8;
                        if (s8 == 24) { s8 = 0; if ((unsigned)q >= 3) ph ^= 1; }
                    }
                }
            } else {
#pragma unroll 1
                for (int i = lane * 16; i < CS_BYTES; i += 512) sts4(sb + OFF_CS + i, 0, 0, 0, 0);
                mbar_wait(bars + 8 * B_ROW, 0, budget);
                uint8_t* oz = scr->o + ((size_t)mt * 64 + nt) * BOX + lane * 16;
#pragma unroll 1
                for (int i = 0; i < ZF_N; i++) { st_rlx4(oz + (i >> 4) * 16 * BOX + (i & 15) * 512, 0, 0, 0, 0); if ((i & 3) == 3) __nanosleep(ZF_NS); }
                __syncwarp();
                fence_gpu();
                mbar_wait(bars + 8 * B_RDONE, 0, budget);
                int tries = BUDGET;
#pragma unroll 1
                for (int i = lane; i < 88; i += 32) {
                    const uint2* rp = &scr->row[2 * (j0 - 8 + i) + par];
                    uint2 v0, v1, v2;
#pragma unroll 1
                    do { v0 = ld_rlx2(rp + (j0 + i < 8 ? 16 : 0)); v1 = ld_rlx2(rp + 176); v2 = ld_rlx2(rp + 352); } while ((((v0.y ^ ep) | (v1.y ^ ep) | (v2.y ^ ep)) & 31) && --tries > 0);
                    sts2(sb + OFF_STAT + i * 8, (v0.x << 16) ^ 0x80000000u, __float_as_uint(rcp(bf_hi(v0.x))));
                    sts2(sb + OFF_STAT + i * 8 + 704, (v1.x << 16) ^ 0x80000000u, __float_as_uint(rcp(bf_hi(v1.x))));
                    sts2(sb + OFF_STAT + i * 8 + 1408, (v2.x << 16) ^ 0x80000000u, __float_as_uint(rcp(bf_hi(v2.x))));
                }
                __syncwarp();
                {
                    const int row = 2047 - ((poll_all(&scr->sel[lane & 7], 31u, ep & 31, budget) >> 5) & 2047), jj = (row >> 1) - j0 - rh * 128;
                    uint32_t boxes = __reduce_or_sync(0xffffffffu, (row & 1) == par && (unsigned)jj < 128 ? 1u << (jj >> 4) : 0u);
                    sts1(sb + OFF_SEL, boxes);
#pragma unroll 1
                    for (int i = 0; boxes; i += 2) {
                        if (boxes & 1) st_rlx4(pf.out + (size_t)(2 * (j0 + rh * 128 + i + (lane >> 4)) + par) * 2048 + cb * 256 + (lane & 15) * 16, 0, 0, 0, 0);
                        else i += 14;
                        if ((i & 14) == 14) boxes >>= 1;
                    }
                }
                if (lane < 24) {
                    uint4 v[3];
#pragma unroll 1
                    while (v[0] = ld_rlx4(&scr->cs[nt][0][lane]), v[1] = ld_rlx4(&scr->cs[nt][1][lane]), v[2] = ld_rlx4(&scr->cs[nt][2][lane]),
                           (((v[0].x ^ ep) | (v[1].x ^ ep) | (v[2].x ^ ep)) & 1) && --tries > 0) __nanosleep(100);
#pragma unroll
                    for (int r = 0; r < 3; r++) sts4(sb + OFF_CS + 64 + lane * 128 + r * 16, v[r].x, v[r].y, v[r].z, v[r].w);
                }
                fence_async_smem();
                __syncwarp();
                if (elect_one()) {
                    mbar_arrive(bars + 8 * B_AUX);
                    TS(21);
                    if (lds1(sb + OFF_SEL)) { fence_gpu(); asm volatile("fence.proxy.async.global;" ::: "memory"); }
                    mbar_arrive(bars + 8 * B_ZERO);
                    TS(25);
                    mbar_expect_tx(bars + 8 * (B_OFULL + 3), BOX); mbar_expect_tx(bars + 8 * (B_OFULL + 9), BOX);
#pragma unroll 1
                    for (int v = 0; v < 2; v++) {
                        const uint32_t ring = sb + v * OFF_X1 + 2 * BOX, fb = bars + 8 * (B_OFULL + v * 6 + 2);
                        mbar_wait(bars + 8 * (B_STAGED + v), 0, budget);
                        asm volatile("red.relaxed.gpu.global.xor.b32 [%0], %1;" ::"l"(&scr->oflag[mt * 2 + 1 - v][0]), "r"(1u << nt) : "memory");
                        TS(13 + 2 * v);
                        mbar_arrive(fb);
                        mbar_wait(bars + 8 * B_G1DONE, 0, budget);
                        bulk_s2c(mapa(ring + BOX, hp ^ 1), ring, BOX, mapa(fb + 8, hp ^ 1));
                        if (v == 0) mbar_wait(bars + 8 * B_FREED, 0, budget);
#pragma unroll
                        for (int n = 0; n < 4; n++) {
                            mbar_expect_tx(bars + 8 * (B_OFULL + (n >> 1) * 6 + 4 + (n & 1)) - v * 32, BOX);
                            mbar_arrive_at(mapa(bars + 8 * B_OEMPTY, n >> 1) + (4 + (n & 1)) * 8 - v * 32);
                        }
                    }
                }
            }
        }
    } else if (warp >= 8) {
        reg_dec<40>();
        const int wq = warp - 8, ta = tid - 256;
        const uint32_t rbuf = sb + OFF_FR + wq * BOX, rbar = bars + 8 * B_ROW;
        const uint4 wv = ldg_nc(wr + ta * 8);
        if (ta == 0) sts1(sb + OFF_EP, ld_rlx(&scr->epoch[0]) + 1);
        sts4(sb + OFF_STAT + ta * 16, wv.x, wv.y, wv.z, wv.w);
        bar_sync(8, 224);
        const uint32_t ep = __shfl_sync(0xffffffffu, lds1(sb + OFF_EP), 0);
        {
            const int s = b * 16 + wq * 4 + (lane >> 3);
            if ((lane & 7) == 0) st_rlx2(&scr->row[s], 0, ep - 1);
            float sw = 0.f;
#pragma unroll 1
            for (int i = 0; i < 16; i++) { const uint32_t q = lds1(sb + OFF_STAT + i * 128 + lane * 4); sw += bf_lo(q) + bf_hi(q); }
#pragma unroll 1
            for (int o = 16; o > 0; o >>= 1) sw += __shfl_xor_sync(0xffffffffu, sw, o);
            float s1 = 0.f, s2 = 0.f, sr = 0.f;
            const uint32_t xa = rbuf + (lane >> 3) * 2048 + (lane & 7) * 16, wa = sb + OFF_STAT + (lane & 7) * 16;
            mbar_wait(rbar, 0, budget);
            TSC(ta == 0, 17);
            {
                float s1b = 0.f, s2b = 0.f, srb = 0.f;
                const uint32_t xb = rbuf + (lane >> 4) * 4096 + (lane & 15) * 16, wb = sb + OFF_STAT + (lane & 15) * 16;
                uint4 w4 = lds4(wb), u = lds4(xb), v = lds4(xb + 2048);
#pragma unroll 1
                for (int i = 1; i <= 8; i++) {
                    const uint32_t o = (i * 256) & 2047;
                    float wf[8];
#pragma unroll
                    for (int c = 0; c < 4; c++) { wf[2 * c] = bf_lo((&w4.x)[c]); wf[2 * c + 1] = bf_hi((&w4.x)[c]); }
                    w4 = lds4(wb + o);
#pragma unroll
                    for (int c = 0; c < 4; c++) {
                        const float a0 = bf_lo((&u.x)[c]), a1 = bf_hi((&u.x)[c]);
                        s1 += a0; s2 = fmaf(a0, a0, s2); sr = fmaf(a0, wf[2 * c], sr);
                        s1 += a1; s2 = fmaf(a1, a1, s2); sr = fmaf(a1, wf[2 * c + 1], sr);
                    }
                    u = lds4(xb + o);
#pragma unroll
                    for (int c = 0; c < 4; c++) {
                        const float a0 = bf_lo((&v.x)[c]), a1 = bf_hi((&v.x)[c]);
                        s1b += a0; s2b = fmaf(a0, a0, s2b); srb = fmaf(a0, wf[2 * c], srb);
                        s1b += a1; s2b = fmaf(a1, a1, s2b); srb = fmaf(a1, wf[2 * c + 1], srb);
                    }
                    v = lds4(xb + 2048 + o);
                }
                const bool up = lane & 8;
                s1 = (up ? s1b : s1) + __shfl_xor_sync(0xffffffffu, up ? s1 : s1b, 8);
                s2 = (up ? s2b : s2) + __shfl_xor_sync(0xffffffffu, up ? s2 : s2b, 8);
                sr = (up ? srb : sr) + __shfl_xor_sync(0xffffffffu, up ? sr : srb, 8);
            }
#pragma unroll
            for (int o = 1; o < 8; o <<= 1) {
                s1 += __shfl_xor_sync(0xffffffffu, s1, o); s2 += __shfl_xor_sync(0xffffffffu, s2, o); sr += __shfl_xor_sync(0xffffffffu, sr, o);
            }
            const float mean = s1 * (1.f / 1024.f), mb = bf16r(mean);
            float var = fmaf(-mean, mean, s2 * (1.f / 1024.f));
            sr = fmaf(-mb, sw, sr);
            if (__builtin_expect(__any_sync(0xffffffffu, mean * mean > 256.f * var), 0)) {
                float a2 = 0.f, ar = 0.f;
#pragma unroll 1
                for (int i = 0; i < 64; i++) {
                    const uint32_t o = (i >> 2) * 128 + (i & 3) * 4, q1 = lds1(xa + o), q2 = lds1(wa + o);
                    a2 = fmaf(bf_lo(q1) - mean, bf_lo(q1) - mean, fmaf(bf_hi(q1) - mean, bf_hi(q1) - mean, a2));
                    ar = fmaf(bf_lo(q1) - mb, bf_lo(q2), fmaf(bf_hi(q1) - mb, bf_hi(q2), ar));
                }
#pragma unroll 1
                for (int o = 1; o < 8; o <<= 1) { a2 += __shfl_xor_sync(0xffffffffu, a2, o); ar += __shfl_xor_sync(0xffffffffu, ar, o); }
                var = a2 * (1.f / 1024.f); sr = ar;
            }
            float den;
            asm("sqrt.approx.f32 %0, %1;" : "=f"(den) : "f"(bf16r(bf16r(var) + 1e-5f)));
            const uint32_t st = pack_bf16(mb, den);
            const uint32_t rb = pack_bf16(0.f, sr * rcp(bf_hi(st)) + 0.f);
            uint32_t ord = (int)rb < 0 ? ~rb & 0xffff0000u : rb | 0x80000000u;
            if ((rb & 0x7fffffffu) > 0x7f800000u) ord = 0;
            if ((lane & 7) == 0) st_rlx2(&scr->row[s], st, ord | ((2047 - s) << 5) | (ep & 31));
            __syncwarp();
            if (lane < 7) mbar_arrive(bars + 8 * (lane < 5 ? B_FEMPTY + lane : B_RDONE));
        }
        TSC(ta == 0, 18);
        if ((b >> 3) == 14) {
            const uint32_t gm = sb + OFF_E, cnt = gm + 64, res = gm + 80, list = gm + 128;
            uint32_t kv[16];
            int tries = BUDGET;
#pragma unroll 1
            do {
                uint32_t bad = 0;
#pragma unroll
                for (int n = 0; n < 16; n++) kv[n] = ld_rlx(&scr->row[n * 128 + ta].y);
#pragma unroll
                for (int n = 0; n < 16; n++) bad |= kv[n] ^ ep;
                if ((bad & 31) == 0) break;
            } while (--tries > 0);
            __syncwarp();
            TSC(ta == 0, 26);
            uint32_t m = 0;
#pragma unroll
            for (int n = 0; n < 16; n++) m = max(m, kv[n]);
            uint32_t gmax = m;
#pragma unroll
            for (int o = 1; o < 8; o <<= 1) gmax = max(gmax, __shfl_xor_sync(0xffffffffu, gmax, o));
            sts1(gm + (ta >> 3) * 4, gmax);
            sts1(cnt, 0);
            bar_sync(12, 128);
            const uint32_t c = lds1(gm + (lane & 15) * 4);
            int rank = 0;
#pragma unroll
            for (int i = 0; i < 2; i++) { const uint4 q = lds4(gm + (lane >> 4) * 32 + i * 16); rank += (q.x > c) + (q.y > c) + (q.z > c) + (q.w > c); }
            rank += __shfl_xor_sync(0xffffffffu, rank, 16);
            const uint32_t thr = redux_max(rank == 7 ? c : 0u);
#pragma unroll 1
            while (m >= thr) {
                uint32_t at, m2 = 0;
                asm volatile("atom.shared.add.u32 %0, [%1], 1;" : "=r"(at) : "r"(cnt) : "memory");
#pragma unroll
                for (int n = 0; n < 16; n++) m2 = max(m2, kv[n] < m ? kv[n] : 0u);
                sts1(list + at * 4, m);
                if (m2 == 0) break;
                m = m2;
            }
            bar_sync(12, 128);
            const int nc = lds1(cnt);
#pragma unroll 1
            for (int i = ta >> 3; i < ((nc + 3) & ~3); i += 16) {
                const uint32_t ki = lds1(list + i * 4);
                int r = 0;
#pragma unroll 1
                for (int n = lane & 7; n < nc; n += 8) r += lds1(list + n * 4) > ki;
                __syncwarp();
#pragma unroll
                for (int o = 1; o < 8; o <<= 1) r += __shfl_xor_sync(0xffffffffu, r, o);
                if (r == (b & 7) && i < nc) sts1(res, ki);
            }
            bar_sync(12, 128);
            const uint32_t k0 = lds1(res);
            const int r0 = 2047 - ((k0 >> 5) & 2047);
            TSC(ta == 0, 22);
            if (ta == 0) st_rlx(&scr->sel[b & 7], k0);
            const uint4 v0 = ldg_nc(x + (size_t)r0 * 1024 + ta * 8);
            const uint32_t s0 = ld_rlx(&scr->row[r0]);
            const float m0 = bf_lo(s0), i0 = rcp(bf_hi(s0));
            const int ao = 14336 + (ta >> 3) * 256 + (b & 7) * 32 + ((ta ^ b) & 7) * 4;
            st_rlx4(scr->act[ep & 1] + ao, norm_pair(v0.x, m0, i0), norm_pair(v0.y, m0, i0), norm_pair(v0.z, m0, i0), norm_pair(v0.w, m0, i0));
            __syncwarp();
            if (lane == 0) red_add(&scr->cnt[8][tries >> 30]);
            st_rlx4(scr->act[~ep & 1] + ao, 0, 0, 0, 0);
        }
        uint32_t s8 = 0, fph = 0, key = 0;
        const uint32_t chk = __shfl_sync(0xffffffffu, sb + OFF_FS + BOX + lane * 32 + (lane & 28), lane);
        int left = BUDGET;
#pragma unroll 1
        for (int ph = 0; ph < 2; ph++) {
            if (ph || b < 112) {
                float acc[4] = {0.f, 0.f, 0.f, 0.f};
                const uint32_t alo = sd + (ph ? dlo(OFF_FS, 8192) : dlo(OFF_FS, 4096)), ahi = ph ? dhi(1024, 1) : dhi(512, 2), astep = ph ? 128 : 64;
                const uint32_t bhi = ph ? dhi(128, 0) : dhi(1024, 1), bstep = ph ? 16 : 2, wrap = ph ? 24 : 40;
                uint32_t prev = 0, prev2 = 0;
#pragma unroll 1
                for (int q = ph ? 7 : 16; q > 0; q--) {
                    const uint32_t da = alo + s8 * (F_BYTES >> 7), db = sd + dlo(OFF_FS + BOX, 128) + s8 * (F_BYTES >> 7);
                    if (q == (ph ? 7 : F1_HOLD)) {
                        wg_wait<0>();
                        if (prev) mbar_arrive(prev);
                        prev = 0;
                        mbar_wait(bars + 8 * (ph ? FFN2_GATE : F1_GATE), 0, left);
                    }
                    mbar_wait_hot(bars + 8 * B_FFULL + s8, fph, left);
                    if (__builtin_expect(__any_sync(0xffffffffu, lds1(chk + s8 * (F_BYTES / 8)) == 0), 0)) {
                        int tries = BUDGET;
#pragma unroll 1
                        for (int n = lane * 4 + (left >> 30); n < 256; n += 128) {
                            uint4 v;
#pragma unroll 1
                            do { v = ld_rlx4(scr->act[ep & 1] + ((ph ? kc * 7 + 7 : 72) - q) * 256 + n); } while (v.x == 0 && --tries > 0);
                            __syncwarp();
                            sts4(sb + OFF_FS + BOX + s8 * (F_BYTES / 8) + n * 4, v.x, v.y, v.z, v.w);
                        }
                        NRETRY();
                        fence_async_smem();
                        __syncwarp();
                    }
                    TSC(TIMING % 10 == 3 && ta == 0, 32 + (ph ? 23 : 16) - q);
                    wg_fence();
#pragma unroll
                    for (int j = 0; j < 4; j++) wgmma_n8<1, 0>(acc, mkdesc(da + j * astep, ahi), mkdesc(db + j * bstep, bhi), 1);
                    wg_commit();
                    uint32_t done = F1_DEPTH == 2 ? prev2 : prev;
                    prev2 = prev;
                    if (lane == 0) prev = bars + 8 * B_FEMPTY + s8;
                    wg_wait<F1_DEPTH>();
                    if (ph) { wg_wait<F2_DEPTH>(); done = F2_DEPTH ? prev2 : prev; }
                    if (done) mbar_arrive(done);
                    s8 += 8;
                    if (s8 == wrap) { s8 = 0; fph ^= 1; }
                }
                wg_wait<0>();
                const int ln = lane + (left >> 30);
                if (ph == 0) {
                    if (prev) mbar_arrive(prev);
                    const bool second = (wq >= 2) != (swap_gu != 0);
                    const uint32_t xa = sb + OFF_GU + ((wq & 1) * 32 + ln) * 16;
                    if (second) sts4(xa, __float_as_uint(acc[0]), __float_as_uint(acc[1]), __float_as_uint(acc[2]), __float_as_uint(acc[3]));
                    bar_sync(12, 128);
                    if (!second) {
                        const float4 up = lds4f(xa);
                        float hv[4];
#pragma unroll
                        for (int c = 0; c < 4; c++) { const float ga = bf16r(acc[c]); hv[c] = bf16r(ga * sigmoidf(ga)) * bf16r((&up.x)[c]); }
                        const int ao = (b * 4 + (wq & 1) * 2) * 32 + ln;
                        st_rlx(scr->act[ep & 1] + ao, max(movm(pack_bf16(hv[0], hv[1])), 1u)); st_rlx(scr->act[ep & 1] + 32 + ao, max(movm(pack_bf16(hv[2], hv[3])), 1u));
                        __syncwarp();
                        if (ln == 0) red_add(&scr->cnt[b / 14][0]);
                        st_rlx(scr->act[~ep & 1] + ao, 0); st_rlx(scr->act[~ep & 1] + 32 + ao, 0);
                    }
                } else {
#pragma unroll
                    for (int c = 0; c < 4; c++) st_rlx(&scr->ypart[kc][2 * (ln & 3) + (c & 1)][c2 * 64 + wq * 16 + (c >> 1) * 8 + (ln >> 2)], (__float_as_uint(acc[c]) & ~1u) | (ep & 1));
                }
                TSC(ta == 0, 22 + ph);
            }
            const int ln = lane + (left >> 30);
            if (ph == 0) {
                if ((ta & 126) == 64) mbar_arrive(bars + 8 * B_F1DONE);
                key = poll_all(&scr->sel[ln & 7], 31u, ep & 31, left);
            }
        }
        {
            const int row = 2047 - ((key >> 5) & 2047);
            const float sig = bf16r(sigmoidf(__uint_as_float(((int)key < 0 ? key & 0x7fffffffu : ~key) & 0xffff0000u)));
            uint32_t own = __ballot_sync(0xffffffffu, (row & 1) == par && (row >> 8) == (mt & 3) * 2 + rh) & 255;
            if (wq & 2) own &= own - 1;
            mbar_wait(bars + 8 * B_ZERO, 0, left);
#pragma unroll 1
            for (; own; own &= own - 1, own &= own - 1) {
                const int j = __ffs(own) - 1, col = cb * 128 + (wq & 1) * 64 + (lane & 15) * 4;
                const uint32_t* src = &scr->ypart[lane >> 4][j][col];
                uint4 v[4]; int tries = BUDGET;
#pragma unroll 1
                do {
#pragma unroll
                    for (int m = 0; m < 4; m++) v[m] = ld_rlx4(src + m * 2 * 8192);
                } while ((((v[0].x ^ ep) | (v[1].x ^ ep) | (v[2].x ^ ep) | (v[3].x ^ ep)) & 1) && --tries > 0);
                __syncwarp();
                float a[4];
                const float sj = __shfl_sync(0xffffffffu, sig, j);
                const int rj = __shfl_sync(0xffffffffu, row, j);
#pragma unroll
                for (int c = 0; c < 4; c++) {
                    a[c] = (__uint_as_float((&v[0].x)[c]) + __uint_as_float((&v[1].x)[c])) + (__uint_as_float((&v[2].x)[c]) + __uint_as_float((&v[3].x)[c]));
                    a[c] = bf16r(a[c] + __shfl_xor_sync(0xffffffffu, a[c], 16)) * sj;
                }
                if (lane < 16) asm volatile("red.relaxed.gpu.global.add.noftz.v2.bf16x2 [%0], {%1, %2};" ::"l"(pf.out + (size_t)rj * 2048 + col * 2), "r"(pack_bf16(a[0], a[1])), "r"(pack_bf16(a[2], a[3])) : "memory");
            }
        }
        TSC(ta == 0, 24);
    } else {
        reg_inc<224>();
        const int w = warp >> 2, wi = warp & 3, g = lane >> 2, t = lane & 3;
        const bool elect = (tid & 127) == 0;
        const uint32_t mad = (lane & 15) * 128 + (((lane >> 4) ^ (lane & 7)) << 4);
        float acc[64];
        const uint32_t ring = sb + w * OFF_X1, ofull = bars + 8 * (B_OFULL + w * 6), oempty = mapa(bars + 8 * B_OEMPTY, w);
        const int r0 = rh * 128 + wi * 32 + (1 - w) * 16 + g;
        {
            float acc0[96], acc1[96];
            const uint32_t sta = sb + OFF_STAT + (8 + w * 128 + wi * 32) * 8;
            {
                const uint32_t xfull = bars + 8 * (B_XFULL + w * 6 + 5), xempty = mapa(bars + 8 * B_XEMPTY, w), dx0 = sd + dlo(w * OFF_X1, 16);
                uint32_t s8 = 16, ps8 = 0, ph = 0;
                cluster_wait();
#pragma unroll 1
                for (int k = 0; k < 16; k++) {
                    const uint32_t dx = dx0 + s8 * (2 * BOX >> 7), dw = sd + dlo(OFF_W, BOX) + s8 * (W_BYTES >> 7);
                    mbar_wait(bars + 8 * B_WFULL + s8, ph, budget);
                    mbar_wait(xfull - 2 * s8, ph, budget);
                    TSC(elect && k == 0, 1 + 8 * w);
                    TSC(TIMING % 10 == 1 && tid == 0, 32 + k);
                    wg_wait<0>();
                    wg_fence();
#pragma unroll
                    for (int kk = 0; kk < 4; kk++) wgmma_n192<0, 1>(acc1, mkdesc(dx + kk * 2, dhi(1024, 1)), mkdesc(dw + kk * 128, dhi(1024, 1)), kk ? 1 : k);
                    wg_commit();
                    if (elect && k > 0) {
                        mbar_arrive(bars + 8 * B_WEMPTY + ps8);
                        if (k <= 13) { mbar_expect_tx(xfull - 2 * ps8 - 8, BOX); mbar_arrive_at(xempty + 2 * ps8 + 8); }
                    }
                    if (k == 15) {
                        mbar_wait(bars + 8 * B_AUX, 0, budget);
                        const uint32_t zero = budget >> 30, pm = t & 1 ? 0x4432 : 0x3232, ra = sta + ((t >> 1) * 16 + g) * 8;
                        const uint32_t a0 = __byte_perm(lds1(ra), 0, pm), a1 = __byte_perm(lds1(ra + 64), 0, pm), a2 = a0 & zero, a3 = a1 & zero;
                        wg_fence();
                        wgmma_rs_n192(acc1, a0, a1, a2, a3, mkdesc(sd + dlo(OFF_CS, 0), dhi(128, 0)));
                        wgmma_rs_n192(acc0, a0, a1, a2, a3, mkdesc(sd + dlo(OFF_CS + 64, 0), dhi(128, 0)));
                        wg_commit();
                    }
                    mbar_wait(xfull - 2 * s8 - 8, ph, budget);
                    wg_wait<0>();
                    wg_fence();
#pragma unroll
                    for (int kk = 0; kk < 4; kk++) wgmma_n192<0, 1>(acc0, mkdesc(dx + 512 + kk * 2, dhi(1024, 1)), mkdesc(dw + kk * 128, dhi(1024, 1)), kk ? 1 : k);
                    wg_commit();
                    if (elect && k <= 12) { mbar_expect_tx(xfull - 2 * s8, BOX); mbar_arrive_at(xempty + 2 * s8); }
                    ps8 = s8;
                    s8 = s8 == 16 ? 0 : s8 + 8;
                    if (s8 == 16) ph ^= 1;
                }
            }
            const uint32_t zero = budget >> 30;
            const bool u0 = 2 * t > g, u1 = 2 * t + 1 > g;
            uint32_t mU = (u0 ? 0xffffu : 0u) | (u1 ? 0xffff0000u : 0u);
            uint32_t ka0 = sta + (2 * t - (u0 ? 8 : 0)) * 8 + 4, ka1 = sta + (2 * t + 1 - (u1 ? 8 : 0)) * 8 + 4;
            float rk[2][4], fu[2][4], fn[2][4];
            auto factors = [&](int h) {
#pragma unroll
                for (int n = 0; n < 4; n += 2) {
                    const float rq = lds1f(sta + (16 * h + 4 * n + g) * 8 + 4) * (0.17677669529663687f * 1.4426950408889634f);
                    rk[h][n] = lds1f(ka0 + h * 128 + n * 32); rk[h][n + 1] = lds1f(ka1 + h * 128 + n * 32);
                    const float f0 = rq * rk[h][n], f1 = rq * rk[h][n + 1];
                    fu[h][n] = u0 ? f0 : 0.f; fn[h][n] = f0 - fu[h][n]; fu[h][n + 1] = u1 ? f1 : 0.f; fn[h][n + 1] = f1 - fu[h][n + 1];
                }
#pragma unroll
                for (int n = 0; n < 4; n++) asm volatile("" : "+f"(fu[h][n]), "+f"(fn[h][n]));
            };
            uint8_t* og = scr->o + ((size_t)(mt * 4 + w * 2) * 16 + nt) * BOX + wi * 256 + lane * 4;
            TSC(elect, 19 + w);
            uint32_t pk0[48], pk1[48], o[16] = {};
#pragma unroll
            for (int j = 0; j < 48; j++) if (j < 16 || (j & 1)) pk1[j] = pack_here(acc1[2 * j], acc1[2 * j + 1]);
            if (warp < 7) {
#pragma unroll
                for (int c = 0; c < 4; c++) stsm4(ring + 4 * BOX + wi * 2048 + c * 512 + lane * 16, pk1[17 + 8 * c], pk1[19 + 8 * c], pk1[21 + 8 * c], pk1[23 + 8 * c]);
                bar_arrive(1 + warp, 64);
            } else if (j0 != 768) {
#pragma unroll
                for (int c = 0; c < 4; c++) {
                    pk1[17 + 8 * c] = max(pk1[17 + 8 * c], 1u);
                    st_rlx4(&scr->halo[b][c * 128 + lane * 4], pk1[17 + 8 * c], pk1[19 + 8 * c], pk1[21 + 8 * c], pk1[23 + 8 * c]);
                }
            }
            TSC(tid == 224, 28);
#pragma unroll
            for (int j = 16; j < 48; j += 2) pk1[j] = pack_here(acc1[2 * j], acc1[2 * j + 1]);
            factors(1);
            uint32_t od = sb + 2 * BOX + wi * 256 + (lane >> 4) * 1024 + (lane & 15) * 16, g1peer = mapa(bars + 8 * B_G1DONE, hp ^ 1);
            uint32_t ha = sb + (warp == 0 ? OFF_HIN : warp <= 4 ? 4 * BOX - 2048 : OFF_X1 + 4 * BOX - 5 * 2048) + warp * 2048 + lane * 16;
            const bool first = warp == 0 && j0 == 0;
            float bias0 = first && u0 ? -INFINITY : 0.f, bias1 = first && u1 ? -INFINITY : 0.f;
            asm volatile("" : "+l"(og), "+r"(mU), "+r"(od), "+r"(ha), "+f"(bias0), "+f"(bias1));
            mbar_wait(bars + 8 * B_XT, 0, budget);
            mbar_wait(bars + 8 * (B_WEMPTY + 1), 0, budget);
            TSC(elect, 12 + 2 * w);
            wg_wait<0>();
            if (elect) { mbar_arrive(bars + 8 * B_G1DONE); mbar_arrive_at(g1peer); }
            TSC(elect, 2 + 8 * w);
            float ci[4];
#pragma unroll
            for (int n = 0; n < 4; n++) ci[n] = __uint_as_float((0x03800000u + n) | (budget >> 30));
            auto hand_over = [&](int v) {
                asm volatile("{\n.reg .pred p;\nsetp.ne.b32 p, %17, 0;\n"
                             "@p stmatrix.sync.aligned.m8n8.x4.shared.b16 [%16], {%0,%1,%2,%3};\n@p stmatrix.sync.aligned.m8n8.x4.shared.b16 [%16 + 2048], {%4,%5,%6,%7};\n"
                             "@p stmatrix.sync.aligned.m8n8.x4.shared.b16 [%16 + 4096], {%8,%9,%10,%11};\n@p stmatrix.sync.aligned.m8n8.x4.shared.b16 [%16 + 6144], {%12,%13,%14,%15};\n"
                             FENCE_PRED "fence.proxy.async.shared::cta;\n}"
                             ::"r"(o[0]), "r"(o[1]), "r"(o[2]), "r"(o[3]), "r"(o[4]), "r"(o[5]), "r"(o[6]), "r"(o[7]), "r"(o[8]), "r"(o[9]), "r"(o[10]), "r"(o[11]),
                               "r"(o[12]), "r"(o[13]), "r"(o[14]), "r"(o[15]), "r"(od + v * OFF_X1), "r"((int)(w == rh)) : "memory");
                TSC(tid == 0, v ? 27 : 5);
#pragma unroll
                for (int i = 0; i < 16; i++) asm volatile("st.global.u32 [%0], %1;" ::"l"(og + (1 - v) * 16 * BOX + (i >> 1) * 1024 + (i & 1) * 128), "r"(o[i]) : "memory");
                __syncwarp();
                if (lane == 0) mbar_arrive(bars + 8 * (B_STAGED + v));
            };
#pragma unroll
            for (int j = 32; j < 48; j++) pk1[j] = movm(pk1[j]);
#pragma unroll
            for (int j = EARLY_PK; j < 48; j++) if (j >= 32 || (j & 1) || EARLY_PK < 17) pk0[j] = pack_here(acc0[2 * j], acc0[2 * j + 1]);
#pragma unroll
            for (int j = 32; j < 48; j++) pk0[j] = movm(pk0[j]);
            factors(0);
            attn_pair<2>(pk1, pk1 + 16, pk1 + 32, pk0 + 17, pk0 + 33, fu[1], fn[1], rk[1], 0.f, 0.f, mU, zero, ci, o);
            hand_over(0);
            TSC(elect, 3 + 8 * w);
#pragma unroll
            for (int j = 0; j < 32; j++) if (j < EARLY_PK || (!(j & 1) && EARLY_PK == 17)) pk0[j] = pack_here(acc0[2 * j], acc0[2 * j + 1]);
            bar_sync(warp ? warp : 11, 64);
            uint32_t hl[16];
            ldsm4(hl, ha); ldsm4(hl + 4, ha + 512); ldsm4t(hl + 8, ha + 1024); ldsm4t(hl + 12, ha + 1536);
            __syncwarp();
            if (lane == 0) mbar_arrive(bars + 8 * B_FREED);
            attn_pair<1>(pk0, pk0 + 16, pk0 + 32, hl, hl + 8, fu[0], fn[0], rk[0], bias0, bias1, mU, zero, ci, o);
            const float2 s0 = lds2f(sb + OFF_STAT + (8 + r0) * 8), s1 = lds2f(sb + OFF_STAT + (16 + r0) * 8);
            const float m0 = s0.x * s0.y, f0 = 1.f + s0.y, m1 = s1.x * s1.y, f1 = 1.f + s1.y;
            uint32_t xt[32];
#pragma unroll
            for (int j = 0; j < 8; j++) ldsm4(xt + 4 * j, ((ring + wi * 2048 + mad) ^ ((j & 3) * 32)) + (j >> 2) * BOX);
            hand_over(1);
#pragma unroll
            for (int j = 0; j < 32; j++) {
                acc[2 * j] = fmaf(bf_lo(xt[j]), j & 1 ? f1 : f0, j & 1 ? m1 : m0); acc[2 * j + 1] = fmaf(bf_hi(xt[j]), j & 1 ? f1 : f0, j & 1 ? m1 : m0);
            }
        }
        TSC(tid == 0, 4);
        {
            const uint32_t da0 = sd + dlo(w * OFF_X1, 1024), db0 = sd + dlo(OFF_WO, BOX);
            const uint32_t chk = ring + wi * 256 + (lane >> 3) * 1032 + (lane & 7) * 32 + (lane & 4);
            uint32_t s8 = 16, ps8 = 0, ph = 0;
            mbar_wait(ofull + s8, 0, budget);
            mbar_wait(bars + 8 * B_WOFULL + s8, 0, budget);
            TSC(TIMING % 10 == 2 && elect, 32 + w * 16);
            const uint32_t ahi = dhi(128, 0) | (budget >> 30), bhi = dhi(1024, 1) | (budget >> 30);
            const int last = w ? HOLD : 16;
            uint32_t rel = elect ? 0x7fe : 0;
#pragma unroll 1
            for (int i = 1;;) {
                const uint32_t da = da0 + s8 * (BOX >> 7), db = db0 + s8 * (BOX >> 6);
                wg_fence();
#pragma unroll
                for (int kk = 0; kk < 4; kk++) {
                    wgmma_n128<0, 1>(acc, mkdesc(da + kk * 128, ahi), mkdesc(db + kk * 128, bhi), 1);
                    if (kk & 1) wg_commit();
                }
                wg_wait<2>();
                if (rel & 1) { mbar_expect_tx(ofull + ps8, BOX); mbar_arrive_at(oempty + ps8); mbar_arrive(bars + 8 * B_WOEMPTY + ps8); }
                if (i == 16) break;
                rel >>= 1;
                ps8 = s8;
#pragma unroll 1
                do {
                    s8 = s8 == 40 ? 0 : s8 + 8;
                    if (s8 == 16) ph ^= 1;
                    uint32_t bad;
                    asm volatile("{\n.reg .pred p, q, r;\n.reg .u32 u, v;\nmbarrier.try_wait.parity.shared::cta.b64 q, [%2], %3;\nmbarrier.try_wait.parity.shared::cta.b64 p, [%1], %3;\n"
                                 "setp.ne.and.u32 r, %5, 1, p;\nmov.u32 u, 1;\nmov.u32 v, 1;\n@r ld.shared.u32 u, [%4];\n@r ld.shared.u32 v, [%4 + 4096];\n"
                                 "and.pred p, p, q;\nmin.u32 u, u, v;\nsetp.eq.or.u32 p, u, 0, !p;\nvote.sync.any.pred p, p, 0xffffffff;\nselp.u32 %0, 1, 0, p;\n}"
                                 : "=r"(bad) : "r"(ofull + s8), "r"(bars + 8 * B_WOFULL + s8), "r"(ph), "r"(chk + s8 * (BOX / 8)), "r"(i) : "memory");
                    if (__builtin_expect(bad, 0)) {
                        mbar_wait(ofull + s8, ph, budget);
                        mbar_wait(bars + 8 * B_WOFULL + s8, ph, budget);
                        if (__any_sync(0xffffffffu, min(lds1(chk + s8 * (BOX / 8)), lds1(chk + s8 * (BOX / 8) + 4096)) == 0)) {
                            const uint32_t at = wi * 256 + (lane >> 4) * 1024 + (lane & 15) * 16;
                            const uint8_t* src = scr->o + ((size_t)((mt * 2 + rh) * 2 + 1 - w) * 16 + ((2 * p + (i < 2 ? i ^ hp : i)) & 15)) * BOX + at;
#pragma unroll 1
                            for (int n = 0; n < 8192; n += 2048) {
                                uint4 v; int tries = 4096;
#pragma unroll 1
                                do { v = ld_rlx4(src + n); } while (v.x == 0 && --tries > 0);
                                sts4(ring + s8 * (BOX / 8) + at + n, v.x, v.y, v.z, v.w);
                            }
                            NRETRY();
                            fence_async_smem();
                            __syncwarp();
                        }
                    }
                    TSC(TIMING % 10 == 1 && tid == 0, 48 + i);
                    TSC(TIMING % 10 == 2 && elect, 32 + w * 16 + i);
                } while (++i > last && i < 16);
                if (i > last) break;
                wg_wait<1>();
            }
            if (w) {
                bar_sync(9, 256);
#pragma unroll 1
                for (int i = HOLD - 10; i < 6; i++) {
                    wg_fence();
#pragma unroll
                    for (int kk = 0; kk < 4; kk++) wgmma_n128<0, 1>(acc, mkdesc(da0 + i * 512 + kk * 128, ahi), mkdesc(db0 + i * 1024 + kk * 128, bhi), 1);
                    wg_commit();
                }
            } else bar_arrive(9, 256);
            const bool add = (__shfl_sync(0xffffffffu, lds1(sb + OFF_SEL), 0) >> (wi * 2 + 1 - w)) & 1;
            wg_wait<0>();
            TSC(elect, 7 + 9 * w);
            const uint32_t os0 = ring + wi * 4096;
#pragma unroll
            for (int hf = 0; hf < OUT_PARTS; hf++) {
#pragma unroll
                for (int j = hf * (8 / OUT_PARTS); j < (hf + 1) * (8 / OUT_PARTS); j++)
                    stsm4(((os0 + mad) ^ ((j & 3) * 32)) + (j >> 2) * 2048, pack_here(acc[8 * j], acc[8 * j + 1]), pack_here(acc[8 * j + 2], acc[8 * j + 3]),
                          pack_here(acc[8 * j + 4], acc[8 * j + 5]), pack_here(acc[8 * j + 6], acc[8 * j + 7]));
                fence_async_smem();
                __syncwarp();
                if (elect_one())
                    asm volatile("{\n.reg .pred p;\nsetp.ne.b32 p, %6, 0;\n@!p cp.async.bulk.tensor.5d.global.shared::cta.bulk_group [%0, {%2, %2, %3, %4, %5}], [%1];\n"
                                 "@p cp.reduce.async.bulk.tensor.5d.global.shared::cta.add.bulk_group [%0, {%2, %2, %3, %4, %5}], [%1];\n}"
                                 ::"l"(&mout), "r"(os0 + hf * 2048), "r"(0), "r"(((j0 + rh * 128) >> 5) + wi), "r"(1 - w), "r"(par * 16 + cb * 2 + hf), "r"((int)add) : "memory");
            }
            asm volatile("cp.async.bulk.commit_group;\ncp.async.bulk.wait_group.read 0;" ::: "memory");
            if (b == 0 && tid == 0) st_rlx(&scr->epoch[0], lds1(sb + OFF_EP));
            TSC(elect, 8 - 2 * w);
            TS_END();
        }
    }
}

typedef CUresult (*EncodeFn)(CUtensorMap*, CUtensorMapDataType, cuuint32_t, void*, const cuuint64_t*, const cuuint64_t*, const cuuint32_t*,
                             const cuuint32_t*, CUtensorMapInterleave, CUtensorMapSwizzle, CUtensorMapL2promotion, CUtensorMapFloatOOBfill);

CUtensorMap make_map(EncodeFn fn, const void* base, int rank, const cuuint64_t* dims, const cuuint64_t* strides, const cuuint32_t* box,
                     CUtensorMapSwizzle swz = CU_TENSOR_MAP_SWIZZLE_128B, CUtensorMapL2promotion pro = CU_TENSOR_MAP_L2_PROMOTION_L2_256B) {
    CUtensorMap m;
    cuuint32_t es[5] = {1, 1, 1, 1, 1};
    fn(&m, CU_TENSOR_MAP_DATA_TYPE_BFLOAT16, rank, (void*)base, dims, strides, box, es, CU_TENSOR_MAP_INTERLEAVE_NONE,
       swz, pro, CU_TENSOR_MAP_FLOAT_OOB_FILL_NONE);
    return m;
}

}

extern "C" void kernel_launch(void* const* d_in, const int* in_sizes, int n_in, void* d_out, int out_size) {
    (void)in_sizes; (void)n_in; (void)out_size;
    const __nv_bfloat16* x = (const __nv_bfloat16*)d_in[0];
    const __nv_bfloat16* wqkv = (const __nv_bfloat16*)d_in[1];
    const __nv_bfloat16* wo = (const __nv_bfloat16*)d_in[2];
    const __nv_bfloat16* wr = (const __nv_bfloat16*)d_in[4];
    const __nv_bfloat16* wg = (const __nv_bfloat16*)d_in[5];
    const __nv_bfloat16* wu = (const __nv_bfloat16*)d_in[6];
    const __nv_bfloat16* wd = (const __nv_bfloat16*)d_in[7];
    static EncodeFn fn = nullptr;
    static Scratch* scr = nullptr;
    if (!fn) {
        void* p = nullptr; cudaDriverEntryPointQueryResult q;
        cudaGetDriverEntryPoint("cuTensorMapEncodeTiled", &p, cudaEnableDefault, &q);
        fn = (EncodeFn)p;
        cudaFuncSetAttribute(fused_kernel, cudaFuncAttributeMaxDynamicSharedMemorySize, SMEM_LAUNCH);
        cudaGetSymbolAddress((void**)&scr, g_scr);
    }
    const cuuint64_t xd[4] = {2048, 16, 32, 2}, xs[4] = {4096, 131072, 65536, 128}, od[5] = {64, 16, 32, 2, 32};
    const cuuint32_t xb[4] = {64, 16, 4, 1}, ob[5] = {64, 16, 1, 1, 2 / OUT_PARTS};
    const cuuint64_t wdm[3] = {1024, 1024, 3}, wst[2] = {6144, 2048};
    const cuuint32_t wb[3] = {64, 64, 3};
    const cuuint64_t wod[3] = {64, 1024, 16}, wdd[3] = {64, 3584, 16}, wos[2] = {2048, 128};
    const cuuint32_t wob[3] = {64, 64, 2}, wdb[3] = {64, 64, 1};
    CUtensorMap mx = make_map(fn, x, 4, xd, xs, xb), mw = make_map(fn, wqkv, 3, wdm, wst, wb);
    CUtensorMap mwo = make_map(fn, wo, 3, wod, wos, wob), mout = make_map(fn, d_out, 5, od, xs, ob);
    const int swap_gu = wu < wg;
    const cuuint64_t gd[3] = {3584, 1024, 2}, gst[2] = {7168, (cuuint64_t)(swap_gu ? (const char*)wg - (const char*)wu : (const char*)wu - (const char*)wg)};
    const cuuint32_t gb[3] = {32, 64, 2};
    CUtensorMap mgu = make_map(fn, swap_gu ? wu : wg, 3, gd, gst, gb, CU_TENSOR_MAP_SWIZZLE_64B, CU_TENSOR_MAP_L2_PROMOTION_L2_128B);
    CUtensorMap mwd = make_map(fn, wd, 3, wdd, wos, wdb, CU_TENSOR_MAP_SWIZZLE_128B, CU_TENSOR_MAP_L2_PROMOTION_L2_128B);
    const cuuint64_t md[2] = {64, 32768}, ms[1] = {128};
    const cuuint32_t mb[2] = {64, 64};
    CUtensorMap mo = make_map(fn, scr, 2, md, ms, mb, CU_TENSOR_MAP_SWIZZLE_NONE, CU_TENSOR_MAP_L2_PROMOTION_NONE);
    cudaLaunchConfig_t cfg = {};
    cfg.gridDim = dim3(132); cfg.blockDim = dim3(512); cfg.dynamicSmemBytes = SMEM_LAUNCH; cfg.stream = cudaStreamPerThread;
    cudaLaunchAttribute at[1];
    at[0].id = cudaLaunchAttributeClusterDimension; at[0].val.clusterDim.x = 2; at[0].val.clusterDim.y = 1; at[0].val.clusterDim.z = 1;
    cfg.attrs = at; cfg.numAttrs = 1;
    cudaLaunchKernelEx(&cfg, fused_kernel, mx, mw, mwo, mout, mgu, mwd, mo, x, wr, scr, swap_gu, Weights{(const char*)wqkv, (const char*)wo, (const char*)wg, (const char*)wu, (const char*)wd, (char*)d_out});
}
```

```cpp
#include <cuda_runtime.h>
#include <cuda.h>
#include <cuda_bf16.h>
#include <stdint.h>

namespace {

constexpr int BOX = 8192, W_BYTES = 3 * BOX;
constexpr int OFF_X1 = 6 * BOX, OFF_FR = 12 * BOX, OFF_E = 16 * BOX, OFF_W = 19 * BOX;
constexpr int OFF_WO = OFF_E;
constexpr int OFF_HIN = OFF_FR + 2048, OFF_GU = OFF_HIN + 2048, OFF_FS = OFF_GU + 1024;
constexpr int F_BYTES = 9216;
constexpr int CS_BYTES = 3136;
constexpr int OFF_CS = OFF_FS + 5 * F_BYTES;
constexpr int OFF_STAT = 28 * BOX;
constexpr int OFF_SEL = OFF_STAT + 2112;
constexpr int OFF_EP = OFF_SEL + 32;
constexpr int OFF_BAR = OFF_EP + 16;
constexpr int B_WFULL = 0, B_XFULL = 3, B_AUX = 15, B_XT = 16, B_ROW = 17, B_WOFULL = 18, B_OFULL = 24, B_FFULL = 36, B_ZERO = 41;
constexpr int B_WEMPTY = 42, B_F1DONE = 45, B_XEMPTY = 46, B_WOEMPTY = 52, B_OEMPTY = 58;
constexpr int B_G1DONE = 66, B_FEMPTY = 67, B_STAGED = 72, B_RDONE = 75, B_FREED = 76, NBAR = 78;
constexpr int SMEM_BYTES = OFF_BAR + NBAR * 8;
static_assert(OFF_FS + 3 * F_BYTES == OFF_E && OFF_CS + CS_BYTES <= OFF_W && SMEM_BYTES + 256 <= 232448 && OFF_BAR % 8 == 0, "smem");
#define POLL_NS 30
#define PF_RATE 8
#define PF_START 7
#define ZF_NS 100
#define FFN2_GATE (B_STAGED + 1)
#define PF_NW 0
#define EARLY_PF 1
#define EARLY_PK 17
#define FENCE_PRED "@p "
#define ZF_GATE B_ROW
#define HOLD 12
#define F1_DEPTH 1
#define F2_DEPTH 0
#define F1_HOLD 2
#define F1_GATE B_G1DONE
#define OUT_PARTS 2
#define ROWS_AT 11
constexpr int BUDGET = 1 << 18;

struct Scratch {
    uint8_t o[2048 * 1024 * 2];
    uint32_t ypart[8][8][1024];
    uint32_t halo[128][512];
    uint32_t act[2][14336 + 4096];
    uint2 row[2048];
    uint4 cs[16][3][24];
    uint32_t oflag[16][32];
    uint32_t cnt[9][32];
    uint32_t sel[32], epoch[32];
};
__device__ __align__(1024) Scratch g_scr;
struct Weights { const char *wqkv, *wo, *wg, *wu, *wd; char* out; };

#define TS(i) do {} while (0)
#define TS_END() do {} while (0)
#define TSC(c, i) do {} while (0)
#define NRETRY() do {} while (0)
constexpr int SMEM_LAUNCH = SMEM_BYTES;
__device__ __forceinline__ uint32_t smem_u32(const void* p) { return (uint32_t)__cvta_generic_to_shared(p); }
__device__ __forceinline__ void mbar_init(uint32_t bar, uint32_t cnt) { asm volatile("mbarrier.init.shared::cta.b64 [%0], %1;" ::"r"(bar), "r"(cnt) : "memory"); }
__device__ __forceinline__ void mbar_expect_tx(uint32_t bar, uint32_t bytes) { asm volatile("mbarrier.arrive.expect_tx.shared::cta.b64 _, [%0], %1;" ::"r"(bar), "r"(bytes) : "memory"); }
__device__ __forceinline__ void mbar_arrive(uint32_t bar) { asm volatile("mbarrier.arrive.shared::cta.b64 _, [%0];" ::"r"(bar) : "memory"); }
__device__ __forceinline__ uint32_t mapa(uint32_t a, uint32_t cta) { uint32_t r; asm("mapa.shared::cluster.u32 %0, %1, %2;" : "=r"(r) : "r"(a), "r"(cta)); return r; }
__device__ __forceinline__ void mbar_arrive_at(uint32_t cbar) { asm volatile("mbarrier.arrive.shared::cluster.b64 _, [%0];" ::"r"(cbar) : "memory"); }
__device__ __forceinline__ void mbar_wait(uint32_t bar, uint32_t parity, int& budget) {
    asm volatile("{\n.reg .pred p;\nLAB_WAIT:\nmbarrier.try_wait.parity.shared::cta.b64 p, [%1], %2;\n"
                 "add.s32 %0, %0, -1;\nsetp.gt.and.s32 p, %0, 0, !p;\n@p bra LAB_WAIT;\n}" : "+r"(budget) : "r"(bar), "r"(parity) : "memory");
}
__device__ __forceinline__ void mbar_wait_hot(uint32_t bar, uint32_t parity, int& budget) {
    asm volatile("{\n.reg .pred p;\nmbarrier.try_wait.parity.shared::cta.b64 p, [%1], %2;\n@p bra LAB_DONE;\nLAB_WAIT:\nmbarrier.try_wait.parity.shared::cta.b64 p, [%1], %2;\n"
                 "add.s32 %0, %0, -1;\nsetp.gt.and.s32 p, %0, 0, !p;\n@p bra LAB_WAIT;\nLAB_DONE:\n}" : "+r"(budget) : "r"(bar), "r"(parity) : "memory");
}
__device__ __forceinline__ void tma_2d_mc(uint32_t dst, const CUtensorMap* m, uint32_t bar, int c0, int c1) {
    asm volatile("cp.async.bulk.tensor.2d.shared::cluster.global.mbarrier::complete_tx::bytes.multicast::cluster [%0], [%1, {%3, %4}], [%2], %5;" ::"r"(dst), "l"(m), "r"(bar), "r"(c0), "r"(c1), "h"((uint16_t)3) : "memory");
}
__device__ __forceinline__ void tma_3d(uint32_t dst, const CUtensorMap* m, uint32_t bar, int c0, int c1, int c2) {
    asm volatile("cp.async.bulk.tensor.3d.shared::cluster.global.mbarrier::complete_tx::bytes [%0], [%1, {%3, %4, %5}], [%2];" ::"r"(dst), "l"(m), "r"(bar), "r"(c0), "r"(c1), "r"(c2) : "memory");
}
__device__ __forceinline__ void tma_4d(uint32_t dst, const CUtensorMap* m, uint32_t bar, int c0, int c1, int c2, int c3) {
    asm volatile("cp.async.bulk.tensor.4d.shared::cluster.global.mbarrier::complete_tx::bytes [%0], [%1, {%3, %4, %5, %6}], [%2];" ::"r"(dst), "l"(m), "r"(bar), "r"(c0), "r"(c1), "r"(c2), "r"(c3) : "memory");
}
__device__ __forceinline__ void tma_4d_mc(uint32_t dst, const CUtensorMap* m, uint32_t bar, int c0, int c1, int c2, int c3) {
    asm volatile("cp.async.bulk.tensor.4d.shared::cluster.global.mbarrier::complete_tx::bytes.multicast::cluster [%0], [%1, {%3, %4, %5, %6}], [%2], %7;" ::"r"(dst), "l"(m), "r"(bar), "r"(c0), "r"(c1), "r"(c2), "r"(c3), "h"((uint16_t)3) : "memory");
}
__device__ __forceinline__ void bulk_pf(const void* p, uint32_t bytes) { asm volatile("cp.async.bulk.prefetch.L2.global [%0], %1;" ::"l"(p), "r"(bytes) : "memory"); }
__device__ __forceinline__ void bulk_g2s(uint32_t dst, const void* src, uint32_t bytes, uint32_t bar) {
    asm volatile("cp.async.bulk.shared::cluster.global.mbarrier::complete_tx::bytes [%0], [%1], %2, [%3];" ::"r"(dst), "l"(src), "r"(bytes), "r"(bar) : "memory");
}
__device__ __forceinline__ void bulk_s2c(uint32_t cdst, uint32_t src, uint32_t bytes, uint32_t cbar) {
    asm volatile("cp.async.bulk.shared::cluster.shared::cta.mbarrier::complete_tx::bytes [%0], [%1], %2, [%3];" ::"r"(cdst), "r"(src), "r"(bytes), "r"(cbar) : "memory");
}
__device__ __forceinline__ void cluster_wait() { asm volatile("barrier.cluster.wait.aligned;" ::: "memory"); }
__device__ __forceinline__ void fence_gpu() { asm volatile("fence.acq_rel.gpu;" ::: "memory"); }
__device__ __forceinline__ void fence_async_smem() { asm volatile("fence.proxy.async.shared::cta;" ::: "memory"); }
__device__ __forceinline__ void wg_fence() { asm volatile("wgmma.fence.sync.aligned;" ::: "memory"); }
__device__ __forceinline__ void wg_commit() { asm volatile("wgmma.commit_group.sync.aligned;" ::: "memory"); }
template <int N> __device__ __forceinline__ void wg_wait() { asm volatile("wgmma.wait_group.sync.aligned %0;" ::"n"(N) : "memory"); }
__device__ __forceinline__ uint64_t mkdesc(uint32_t lo, uint32_t hi) { return ((uint64_t)hi << 32) | lo; }
__host__ __device__ constexpr uint32_t dhi(uint32_t sbo, uint32_t mode) { return (sbo >> 4) | (mode << 30); }
__host__ __device__ constexpr uint32_t dlo(uint32_t off, uint32_t lbo) { return (off >> 4) + ((lbo >> 4) << 16); }
__device__ __forceinline__ bool elect_one() {
    uint32_t e;
    asm volatile("{\n.reg .pred p;\nelect.sync _|p, 0xffffffff;\nselp.u32 %0, 1, 0, p;\n}" : "=r"(e));
    return e;
}
template <int R> __device__ __forceinline__ void reg_inc() { asm volatile("setmaxnreg.inc.sync.aligned.u32 %0;" ::"n"(R)); }
template <int R> __device__ __forceinline__ void reg_dec() { asm volatile("setmaxnreg.dec.sync.aligned.u32 %0;" ::"n"(R)); }
__device__ __forceinline__ void bar_sync(int id, int n) { asm volatile("bar.sync %0, %1;" ::"r"(id), "r"(n) : "memory"); }
__device__ __forceinline__ void bar_arrive(int id, int n) { asm volatile("bar.arrive %0, %1;" ::"r"(id), "r"(n) : "memory"); }
__device__ __forceinline__ uint32_t pack_bf16(float lo, float hi) { uint32_t r; asm("cvt.rn.bf16x2.f32 %0, %1, %2;" : "=r"(r) : "f"(hi), "f"(lo)); return r; }
__device__ __forceinline__ uint32_t pack_here(float lo, float hi) { uint32_t r; asm volatile("cvt.rn.bf16x2.f32 %0, %1, %2;" : "=r"(r) : "f"(hi), "f"(lo)); return r; }
__device__ __forceinline__ float bf_lo(uint32_t u) { return __uint_as_float(u << 16); }
__device__ __forceinline__ float bf_hi(uint32_t u) { return __uint_as_float(u & 0xffff0000u); }
__device__ __forceinline__ float bf16r(float v) { return bf_lo(pack_bf16(v, 0.f)); }
__device__ __forceinline__ float rcp(float x) { float r; asm("rcp.approx.ftz.f32 %0, %1;" : "=f"(r) : "f"(x)); return r; }
__device__ __forceinline__ float ex2(float x) { float r; asm("ex2.approx.ftz.f32 %0, %1;" : "=f"(r) : "f"(x)); return r; }
__device__ __forceinline__ float sigmoidf(float v) { return rcp(1.f + ex2(v * -1.4426950408889634f)); }
__device__ __forceinline__ uint32_t movm(uint32_t a) { uint32_t d; asm volatile("movmatrix.sync.aligned.m8n8.trans.b16 %0, %1;" : "=r"(d) : "r"(a)); return d; }
__device__ __forceinline__ void mma16816(float (&c)[4], uint32_t a0, uint32_t a1, uint32_t a2, uint32_t a3, uint32_t b0, uint32_t b1) {
    asm volatile("mma.sync.aligned.m16n8k16.row.col.f32.bf16.bf16.f32 {%0,%1,%2,%3}, {%4,%5,%6,%7}, {%8,%9}, {%0,%1,%2,%3};"
                 : "+f"(c[0]), "+f"(c[1]), "+f"(c[2]), "+f"(c[3]) : "r"(a0), "r"(a1), "r"(a2), "r"(a3), "r"(b0), "r"(b1));
}
__device__ __forceinline__ void mma1688(float (&c)[4], uint32_t a0, uint32_t a1, uint32_t b0) {
    asm volatile("mma.sync.aligned.m16n8k8.row.col.f32.bf16.bf16.f32 {%0,%1,%2,%3}, {%4,%5}, {%6}, {%0,%1,%2,%3};"
                 : "+f"(c[0]), "+f"(c[1]), "+f"(c[2]), "+f"(c[3]) : "r"(a0), "r"(a1), "r"(b0));
}
__device__ __forceinline__ void stsm4(uint32_t a, uint32_t r0, uint32_t r1, uint32_t r2, uint32_t r3) {
    asm volatile("stmatrix.sync.aligned.m8n8.x4.shared.b16 [%0], {%1,%2,%3,%4};" ::"r"(a), "r"(r0), "r"(r1), "r"(r2), "r"(r3) : "memory");
}
__device__ __forceinline__ void ldsm4(uint32_t* r, uint32_t a) {
    asm volatile("ldmatrix.sync.aligned.m8n8.x4.shared.b16 {%0,%1,%2,%3}, [%4];" : "=r"(r[0]), "=r"(r[1]), "=r"(r[2]), "=r"(r[3]) : "r"(a) : "memory");
}
__device__ __forceinline__ void ldsm4t(uint32_t* r, uint32_t a) {
    asm volatile("ldmatrix.sync.aligned.m8n8.x4.trans.shared.b16 {%0,%1,%2,%3}, [%4];" : "=r"(r[0]), "=r"(r[1]), "=r"(r[2]), "=r"(r[3]) : "r"(a) : "memory");
}
__device__ __forceinline__ uint32_t ld_rlx(const void* p) { uint32_t v; asm volatile("ld.relaxed.gpu.global.u32 %0, [%1];" : "=r"(v) : "l"(p) : "memory"); return v; }
__device__ __forceinline__ uint32_t ld_acq(const void* p) { uint32_t v; asm volatile("ld.acquire.gpu.global.u32 %0, [%1];" : "=r"(v) : "l"(p) : "memory"); return v; }
__device__ __forceinline__ uint2 ld_rlx2(const void* p) { uint2 v; asm volatile("ld.relaxed.gpu.global.v2.u32 {%0,%1}, [%2];" : "=r"(v.x), "=r"(v.y) : "l"(p) : "memory"); return v; }
__device__ __forceinline__ uint4 ld_rlx4(const void* p) { uint4 v; asm volatile("ld.relaxed.gpu.global.v4.u32 {%0,%1,%2,%3}, [%4];" : "=r"(v.x), "=r"(v.y), "=r"(v.z), "=r"(v.w) : "l"(p) : "memory"); return v; }
__device__ __forceinline__ void st_rlx(void* p, uint32_t v) { asm volatile("st.relaxed.gpu.global.u32 [%0], %1;" ::"l"(p), "r"(v) : "memory"); }
__device__ __forceinline__ void st_rlx2(void* p, uint32_t a, uint32_t b) { asm volatile("st.relaxed.gpu.global.v2.u32 [%0], {%1,%2};" ::"l"(p), "r"(a), "r"(b) : "memory"); }
__device__ __forceinline__ void st_rlx4(void* p, uint32_t a, uint32_t b, uint32_t c, uint32_t d) { asm volatile("st.relaxed.gpu.global.v4.u32 [%0], {%1,%2,%3,%4};" ::"l"(p), "r"(a), "r"(b), "r"(c), "r"(d) : "memory"); }
__device__ __forceinline__ void red_add(uint32_t* p) { asm volatile("red.relaxed.gpu.global.add.u32 [%0], 1;" ::"l"(p) : "memory"); }
__device__ __forceinline__ uint4 ldg_nc(const void* p) { uint4 v; asm volatile("ld.global.nc.v4.u32 {%0,%1,%2,%3}, [%4];" : "=r"(v.x), "=r"(v.y), "=r"(v.z), "=r"(v.w) : "l"(p)); return v; }
__device__ __forceinline__ void sts4(uint32_t a, uint32_t x, uint32_t y, uint32_t z, uint32_t w) { asm volatile("st.shared.v4.u32 [%0], {%1,%2,%3,%4};" ::"r"(a), "r"(x), "r"(y), "r"(z), "r"(w) : "memory"); }
__device__ __forceinline__ void sts2(uint32_t a, uint32_t x, uint32_t y) { asm volatile("st.shared.v2.u32 [%0], {%1,%2};" ::"r"(a), "r"(x), "r"(y) : "memory"); }
__device__ __forceinline__ void sts1(uint32_t a, uint32_t v) { asm volatile("st.shared.u32 [%0], %1;" ::"r"(a), "r"(v) : "memory"); }
__device__ __forceinline__ uint4 lds4(uint32_t a) { uint4 v; asm volatile("ld.shared.v4.u32 {%0,%1,%2,%3}, [%4];" : "=r"(v.x), "=r"(v.y), "=r"(v.z), "=r"(v.w) : "r"(a) : "memory"); return v; }
__device__ __forceinline__ float4 lds4f(uint32_t a) { float4 v; asm volatile("ld.shared.v4.f32 {%0,%1,%2,%3}, [%4];" : "=f"(v.x), "=f"(v.y), "=f"(v.z), "=f"(v.w) : "r"(a) : "memory"); return v; }
__device__ __forceinline__ float2 lds2f(uint32_t a) { float2 v; asm volatile("ld.shared.v2.f32 {%0,%1}, [%2];" : "=f"(v.x), "=f"(v.y) : "r"(a) : "memory"); return v; }
__device__ __forceinline__ float lds1f(uint32_t a) { float v; asm volatile("ld.shared.f32 %0, [%1];" : "=f"(v) : "r"(a) : "memory"); return v; }
__device__ __forceinline__ uint32_t lds1(uint32_t a) { uint32_t v; asm volatile("ld.shared.u32 %0, [%1];" : "=r"(v) : "r"(a) : "memory"); return v; }
__device__ __forceinline__ uint32_t redux_max(uint32_t v) { uint32_t r; asm volatile("redux.sync.max.u32 %0, %1, 0xffffffff;" : "=r"(r) : "r"(v)); return r; }
__device__ __forceinline__ uint32_t poll_all(const uint32_t* p, uint32_t mask, uint32_t want, int& budget) {
    uint32_t v;
#pragma unroll 1
    while (v = ld_acq(p), !__all_sync(0xffffffffu, (v & mask) == want) && --budget > 0) __nanosleep(POLL_NS);
    return v;
}

template <int TA, int TB>
__device__ __forceinline__ void wgmma_n192(float (&d)[96], uint64_t da, uint64_t db, int keep) {
    asm volatile("{\n.reg .pred p;\nsetp.ne.b32 p, %98, 0;\n"
        "wgmma.mma_async.sync.aligned.m64n192k16.f32.bf16.bf16 "
        "{%0, %1, %2, %3, %4, %5, %6, %7, %8, %9, %10, %11, %12, %13, %14, %15, "
        "%16, %17, %18, %19, %20, %21, %22, %23, %24, %25, %26, %27, %28, %29, %30, %31, "
        "%32, %33, %34, %35, %36, %37, %38, %39, %40, %41, %42, %43, %44, %45, %46, %47, "
        "%48, %49, %50, %51, %52, %53, %54, %55, %56, %57, %58, %59, %60, %61, %62, %63, "
        "%64, %65, %66, %67, %68, %69, %70, %71, %72, %73, %74, %75, %76, %77, %78, %79, "
        "%80, %81, %82, %83, %84, %85, %86, %87, %88, %89, %90, %91, %92, %93, %94, %95}, "
        "%96, %97, p, 1, 1, %99, %100;\n}\n"
        : "+f"(d[0]), "+f"(d[1]), "+f"(d[2]), "+f"(d[3]), "+f"(d[4]), "+f"(d[5]), "+f"(d[6]), "+f"(d[7]),
          "+f"(d[8]), "+f"(d[9]), "+f"(d[10]), "+f"(d[11]), "+f"(d[12]), "+f"(d[13]), "+f"(d[14]), "+f"(d[15]),
          "+f"(d[16]), "+f"(d[17]), "+f"(d[18]), "+f"(d[19]), "+f"(d[20]), "+f"(d[21]), "+f"(d[22]), "+f"(d[23]),
          "+f"(d[24]), "+f"(d[25]), "+f"(d[26]), "+f"(d[27]), "+f"(d[28]), "+f"(d[29]), "+f"(d[30]), "+f"(d[31]),
          "+f"(d[32]), "+f"(d[33]), "+f"(d[34]), "+f"(d[35]), "+f"(d[36]), "+f"(d[37]), "+f"(d[38]), "+f"(d[39]),
          "+f"(d[40]), "+f"(d[41]), "+f"(d[42]), "+f"(d[43]), "+f"(d[44]), "+f"(d[45]), "+f"(d[46]), "+f"(d[47]),
          "+f"(d[48]), "+f"(d[49]), "+f"(d[50]), "+f"(d[51]), "+f"(d[52]), "+f"(d[53]), "+f"(d[54]), "+f"(d[55]),
          "+f"(d[56]), "+f"(d[57]), "+f"(d[58]), "+f"(d[59]), "+f"(d[60]), "+f"(d[61]), "+f"(d[62]), "+f"(d[63]),
          "+f"(d[64]), "+f"(d[65]), "+f"(d[66]), "+f"(d[67]), "+f"(d[68]), "+f"(d[69]), "+f"(d[70]), "+f"(d[71]),
          "+f"(d[72]), "+f"(d[73]), "+f"(d[74]), "+f"(d[75]), "+f"(d[76]), "+f"(d[77]), "+f"(d[78]), "+f"(d[79]),
          "+f"(d[80]), "+f"(d[81]), "+f"(d[82]), "+f"(d[83]), "+f"(d[84]), "+f"(d[85]), "+f"(d[86]), "+f"(d[87]),
          "+f"(d[88]), "+f"(d[89]), "+f"(d[90]), "+f"(d[91]), "+f"(d[92]), "+f"(d[93]), "+f"(d[94]), "+f"(d[95])
        : "l"(da), "l"(db), "r"(keep), "n"(TA), "n"(TB));
}
template <int TA, int TB>
__device__ __forceinline__ void wgmma_n128(float (&d)[64], uint64_t da, uint64_t db, int keep) {
    asm volatile("{\n.reg .pred p;\nsetp.ne.b32 p, %66, 0;\n"
        "wgmma.mma_async.sync.aligned.m64n128k16.f32.bf16.bf16 "
        "{%0, %1, %2, %3, %4, %5, %6, %7, %8, %9, %10, %11, %12, %13, %14, %15, "
        "%16, %17, %18, %19, %20, %21, %22, %23, %24, %25, %26, %27, %28, %29, %30, %31, "
        "%32, %33, %34, %35, %36, %37, %38, %39, %40, %41, %42, %43, %44, %45, %46, %47, "
        "%48, %49, %50, %51, %52, %53, %54, %55, %56, %57, %58, %59, %60, %61, %62, %63}, "
        "%64, %65, p, 1, 1, %67, %68;\n}\n"
        : "+f"(d[0]), "+f"(d[1]), "+f"(d[2]), "+f"(d[3]), "+f"(d[4]), "+f"(d[5]), "+f"(d[6]), "+f"(d[7]),
          "+f"(d[8]), "+f"(d[9]), "+f"(d[10]), "+f"(d[11]), "+f"(d[12]), "+f"(d[13]), "+f"(d[14]), "+f"(d[15]),
          "+f"(d[16]), "+f"(d[17]), "+f"(d[18]), "+f"(d[19]), "+f"(d[20]), "+f"(d[21]), "+f"(d[22]), "+f"(d[23]),
          "+f"(d[24]), "+f"(d[25]), "+f"(d[26]), "+f"(d[27]), "+f"(d[28]), "+f"(d[29]), "+f"(d[30]), "+f"(d[31]),
          "+f"(d[32]), "+f"(d[33]), "+f"(d[34]), "+f"(d[35]), "+f"(d[36]), "+f"(d[37]), "+f"(d[38]), "+f"(d[39]),
          "+f"(d[40]), "+f"(d[41]), "+f"(d[42]), "+f"(d[43]), "+f"(d[44]), "+f"(d[45]), "+f"(d[46]), "+f"(d[47]),
          "+f"(d[48]), "+f"(d[49]), "+f"(d[50]), "+f"(d[51]), "+f"(d[52]), "+f"(d[53]), "+f"(d[54]), "+f"(d[55]),
          "+f"(d[56]), "+f"(d[57]), "+f"(d[58]), "+f"(d[59]), "+f"(d[60]), "+f"(d[61]), "+f"(d[62]), "+f"(d[63])
        : "l"(da), "l"(db), "r"(keep), "n"(TA), "n"(TB));
}
template <int TA, int TB>
__device__ __forceinline__ void wgmma_n8(float (&d)[4], uint64_t da, uint64_t db, int keep) {
    asm volatile("{\n.reg .pred p;\nsetp.ne.b32 p, %6, 0;\n"
        "wgmma.mma_async.sync.aligned.m64n8k16.f32.bf16.bf16 "
        "{%0, %1, %2, %3}, "
        "%4, %5, p, 1, 1, %7, %8;\n}\n"
        : "+f"(d[0]), "+f"(d[1]), "+f"(d[2]), "+f"(d[3])
        : "l"(da), "l"(db), "r"(keep), "n"(TA), "n"(TB));
}
__device__ __forceinline__ void wgmma_rs_n192(float (&d)[96], uint32_t a0, uint32_t a1, uint32_t a2, uint32_t a3, uint64_t db) {
    asm volatile("{\n.reg .pred p;\nsetp.ne.b32 p, 1, 0;\n"
        "wgmma.mma_async.sync.aligned.m64n192k16.f32.bf16.bf16 "
        "{%0, %1, %2, %3, %4, %5, %6, %7, %8, %9, %10, %11, %12, %13, %14, %15, "
        "%16, %17, %18, %19, %20, %21, %22, %23, %24, %25, %26, %27, %28, %29, %30, %31, "
        "%32, %33, %34, %35, %36, %37, %38, %39, %40, %41, %42, %43, %44, %45, %46, %47, "
        "%48, %49, %50, %51, %52, %53, %54, %55, %56, %57, %58, %59, %60, %61, %62, %63, "
        "%64, %65, %66, %67, %68, %69, %70, %71, %72, %73, %74, %75, %76, %77, %78, %79, "
        "%80, %81, %82, %83, %84, %85, %86, %87, %88, %89, %90, %91, %92, %93, %94, %95}, "
        "{%96, %97, %98, %99}, %100, p, 1, 1, 1;\n}\n"
        : "+f"(d[0]), "+f"(d[1]), "+f"(d[2]), "+f"(d[3]), "+f"(d[4]), "+f"(d[5]), "+f"(d[6]), "+f"(d[7]),
          "+f"(d[8]), "+f"(d[9]), "+f"(d[10]), "+f"(d[11]), "+f"(d[12]), "+f"(d[13]), "+f"(d[14]), "+f"(d[15]),
          "+f"(d[16]), "+f"(d[17]), "+f"(d[18]), "+f"(d[19]), "+f"(d[20]), "+f"(d[21]), "+f"(d[22]), "+f"(d[23]),
          "+f"(d[24]), "+f"(d[25]), "+f"(d[26]), "+f"(d[27]), "+f"(d[28]), "+f"(d[29]), "+f"(d[30]), "+f"(d[31]),
          "+f"(d[32]), "+f"(d[33]), "+f"(d[34]), "+f"(d[35]), "+f"(d[36]), "+f"(d[37]), "+f"(d[38]), "+f"(d[39]),
          "+f"(d[40]), "+f"(d[41]), "+f"(d[42]), "+f"(d[43]), "+f"(d[44]), "+f"(d[45]), "+f"(d[46]), "+f"(d[47]),
          "+f"(d[48]), "+f"(d[49]), "+f"(d[50]), "+f"(d[51]), "+f"(d[52]), "+f"(d[53]), "+f"(d[54]), "+f"(d[55]),
          "+f"(d[56]), "+f"(d[57]), "+f"(d[58]), "+f"(d[59]), "+f"(d[60]), "+f"(d[61]), "+f"(d[62]), "+f"(d[63]),
          "+f"(d[64]), "+f"(d[65]), "+f"(d[66]), "+f"(d[67]), "+f"(d[68]), "+f"(d[69]), "+f"(d[70]), "+f"(d[71]),
          "+f"(d[72]), "+f"(d[73]), "+f"(d[74]), "+f"(d[75]), "+f"(d[76]), "+f"(d[77]), "+f"(d[78]), "+f"(d[79]),
          "+f"(d[80]), "+f"(d[81]), "+f"(d[82]), "+f"(d[83]), "+f"(d[84]), "+f"(d[85]), "+f"(d[86]), "+f"(d[87]),
          "+f"(d[88]), "+f"(d[89]), "+f"(d[90]), "+f"(d[91]), "+f"(d[92]), "+f"(d[93]), "+f"(d[94]), "+f"(d[95])
        : "r"(a0), "r"(a1), "r"(a2), "r"(a3), "l"(db));
}

template <int HS>
__device__ __forceinline__ void attn_pair(const uint32_t* q, const uint32_t* k, const uint32_t* v, const uint32_t* kh, const uint32_t* vh,
                                          const float* fu, const float* fn, const float* rk, float bias0, float bias1, uint32_t mU, uint32_t zero, const float* ci, uint32_t* o) {
    float s0[2][4] = {}, s1[2][4] = {}, s2[2][4] = {};
#pragma unroll
    for (int n = 0; n < 4; n++) {
        const int hd = n & 1, a = 8 * hd + 2 * (n & 2);
        mma16816(s1[hd], q[a], q[a + 1], q[a + 2], q[a + 3], k[a], k[a + 2]);
        mma16816(s2[hd], q[a], q[a + 1], q[a + 2], q[a + 3], k[a + 1], k[a + 3]);
    }
#pragma unroll
    for (int n = 0; n < 4; n++) {
        const int hd = n & 1, a = 8 * hd + 2 * (n & 2);
        mma16816(s0[hd], q[a], q[a + 1], q[a + 2], q[a + 3], kh[HS * (a / 2)], kh[HS * (a / 2 + 1)]);
    }
    float e[2][4], m[2][2];
#pragma unroll
    for (int hd = 0; hd < 2; hd++) {
        e[hd][2] = fmaf(s1[hd][2], fu[2], s2[hd][2] * fn[2]); e[hd][3] = fmaf(s1[hd][3], fu[3], s2[hd][3] * fn[3]);
        e[hd][0] = fmaf(s0[hd][0], fu[0], fmaf(s1[hd][0], fn[0], bias0)); e[hd][1] = fmaf(s0[hd][1], fu[1], fmaf(s1[hd][1], fn[1], bias1));
        m[hd][1] = fmaxf(e[hd][2], e[hd][3]); m[hd][0] = fmaxf(e[hd][0], e[hd][1]);
    }
#pragma unroll
    for (int x = 1; x < 3; x++)
#pragma unroll
        for (int n = 0; n < 4; n++) m[n & 1][1 - (n >> 1)] = fmaxf(m[n & 1][1 - (n >> 1)], __shfl_xor_sync(0xffffffffu, m[n & 1][1 - (n >> 1)], x));
#pragma unroll
    for (int hd = 0; hd < 2; hd++) {
#pragma unroll
        for (int n = 0; n < 4; n++) e[hd][n] = ex2(e[hd][n] - m[hd][n >> 1]);
        float sum[4] = {};
        mma1688(sum, pack_bf16(e[hd][0], e[hd][1]), pack_bf16(e[hd][2], e[hd][3]), 0x3f803f80u);
        const float i0 = rcp(sum[0]), i1 = rcp(sum[2]);
        const uint32_t plo = pack_bf16(e[hd][0] * rk[0] * i0, e[hd][1] * rk[1] * i0), phi = pack_bf16(e[hd][2] * rk[2] * i1, e[hd][3] * rk[3] * i1);
        const uint32_t z0 = plo & zero, z1 = phi & zero;
        const uint32_t a0 = plo & ~mU, a1 = phi & mU, a3 = phi & ~mU, b0 = plo & mU;
#pragma unroll
        for (int jj = 0; jj < 4; jj++) {
            float c[4];
            asm volatile("mma.sync.aligned.m16n8k16.row.col.f32.bf16.bf16.f32 {%0,%1,%2,%3}, {%4,%5,%6,%7}, {%8,%9}, {%10,%11,%12,%13};"
                         : "=f"(c[0]), "=f"(c[1]), "=f"(c[2]), "=f"(c[3])
                         : "r"(a0), "r"(a1), "r"(z0), "r"(a3), "r"(v[8 * hd + 2 * jj]), "r"(v[8 * hd + 2 * jj + 1]), "f"(ci[0]), "f"(ci[1]), "f"(ci[2]), "f"(ci[3]));
            mma1688(c, b0, z1, vh[HS * (4 * hd + jj)]);
            o[8 * hd + 2 * jj] = pack_bf16(c[0], c[1]); o[8 * hd + 2 * jj + 1] = pack_bf16(c[2], c[3]);
        }
    }
}

__device__ __forceinline__ uint32_t norm_pair(uint32_t u, float m, float rinv) {
    const uint32_t d = pack_bf16(bf_lo(u) - m, bf_hi(u) - m);
    return max(pack_bf16(bf_lo(d) * rinv, bf_hi(d) * rinv), 1u);
}

__global__ void __launch_bounds__(512, 1)
fused_kernel(const __grid_constant__ CUtensorMap mx, const __grid_constant__ CUtensorMap mw, const __grid_constant__ CUtensorMap mwo,
             const __grid_constant__ CUtensorMap mout, const __grid_constant__ CUtensorMap mgu, const __grid_constant__ CUtensorMap mwd,
             const __grid_constant__ CUtensorMap mo,
             const __nv_bfloat16* __restrict__ x, const __nv_bfloat16* __restrict__ wr, Scratch* __restrict__ scr, int swap_gu, const Weights pf) {
    extern __shared__ __align__(1024) uint8_t smem[];
    const uint32_t sb = smem_u32(smem);
    const uint32_t bars = sb + OFF_BAR;
    const int tid = threadIdx.x, lane = tid & 31, warp = __shfl_sync(0xffffffffu, tid >> 5, 0);
    const uint32_t sd = (sb & 0x3FFFF) >> 4;
    const int hp = blockIdx.x & 1, cl = blockIdx.x >> 1;
    int pr = cl - 4 + (max(cl - 36, 0) * 37 >> 8);
    asm("{\n.reg .pred p;\nsetp.lt.s32 p, %1, 4;\nselp.s32 %0, %2, %0, p;\n}" : "+r"(pr) : "r"(cl), "r"(39 + 8 * cl));
    const int b = pr * 2 + hp, mt = pr >> 3, p = pr & 7, nt = 2 * p + hp, rh = p & 1, cb = (p & 6) + hp;
    const int par = mt >> 2, j0 = (mt & 3) * 256;
    int budget = BUDGET;

    TSC(tid == 0, 0);
    if (b < 128 && tid >= 32 && tid < 112) {
        const char* a = tid < 64 ? (const char*)x + (size_t)(16 * b + ((tid >> 1) & 15)) * 2048 + (tid & 1) * 128 : pf.wqkv + (size_t)b * 6144 + (tid - 64) * 128;
        asm volatile("prefetch.global.L2 [%0];" ::"l"(a));
    }
    auto load_w = [&](int k, int s) {
        const uint32_t full = bars + 8 * (B_WFULL + s);
        mbar_expect_tx(full, W_BYTES);
        tma_3d(sb + OFF_W + s * W_BYTES, &mw, full, nt * 64, k * 64, 0);
    };
    auto load_x = [&](int n) {
        const int w = n & 1, j = n < 4 ? (n >> 1) + 4 : (n >> 1) - 2;
        const uint32_t full = bars + 8 * (B_XFULL + w * 6 + 5 - j);
        mbar_expect_tx(full, BOX);
        tma_4d(sb + w * OFF_X1 + j * BOX, &mx, full, par * 1024 + (n >> 2) * 64, 0, (j0 + w * 128) >> 5, (~n >> 1) & 1);
    };
    if (warp < NBAR / 6 && elect_one()) {
        const uint32_t cnt = warp < B_WEMPTY / 6 ? 1 : warp < B_G1DONE / 6 ? 2 : warp < B_STAGED / 6 ? 4 : 8;
#pragma unroll
        for (int i = 0; i < 6; i++) mbar_init(bars + 48 * warp + 8 * i, cnt);
        asm volatile("fence.mbarrier_init.release.cluster;" ::: "memory");
        if (warp == 0 && b < 128) { load_x(0); load_w(0, 2); }
    }
    __syncthreads();

    if (b >= 128) {
        const int hc = b - 128, g = lane >> 2, t = lane & 3;
        const uint32_t ep = ld_rlx(&scr->epoch[0]) + 1;
        if (warp < 12) {
            const int n = warp / 3, part = warp - 3 * n;
            auto load = [&](int k) {
                const uint32_t full = bars + 8 * (2 * n + (k & 1));
                mbar_expect_tx(full, W_BYTES);
                tma_3d(sb + (2 * n + (k & 1)) * W_BYTES, &mw, full, (4 * hc + n) * 64, k * 64, 0);
            };
            if (part == 0 && elect_one()) { load(0); load(1); }
            __syncwarp();
            float c0[4] = {0.f, 0.f, 0.f, 0.f}, c1[4] = {0.f, 0.f, 0.f, 0.f};
            const uint32_t sel = g == 0 ? 0x3f80u : g == 1 ? 0x3f800000u : 0u;
            const uint32_t a = sb + 2 * n * W_BYTES + part * BOX + t * 256 + ((g ^ (2 * t)) << 4);
#pragma unroll 1
            for (int k = 0; k < 16; k++) {
                mbar_wait(bars + 8 * (2 * n + (k & 1)), (k >> 1) & 1, budget);
                uint4 v[8], u[8];
#pragma unroll
                for (int i = 0; i < 8; i++) { v[i] = lds4(a + (k & 1) * W_BYTES + i * 1024); u[i] = lds4(((a + 128) ^ 16) + (k & 1) * W_BYTES + i * 1024); }
#pragma unroll
                for (int i = 0; i < 8; i++) { mma16816(c0, v[i].x, v[i].y, u[i].x, u[i].y, sel, sel); mma16816(c1, v[i].z, v[i].w, u[i].z, u[i].w, sel, sel); }
                bar_sync(1 + n, 96);
                if (part == 0 && k < 14 && elect_one()) load(k + 2);
                __syncwarp();
            }
            if (t == 0) {
#pragma unroll
                for (int r = 0; r < 3; r++) {
                    const uint32_t q0 = (pack_bf16(c0[0], c0[1]) & ~1u) | (ep & 1), q1 = pack_bf16(c0[2], c0[3]), q2 = pack_bf16(c1[0], c1[1]), q3 = pack_bf16(c1[2], c1[3]);
                    st_rlx4(&scr->cs[4 * hc + n][r][part * 8 + g], q0, q1, q2, q3);
                    c0[0] -= bf_lo(q0); c0[1] -= bf_hi(q0); c0[2] -= bf_lo(q1); c0[3] -= bf_hi(q1);
                    c1[0] -= bf_lo(q2); c1[1] -= bf_hi(q2); c1[2] -= bf_lo(q3); c1[3] -= bf_hi(q3);
                }
            }
            TSC(tid == 0, 19);
        }
        if (warp < 8) TS_END();
        return;
    }
    asm volatile("barrier.cluster.arrive.relaxed.aligned;" ::: "memory");

    const int kc = b >> 4, c2 = b & 15;
    if (warp >= 12) {
        reg_dec<24>();
        if (warp == 12) {
            if (elect_one()) {
#pragma unroll 1
                for (int n = 1; n < 12; n++) {
                    load_x(n);
                    if (n == ROWS_AT) { mbar_expect_tx(bars + 8 * B_ROW, 4 * BOX); bulk_g2s(sb + OFF_FR, x + (size_t)b * 16 * 1024, 4 * BOX, bars + 8 * B_ROW); }
                    if (n == 3 || n == 7) load_w((n + 1) >> 2, n >> 2);
                }
                int s = 2; uint32_t ph = 0;
#pragma unroll 1
                for (int k = 3; k < 16; k++) {
                    mbar_wait(bars + 8 * (B_WEMPTY + s), ph, budget);
                    load_w(k, s);
                    if (++s == 3) s = 0;
                    if (s == 2) ph ^= 1;
                }
                s = 2;
#pragma unroll 1
                for (int i = 0; i < 16; i++) {
                    mbar_wait(bars + 8 * (i < 2 ? B_WEMPTY + i : i < 4 ? B_G1DONE : i < 6 ? B_F1DONE : B_WOEMPTY + s), i >= 12, budget);
                    if (i == 0) {
                        mbar_expect_tx(bars + 8 * B_XT, 4 * BOX);
#pragma unroll 1
                        for (int n = 0; n < 4; n++)
                            tma_4d(sb + (n >> 1) * OFF_X1 + (n & 1) * BOX, &mx, bars + 8 * B_XT, par * 1024 + cb * 128 + (n & 1) * 64, 0, (j0 + rh * 128) >> 5, 1 - (n >> 1));
                    }
                    const uint32_t full = bars + 8 * (B_WOFULL + s);
                    mbar_expect_tx(full, 2 * BOX);
                    tma_3d(sb + OFF_WO + s * 2 * BOX, &mwo, full, 0, ((2 * p + (i < 2 ? i ^ hp : i)) & 15) * 64, cb * 2);
                    TSC(TIMING % 10 == 4, 48 + i);
                    if (++s == 6) s = 0;
                }
            }
        } else {
            bar_sync(8, 224);
            const uint32_t ep = __shfl_sync(0xffffffffu, lds1(sb + OFF_EP), 0);
            if (warp == 13) {
                cluster_wait();
                if (elect_one()) {
                    int j = 4, q = 0, left = BUDGET; uint32_t ph = 0;
#pragma unroll 1
                    for (int n = 6; n < 32; n++) {
                        mbar_wait(bars + 8 * (B_XEMPTY + j), ph, left);
                        tma_4d_mc(sb + hp * OFF_X1 + j * BOX, &mx, bars + 8 * (B_XFULL + hp * 6 + 5 - j), par * 1024 + (n >> 1) * 64, 0, (j0 + hp * 128) >> 5, ~n & 1);
                        if (++j == 6) j = 0;
                        if (j == 4) ph ^= 1;
#pragma unroll 1
                        for (; q < (PF_RATE * (n - PF_START) >> 3) && q < 18 + PF_NW; q++) {
                            const int u = q - PF_NW;
                            if (u < 0) bulk_pf(pf.wqkv + (size_t)(1024 + 128 * u + b) * 6144, 6144);
                            else if (u < 16) bulk_pf((b < 64 ? pf.wg : pf.wu) + (size_t)(u * 64 + (b & 63)) * 7168, 7168);
                            else bulk_pf(pf.wo + (size_t)((u - 16) * 128 + b) * 8192, 8192);
                        }
                    }
                }
                __syncwarp();
                uint32_t* hs = &scr->halo[b - 16][lane * 4];
                int tries = BUDGET;
#pragma unroll 1
                for (int c = 0; c < 4; c += 2) {
                    uint4 v0 = make_uint4(0, 0, 0, 0), v1 = v0;
                    if (j0) {
#pragma unroll 1
                        do { v0 = ld_rlx4(hs + c * 128); v1 = ld_rlx4(hs + c * 128 + 128); } while ((v0.x == 0 || v1.x == 0) && --tries > 0);
                        st_rlx(hs + c * 128, 0); st_rlx(hs + c * 128 + 128, 0);
                    }
                    __syncwarp();
                    stsm4(sb + OFF_HIN + c * 512 + lane * 16, v0.x, v0.y, v0.z, v0.w);
                    stsm4(sb + OFF_HIN + c * 512 + 512 + lane * 16, v1.x, v1.y, v1.z, v1.w);
                }
                bar_arrive(11, 64);
                TSC(lane == 0, 31);
                const int src = ((mt * 2 + rh) * 2 + 1 - hp) * 1024;
                if (elect_one()) {
                    const uint32_t* fl = &scr->oflag[mt * 2 + 1 - hp][0];
                    const uint32_t inv = (ep & 1) - 1;
                    uint32_t ready = 0, ph = 0;
                    int s = 4;
#pragma unroll 1
                    for (int i = 2; i < 16; i++) {
                        const int kb = (2 * p + i) & 15;
#pragma unroll 1
                        while (!((ready >> kb) & 1) && --budget > 0) ready = ld_rlx(fl) ^ inv;
                        TSC(i == 2, 30);
                        mbar_wait(bars + 8 * (B_OEMPTY + s), ph, budget);
                        tma_2d_mc(sb + hp * OFF_X1 + s * BOX, &mo, bars + 8 * (B_OFULL + hp * 6 + s), 0, src + kb * 64);
                        TSC(TIMING % 10 == 4 && hp == 0, 32 + i);
                        if (++s == 6) s = 0;
                        if (s == 4) ph ^= 1;
                    }
                }
            } else if (warp == 14) {
                if (elect_one()) {
                    uint32_t s8 = 0, ph = 0;
                    int tries = BUDGET;
                    const uint32_t* act = scr->act[ep & 1];
                    auto counted = [&](int c, uint32_t n) {
#pragma unroll 1
                        while (ld_rlx(&scr->cnt[c][0]) != ep * n && --tries > 0) __nanosleep(POLL_NS);
                    };
                    auto weights = [&](const CUtensorMap* m, int c0, int c1, int c2_) {
                        mbar_wait(bars + 8 * B_FEMPTY + s8, ph, budget);
                        mbar_expect_tx(bars + 8 * B_FFULL + s8, F_BYTES);
                        tma_3d(sb + OFF_FS + s8 * (F_BYTES / 8), m, bars + 8 * B_FFULL + s8, c0, c1, c2_);
                    };
                    if (b < 112) {
                        counted(8, 32);
                        TS(26);
#pragma unroll 1
                        for (int q = 0; q < 16; q++) {
                            weights(&mgu, b * 32, q * 64, 0);
                            bulk_g2s(sb + OFF_FS + BOX + s8 * (F_BYTES / 8), act + 14336 + q * 256, 1024, bars + 8 * B_FFULL + s8);
                            TSC(TIMING % 10 == 5, 32 + q);
                            if (q >= 8) bulk_pf(pf.wd + (size_t)((q - 8) * 112 + b) * 8192, 8192);
                            s8 += 8;
                            if (s8 == 40) { s8 = 0; ph ^= 1; }
                        }
                    }
#pragma unroll 1
                    for (int q = -3; q < 7; q++) {
                        if (q == 0) { counted(kc, 28); TS(29); }
                        if ((unsigned)q >= 3) weights(&mwd, 0, kc * 448 + (q < 0 ? q + 3 : q) * 64, c2);
                        if (q >= 0) bulk_g2s(sb + OFF_FS + BOX + s8 * (F_BYTES / 8), act + (kc * 7 + q) * 256, 1024, bars + 8 * B_FFULL + s8);
                        TSC(TIMING % 10 == 5, 51 + q);
                        s8 += 8;
                        if (s8 == 24) { s8 = 0; if ((unsigned)q >= 3) ph ^= 1; }
                    }
                }
            } else {
#pragma unroll 1
                for (int i = lane * 16; i < CS_BYTES; i += 512) sts4(sb + OFF_CS + i, 0, 0, 0, 0);
                mbar_wait(bars + 8 * ZF_GATE, 0, budget);
                uint8_t* oz = scr->o + ((size_t)mt * 64 + nt) * BOX + lane * 16;
#pragma unroll 1
                for (int i = 0; i < 16; i++, oz += 512) {
#pragma unroll
                    for (int n = 0; n < 4; n++) st_rlx4(oz + n * 16 * BOX, 0, 0, 0, 0);
                    __nanosleep(ZF_NS);
                }
                __syncwarp();
                fence_gpu();
                mbar_wait(bars + 8 * B_RDONE, 0, budget);
                int tries = BUDGET;
#pragma unroll 1
                for (int i = lane; i < 88; i += 32) {
                    const uint2* rp = &scr->row[2 * (j0 - 8 + i) + par];
                    uint2 v0, v1, v2;
#pragma unroll 1
                    do { v0 = ld_rlx2(rp + (j0 + i < 8 ? 16 : 0)); v1 = ld_rlx2(rp + 176); v2 = ld_rlx2(rp + 352); } while ((((v0.y ^ ep) | (v1.y ^ ep) | (v2.y ^ ep)) & 31) && --tries > 0);
                    sts2(sb + OFF_STAT + i * 8, (v0.x << 16) ^ 0x80000000u, __float_as_uint(rcp(bf_hi(v0.x))));
                    sts2(sb + OFF_STAT + i * 8 + 704, (v1.x << 16) ^ 0x80000000u, __float_as_uint(rcp(bf_hi(v1.x))));
                    sts2(sb + OFF_STAT + i * 8 + 1408, (v2.x << 16) ^ 0x80000000u, __float_as_uint(rcp(bf_hi(v2.x))));
                }
                __syncwarp();
                {
                    const int row = 2047 - ((poll_all(&scr->sel[lane & 7], 31u, ep & 31, budget) >> 5) & 2047), jj = (row >> 1) - j0 - rh * 128;
                    uint32_t boxes = __reduce_or_sync(0xffffffffu, (row & 1) == par && (unsigned)jj < 128 ? 1u << (jj >> 4) : 0u);
                    sts1(sb + OFF_SEL, boxes);
#pragma unroll 1
                    for (int i = 0; boxes; i += 2) {
                        if (boxes & 1) st_rlx4(pf.out + (size_t)(2 * (j0 + rh * 128 + i + (lane >> 4)) + par) * 2048 + cb * 256 + (lane & 15) * 16, 0, 0, 0, 0);
                        else i += 14;
                        if ((i & 14) == 14) boxes >>= 1;
                    }
                }
                if (lane < 24) {
                    uint4 v[3];
#pragma unroll 1
                    while (v[0] = ld_rlx4(&scr->cs[nt][0][lane]), v[1] = ld_rlx4(&scr->cs[nt][1][lane]), v[2] = ld_rlx4(&scr->cs[nt][2][lane]),
                           (((v[0].x ^ ep) | (v[1].x ^ ep) | (v[2].x ^ ep)) & 1) && --tries > 0) __nanosleep(100);
#pragma unroll
                    for (int r = 0; r < 3; r++) sts4(sb + OFF_CS + 64 + lane * 128 + r * 16, v[r].x, v[r].y, v[r].z, v[r].w);
                }
                fence_async_smem();
                __syncwarp();
                if (elect_one()) {
                    mbar_arrive(bars + 8 * B_AUX);
                    TS(21);
                    if (lds1(sb + OFF_SEL)) { fence_gpu(); asm volatile("fence.proxy.async.global;" ::: "memory"); }
                    mbar_arrive(bars + 8 * B_ZERO);
                    TS(25);
                    mbar_expect_tx(bars + 8 * (B_OFULL + 3), BOX); mbar_expect_tx(bars + 8 * (B_OFULL + 9), BOX);
#pragma unroll 1
                    for (int v = 0; v < 2; v++) {
                        const uint32_t ring = sb + v * OFF_X1 + 2 * BOX, fb = bars + 8 * (B_OFULL + v * 6 + 2);
                        mbar_wait(bars + 8 * (B_STAGED + v), 0, budget);
                        asm volatile("red.relaxed.gpu.global.xor.b32 [%0], %1;" ::"l"(&scr->oflag[mt * 2 + 1 - v][0]), "r"(1u << nt) : "memory");
                        TS(13 + 2 * v);
                        mbar_arrive(fb);
                        mbar_wait(bars + 8 * B_G1DONE, 0, budget);
                        bulk_s2c(mapa(ring + BOX, hp ^ 1), ring, BOX, mapa(fb + 8, hp ^ 1));
                        if (v == 0) mbar_wait(bars + 8 * B_FREED, 0, budget);
#pragma unroll
                        for (int n = 0; n < 4; n++) {
                            mbar_expect_tx(bars + 8 * (B_OFULL + (n >> 1) * 6 + 4 + (n & 1)) - v * 32, BOX);
                            mbar_arrive_at(mapa(bars + 8 * B_OEMPTY, n >> 1) + (4 + (n & 1)) * 8 - v * 32);
                        }
                    }
                }
            }
        }
    } else if (warp >= 8) {
        reg_dec<40>();
        const int wq = warp - 8, ta = tid - 256;
        const uint32_t rbuf = sb + OFF_FR + wq * BOX, rbar = bars + 8 * B_ROW;
        const uint4 wv = ldg_nc(wr + ta * 8);
        if (ta == 0) sts1(sb + OFF_EP, ld_rlx(&scr->epoch[0]) + 1);
        sts4(sb + OFF_STAT + ta * 16, wv.x, wv.y, wv.z, wv.w);
        bar_sync(8, 224);
        const uint32_t ep = __shfl_sync(0xffffffffu, lds1(sb + OFF_EP), 0);
        {
            const int s = b * 16 + wq * 4 + (lane >> 3);
            if ((lane & 7) == 0) st_rlx2(&scr->row[s], 0, ep - 1);
            float sw = 0.f;
#pragma unroll 1
            for (int i = 0; i < 16; i++) { const uint32_t q = lds1(sb + OFF_STAT + i * 128 + lane * 4); sw += bf_lo(q) + bf_hi(q); }
#pragma unroll 1
            for (int o = 16; o > 0; o >>= 1) sw += __shfl_xor_sync(0xffffffffu, sw, o);
            float s1 = 0.f, s2 = 0.f, sr = 0.f;
            const uint32_t xa = rbuf + (lane >> 3) * 2048 + (lane & 7) * 16, wa = sb + OFF_STAT + (lane & 7) * 16;
            mbar_wait(rbar, 0, budget);
            TSC(ta == 0, 17);
            {
                float s1b = 0.f, s2b = 0.f, srb = 0.f;
                const uint32_t xb = rbuf + (lane >> 4) * 4096 + (lane & 15) * 16, wb = sb + OFF_STAT + (lane & 15) * 16;
                uint4 w4 = lds4(wb), u = lds4(xb), v = lds4(xb + 2048);
#pragma unroll 1
                for (int i = 1; i <= 8; i++) {
                    const uint32_t o = (i * 256) & 2047;
                    float wf[8];
#pragma unroll
                    for (int c = 0; c < 4; c++) { wf[2 * c] = bf_lo((&w4.x)[c]); wf[2 * c + 1] = bf_hi((&w4.x)[c]); }
                    w4 = lds4(wb + o);
#pragma unroll
                    for (int c = 0; c < 4; c++) {
                        const float a0 = bf_lo((&u.x)[c]), a1 = bf_hi((&u.x)[c]);
                        s1 += a0; s2 = fmaf(a0, a0, s2); sr = fmaf(a0, wf[2 * c], sr);
                        s1 += a1; s2 = fmaf(a1, a1, s2); sr = fmaf(a1, wf[2 * c + 1], sr);
                    }
                    u = lds4(xb + o);
#pragma unroll
                    for (int c = 0; c < 4; c++) {
                        const float a0 = bf_lo((&v.x)[c]), a1 = bf_hi((&v.x)[c]);
                        s1b += a0; s2b = fmaf(a0, a0, s2b); srb = fmaf(a0, wf[2 * c], srb);
                        s1b += a1; s2b = fmaf(a1, a1, s2b); srb = fmaf(a1, wf[2 * c + 1], srb);
                    }
                    v = lds4(xb + 2048 + o);
                }
                const bool up = lane & 8;
                s1 = (up ? s1b : s1) + __shfl_xor_sync(0xffffffffu, up ? s1 : s1b, 8);
                s2 = (up ? s2b : s2) + __shfl_xor_sync(0xffffffffu, up ? s2 : s2b, 8);
                sr = (up ? srb : sr) + __shfl_xor_sync(0xffffffffu, up ? sr : srb, 8);
            }
#pragma unroll
            for (int o = 1; o < 8; o <<= 1) {
                s1 += __shfl_xor_sync(0xffffffffu, s1, o); s2 += __shfl_xor_sync(0xffffffffu, s2, o); sr += __shfl_xor_sync(0xffffffffu, sr, o);
            }
            const float mean = s1 * (1.f / 1024.f), mb = bf16r(mean);
            float var = fmaf(-mean, mean, s2 * (1.f / 1024.f));
            sr = fmaf(-mb, sw, sr);
            if (__builtin_expect(__any_sync(0xffffffffu, mean * mean > 256.f * var), 0)) {
                float a2 = 0.f, ar = 0.f;
#pragma unroll 1
                for (int i = 0; i < 64; i++) {
                    const uint32_t o = (i >> 2) * 128 + (i & 3) * 4, q1 = lds1(xa + o), q2 = lds1(wa + o);
                    a2 = fmaf(bf_lo(q1) - mean, bf_lo(q1) - mean, fmaf(bf_hi(q1) - mean, bf_hi(q1) - mean, a2));
                    ar = fmaf(bf_lo(q1) - mb, bf_lo(q2), fmaf(bf_hi(q1) - mb, bf_hi(q2), ar));
                }
#pragma unroll 1
                for (int o = 1; o < 8; o <<= 1) { a2 += __shfl_xor_sync(0xffffffffu, a2, o); ar += __shfl_xor_sync(0xffffffffu, ar, o); }
                var = a2 * (1.f / 1024.f); sr = ar;
            }
            float den;
            asm("sqrt.approx.f32 %0, %1;" : "=f"(den) : "f"(bf16r(bf16r(var) + 1e-5f)));
            const uint32_t st = pack_bf16(mb, den);
            const uint32_t rb = pack_bf16(0.f, sr * rcp(bf_hi(st)) + 0.f);
            uint32_t ord = (int)rb < 0 ? ~rb & 0xffff0000u : rb | 0x80000000u;
            if ((rb & 0x7fffffffu) > 0x7f800000u) ord = 0;
            if ((lane & 7) == 0) st_rlx2(&scr->row[s], st, ord | ((2047 - s) << 5) | (ep & 31));
            __syncwarp();
            if (lane < 7) mbar_arrive(bars + 8 * (lane < 5 ? B_FEMPTY + lane : B_RDONE));
        }
        TSC(ta == 0, 18);
        if ((b >> 3) == 14) {
            const uint32_t gm = sb + OFF_E, cnt = gm + 64, res = gm + 80, list = gm + 128;
            uint32_t kv[16];
            int tries = BUDGET;
#pragma unroll 1
            do {
                uint32_t bad = 0;
#pragma unroll
                for (int n = 0; n < 16; n++) kv[n] = ld_rlx(&scr->row[n * 128 + ta].y);
#pragma unroll
                for (int n = 0; n < 16; n++) bad |= kv[n] ^ ep;
                if ((bad & 31) == 0) break;
            } while (--tries > 0);
            __syncwarp();
            TSC(ta == 0, 26);
            uint32_t m = 0;
#pragma unroll
            for (int n = 0; n < 16; n++) m = max(m, kv[n]);
            uint32_t gmax = m;
#pragma unroll
            for (int o = 1; o < 8; o <<= 1) gmax = max(gmax, __shfl_xor_sync(0xffffffffu, gmax, o));
            sts1(gm + (ta >> 3) * 4, gmax);
            sts1(cnt, 0);
            bar_sync(12, 128);
            const uint32_t c = lds1(gm + (lane & 15) * 4);
            int rank = 0;
#pragma unroll
            for (int i = 0; i < 2; i++) { const uint4 q = lds4(gm + (lane >> 4) * 32 + i * 16); rank += (q.x > c) + (q.y > c) + (q.z > c) + (q.w > c); }
            rank += __shfl_xor_sync(0xffffffffu, rank, 16);
            const uint32_t thr = redux_max(rank == 7 ? c : 0u);
#pragma unroll 1
            while (m >= thr) {
                uint32_t at, m2 = 0;
                asm volatile("atom.shared.add.u32 %0, [%1], 1;" : "=r"(at) : "r"(cnt) : "memory");
#pragma unroll
                for (int n = 0; n < 16; n++) m2 = max(m2, kv[n] < m ? kv[n] : 0u);
                sts1(list + at * 4, m);
                if (m2 == 0) break;
                m = m2;
            }
            bar_sync(12, 128);
            const int nc = lds1(cnt);
#pragma unroll 1
            for (int i = ta >> 3; i < ((nc + 3) & ~3); i += 16) {
                const uint32_t ki = lds1(list + i * 4);
                int r = 0;
#pragma unroll 1
                for (int n = lane & 7; n < nc; n += 8) r += lds1(list + n * 4) > ki;
                __syncwarp();
#pragma unroll
                for (int o = 1; o < 8; o <<= 1) r += __shfl_xor_sync(0xffffffffu, r, o);
                if (r == (b & 7) && i < nc) sts1(res, ki);
            }
            bar_sync(12, 128);
            const uint32_t k0 = lds1(res);
            const int r0 = 2047 - ((k0 >> 5) & 2047);
            TSC(ta == 0, 22);
            if (ta == 0) st_rlx(&scr->sel[b & 7], k0);
            const uint4 v0 = ldg_nc(x + (size_t)r0 * 1024 + ta * 8);
            const uint32_t s0 = ld_rlx(&scr->row[r0]);
            const float m0 = bf_lo(s0), i0 = rcp(bf_hi(s0));
            const int ao = 14336 + (ta >> 3) * 256 + (b & 7) * 32 + ((ta ^ b) & 7) * 4;
            st_rlx4(scr->act[ep & 1] + ao, norm_pair(v0.x, m0, i0), norm_pair(v0.y, m0, i0), norm_pair(v0.z, m0, i0), norm_pair(v0.w, m0, i0));
            __syncwarp();
            if (lane == 0) red_add(&scr->cnt[8][tries >> 30]);
            st_rlx4(scr->act[~ep & 1] + ao, 0, 0, 0, 0);
        }
        uint32_t s8 = 0, fph = 0, key = 0;
        const uint32_t chk = __shfl_sync(0xffffffffu, sb + OFF_FS + BOX + lane * 32 + (lane & 28), lane);
        int left = BUDGET;
#pragma unroll 1
        for (int ph = 0; ph < 2; ph++) {
            if (ph || b < 112) {
                float acc[4] = {0.f, 0.f, 0.f, 0.f};
                const uint32_t alo = sd + (ph ? dlo(OFF_FS, 8192) : dlo(OFF_FS, 4096)), ahi = ph ? dhi(1024, 1) : dhi(512, 2), astep = ph ? 128 : 64;
                const uint32_t bhi = ph ? dhi(128, 0) : dhi(1024, 1), bstep = ph ? 16 : 2, wrap = ph ? 24 : 40;
                uint32_t prev = 0, prev2 = 0;
#pragma unroll 1
                for (int q = ph ? 7 : 16; q > 0; q--) {
                    const uint32_t da = alo + s8 * (F_BYTES >> 7), db = sd + dlo(OFF_FS + BOX, 128) + s8 * (F_BYTES >> 7);
                    if (q == (ph ? 7 : F1_HOLD)) {
                        wg_wait<0>();
                        if (prev) mbar_arrive(prev);
                        prev = 0;
                        mbar_wait(bars + 8 * (ph ? FFN2_GATE : F1_GATE), 0, left);
                    }
                    mbar_wait_hot(bars + 8 * B_FFULL + s8, fph, left);
                    if (__builtin_expect(__any_sync(0xffffffffu, lds1(chk + s8 * (F_BYTES / 8)) == 0), 0)) {
                        int tries = BUDGET;
#pragma unroll 1
                        for (int n = lane * 4 + (left >> 30); n < 256; n += 128) {
                            uint4 v;
#pragma unroll 1
                            do { v = ld_rlx4(scr->act[ep & 1] + ((ph ? kc * 7 + 7 : 72) - q) * 256 + n); } while (v.x == 0 && --tries > 0);
                            __syncwarp();
                            sts4(sb + OFF_FS + BOX + s8 * (F_BYTES / 8) + n * 4, v.x, v.y, v.z, v.w);
                        }
                        NRETRY();
                        fence_async_smem();
                        __syncwarp();
                    }
                    TSC(TIMING % 10 == 3 && ta == 0, 32 + (ph ? 23 : 16) - q);
                    wg_fence();
#pragma unroll
                    for (int j = 0; j < 4; j++) wgmma_n8<1, 0>(acc, mkdesc(da + j * astep, ahi), mkdesc(db + j * bstep, bhi), 1);
                    wg_commit();
                    uint32_t done = F1_DEPTH == 2 ? prev2 : prev;
                    prev2 = prev;
                    if (lane == 0) prev = bars + 8 * B_FEMPTY + s8;
                    wg_wait<F1_DEPTH>();
                    if (ph) { wg_wait<F2_DEPTH>(); done = F2_DEPTH ? prev2 : prev; }
                    if (done) mbar_arrive(done);
                    s8 += 8;
                    if (s8 == wrap) { s8 = 0; fph ^= 1; }
                }
                wg_wait<0>();
                const int ln = lane + (left >> 30);
                if (ph == 0) {
                    if (prev) mbar_arrive(prev);
                    const bool second = (wq >= 2) != (swap_gu != 0);
                    const uint32_t xa = sb + OFF_GU + ((wq & 1) * 32 + ln) * 16;
                    if (second) sts4(xa, __float_as_uint(acc[0]), __float_as_uint(acc[1]), __float_as_uint(acc[2]), __float_as_uint(acc[3]));
                    bar_sync(12, 128);
                    if (!second) {
                        const float4 up = lds4f(xa);
                        float hv[4];
#pragma unroll
                        for (int c = 0; c < 4; c++) { const float ga = bf16r(acc[c]); hv[c] = bf16r(ga * sigmoidf(ga)) * bf16r((&up.x)[c]); }
                        const int ao = (b * 4 + (wq & 1) * 2) * 32 + ln;
                        st_rlx(scr->act[ep & 1] + ao, max(movm(pack_bf16(hv[0], hv[1])), 1u)); st_rlx(scr->act[ep & 1] + 32 + ao, max(movm(pack_bf16(hv[2], hv[3])), 1u));
                        __syncwarp();
                        if (ln == 0) red_add(&scr->cnt[b / 14][0]);
                        st_rlx(scr->act[~ep & 1] + ao, 0); st_rlx(scr->act[~ep & 1] + 32 + ao, 0);
                    }
                } else {
#pragma unroll
                    for (int c = 0; c < 4; c++) st_rlx(&scr->ypart[kc][2 * (ln & 3) + (c & 1)][c2 * 64 + wq * 16 + (c >> 1) * 8 + (ln >> 2)], (__float_as_uint(acc[c]) & ~1u) | (ep & 1));
                }
                TSC(ta == 0, 22 + ph);
            }
            const int ln = lane + (left >> 30);
            if (ph == 0) {
                if ((ta & 126) == 64) mbar_arrive(bars + 8 * B_F1DONE);
                key = poll_all(&scr->sel[ln & 7], 31u, ep & 31, left);
            }
        }
        {
            const int row = 2047 - ((key >> 5) & 2047);
            const float sig = bf16r(sigmoidf(__uint_as_float(((int)key < 0 ? key & 0x7fffffffu : ~key) & 0xffff0000u)));
            uint32_t own = __ballot_sync(0xffffffffu, (row & 1) == par && (row >> 8) == (mt & 3) * 2 + rh) & 255;
            if (wq & 2) own &= own - 1;
            mbar_wait(bars + 8 * B_ZERO, 0, left);
#pragma unroll 1
            for (; own; own &= own - 1, own &= own - 1) {
                const int j = __ffs(own) - 1, col = cb * 128 + (wq & 1) * 64 + (lane & 15) * 4;
                const uint32_t* src = &scr->ypart[lane >> 4][j][col];
                uint4 v[4]; int tries = BUDGET;
#pragma unroll 1
                do {
#pragma unroll
                    for (int m = 0; m < 4; m++) v[m] = ld_rlx4(src + m * 2 * 8192);
                } while ((((v[0].x ^ ep) | (v[1].x ^ ep) | (v[2].x ^ ep) | (v[3].x ^ ep)) & 1) && --tries > 0);
                __syncwarp();
                float a[4];
                const float sj = __shfl_sync(0xffffffffu, sig, j);
                const int rj = __shfl_sync(0xffffffffu, row, j);
#pragma unroll
                for (int c = 0; c < 4; c++) {
                    a[c] = (__uint_as_float((&v[0].x)[c]) + __uint_as_float((&v[1].x)[c])) + (__uint_as_float((&v[2].x)[c]) + __uint_as_float((&v[3].x)[c]));
                    a[c] = bf16r(a[c] + __shfl_xor_sync(0xffffffffu, a[c], 16)) * sj;
                }
                if (lane < 16) asm volatile("red.relaxed.gpu.global.add.noftz.v2.bf16x2 [%0], {%1, %2};" ::"l"(pf.out + (size_t)rj * 2048 + col * 2), "r"(pack_bf16(a[0], a[1])), "r"(pack_bf16(a[2], a[3])) : "memory");
            }
        }
        TSC(ta == 0, 24);
    } else {
        reg_inc<224>();
        const int w = warp >> 2, wi = warp & 3, g = lane >> 2, t = lane & 3;
        const bool elect = (tid & 127) == 0;
        const uint32_t mad = (lane & 15) * 128 + (((lane >> 4) ^ (lane & 7)) << 4);
        float acc[64];
        const uint32_t ring = sb + w * OFF_X1, ofull = bars + 8 * (B_OFULL + w * 6), oempty = mapa(bars + 8 * B_OEMPTY, w);
        const int r0 = rh * 128 + wi * 32 + (1 - w) * 16 + g;
        {
            float acc0[96], acc1[96];
            const uint32_t sta = sb + OFF_STAT + (8 + w * 128 + wi * 32) * 8;
            {
                const uint32_t xfull = bars + 8 * (B_XFULL + w * 6 + 5), xempty = mapa(bars + 8 * B_XEMPTY, w), dx0 = sd + dlo(w * OFF_X1, 16);
                uint32_t s8 = 16, ps8 = 0, ph = 0;
                cluster_wait();
#pragma unroll 1
                for (int k = 0; k < 16; k++) {
                    const uint32_t dx = dx0 + s8 * (2 * BOX >> 7), dw = sd + dlo(OFF_W, BOX) + s8 * (W_BYTES >> 7);
                    mbar_wait(bars + 8 * B_WFULL + s8, ph, budget);
                    mbar_wait(xfull - 2 * s8, ph, budget);
                    TSC(elect && k == 0, 1 + 8 * w);
                    TSC(TIMING % 10 == 1 && tid == 0, 32 + k);
                    wg_wait<0>();
                    wg_fence();
#pragma unroll
                    for (int kk = 0; kk < 4; kk++) wgmma_n192<0, 1>(acc1, mkdesc(dx + kk * 2, dhi(1024, 1)), mkdesc(dw + kk * 128, dhi(1024, 1)), kk ? 1 : k);
                    wg_commit();
                    if (elect && k > 0) {
                        mbar_arrive(bars + 8 * B_WEMPTY + ps8);
                        if (k <= 13) { mbar_expect_tx(xfull - 2 * ps8 - 8, BOX); mbar_arrive_at(xempty + 2 * ps8 + 8); }
                    }
                    if (k == 15) {
                        mbar_wait(bars + 8 * B_AUX, 0, budget);
                        const uint32_t zero = budget >> 30, pm = t & 1 ? 0x4432 : 0x3232, ra = sta + ((t >> 1) * 16 + g) * 8;
                        const uint32_t a0 = __byte_perm(lds1(ra), 0, pm), a1 = __byte_perm(lds1(ra + 64), 0, pm), a2 = a0 & zero, a3 = a1 & zero;
                        wg_fence();
                        wgmma_rs_n192(acc1, a0, a1, a2, a3, mkdesc(sd + dlo(OFF_CS, 0), dhi(128, 0)));
                        wgmma_rs_n192(acc0, a0, a1, a2, a3, mkdesc(sd + dlo(OFF_CS + 64, 0), dhi(128, 0)));
                        wg_commit();
                    }
                    mbar_wait(xfull - 2 * s8 - 8, ph, budget);
                    wg_wait<0>();
                    wg_fence();
#pragma unroll
                    for (int kk = 0; kk < 4; kk++) wgmma_n192<0, 1>(acc0, mkdesc(dx + 512 + kk * 2, dhi(1024, 1)), mkdesc(dw + kk * 128, dhi(1024, 1)), kk ? 1 : k);
                    wg_commit();
                    if (elect && k <= 12) { mbar_expect_tx(xfull - 2 * s8, BOX); mbar_arrive_at(xempty + 2 * s8); }
                    ps8 = s8;
                    s8 = s8 == 16 ? 0 : s8 + 8;
                    if (s8 == 16) ph ^= 1;
                }
            }
            const uint32_t zero = budget >> 30;
            const bool u0 = 2 * t > g, u1 = 2 * t + 1 > g;
            uint32_t mU = (u0 ? 0xffffu : 0u) | (u1 ? 0xffff0000u : 0u);
            uint32_t ka0 = sta + (2 * t - (u0 ? 8 : 0)) * 8 + 4, ka1 = sta + (2 * t + 1 - (u1 ? 8 : 0)) * 8 + 4;
            float rk[2][4], fu[2][4], fn[2][4];
            auto factors = [&](int h) {
#pragma unroll
                for (int n = 0; n < 4; n += 2) {
                    const float rq = lds1f(sta + (16 * h + 4 * n + g) * 8 + 4) * (0.17677669529663687f * 1.4426950408889634f);
                    rk[h][n] = lds1f(ka0 + h * 128 + n * 32); rk[h][n + 1] = lds1f(ka1 + h * 128 + n * 32);
                    const float f0 = rq * rk[h][n], f1 = rq * rk[h][n + 1];
                    fu[h][n] = u0 ? f0 : 0.f; fn[h][n] = f0 - fu[h][n]; fu[h][n + 1] = u1 ? f1 : 0.f; fn[h][n + 1] = f1 - fu[h][n + 1];
                }
#pragma unroll
                for (int n = 0; n < 4; n++) asm volatile("" : "+f"(fu[h][n]), "+f"(fn[h][n]));
            };
            uint8_t* og = scr->o + ((size_t)(mt * 4 + w * 2) * 16 + nt) * BOX + wi * 256 + lane * 4;
            TSC(elect, 19 + w);
            uint32_t pk0[48], pk1[48], o[16] = {};
#pragma unroll
            for (int j = 0; j < 48; j++) if (j < 16 || (j & 1)) pk1[j] = pack_here(acc1[2 * j], acc1[2 * j + 1]);
            if (warp < 7) {
#pragma unroll
                for (int c = 0; c < 4; c++) stsm4(ring + 4 * BOX + wi * 2048 + c * 512 + lane * 16, pk1[17 + 8 * c], pk1[19 + 8 * c], pk1[21 + 8 * c], pk1[23 + 8 * c]);
                bar_arrive(1 + warp, 64);
            } else if (j0 != 768) {
#pragma unroll
                for (int c = 0; c < 4; c++) {
                    pk1[17 + 8 * c] = max(pk1[17 + 8 * c], 1u);
                    st_rlx4(&scr->halo[b][c * 128 + lane * 4], pk1[17 + 8 * c], pk1[19 + 8 * c], pk1[21 + 8 * c], pk1[23 + 8 * c]);
                }
            }
            TSC(tid == 224, 28);
#pragma unroll
            for (int j = 16; j < 48; j += 2) pk1[j] = pack_here(acc1[2 * j], acc1[2 * j + 1]);
            factors(1);
            uint32_t od = sb + 2 * BOX + wi * 256 + (lane >> 4) * 1024 + (lane & 15) * 16, g1peer = mapa(bars + 8 * B_G1DONE, hp ^ 1);
            uint32_t ha = sb + (warp == 0 ? OFF_HIN : warp <= 4 ? 4 * BOX - 2048 : OFF_X1 + 4 * BOX - 5 * 2048) + warp * 2048 + lane * 16;
            const bool first = warp == 0 && j0 == 0;
            float bias0 = first && u0 ? -INFINITY : 0.f, bias1 = first && u1 ? -INFINITY : 0.f;
            asm volatile("" : "+l"(og), "+r"(mU), "+r"(od), "+r"(ha), "+f"(bias0), "+f"(bias1));
            mbar_wait(bars + 8 * B_XT, 0, budget);
            mbar_wait(bars + 8 * (B_WEMPTY + 1), 0, budget);
            TSC(elect, 12 + 2 * w);
            wg_wait<0>();
            if (elect) { mbar_arrive(bars + 8 * B_G1DONE); mbar_arrive_at(g1peer); }
            TSC(elect, 2 + 8 * w);
            float ci[4];
#pragma unroll
            for (int n = 0; n < 4; n++) ci[n] = __uint_as_float((0x03800000u + n) | (budget >> 30));
            auto hand_over = [&](int v) {
                asm volatile("{\n.reg .pred p;\nsetp.ne.b32 p, %17, 0;\n"
                             "@p stmatrix.sync.aligned.m8n8.x4.shared.b16 [%16], {%0,%1,%2,%3};\n@p stmatrix.sync.aligned.m8n8.x4.shared.b16 [%16 + 2048], {%4,%5,%6,%7};\n"
                             "@p stmatrix.sync.aligned.m8n8.x4.shared.b16 [%16 + 4096], {%8,%9,%10,%11};\n@p stmatrix.sync.aligned.m8n8.x4.shared.b16 [%16 + 6144], {%12,%13,%14,%15};\n"
                             FENCE_PRED "fence.proxy.async.shared::cta;\n}"
                             ::"r"(o[0]), "r"(o[1]), "r"(o[2]), "r"(o[3]), "r"(o[4]), "r"(o[5]), "r"(o[6]), "r"(o[7]), "r"(o[8]), "r"(o[9]), "r"(o[10]), "r"(o[11]),
                               "r"(o[12]), "r"(o[13]), "r"(o[14]), "r"(o[15]), "r"(od + v * OFF_X1), "r"((int)(w == rh)) : "memory");
                TSC(tid == 0, v ? 27 : 5);
#pragma unroll
                for (int i = 0; i < 16; i++) asm volatile("st.global.u32 [%0], %1;" ::"l"(og + (1 - v) * 16 * BOX + (i >> 1) * 1024 + (i & 1) * 128), "r"(o[i]) : "memory");
                __syncwarp();
                if (lane == 0) mbar_arrive(bars + 8 * (B_STAGED + v));
            };
#pragma unroll
            for (int j = 32; j < 48; j++) pk1[j] = movm(pk1[j]);
#pragma unroll
            for (int j = EARLY_PK; j < 48; j++) if (j >= 32 || (j & 1) || EARLY_PK < 17) pk0[j] = pack_here(acc0[2 * j], acc0[2 * j + 1]);
#pragma unroll
            for (int j = 32; j < 48; j++) pk0[j] = movm(pk0[j]);
            factors(0);
            attn_pair<2>(pk1, pk1 + 16, pk1 + 32, pk0 + 17, pk0 + 33, fu[1], fn[1], rk[1], 0.f, 0.f, mU, zero, ci, o);
            hand_over(0);
            TSC(elect, 3 + 8 * w);
#pragma unroll
            for (int j = 0; j < 32; j++) if (j < EARLY_PK || (!(j & 1) && EARLY_PK == 17)) pk0[j] = pack_here(acc0[2 * j], acc0[2 * j + 1]);
            bar_sync(warp ? warp : 11, 64);
            uint32_t hl[16];
            ldsm4(hl, ha); ldsm4(hl + 4, ha + 512); ldsm4t(hl + 8, ha + 1024); ldsm4t(hl + 12, ha + 1536);
            __syncwarp();
            if (lane == 0) mbar_arrive(bars + 8 * B_FREED);
            attn_pair<1>(pk0, pk0 + 16, pk0 + 32, hl, hl + 8, fu[0], fn[0], rk[0], bias0, bias1, mU, zero, ci, o);
            const float2 s0 = lds2f(sb + OFF_STAT + (8 + r0) * 8), s1 = lds2f(sb + OFF_STAT + (16 + r0) * 8);
            const float m0 = s0.x * s0.y, f0 = 1.f + s0.y, m1 = s1.x * s1.y, f1 = 1.f + s1.y;
            uint32_t xt[32];
#pragma unroll
            for (int j = 0; j < 8; j++) ldsm4(xt + 4 * j, ((ring + wi * 2048 + mad) ^ ((j & 3) * 32)) + (j >> 2) * BOX);
            hand_over(1);
#pragma unroll
            for (int j = 0; j < 32; j++) {
                acc[2 * j] = fmaf(bf_lo(xt[j]), j & 1 ? f1 : f0, j & 1 ? m1 : m0); acc[2 * j + 1] = fmaf(bf_hi(xt[j]), j & 1 ? f1 : f0, j & 1 ? m1 : m0);
            }
        }
        TSC(tid == 0, 4);
        {
            const uint32_t da0 = sd + dlo(w * OFF_X1, 1024), db0 = sd + dlo(OFF_WO, BOX);
            const uint32_t chk = ring + wi * 256 + (lane >> 3) * 1032 + (lane & 7) * 32 + (lane & 4);
            uint32_t s8 = 16, ps8 = 0, ph = 0;
            mbar_wait(ofull + s8, 0, budget);
            mbar_wait(bars + 8 * B_WOFULL + s8, 0, budget);
            TSC(TIMING % 10 == 2 && elect, 32 + w * 16);
            const uint32_t ahi = dhi(128, 0) | (budget >> 30), bhi = dhi(1024, 1) | (budget >> 30);
            const int last = w ? HOLD : 16;
            uint32_t rel = elect ? 0x7fe : 0;
#pragma unroll 1
            for (int i = 1;;) {
                const uint32_t da = da0 + s8 * (BOX >> 7), db = db0 + s8 * (BOX >> 6);
                wg_fence();
#pragma unroll
                for (int kk = 0; kk < 4; kk++) {
                    wgmma_n128<0, 1>(acc, mkdesc(da + kk * 128, ahi), mkdesc(db + kk * 128, bhi), 1);
                    if (kk & 1) wg_commit();
                }
                wg_wait<2>();
                if (rel & 1) { mbar_expect_tx(ofull + ps8, BOX); mbar_arrive_at(oempty + ps8); mbar_arrive(bars + 8 * B_WOEMPTY + ps8); }
                if (i == 16) break;
                rel >>= 1;
                ps8 = s8;
#pragma unroll 1
                do {
                    s8 = s8 == 40 ? 0 : s8 + 8;
                    if (s8 == 16) ph ^= 1;
                    uint32_t bad;
                    asm volatile("{\n.reg .pred p, q, r;\n.reg .u32 u, v;\nmbarrier.try_wait.parity.shared::cta.b64 q, [%2], %3;\nmbarrier.try_wait.parity.shared::cta.b64 p, [%1], %3;\n"
                                 "setp.ne.and.u32 r, %5, 1, p;\nmov.u32 u, 1;\nmov.u32 v, 1;\n@r ld.shared.u32 u, [%4];\n@r ld.shared.u32 v, [%4 + 4096];\n"
                                 "and.pred p, p, q;\nmin.u32 u, u, v;\nsetp.eq.or.u32 p, u, 0, !p;\nvote.sync.any.pred p, p, 0xffffffff;\nselp.u32 %0, 1, 0, p;\n}"
                                 : "=r"(bad) : "r"(ofull + s8), "r"(bars + 8 * B_WOFULL + s8), "r"(ph), "r"(chk + s8 * (BOX / 8)), "r"(i) : "memory");
                    if (__builtin_expect(bad, 0)) {
                        mbar_wait(ofull + s8, ph, budget);
                        mbar_wait(bars + 8 * B_WOFULL + s8, ph, budget);
                        if (__any_sync(0xffffffffu, min(lds1(chk + s8 * (BOX / 8)), lds1(chk + s8 * (BOX / 8) + 4096)) == 0)) {
                            const uint32_t at = wi * 256 + (lane >> 4) * 1024 + (lane & 15) * 16;
                            const uint8_t* src = scr->o + ((size_t)((mt * 2 + rh) * 2 + 1 - w) * 16 + ((2 * p + (i < 2 ? i ^ hp : i)) & 15)) * BOX + at;
#pragma unroll 1
                            for (int n = 0; n < 8192; n += 2048) {
                                uint4 v; int tries = 4096;
#pragma unroll 1
                                do { v = ld_rlx4(src + n); } while (v.x == 0 && --tries > 0);
                                sts4(ring + s8 * (BOX / 8) + at + n, v.x, v.y, v.z, v.w);
                            }
                            NRETRY();
                            fence_async_smem();
                            __syncwarp();
                        }
                    }
                    TSC(TIMING % 10 == 1 && tid == 0, 48 + i);
                    TSC(TIMING % 10 == 2 && elect, 32 + w * 16 + i);
                } while (++i > last && i < 16);
                if (i > last) break;
                wg_wait<1>();
            }
            if (w) {
                bar_sync(9, 256);
#pragma unroll 1
                for (int i = HOLD - 10; i < 6; i++) {
                    wg_fence();
#pragma unroll
                    for (int kk = 0; kk < 4; kk++) wgmma_n128<0, 1>(acc, mkdesc(da0 + i * 512 + kk * 128, ahi), mkdesc(db0 + i * 1024 + kk * 128, bhi), 1);
                    wg_commit();
                }
            } else bar_arrive(9, 256);
            const bool add = (__shfl_sync(0xffffffffu, lds1(sb + OFF_SEL), 0) >> (wi * 2 + 1 - w)) & 1;
            wg_wait<0>();
            TSC(elect, 7 + 9 * w);
            const uint32_t os0 = ring + wi * 4096;
#pragma unroll
            for (int hf = 0; hf < OUT_PARTS; hf++) {
#pragma unroll
                for (int j = hf * (8 / OUT_PARTS); j < (hf + 1) * (8 / OUT_PARTS); j++)
                    stsm4(((os0 + mad) ^ ((j & 3) * 32)) + (j >> 2) * 2048, pack_here(acc[8 * j], acc[8 * j + 1]), pack_here(acc[8 * j + 2], acc[8 * j + 3]),
                          pack_here(acc[8 * j + 4], acc[8 * j + 5]), pack_here(acc[8 * j + 6], acc[8 * j + 7]));
                fence_async_smem();
                __syncwarp();
                if (elect_one())
                    asm volatile("{\n.reg .pred p;\nsetp.ne.b32 p, %6, 0;\n@!p cp.async.bulk.tensor.5d.global.shared::cta.bulk_group [%0, {%2, %2, %3, %4, %5}], [%1];\n"
                                 "@p cp.reduce.async.bulk.tensor.5d.global.shared::cta.add.bulk_group [%0, {%2, %2, %3, %4, %5}], [%1];\n}"
                                 ::"l"(&mout), "r"(os0 + hf * 2048), "r"(0), "r"(((j0 + rh * 128) >> 5) + wi), "r"(1 - w), "r"(par * 16 + cb * 2 + hf), "r"((int)add) : "memory");
            }
            asm volatile("cp.async.bulk.commit_group;\ncp.async.bulk.wait_group.read 0;" ::: "memory");
            if (b == 0 && tid == 0) st_rlx(&scr->epoch[0], lds1(sb + OFF_EP));
            TSC(elect, 8 - 2 * w);
            TS_END();
        }
    }
}

typedef CUresult (*EncodeFn)(CUtensorMap*, CUtensorMapDataType, cuuint32_t, void*, const cuuint64_t*, const cuuint64_t*, const cuuint32_t*,
                             const cuuint32_t*, CUtensorMapInterleave, CUtensorMapSwizzle, CUtensorMapL2promotion, CUtensorMapFloatOOBfill);

CUtensorMap make_map(EncodeFn fn, const void* base, int rank, const cuuint64_t* dims, const cuuint64_t* strides, const cuuint32_t* box,
                     CUtensorMapSwizzle swz = CU_TENSOR_MAP_SWIZZLE_128B, CUtensorMapL2promotion pro = CU_TENSOR_MAP_L2_PROMOTION_L2_256B) {
    CUtensorMap m;
    cuuint32_t es[5] = {1, 1, 1, 1, 1};
    fn(&m, CU_TENSOR_MAP_DATA_TYPE_BFLOAT16, rank, (void*)base, dims, strides, box, es, CU_TENSOR_MAP_INTERLEAVE_NONE,
       swz, pro, CU_TENSOR_MAP_FLOAT_OOB_FILL_NONE);
    return m;
}

}

extern "C" void kernel_launch(void* const* d_in, const int* in_sizes, int n_in, void* d_out, int out_size) {
    (void)in_sizes; (void)n_in; (void)out_size;
    const __nv_bfloat16* x = (const __nv_bfloat16*)d_in[0];
    const __nv_bfloat16* wqkv = (const __nv_bfloat16*)d_in[1];
    const __nv_bfloat16* wo = (const __nv_bfloat16*)d_in[2];
    const __nv_bfloat16* wr = (const __nv_bfloat16*)d_in[4];
    const __nv_bfloat16* wg = (const __nv_bfloat16*)d_in[5];
    const __nv_bfloat16* wu = (const __nv_bfloat16*)d_in[6];
    const __nv_bfloat16* wd = (const __nv_bfloat16*)d_in[7];
    static EncodeFn fn = nullptr;
    static Scratch* scr = nullptr;
    if (!fn) {
        void* p = nullptr; cudaDriverEntryPointQueryResult q;
        cudaGetDriverEntryPoint("cuTensorMapEncodeTiled", &p, cudaEnableDefault, &q);
        fn = (EncodeFn)p;
        cudaFuncSetAttribute(fused_kernel, cudaFuncAttributeMaxDynamicSharedMemorySize, SMEM_LAUNCH);
        cudaGetSymbolAddress((void**)&scr, g_scr);
    }
    const cuuint64_t xd[4] = {2048, 16, 32, 2}, xs[4] = {4096, 131072, 65536, 128}, od[5] = {64, 16, 32, 2, 32};
    const cuuint32_t xb[4] = {64, 16, 4, 1}, ob[5] = {64, 16, 1, 1, 2 / OUT_PARTS};
    const cuuint64_t wdm[3] = {1024, 1024, 3}, wst[2] = {6144, 2048};
    const cuuint32_t wb[3] = {64, 64, 3};
    const cuuint64_t wod[3] = {64, 1024, 16}, wdd[3] = {64, 3584, 16}, wos[2] = {2048, 128};
    const cuuint32_t wob[3] = {64, 64, 2}, wdb[3] = {64, 64, 1};
    CUtensorMap mx = make_map(fn, x, 4, xd, xs, xb), mw = make_map(fn, wqkv, 3, wdm, wst, wb);
    CUtensorMap mwo = make_map(fn, wo, 3, wod, wos, wob), mout = make_map(fn, d_out, 5, od, xs, ob);
    const int swap_gu = wu < wg;
    const cuuint64_t gd[3] = {3584, 1024, 2}, gst[2] = {7168, (cuuint64_t)(swap_gu ? (const char*)wg - (const char*)wu : (const char*)wu - (const char*)wg)};
    const cuuint32_t gb[3] = {32, 64, 2};
    CUtensorMap mgu = make_map(fn, swap_gu ? wu : wg, 3, gd, gst, gb, CU_TENSOR_MAP_SWIZZLE_64B, CU_TENSOR_MAP_L2_PROMOTION_L2_128B);
    CUtensorMap mwd = make_map(fn, wd, 3, wdd, wos, wdb, CU_TENSOR_MAP_SWIZZLE_128B, CU_TENSOR_MAP_L2_PROMOTION_L2_128B);
    const cuuint64_t md[2] = {64, 32768}, ms[1] = {128};
    const cuuint32_t mb[2] = {64, 64};
    CUtensorMap mo = make_map(fn, scr, 2, md, ms, mb, CU_TENSOR_MAP_SWIZZLE_NONE, CU_TENSOR_MAP_L2_PROMOTION_NONE);
    cudaLaunchConfig_t cfg = {};
    cfg.gridDim = dim3(132); cfg.blockDim = dim3(512); cfg.dynamicSmemBytes = SMEM_LAUNCH; cfg.stream = cudaStreamPerThread;
    cudaLaunchAttribute at[1];
    at[0].id = cudaLaunchAttributeClusterDimension; at[0].val.clusterDim.x = 2; at[0].val.clusterDim.y = 1; at[0].val.clusterDim.z = 1;
    cfg.attrs = at; cfg.numAttrs = 1;
    cudaLaunchKernelEx(&cfg, fused_kernel, mx, mw, mwo, mout, mgu, mwd, mo, x, wr, scr, swap_gu, Weights{(const char*)wqkv, (const char*)wo, (const char*)wg, (const char*)wu, (const char*)wd, (char*)d_out});
}
```

```cpp
#include <cuda_runtime.h>
#include <cuda.h>
#include <cuda_bf16.h>
#include <stdint.h>

namespace {

constexpr int BOX = 8192, W_BYTES = 3 * BOX;
constexpr int OFF_X1 = 6 * BOX, OFF_FR = 12 * BOX, OFF_E = 16 * BOX, OFF_W = 19 * BOX;
constexpr int OFF_WO = OFF_E;
constexpr int OFF_HIN = OFF_FR + 2048, OFF_GU = OFF_HIN + 2048, OFF_FS = OFF_GU + 1024;
constexpr int F_BYTES = 9216;
constexpr int CS_BYTES = 3136;
constexpr int OFF_CS = OFF_FS + 5 * F_BYTES;
constexpr int OFF_STAT = 28 * BOX;
constexpr int OFF_SEL = OFF_STAT + 2112;
constexpr int OFF_EP = OFF_SEL + 32;
constexpr int OFF_BAR = OFF_EP + 16;
constexpr int B_WFULL = 0, B_XFULL = 3, B_AUX = 15, B_XT = 16, B_ROW = 17, B_WOFULL = 18, B_OFULL = 24, B_FFULL = 36, B_ZERO = 41;
constexpr int B_WEMPTY = 42, B_F1DONE = 45, B_XEMPTY = 46, B_WOEMPTY = 52, B_OEMPTY = 58;
constexpr int B_G1DONE = 66, B_FEMPTY = 67, B_STAGED = 72, B_RDONE = 75, B_FREED = 76, NBAR = 78;
constexpr int SMEM_BYTES = OFF_BAR + NBAR * 8;
static_assert(OFF_FS + 3 * F_BYTES == OFF_E && OFF_CS + CS_BYTES <= OFF_W && SMEM_BYTES + 256 <= 232448 && OFF_BAR % 8 == 0, "smem");
#define POLL_NS 30
#define PF_RATE 8
#define PF_START 7
#define ZF_NS 100
#define FFN2_GATE (B_STAGED + 1)
#define PF_NW 0
#define EARLY_PK 17
#define FENCE_PRED "@p "
#define ZF_GATE B_ROW
#define HOLD 12
#define F1_DEPTH 1
#define F2_DEPTH 0
#define F1_HOLD 2
#define F1_GATE B_G1DONE
#define OUT_PARTS 2
#define ROWS_AT 11
constexpr int BUDGET = 1 << 18;

struct Scratch {
    uint8_t o[2048 * 1024 * 2];
    uint32_t ypart[8][8][1024];
    uint32_t halo[128][512];
    uint32_t act[2][14336 + 4096];
    uint2 row[2048];
    uint4 cs[16][3][24];
    uint32_t oflag[16][32];
    uint32_t cnt[9][32];
    uint32_t sel[32], epoch[32];
};
__device__ __align__(1024) Scratch g_scr;
struct Weights { const char *wqkv, *wo, *wg, *wu, *wd; char* out; };

#define TS(i) do {} while (0)
#define TS_END() do {} while (0)
#define TSC(c, i) do {} while (0)
#define NRETRY() do {} while (0)
constexpr int SMEM_LAUNCH = SMEM_BYTES;
__device__ __forceinline__ uint32_t smem_u32(const void* p) { return (uint32_t)__cvta_generic_to_shared(p); }
__device__ __forceinline__ void mbar_init(uint32_t bar, uint32_t cnt) { asm volatile("mbarrier.init.shared::cta.b64 [%0], %1;" ::"r"(bar), "r"(cnt) : "memory"); }
__device__ __forceinline__ void mbar_expect_tx(uint32_t bar, uint32_t bytes) { asm volatile("mbarrier.arrive.expect_tx.shared::cta.b64 _, [%0], %1;" ::"r"(bar), "r"(bytes) : "memory"); }
__device__ __forceinline__ void mbar_arrive(uint32_t bar) { asm volatile("mbarrier.arrive.shared::cta.b64 _, [%0];" ::"r"(bar) : "memory"); }
__device__ __forceinline__ uint32_t mapa(uint32_t a, uint32_t cta) { uint32_t r; asm("mapa.shared::cluster.u32 %0, %1, %2;" : "=r"(r) : "r"(a), "r"(cta)); return r; }
__device__ __forceinline__ void mbar_arrive_at(uint32_t cbar) { asm volatile("mbarrier.arrive.shared::cluster.b64 _, [%0];" ::"r"(cbar) : "memory"); }
__device__ __forceinline__ void mbar_wait(uint32_t bar, uint32_t parity, int& budget) {
    asm volatile("{\n.reg .pred p;\nLAB_WAIT:\nmbarrier.try_wait.parity.shared::cta.b64 p, [%1], %2;\n"
                 "add.s32 %0, %0, -1;\nsetp.gt.and.s32 p, %0, 0, !p;\n@p bra LAB_WAIT;\n}" : "+r"(budget) : "r"(bar), "r"(parity) : "memory");
}
__device__ __forceinline__ void mbar_wait_hot(uint32_t bar, uint32_t parity, int& budget) {
    asm volatile("{\n.reg .pred p;\nmbarrier.try_wait.parity.shared::cta.b64 p, [%1], %2;\n@p bra LAB_DONE;\nLAB_WAIT:\nmbarrier.try_wait.parity.shared::cta.b64 p, [%1], %2;\n"
                 "add.s32 %0, %0, -1;\nsetp.gt.and.s32 p, %0, 0, !p;\n@p bra LAB_WAIT;\nLAB_DONE:\n}" : "+r"(budget) : "r"(bar), "r"(parity) : "memory");
}
__device__ __forceinline__ void tma_2d_mc(uint32_t dst, const CUtensorMap* m, uint32_t bar, int c0, int c1) {
    asm volatile("cp.async.bulk.tensor.2d.shared::cluster.global.mbarrier::complete_tx::bytes.multicast::cluster [%0], [%1, {%3, %4}], [%2], %5;" ::"r"(dst), "l"(m), "r"(bar), "r"(c0), "r"(c1), "h"((uint16_t)3) : "memory");
}
__device__ __forceinline__ void tma_3d(uint32_t dst, const CUtensorMap* m, uint32_t bar, int c0, int c1, int c2) {
    asm volatile("cp.async.bulk.tensor.3d.shared::cluster.global.mbarrier::complete_tx::bytes [%0], [%1, {%3, %4, %5}], [%2];" ::"r"(dst), "l"(m), "r"(bar), "r"(c0), "r"(c1), "r"(c2) : "memory");
}
__device__ __forceinline__ void tma_4d(uint32_t dst, const CUtensorMap* m, uint32_t bar, int c0, int c1, int c2, int c3) {
    asm volatile("cp.async.bulk.tensor.4d.shared::cluster.global.mbarrier::complete_tx::bytes [%0], [%1, {%3, %4, %5, %6}], [%2];" ::"r"(dst), "l"(m), "r"(bar), "r"(c0), "r"(c1), "r"(c2), "r"(c3) : "memory");
}
__device__ __forceinline__ void tma_4d_mc(uint32_t dst, const CUtensorMap* m, uint32_t bar, int c0, int c1, int c2, int c3) {
    asm volatile("cp.async.bulk.tensor.4d.shared::cluster.global.mbarrier::complete_tx::bytes.multicast::cluster [%0], [%1, {%3, %4, %5, %6}], [%2], %7;" ::"r"(dst), "l"(m), "r"(bar), "r"(c0), "r"(c1), "r"(c2), "r"(c3), "h"((uint16_t)3) : "memory");
}
__device__ __forceinline__ void bulk_pf(const void* p, uint32_t bytes) { asm volatile("cp.async.bulk.prefetch.L2.global [%0], %1;" ::"l"(p), "r"(bytes) : "memory"); }
__device__ __forceinline__ void bulk_g2s(uint32_t dst, const void* src, uint32_t bytes, uint32_t bar) {
    asm volatile("cp.async.bulk.shared::cluster.global.mbarrier::complete_tx::bytes [%0], [%1], %2, [%3];" ::"r"(dst), "l"(src), "r"(bytes), "r"(bar) : "memory");
}
__device__ __forceinline__ void bulk_s2c(uint32_t cdst, uint32_t src, uint32_t bytes, uint32_t cbar) {
    asm volatile("cp.async.bulk.shared::cluster.shared::cta.mbarrier::complete_tx::bytes [%0], [%1], %2, [%3];" ::"r"(cdst), "r"(src), "r"(bytes), "r"(cbar) : "memory");
}
__device__ __forceinline__ void cluster_wait() { asm volatile("barrier.cluster.wait.aligned;" ::: "memory"); }
__device__ __forceinline__ void fence_gpu() { asm volatile("fence.acq_rel.gpu;" ::: "memory"); }
__device__ __forceinline__ void fence_async_smem() { asm volatile("fence.proxy.async.shared::cta;" ::: "memory"); }
__device__ __forceinline__ void wg_fence() { asm volatile("wgmma.fence.sync.aligned;" ::: "memory"); }
__device__ __forceinline__ void wg_commit() { asm volatile("wgmma.commit_group.sync.aligned;" ::: "memory"); }
template <int N> __device__ __forceinline__ void wg_wait() { asm volatile("wgmma.wait_group.sync.aligned %0;" ::"n"(N) : "memory"); }
__device__ __forceinline__ uint64_t mkdesc(uint32_t lo, uint32_t hi) { return ((uint64_t)hi << 32) | lo; }
__host__ __device__ constexpr uint32_t dhi(uint32_t sbo, uint32_t mode) { return (sbo >> 4) | (mode << 30); }
__host__ __device__ constexpr uint32_t dlo(uint32_t off, uint32_t lbo) { return (off >> 4) + ((lbo >> 4) << 16); }
__device__ __forceinline__ bool elect_one() {
    uint32_t e;
    asm volatile("{\n.reg .pred p;\nelect.sync _|p, 0xffffffff;\nselp.u32 %0, 1, 0, p;\n}" : "=r"(e));
    return e;
}
template <int R> __device__ __forceinline__ void reg_inc() { asm volatile("setmaxnreg.inc.sync.aligned.u32 %0;" ::"n"(R)); }
template <int R> __device__ __forceinline__ void reg_dec() { asm volatile("setmaxnreg.dec.sync.aligned.u32 %0;" ::"n"(R)); }
__device__ __forceinline__ void bar_sync(int id, int n) { asm volatile("bar.sync %0, %1;" ::"r"(id), "r"(n) : "memory"); }
__device__ __forceinline__ void bar_arrive(int id, int n) { asm volatile("bar.arrive %0, %1;" ::"r"(id), "r"(n) : "memory"); }
__device__ __forceinline__ uint32_t pack_bf16(float lo, float hi) { uint32_t r; asm("cvt.rn.bf16x2.f32 %0, %1, %2;" : "=r"(r) : "f"(hi), "f"(lo)); return r; }
__device__ __forceinline__ uint32_t pack_here(float lo, float hi) { uint32_t r; asm volatile("cvt.rn.bf16x2.f32 %0, %1, %2;" : "=r"(r) : "f"(hi), "f"(lo)); return r; }
__device__ __forceinline__ float bf_lo(uint32_t u) { return __uint_as_float(u << 16); }
__device__ __forceinline__ float bf_hi(uint32_t u) { return __uint_as_float(u & 0xffff0000u); }
__device__ __forceinline__ float bf16r(float v) { return bf_lo(pack_bf16(v, 0.f)); }
__device__ __forceinline__ float rcp(float x) { float r; asm("rcp.approx.ftz.f32 %0, %1;" : "=f"(r) : "f"(x)); return r; }
__device__ __forceinline__ float ex2(float x) { float r; asm("ex2.approx.ftz.f32 %0, %1;" : "=f"(r) : "f"(x)); return r; }
__device__ __forceinline__ float sigmoidf(float v) { return rcp(1.f + ex2(v * -1.4426950408889634f)); }
__device__ __forceinline__ uint32_t movm(uint32_t a) { uint32_t d; asm volatile("movmatrix.sync.aligned.m8n8.trans.b16 %0, %1;" : "=r"(d) : "r"(a)); return d; }
__device__ __forceinline__ void mma16816(float (&c)[4], uint32_t a0, uint32_t a1, uint32_t a2, uint32_t a3, uint32_t b0, uint32_t b1) {
    asm volatile("mma.sync.aligned.m16n8k16.row.col.f32.bf16.bf16.f32 {%0,%1,%2,%3}, {%4,%5,%6,%7}, {%8,%9}, {%0,%1,%2,%3};"
                 : "+f"(c[0]), "+f"(c[1]), "+f"(c[2]), "+f"(c[3]) : "r"(a0), "r"(a1), "r"(a2), "r"(a3), "r"(b0), "r"(b1));
}
__device__ __forceinline__ void mma1688(float (&c)[4], uint32_t a0, uint32_t a1, uint32_t b0) {
    asm volatile("mma.sync.aligned.m16n8k8.row.col.f32.bf16.bf16.f32 {%0,%1,%2,%3}, {%4,%5}, {%6}, {%0,%1,%2,%3};"
                 : "+f"(c[0]), "+f"(c[1]), "+f"(c[2]), "+f"(c[3]) : "r"(a0), "r"(a1), "r"(b0));
}
__device__ __forceinline__ void stsm4(uint32_t a, uint32_t r0, uint32_t r1, uint32_t r2, uint32_t r3) {
    asm volatile("stmatrix.sync.aligned.m8n8.x4.shared.b16 [%0], {%1,%2,%3,%4};" ::"r"(a), "r"(r0), "r"(r1), "r"(r2), "r"(r3) : "memory");
}
__device__ __forceinline__ void ldsm4(uint32_t* r, uint32_t a) {
    asm volatile("ldmatrix.sync.aligned.m8n8.x4.shared.b16 {%0,%1,%2,%3}, [%4];" : "=r"(r[0]), "=r"(r[1]), "=r"(r[2]), "=r"(r[3]) : "r"(a) : "memory");
}
__device__ __forceinline__ void ldsm4t(uint32_t* r, uint32_t a) {
    asm volatile("ldmatrix.sync.aligned.m8n8.x4.trans.shared.b16 {%0,%1,%2,%3}, [%4];" : "=r"(r[0]), "=r"(r[1]), "=r"(r[2]), "=r"(r[3]) : "r"(a) : "memory");
}
__device__ __forceinline__ uint32_t ld_rlx(const void* p) { uint32_t v; asm volatile("ld.relaxed.gpu.global.u32 %0, [%1];" : "=r"(v) : "l"(p) : "memory"); return v; }
__device__ __forceinline__ uint32_t ld_acq(const void* p) { uint32_t v; asm volatile("ld.acquire.gpu.global.u32 %0, [%1];" : "=r"(v) : "l"(p) : "memory"); return v; }
__device__ __forceinline__ uint2 ld_rlx2(const void* p) { uint2 v; asm volatile("ld.relaxed.gpu.global.v2.u32 {%0,%1}, [%2];" : "=r"(v.x), "=r"(v.y) : "l"(p) : "memory"); return v; }
__device__ __forceinline__ uint4 ld_rlx4(const void* p) { uint4 v; asm volatile("ld.relaxed.gpu.global.v4.u32 {%0,%1,%2,%3}, [%4];" : "=r"(v.x), "=r"(v.y), "=r"(v.z), "=r"(v.w) : "l"(p) : "memory"); return v; }
__device__ __forceinline__ void st_rlx(void* p, uint32_t v) { asm volatile("st.relaxed.gpu.global.u32 [%0], %1;" ::"l"(p), "r"(v) : "memory"); }
__device__ __forceinline__ void st_rlx2(void* p, uint32_t a, uint32_t b) { asm volatile("st.relaxed.gpu.global.v2.u32 [%0], {%1,%2};" ::"l"(p), "r"(a), "r"(b) : "memory"); }
__device__ __forceinline__ void st_rlx4(void* p, uint32_t a, uint32_t b, uint32_t c, uint32_t d) { asm volatile("st.relaxed.gpu.global.v4.u32 [%0], {%1,%2,%3,%4};" ::"l"(p), "r"(a), "r"(b), "r"(c), "r"(d) : "memory"); }
__device__ __forceinline__ void red_add(uint32_t* p) { asm volatile("red.relaxed.gpu.global.add.u32 [%0], 1;" ::"l"(p) : "memory"); }
__device__ __forceinline__ uint4 ldg_nc(const void* p) { uint4 v; asm volatile("ld.global.nc.v4.u32 {%0,%1,%2,%3}, [%4];" : "=r"(v.x), "=r"(v.y), "=r"(v.z), "=r"(v.w) : "l"(p)); return v; }
__device__ __forceinline__ void sts4(uint32_t a, uint32_t x, uint32_t y, uint32_t z, uint32_t w) { asm volatile("st.shared.v4.u32 [%0], {%1,%2,%3,%4};" ::"r"(a), "r"(x), "r"(y), "r"(z), "r"(w) : "memory"); }
__device__ __forceinline__ void sts2(uint32_t a, uint32_t x, uint32_t y) { asm volatile("st.shared.v2.u32 [%0], {%1,%2};" ::"r"(a), "r"(x), "r"(y) : "memory"); }
__device__ __forceinline__ void sts1(uint32_t a, uint32_t v) { asm volatile("st.shared.u32 [%0], %1;" ::"r"(a), "r"(v) : "memory"); }
__device__ __forceinline__ uint4 lds4(uint32_t a) { uint4 v; asm volatile("ld.shared.v4.u32 {%0,%1,%2,%3}, [%4];" : "=r"(v.x), "=r"(v.y), "=r"(v.z), "=r"(v.w) : "r"(a) : "memory"); return v; }
__device__ __forceinline__ float4 lds4f(uint32_t a) { float4 v; asm volatile("ld.shared.v4.f32 {%0,%1,%2,%3}, [%4];" : "=f"(v.x), "=f"(v.y), "=f"(v.z), "=f"(v.w) : "r"(a) : "memory"); return v; }
__device__ __forceinline__ float2 lds2f(uint32_t a) { float2 v; asm volatile("ld.shared.v2.f32 {%0,%1}, [%2];" : "=f"(v.x), "=f"(v.y) : "r"(a) : "memory"); return v; }
__device__ __forceinline__ float lds1f(uint32_t a) { float v; asm volatile("ld.shared.f32 %0, [%1];" : "=f"(v) : "r"(a) : "memory"); return v; }
__device__ __forceinline__ uint32_t lds1(uint32_t a) { uint32_t v; asm volatile("ld.shared.u32 %0, [%1];" : "=r"(v) : "r"(a) : "memory"); return v; }
__device__ __forceinline__ uint32_t redux_max(uint32_t v) { uint32_t r; asm volatile("redux.sync.max.u32 %0, %1, 0xffffffff;" : "=r"(r) : "r"(v)); return r; }
__device__ __forceinline__ uint32_t poll_all(const uint32_t* p, uint32_t mask, uint32_t want, int& budget) {
    uint32_t v;
#pragma unroll 1
    while (v = ld_acq(p), !__all_sync(0xffffffffu, (v & mask) == want) && --budget > 0) __nanosleep(POLL_NS);
    return v;
}

template <int TA, int TB>
__device__ __forceinline__ void wgmma_n192(float (&d)[96], uint64_t da, uint64_t db, int keep) {
    asm volatile("{\n.reg .pred p;\nsetp.ne.b32 p, %98, 0;\n"
        "wgmma.mma_async.sync.aligned.m64n192k16.f32.bf16.bf16 "
        "{%0, %1, %2, %3, %4, %5, %6, %7, %8, %9, %10, %11, %12, %13, %14, %15, "
        "%16, %17, %18, %19, %20, %21, %22, %23, %24, %25, %26, %27, %28, %29, %30, %31, "
        "%32, %33, %34, %35, %36, %37, %38, %39, %40, %41, %42, %43, %44, %45, %46, %47, "
        "%48, %49, %50, %51, %52, %53, %54, %55, %56, %57, %58, %59, %60, %61, %62, %63, "
        "%64, %65, %66, %67, %68, %69, %70, %71, %72, %73, %74, %75, %76, %77, %78, %79, "
        "%80, %81, %82, %83, %84, %85, %86, %87, %88, %89, %90, %91, %92, %93, %94, %95}, "
        "%96, %97, p, 1, 1, %99, %100;\n}\n"
        : "+f"(d[0]), "+f"(d[1]), "+f"(d[2]), "+f"(d[3]), "+f"(d[4]), "+f"(d[5]), "+f"(d[6]), "+f"(d[7]),
          "+f"(d[8]), "+f"(d[9]), "+f"(d[10]), "+f"(d[11]), "+f"(d[12]), "+f"(d[13]), "+f"(d[14]), "+f"(d[15]),
          "+f"(d[16]), "+f"(d[17]), "+f"(d[18]), "+f"(d[19]), "+f"(d[20]), "+f"(d[21]), "+f"(d[22]), "+f"(d[23]),
          "+f"(d[24]), "+f"(d[25]), "+f"(d[26]), "+f"(d[27]), "+f"(d[28]), "+f"(d[29]), "+f"(d[30]), "+f"(d[31]),
          "+f"(d[32]), "+f"(d[33]), "+f"(d[34]), "+f"(d[35]), "+f"(d[36]), "+f"(d[37]), "+f"(d[38]), "+f"(d[39]),
          "+f"(d[40]), "+f"(d[41]), "+f"(d[42]), "+f"(d[43]), "+f"(d[44]), "+f"(d[45]), "+f"(d[46]), "+f"(d[47]),
          "+f"(d[48]), "+f"(d[49]), "+f"(d[50]), "+f"(d[51]), "+f"(d[52]), "+f"(d[53]), "+f"(d[54]), "+f"(d[55]),
          "+f"(d[56]), "+f"(d[57]), "+f"(d[58]), "+f"(d[59]), "+f"(d[60]), "+f"(d[61]), "+f"(d[62]), "+f"(d[63]),
          "+f"(d[64]), "+f"(d[65]), "+f"(d[66]), "+f"(d[67]), "+f"(d[68]), "+f"(d[69]), "+f"(d[70]), "+f"(d[71]),
          "+f"(d[72]), "+f"(d[73]), "+f"(d[74]), "+f"(d[75]), "+f"(d[76]), "+f"(d[77]), "+f"(d[78]), "+f"(d[79]),
          "+f"(d[80]), "+f"(d[81]), "+f"(d[82]), "+f"(d[83]), "+f"(d[84]), "+f"(d[85]), "+f"(d[86]), "+f"(d[87]),
          "+f"(d[88]), "+f"(d[89]), "+f"(d[90]), "+f"(d[91]), "+f"(d[92]), "+f"(d[93]), "+f"(d[94]), "+f"(d[95])
        : "l"(da), "l"(db), "r"(keep), "n"(TA), "n"(TB));
}
template <int TA, int TB>
__device__ __forceinline__ void wgmma_n128(float (&d)[64], uint64_t da, uint64_t db, int keep) {
    asm volatile("{\n.reg .pred p;\nsetp.ne.b32 p, %66, 0;\n"
        "wgmma.mma_async.sync.aligned.m64n128k16.f32.bf16.bf16 "
        "{%0, %1, %2, %3, %4, %5, %6, %7, %8, %9, %10, %11, %12, %13, %14, %15, "
        "%16, %17, %18, %19, %20, %21, %22, %23, %24, %25, %26, %27, %28, %29, %30, %31, "
        "%32, %33, %34, %35, %36, %37, %38, %39, %40, %41, %42, %43, %44, %45, %46, %47, "
        "%48, %49, %50, %51, %52, %53, %54, %55, %56, %57, %58, %59, %60, %61, %62, %63}, "
        "%64, %65, p, 1, 1, %67, %68;\n}\n"
        : "+f"(d[0]), "+f"(d[1]), "+f"(d[2]), "+f"(d[3]), "+f"(d[4]), "+f"(d[5]), "+f"(d[6]), "+f"(d[7]),
          "+f"(d[8]), "+f"(d[9]), "+f"(d[10]), "+f"(d[11]), "+f"(d[12]), "+f"(d[13]), "+f"(d[14]), "+f"(d[15]),
          "+f"(d[16]), "+f"(d[17]), "+f"(d[18]), "+f"(d[19]), "+f"(d[20]), "+f"(d[21]), "+f"(d[22]), "+f"(d[23]),
          "+f"(d[24]), "+f"(d[25]), "+f"(d[26]), "+f"(d[27]), "+f"(d[28]), "+f"(d[29]), "+f"(d[30]), "+f"(d[31]),
          "+f"(d[32]), "+f"(d[33]), "+f"(d[34]), "+f"(d[35]), "+f"(d[36]), "+f"(d[37]), "+f"(d[38]), "+f"(d[39]),
          "+f"(d[40]), "+f"(d[41]), "+f"(d[42]), "+f"(d[43]), "+f"(d[44]), "+f"(d[45]), "+f"(d[46]), "+f"(d[47]),
          "+f"(d[48]), "+f"(d[49]), "+f"(d[50]), "+f"(d[51]), "+f"(d[52]), "+f"(d[53]), "+f"(d[54]), "+f"(d[55]),
          "+f"(d[56]), "+f"(d[57]), "+f"(d[58]), "+f"(d[59]), "+f"(d[60]), "+f"(d[61]), "+f"(d[62]), "+f"(d[63])
        : "l"(da), "l"(db), "r"(keep), "n"(TA), "n"(TB));
}
template <int TA, int TB>
__device__ __forceinline__ void wgmma_n8(float (&d)[4], uint64_t da, uint64_t db, int keep) {
    asm volatile("{\n.reg .pred p;\nsetp.ne.b32 p, %6, 0;\n"
        "wgmma.mma_async.sync.aligned.m64n8k16.f32.bf16.bf16 "
        "{%0, %1, %2, %3}, "
        "%4, %5, p, 1, 1, %7, %8;\n}\n"
        : "+f"(d[0]), "+f"(d[1]), "+f"(d[2]), "+f"(d[3])
        : "l"(da), "l"(db), "r"(keep), "n"(TA), "n"(TB));
}
__device__ __forceinline__ void wgmma_rs_n192(float (&d)[96], uint32_t a0, uint32_t a1, uint32_t a2, uint32_t a3, uint64_t db) {
    asm volatile("{\n.reg .pred p;\nsetp.ne.b32 p, 1, 0;\n"
        "wgmma.mma_async.sync.aligned.m64n192k16.f32.bf16.bf16 "
        "{%0, %1, %2, %3, %4, %5, %6, %7, %8, %9, %10, %11, %12, %13, %14, %15, "
        "%16, %17, %18, %19, %20, %21, %22, %23, %24, %25, %26, %27, %28, %29, %30, %31, "
        "%32, %33, %34, %35, %36, %37, %38, %39, %40, %41, %42, %43, %44, %45, %46, %47, "
        "%48, %49, %50, %51, %52, %53, %54, %55, %56, %57, %58, %59, %60, %61, %62, %63, "
        "%64, %65, %66, %67, %68, %69, %70, %71, %72, %73, %74, %75, %76, %77, %78, %79, "
        "%80, %81, %82, %83, %84, %85, %86, %87, %88, %89, %90, %91, %92, %93, %94, %95}, "
        "{%96, %97, %98, %99}, %100, p, 1, 1, 1;\n}\n"
        : "+f"(d[0]), "+f"(d[1]), "+f"(d[2]), "+f"(d[3]), "+f"(d[4]), "+f"(d[5]), "+f"(d[6]), "+f"(d[7]),
          "+f"(d[8]), "+f"(d[9]), "+f"(d[10]), "+f"(d[11]), "+f"(d[12]), "+f"(d[13]), "+f"(d[14]), "+f"(d[15]),
          "+f"(d[16]), "+f"(d[17]), "+f"(d[18]), "+f"(d[19]), "+f"(d[20]), "+f"(d[21]), "+f"(d[22]), "+f"(d[23]),
          "+f"(d[24]), "+f"(d[25]), "+f"(d[26]), "+f"(d[27]), "+f"(d[28]), "+f"(d[29]), "+f"(d[30]), "+f"(d[31]),
          "+f"(d[32]), "+f"(d[33]), "+f"(d[34]), "+f"(d[35]), "+f"(d[36]), "+f"(d[37]), "+f"(d[38]), "+f"(d[39]),
          "+f"(d[40]), "+f"(d[41]), "+f"(d[42]), "+f"(d[43]), "+f"(d[44]), "+f"(d[45]), "+f"(d[46]), "+f"(d[47]),
          "+f"(d[48]), "+f"(d[49]), "+f"(d[50]), "+f"(d[51]), "+f"(d[52]), "+f"(d[53]), "+f"(d[54]), "+f"(d[55]),
          "+f"(d[56]), "+f"(d[57]), "+f"(d[58]), "+f"(d[59]), "+f"(d[60]), "+f"(d[61]), "+f"(d[62]), "+f"(d[63]),
          "+f"(d[64]), "+f"(d[65]), "+f"(d[66]), "+f"(d[67]), "+f"(d[68]), "+f"(d[69]), "+f"(d[70]), "+f"(d[71]),
          "+f"(d[72]), "+f"(d[73]), "+f"(d[74]), "+f"(d[75]), "+f"(d[76]), "+f"(d[77]), "+f"(d[78]), "+f"(d[79]),
          "+f"(d[80]), "+f"(d[81]), "+f"(d[82]), "+f"(d[83]), "+f"(d[84]), "+f"(d[85]), "+f"(d[86]), "+f"(d[87]),
          "+f"(d[88]), "+f"(d[89]), "+f"(d[90]), "+f"(d[91]), "+f"(d[92]), "+f"(d[93]), "+f"(d[94]), "+f"(d[95])
        : "r"(a0), "r"(a1), "r"(a2), "r"(a3), "l"(db));
}

template <int HS>
__device__ __forceinline__ void attn_pair(const uint32_t* q, const uint32_t* k, const uint32_t* v, const uint32_t* kh, const uint32_t* vh,
                                          const float* fu, const float* fn, const float* rk, float bias0, float bias1, uint32_t mU, uint32_t zero, const float* ci, uint32_t* o) {
    float s0[2][4] = {}, s1[2][4] = {}, s2[2][4] = {};
#pragma unroll
    for (int n = 0; n < 4; n++) {
        const int hd = n & 1, a = 8 * hd + 2 * (n & 2);
        mma16816(s1[hd], q[a], q[a + 1], q[a + 2], q[a + 3], k[a], k[a + 2]);
        mma16816(s2[hd], q[a], q[a + 1], q[a + 2], q[a + 3], k[a + 1], k[a + 3]);
    }
#pragma unroll
    for (int n = 0; n < 4; n++) {
        const int hd = n & 1, a = 8 * hd + 2 * (n & 2);
        mma16816(s0[hd], q[a], q[a + 1], q[a + 2], q[a + 3], kh[HS * (a / 2)], kh[HS * (a / 2 + 1)]);
    }
    float e[2][4], m[2][2];
#pragma unroll
    for (int hd = 0; hd < 2; hd++) {
        e[hd][2] = fmaf(s1[hd][2], fu[2], s2[hd][2] * fn[2]); e[hd][3] = fmaf(s1[hd][3], fu[3], s2[hd][3] * fn[3]);
        e[hd][0] = fmaf(s0[hd][0], fu[0], fmaf(s1[hd][0], fn[0], bias0)); e[hd][1] = fmaf(s0[hd][1], fu[1], fmaf(s1[hd][1], fn[1], bias1));
        m[hd][1] = fmaxf(e[hd][2], e[hd][3]); m[hd][0] = fmaxf(e[hd][0], e[hd][1]);
    }
#pragma unroll
    for (int x = 1; x < 3; x++)
#pragma unroll
        for (int n = 0; n < 4; n++) m[n & 1][1 - (n >> 1)] = fmaxf(m[n & 1][1 - (n >> 1)], __shfl_xor_sync(0xffffffffu, m[n & 1][1 - (n >> 1)], x));
#pragma unroll
    for (int hd = 0; hd < 2; hd++) {
#pragma unroll
        for (int n = 0; n < 4; n++) e[hd][n] = ex2(e[hd][n] - m[hd][n >> 1]);
        float sum[4] = {};
        mma1688(sum, pack_bf16(e[hd][0], e[hd][1]), pack_bf16(e[hd][2], e[hd][3]), 0x3f803f80u);
        const float i0 = rcp(sum[0]), i1 = rcp(sum[2]);
        const uint32_t plo = pack_bf16(e[hd][0] * rk[0] * i0, e[hd][1] * rk[1] * i0), phi = pack_bf16(e[hd][2] * rk[2] * i1, e[hd][3] * rk[3] * i1);
        const uint32_t z0 = plo & zero, z1 = phi & zero;
        const uint32_t a0 = plo & ~mU, a1 = phi & mU, a3 = phi & ~mU, b0 = plo & mU;
#pragma unroll
        for (int jj = 0; jj < 4; jj++) {
            float c[4];
            asm volatile("mma.sync.aligned.m16n8k16.row.col.f32.bf16.bf16.f32 {%0,%1,%2,%3}, {%4,%5,%6,%7}, {%8,%9}, {%10,%11,%12,%13};"
                         : "=f"(c[0]), "=f"(c[1]), "=f"(c[2]), "=f"(c[3])
                         : "r"(a0), "r"(a1), "r"(z0), "r"(a3), "r"(v[8 * hd + 2 * jj]), "r"(v[8 * hd + 2 * jj + 1]), "f"(ci[0]), "f"(ci[1]), "f"(ci[2]), "f"(ci[3]));
            mma1688(c, b0, z1, vh[HS * (4 * hd + jj)]);
            o[8 * hd + 2 * jj] = pack_bf16(c[0], c[1]); o[8 * hd + 2 * jj + 1] = pack_bf16(c[2], c[3]);
        }
    }
}

__device__ __forceinline__ uint32_t norm_pair(uint32_t u, float m, float rinv) {
    const uint32_t d = pack_bf16(bf_lo(u) - m, bf_hi(u) - m);
    return max(pack_bf16(bf_lo(d) * rinv, bf_hi(d) * rinv), 1u);
}

__global__ void __launch_bounds__(512, 1)
fused_kernel(const __grid_constant__ CUtensorMap mx, const __grid_constant__ CUtensorMap mw, const __grid_constant__ CUtensorMap mwo,
             const __grid_constant__ CUtensorMap mout, const __grid_constant__ CUtensorMap mgu, const __grid_constant__ CUtensorMap mwd,
             const __grid_constant__ CUtensorMap mo,
             const __nv_bfloat16* __restrict__ x, const __nv_bfloat16* __restrict__ wr, Scratch* __restrict__ scr, int swap_gu, const Weights pf) {
    extern __shared__ __align__(1024) uint8_t smem[];
    const uint32_t sb = smem_u32(smem);
    const uint32_t bars = sb + OFF_BAR;
    const int tid = threadIdx.x, lane = tid & 31, warp = __shfl_sync(0xffffffffu, tid >> 5, 0);
    const uint32_t sd = (sb & 0x3FFFF) >> 4;
    const int hp = blockIdx.x & 1, cl = blockIdx.x >> 1;
    int pr = cl - 4 + (max(cl - 36, 0) * 37 >> 8);
    asm("{\n.reg .pred p;\nsetp.lt.s32 p, %1, 4;\nselp.s32 %0, %2, %0, p;\n}" : "+r"(pr) : "r"(cl), "r"(39 + 8 * cl));
    const int b = pr * 2 + hp, mt = pr >> 3, p = pr & 7, nt = 2 * p + hp, rh = p & 1, cb = (p & 6) + hp;
    const int par = mt >> 2, j0 = (mt & 3) * 256;
    int budget = BUDGET;

    TSC(tid == 0, 0);
    auto load_w = [&](int k, int s) {
        const uint32_t full = bars + 8 * (B_WFULL + s);
        mbar_expect_tx(full, W_BYTES);
        tma_3d(sb + OFF_W + s * W_BYTES, &mw, full, nt * 64, k * 64, 0);
    };
    auto load_x = [&](int n) {
        const int w = n & 1, j = n < 4 ? (n >> 1) + 4 : (n >> 1) - 2;
        const uint32_t full = bars + 8 * (B_XFULL + w * 6 + 5 - j);
        mbar_expect_tx(full, BOX);
        tma_4d(sb + w * OFF_X1 + j * BOX, &mx, full, par * 1024 + (n >> 2) * 64, 0, (j0 + w * 128) >> 5, (~n >> 1) & 1);
    };
    if (warp < NBAR / 6 && elect_one()) {
        const uint32_t cnt = warp < B_WEMPTY / 6 ? 1 : warp < B_G1DONE / 6 ? 2 : warp < B_STAGED / 6 ? 4 : 8;
#pragma unroll
        for (int i = 0; i < 6; i++) mbar_init(bars + 48 * warp + 8 * i, cnt);
        asm volatile("fence.mbarrier_init.release.cluster;" ::: "memory");
        if (warp == 0 && b < 128) { load_x(0); load_w(0, 2); }
    }
    __syncthreads();

    if (b >= 128) {
        const int hc = b - 128, g = lane >> 2, t = lane & 3;
        const uint32_t ep = ld_rlx(&scr->epoch[0]) + 1;
        if (warp < 12) {
            const int n = warp / 3, part = warp - 3 * n;
            auto load = [&](int k) {
                const uint32_t full = bars + 8 * (2 * n + (k & 1));
                mbar_expect_tx(full, W_BYTES);
                tma_3d(sb + (2 * n + (k & 1)) * W_BYTES, &mw, full, (4 * hc + n) * 64, k * 64, 0);
            };
            if (part == 0 && elect_one()) { load(0); load(1); }
            __syncwarp();
            float c0[4] = {0.f, 0.f, 0.f, 0.f}, c1[4] = {0.f, 0.f, 0.f, 0.f};
            const uint32_t sel = g == 0 ? 0x3f80u : g == 1 ? 0x3f800000u : 0u;
            const uint32_t a = sb + 2 * n * W_BYTES + part * BOX + t * 256 + ((g ^ (2 * t)) << 4);
#pragma unroll 1
            for (int k = 0; k < 16; k++) {
                mbar_wait(bars + 8 * (2 * n + (k & 1)), (k >> 1) & 1, budget);
                uint4 v[8], u[8];
#pragma unroll
                for (int i = 0; i < 8; i++) { v[i] = lds4(a + (k & 1) * W_BYTES + i * 1024); u[i] = lds4(((a + 128) ^ 16) + (k & 1) * W_BYTES + i * 1024); }
#pragma unroll
                for (int i = 0; i < 8; i++) { mma16816(c0, v[i].x, v[i].y, u[i].x, u[i].y, sel, sel); mma16816(c1, v[i].z, v[i].w, u[i].z, u[i].w, sel, sel); }
                bar_sync(1 + n, 96);
                if (part == 0 && k < 14 && elect_one()) load(k + 2);
                __syncwarp();
            }
            if (t == 0) {
#pragma unroll
                for (int r = 0; r < 3; r++) {
                    const uint32_t q0 = (pack_bf16(c0[0], c0[1]) & ~1u) | (ep & 1), q1 = pack_bf16(c0[2], c0[3]), q2 = pack_bf16(c1[0], c1[1]), q3 = pack_bf16(c1[2], c1[3]);
                    st_rlx4(&scr->cs[4 * hc + n][r][part * 8 + g], q0, q1, q2, q3);
                    c0[0] -= bf_lo(q0); c0[1] -= bf_hi(q0); c0[2] -= bf_lo(q1); c0[3] -= bf_hi(q1);
                    c1[0] -= bf_lo(q2); c1[1] -= bf_hi(q2); c1[2] -= bf_lo(q3); c1[3] -= bf_hi(q3);
                }
            }
            TSC(tid == 0, 19);
        }
        if (warp < 8) TS_END();
        return;
    }
    asm volatile("barrier.cluster.arrive.relaxed.aligned;" ::: "memory");

    const int kc = b >> 4, c2 = b & 15;
    if (warp >= 12) {
        reg_dec<24>();
        if (warp == 12) {
            if (elect_one()) {
#pragma unroll 1
                for (int n = 1; n < 12; n++) {
                    load_x(n);
                    if (n == ROWS_AT) { mbar_expect_tx(bars + 8 * B_ROW, 4 * BOX); bulk_g2s(sb + OFF_FR, x + (size_t)b * 16 * 1024, 4 * BOX, bars + 8 * B_ROW); }
                    if (n == 3 || n == 7) load_w((n + 1) >> 2, n >> 2);
                }
                int s = 2; uint32_t ph = 0;
#pragma unroll 1
                for (int k = 3; k < 16; k++) {
                    mbar_wait(bars + 8 * (B_WEMPTY + s), ph, budget);
                    load_w(k, s);
                    if (++s == 3) s = 0;
                    if (s == 2) ph ^= 1;
                }
                s = 2;
#pragma unroll 1
                for (int i = 0; i < 16; i++) {
                    mbar_wait(bars + 8 * (i < 2 ? B_WEMPTY + i : i < 4 ? B_G1DONE : i < 6 ? B_F1DONE : B_WOEMPTY + s), i >= 12, budget);
                    if (i == 0) {
                        mbar_expect_tx(bars + 8 * B_XT, 4 * BOX);
#pragma unroll 1
                        for (int n = 0; n < 4; n++)
                            tma_4d(sb + (n >> 1) * OFF_X1 + (n & 1) * BOX, &mx, bars + 8 * B_XT, par * 1024 + cb * 128 + (n & 1) * 64, 0, (j0 + rh * 128) >> 5, 1 - (n >> 1));
                    }
                    const uint32_t full = bars + 8 * (B_WOFULL + s);
                    mbar_expect_tx(full, 2 * BOX);
                    tma_3d(sb + OFF_WO + s * 2 * BOX, &mwo, full, 0, ((2 * p + (i < 2 ? i ^ hp : i)) & 15) * 64, cb * 2);
                    TSC(TIMING % 10 == 4, 48 + i);
                    if (++s == 6) s = 0;
                }
            }
        } else {
            bar_sync(8, 224);
            const uint32_t ep = __shfl_sync(0xffffffffu, lds1(sb + OFF_EP), 0);
            if (warp == 13) {
                cluster_wait();
                if (elect_one()) {
                    int j = 4, q = 0, left = BUDGET; uint32_t ph = 0;
#pragma unroll 1
                    for (int n = 6; n < 32; n++) {
                        mbar_wait(bars + 8 * (B_XEMPTY + j), ph, left);
                        tma_4d_mc(sb + hp * OFF_X1 + j * BOX, &mx, bars + 8 * (B_XFULL + hp * 6 + 5 - j), par * 1024 + (n >> 1) * 64, 0, (j0 + hp * 128) >> 5, ~n & 1);
                        if (++j == 6) j = 0;
                        if (j == 4) ph ^= 1;
#pragma unroll 1
                        for (; q < (PF_RATE * (n - PF_START) >> 3) && q < 18 + PF_NW; q++) {
                            const int u = q - PF_NW;
                            if (u < 0) bulk_pf(pf.wqkv + (size_t)(1024 + 128 * u + b) * 6144, 6144);
                            else if (u < 16) bulk_pf((b < 64 ? pf.wg : pf.wu) + (size_t)(u * 64 + (b & 63)) * 7168, 7168);
                            else bulk_pf(pf.wo + (size_t)((u - 16) * 128 + b) * 8192, 8192);
                        }
                    }
                }
                __syncwarp();
                uint32_t* hs = &scr->halo[b - 16][lane * 4];
                int tries = BUDGET;
#pragma unroll 1
                for (int c = 0; c < 4; c += 2) {
                    uint4 v0 = make_uint4(0, 0, 0, 0), v1 = v0;
                    if (j0) {
#pragma unroll 1
                        do { v0 = ld_rlx4(hs + c * 128); v1 = ld_rlx4(hs + c * 128 + 128); } while ((v0.x == 0 || v1.x == 0) && --tries > 0);
                        st_rlx(hs + c * 128, 0); st_rlx(hs + c * 128 + 128, 0);
                    }
                    __syncwarp();
                    stsm4(sb + OFF_HIN + c * 512 + lane * 16, v0.x, v0.y, v0.z, v0.w);
                    stsm4(sb + OFF_HIN + c * 512 + 512 + lane * 16, v1.x, v1.y, v1.z, v1.w);
                }
                bar_arrive(11, 64);
                TSC(lane == 0, 31);
                const int src = ((mt * 2 + rh) * 2 + 1 - hp) * 1024;
                if (elect_one()) {
                    const uint32_t* fl = &scr->oflag[mt * 2 + 1 - hp][0];
                    const uint32_t inv = (ep & 1) - 1;
                    uint32_t ready = 0, ph = 0;
                    int s = 4;
#pragma unroll 1
                    for (int i = 2; i < 16; i++) {
                        const int kb = (2 * p + i) & 15;
#pragma unroll 1
                        while (!((ready >> kb) & 1) && --budget > 0) ready = ld_rlx(fl) ^ inv;
                        TSC(i == 2, 30);
                        mbar_wait(bars + 8 * (B_OEMPTY + s), ph, budget);
                        tma_2d_mc(sb + hp * OFF_X1 + s * BOX, &mo, bars + 8 * (B_OFULL + hp * 6 + s), 0, src + kb * 64);
                        TSC(TIMING % 10 == 4 && hp == 0, 32 + i);
                        if (++s == 6) s = 0;
                        if (s == 4) ph ^= 1;
                    }
                }
            } else if (warp == 14) {
                if (elect_one()) {
                    uint32_t s8 = 0, ph = 0;
                    int tries = BUDGET;
                    const uint32_t* act = scr->act[ep & 1];
                    auto counted = [&](int c, uint32_t n) {
#pragma unroll 1
                        while (ld_rlx(&scr->cnt[c][0]) != ep * n && --tries > 0) __nanosleep(POLL_NS);
                    };
                    auto weights = [&](const CUtensorMap* m, int c0, int c1, int c2_) {
                        mbar_wait(bars + 8 * B_FEMPTY + s8, ph, budget);
                        mbar_expect_tx(bars + 8 * B_FFULL + s8, F_BYTES);
                        tma_3d(sb + OFF_FS + s8 * (F_BYTES / 8), m, bars + 8 * B_FFULL + s8, c0, c1, c2_);
                    };
                    if (b < 112) {
                        counted(8, 32);
                        TS(26);
#pragma unroll 1
                        for (int q = 0; q < 16; q++) {
                            weights(&mgu, b * 32, q * 64, 0);
                            bulk_g2s(sb + OFF_FS + BOX + s8 * (F_BYTES / 8), act + 14336 + q * 256, 1024, bars + 8 * B_FFULL + s8);
                            TSC(TIMING % 10 == 5, 32 + q);
                            if (q >= 8) bulk_pf(pf.wd + (size_t)((q - 8) * 112 + b) * 8192, 8192);
                            s8 += 8;
                            if (s8 == 40) { s8 = 0; ph ^= 1; }
                        }
                    }
#pragma unroll 1
                    for (int q = -3; q < 7; q++) {
                        if (q == 0) { counted(kc, 28); TS(29); }
                        if ((unsigned)q >= 3) weights(&mwd, 0, kc * 448 + (q < 0 ? q + 3 : q) * 64, c2);
                        if (q >= 0) bulk_g2s(sb + OFF_FS + BOX + s8 * (F_BYTES / 8), act + (kc * 7 + q) * 256, 1024, bars + 8 * B_FFULL + s8);
                        TSC(TIMING % 10 == 5, 51 + q);
                        s8 += 8;
                        if (s8 == 24) { s8 = 0; if ((unsigned)q >= 3) ph ^= 1; }
                    }
                }
            } else {
#pragma unroll 1
                for (int i = lane * 16; i < CS_BYTES; i += 512) sts4(sb + OFF_CS + i, 0, 0, 0, 0);
                mbar_wait(bars + 8 * ZF_GATE, 0, budget);
                uint8_t* oz = scr->o + ((size_t)mt * 64 + nt) * BOX + lane * 16;
#pragma unroll 1
                for (int i = 0; i < 16; i++, oz += 512) {
#pragma unroll
                    for (int n = 0; n < 4; n++) st_rlx4(oz + n * 16 * BOX, 0, 0, 0, 0);
                    __nanosleep(ZF_NS);
                }
                __syncwarp();
                fence_gpu();
                mbar_wait(bars + 8 * B_RDONE, 0, budget);
                int tries = BUDGET;
#pragma unroll 1
                for (int i = lane; i < 88; i += 32) {
                    const uint2* rp = &scr->row[2 * (j0 - 8 + i) + par];
                    uint2 v0, v1, v2;
#pragma unroll 1
                    do { v0 = ld_rlx2(rp + (j0 + i < 8 ? 16 : 0)); v1 = ld_rlx2(rp + 176); v2 = ld_rlx2(rp + 352); } while ((((v0.y ^ ep) | (v1.y ^ ep) | (v2.y ^ ep)) & 31) && --tries > 0);
                    sts2(sb + OFF_STAT + i * 8, (v0.x << 16) ^ 0x80000000u, __float_as_uint(rcp(bf_hi(v0.x))));
                    sts2(sb + OFF_STAT + i * 8 + 704, (v1.x << 16) ^ 0x80000000u, __float_as_uint(rcp(bf_hi(v1.x))));
                    sts2(sb + OFF_STAT + i * 8 + 1408, (v2.x << 16) ^ 0x80000000u, __float_as_uint(rcp(bf_hi(v2.x))));
                }
                __syncwarp();
                {
                    const int row = 2047 - ((poll_all(&scr->sel[lane & 7], 31u, ep & 31, budget) >> 5) & 2047), jj = (row >> 1) - j0 - rh * 128;
                    uint32_t boxes = __reduce_or_sync(0xffffffffu, (row & 1) == par && (unsigned)jj < 128 ? 1u << (jj >> 4) : 0u);
                    sts1(sb + OFF_SEL, boxes);
#pragma unroll 1
                    for (int i = 0; boxes; i += 2) {
                        if (boxes & 1) st_rlx4(pf.out + (size_t)(2 * (j0 + rh * 128 + i + (lane >> 4)) + par) * 2048 + cb * 256 + (lane & 15) * 16, 0, 0, 0, 0);
                        else i += 14;
                        if ((i & 14) == 14) boxes >>= 1;
                    }
                }
                if (lane < 24) {
                    uint4 v[3];
#pragma unroll 1
                    while (v[0] = ld_rlx4(&scr->cs[nt][0][lane]), v[1] = ld_rlx4(&scr->cs[nt][1][lane]), v[2] = ld_rlx4(&scr->cs[nt][2][lane]),
                           (((v[0].x ^ ep) | (v[1].x ^ ep) | (v[2].x ^ ep)) & 1) && --tries > 0) __nanosleep(100);
#pragma unroll
                    for (int r = 0; r < 3; r++) sts4(sb + OFF_CS + 64 + lane * 128 + r * 16, v[r].x, v[r].y, v[r].z, v[r].w);
                }
                fence_async_smem();
                __syncwarp();
                if (elect_one()) {
                    mbar_arrive(bars + 8 * B_AUX);
                    TS(21);
                    if (lds1(sb + OFF_SEL)) { fence_gpu(); asm volatile("fence.proxy.async.global;" ::: "memory"); }
                    mbar_arrive(bars + 8 * B_ZERO);
                    TS(25);
                    mbar_expect_tx(bars + 8 * (B_OFULL + 3), BOX); mbar_expect_tx(bars + 8 * (B_OFULL + 9), BOX);
#pragma unroll 1
                    for (int v = 0; v < 2; v++) {
                        const uint32_t ring = sb + v * OFF_X1 + 2 * BOX, fb = bars + 8 * (B_OFULL + v * 6 + 2);
                        mbar_wait(bars + 8 * (B_STAGED + v), 0, budget);
                        asm volatile("red.relaxed.gpu.global.xor.b32 [%0], %1;" ::"l"(&scr->oflag[mt * 2 + 1 - v][0]), "r"(1u << nt) : "memory");
                        TS(13 + 2 * v);
                        mbar_arrive(fb);
                        mbar_wait(bars + 8 * B_G1DONE, 0, budget);
                        bulk_s2c(mapa(ring + BOX, hp ^ 1), ring, BOX, mapa(fb + 8, hp ^ 1));
                        if (v == 0) mbar_wait(bars + 8 * B_FREED, 0, budget);
#pragma unroll
                        for (int n = 0; n < 4; n++) {
                            mbar_expect_tx(bars + 8 * (B_OFULL + (n >> 1) * 6 + 4 + (n & 1)) - v * 32, BOX);
                            mbar_arrive_at(mapa(bars + 8 * B_OEMPTY, n >> 1) + (4 + (n & 1)) * 8 - v * 32);
                        }
                    }
                }
            }
        }
    } else if (warp >= 8) {
        reg_dec<40>();
        const int wq = warp - 8, ta = tid - 256;
        const uint32_t rbuf = sb + OFF_FR + wq * BOX, rbar = bars + 8 * B_ROW;
        const uint4 wv = ldg_nc(wr + ta * 8);
        if (ta == 0) sts1(sb + OFF_EP, ld_rlx(&scr->epoch[0]) + 1);
        sts4(sb + OFF_STAT + ta * 16, wv.x, wv.y, wv.z, wv.w);
        bar_sync(8, 224);
        const uint32_t ep = __shfl_sync(0xffffffffu, lds1(sb + OFF_EP), 0);
        {
            const int s = b * 16 + wq * 4 + (lane >> 3);
            if ((lane & 7) == 0) st_rlx2(&scr->row[s], 0, ep - 1);
            float sw = 0.f;
#pragma unroll 1
            for (int i = 0; i < 16; i++) { const uint32_t q = lds1(sb + OFF_STAT + i * 128 + lane * 4); sw += bf_lo(q) + bf_hi(q); }
#pragma unroll 1
            for (int o = 16; o > 0; o >>= 1) sw += __shfl_xor_sync(0xffffffffu, sw, o);
            float s1 = 0.f, s2 = 0.f, sr = 0.f;
            const uint32_t xa = rbuf + (lane >> 3) * 2048 + (lane & 7) * 16, wa = sb + OFF_STAT + (lane & 7) * 16;
            mbar_wait(rbar, 0, budget);
            TSC(ta == 0, 17);
            {
                float s1b = 0.f, s2b = 0.f, srb = 0.f;
                const uint32_t xb = rbuf + (lane >> 4) * 4096 + (lane & 15) * 16, wb = sb + OFF_STAT + (lane & 15) * 16;
                uint4 w4 = lds4(wb), u = lds4(xb), v = lds4(xb + 2048);
#pragma unroll 1
                for (int i = 1; i <= 8; i++) {
                    const uint32_t o = (i * 256) & 2047;
                    float wf[8];
#pragma unroll
                    for (int c = 0; c < 4; c++) { wf[2 * c] = bf_lo((&w4.x)[c]); wf[2 * c + 1] = bf_hi((&w4.x)[c]); }
                    w4 = lds4(wb + o);
#pragma unroll
                    for (int c = 0; c < 4; c++) {
                        const float a0 = bf_lo((&u.x)[c]), a1 = bf_hi((&u.x)[c]);
                        s1 += a0; s2 = fmaf(a0, a0, s2); sr = fmaf(a0, wf[2 * c], sr);
                        s1 += a1; s2 = fmaf(a1, a1, s2); sr = fmaf(a1, wf[2 * c + 1], sr);
                    }
                    u = lds4(xb + o);
#pragma unroll
                    for (int c = 0; c < 4; c++) {
                        const float a0 = bf_lo((&v.x)[c]), a1 = bf_hi((&v.x)[c]);
                        s1b += a0; s2b = fmaf(a0, a0, s2b); srb = fmaf(a0, wf[2 * c], srb);
                        s1b += a1; s2b = fmaf(a1, a1, s2b); srb = fmaf(a1, wf[2 * c + 1], srb);
                    }
                    v = lds4(xb + 2048 + o);
                }
                const bool up = lane & 8;
                s1 = (up ? s1b : s1) + __shfl_xor_sync(0xffffffffu, up ? s1 : s1b, 8);
                s2 = (up ? s2b : s2) + __shfl_xor_sync(0xffffffffu, up ? s2 : s2b, 8);
                sr = (up ? srb : sr) + __shfl_xor_sync(0xffffffffu, up ? sr : srb, 8);
            }
#pragma unroll
            for (int o = 1; o < 8; o <<= 1) {
                s1 += __shfl_xor_sync(0xffffffffu, s1, o); s2 += __shfl_xor_sync(0xffffffffu, s2, o); sr += __shfl_xor_sync(0xffffffffu, sr, o);
            }
            const float mean = s1 * (1.f / 1024.f), mb = bf16r(mean);
            float var = fmaf(-mean, mean, s2 * (1.f / 1024.f));
            sr = fmaf(-mb, sw, sr);
            if (__builtin_expect(__any_sync(0xffffffffu, mean * mean > 256.f * var), 0)) {
                float a2 = 0.f, ar = 0.f;
#pragma unroll 1
                for (int i = 0; i < 64; i++) {
                    const uint32_t o = (i >> 2) * 128 + (i & 3) * 4, q1 = lds1(xa + o), q2 = lds1(wa + o);
                    a2 = fmaf(bf_lo(q1) - mean, bf_lo(q1) - mean, fmaf(bf_hi(q1) - mean, bf_hi(q1) - mean, a2));
                    ar = fmaf(bf_lo(q1) - mb, bf_lo(q2), fmaf(bf_hi(q1) - mb, bf_hi(q2), ar));
                }
#pragma unroll 1
                for (int o = 1; o < 8; o <<= 1) { a2 += __shfl_xor_sync(0xffffffffu, a2, o); ar += __shfl_xor_sync(0xffffffffu, ar, o); }
                var = a2 * (1.f / 1024.f); sr = ar;
            }
            float den;
            asm("sqrt.approx.f32 %0, %1;" : "=f"(den) : "f"(bf16r(bf16r(var) + 1e-5f)));
            const uint32_t st = pack_bf16(mb, den);
            const uint32_t rb = pack_bf16(0.f, sr * rcp(bf_hi(st)) + 0.f);
            uint32_t ord = (int)rb < 0 ? ~rb & 0xffff0000u : rb | 0x80000000u;
            if ((rb & 0x7fffffffu) > 0x7f800000u) ord = 0;
            if ((lane & 7) == 0) st_rlx2(&scr->row[s], st, ord | ((2047 - s) << 5) | (ep & 31));
            __syncwarp();
            if (lane < 7) mbar_arrive(bars + 8 * (lane < 5 ? B_FEMPTY + lane : B_RDONE));
        }
        TSC(ta == 0, 18);
        if ((b >> 3) == 14) {
            const uint32_t gm = sb + OFF_E, cnt = gm + 64, res = gm + 80, list = gm + 128;
            uint32_t kv[16];
            int tries = BUDGET;
#pragma unroll 1
            do {
                uint32_t bad = 0;
#pragma unroll
                for (int n = 0; n < 16; n++) kv[n] = ld_rlx(&scr->row[n * 128 + ta].y);
#pragma unroll
                for (int n = 0; n < 16; n++) bad |= kv[n] ^ ep;
                if ((bad & 31) == 0) break;
            } while (--tries > 0);
            __syncwarp();
            TSC(ta == 0, 26);
            uint32_t m = 0;
#pragma unroll
            for (int n = 0; n < 16; n++) m = max(m, kv[n]);
            uint32_t gmax = m;
#pragma unroll
            for (int o = 1; o < 8; o <<= 1) gmax = max(gmax, __shfl_xor_sync(0xffffffffu, gmax, o));
            sts1(gm + (ta >> 3) * 4, gmax);
            sts1(cnt, 0);
            bar_sync(12, 128);
            const uint32_t c = lds1(gm + (lane & 15) * 4);
            int rank = 0;
#pragma unroll
            for (int i = 0; i < 2; i++) { const uint4 q = lds4(gm + (lane >> 4) * 32 + i * 16); rank += (q.x > c) + (q.y > c) + (q.z > c) + (q.w > c); }
            rank += __shfl_xor_sync(0xffffffffu, rank, 16);
            const uint32_t thr = redux_max(rank == 7 ? c : 0u);
#pragma unroll 1
            while (m >= thr) {
                uint32_t at, m2 = 0;
                asm volatile("atom.shared.add.u32 %0, [%1], 1;" : "=r"(at) : "r"(cnt) : "memory");
#pragma unroll
                for (int n = 0; n < 16; n++) m2 = max(m2, kv[n] < m ? kv[n] : 0u);
                sts1(list + at * 4, m);
                if (m2 == 0) break;
                m = m2;
            }
            bar_sync(12, 128);
            const int nc = lds1(cnt);
#pragma unroll 1
            for (int i = ta >> 3; i < ((nc + 3) & ~3); i += 16) {
                const uint32_t ki = lds1(list + i * 4);
                int r = 0;
#pragma unroll 1
                for (int n = lane & 7; n < nc; n += 8) r += lds1(list + n * 4) > ki;
                __syncwarp();
#pragma unroll
                for (int o = 1; o < 8; o <<= 1) r += __shfl_xor_sync(0xffffffffu, r, o);
                if (r == (b & 7) && i < nc) sts1(res, ki);
            }
            bar_sync(12, 128);
            const uint32_t k0 = lds1(res);
            const int r0 = 2047 - ((k0 >> 5) & 2047);
            TSC(ta == 0, 22);
            if (ta == 0) st_rlx(&scr->sel[b & 7], k0);
            const uint4 v0 = ldg_nc(x + (size_t)r0 * 1024 + ta * 8);
            const uint32_t s0 = ld_rlx(&scr->row[r0]);
            const float m0 = bf_lo(s0), i0 = rcp(bf_hi(s0));
            const int ao = 14336 + (ta >> 3) * 256 + (b & 7) * 32 + ((ta ^ b) & 7) * 4;
            st_rlx4(scr->act[ep & 1] + ao, norm_pair(v0.x, m0, i0), norm_pair(v0.y, m0, i0), norm_pair(v0.z, m0, i0), norm_pair(v0.w, m0, i0));
            __syncwarp();
            if (lane == 0) red_add(&scr->cnt[8][tries >> 30]);
            st_rlx4(scr->act[~ep & 1] + ao, 0, 0, 0, 0);
        }
        uint32_t s8 = 0, fph = 0, key = 0;
        const uint32_t chk = __shfl_sync(0xffffffffu, sb + OFF_FS + BOX + lane * 32 + (lane & 28), lane);
        int left = BUDGET;
#pragma unroll 1
        for (int ph = 0; ph < 2; ph++) {
            if (ph || b < 112) {
                float acc[4] = {0.f, 0.f, 0.f, 0.f};
                const uint32_t alo = sd + (ph ? dlo(OFF_FS, 8192) : dlo(OFF_FS, 4096)), ahi = ph ? dhi(1024, 1) : dhi(512, 2), astep = ph ? 128 : 64;
                const uint32_t bhi = ph ? dhi(128, 0) : dhi(1024, 1), bstep = ph ? 16 : 2, wrap = ph ? 24 : 40;
                uint32_t prev = 0, prev2 = 0;
#pragma unroll 1
                for (int q = ph ? 7 : 16; q > 0; q--) {
                    const uint32_t da = alo + s8 * (F_BYTES >> 7), db = sd + dlo(OFF_FS + BOX, 128) + s8 * (F_BYTES >> 7);
                    if (q == (ph ? 7 : F1_HOLD)) {
                        wg_wait<0>();
                        if (prev) mbar_arrive(prev);
                        prev = 0;
                        mbar_wait(bars + 8 * (ph ? FFN2_GATE : F1_GATE), 0, left);
                    }
                    mbar_wait_hot(bars + 8 * B_FFULL + s8, fph, left);
                    if (__builtin_expect(__any_sync(0xffffffffu, lds1(chk + s8 * (F_BYTES / 8)) == 0), 0)) {
                        int tries = BUDGET;
#pragma unroll 1
                        for (int n = lane * 4 + (left >> 30); n < 256; n += 128) {
                            uint4 v;
#pragma unroll 1
                            do { v = ld_rlx4(scr->act[ep & 1] + ((ph ? kc * 7 + 7 : 72) - q) * 256 + n); } while (v.x == 0 && --tries > 0);
                            __syncwarp();
                            sts4(sb + OFF_FS + BOX + s8 * (F_BYTES / 8) + n * 4, v.x, v.y, v.z, v.w);
                        }
                        NRETRY();
                        fence_async_smem();
                        __syncwarp();
                    }
                    TSC(TIMING % 10 == 3 && ta == 0, 32 + (ph ? 23 : 16) - q);
                    wg_fence();
#pragma unroll
                    for (int j = 0; j < 4; j++) wgmma_n8<1, 0>(acc, mkdesc(da + j * astep, ahi), mkdesc(db + j * bstep, bhi), 1);
                    wg_commit();
                    uint32_t done = F1_DEPTH == 2 ? prev2 : prev;
                    prev2 = prev;
                    if (lane == 0) prev = bars + 8 * B_FEMPTY + s8;
                    wg_wait<F1_DEPTH>();
                    if (ph) { wg_wait<F2_DEPTH>(); done = F2_DEPTH ? prev2 : prev; }
                    if (done) mbar_arrive(done);
                    s8 += 8;
                    if (s8 == wrap) { s8 = 0; fph ^= 1; }
                }
                wg_wait<0>();
                const int ln = lane + (left >> 30);
                if (ph == 0) {
                    if (prev) mbar_arrive(prev);
                    const bool second = (wq >= 2) != (swap_gu != 0);
                    const uint32_t xa = sb + OFF_GU + ((wq & 1) * 32 + ln) * 16;
                    if (second) sts4(xa, __float_as_uint(acc[0]), __float_as_uint(acc[1]), __float_as_uint(acc[2]), __float_as_uint(acc[3]));
                    bar_sync(12, 128);
                    if (!second) {
                        const float4 up = lds4f(xa);
                        float hv[4];
#pragma unroll
                        for (int c = 0; c < 4; c++) { const float ga = bf16r(acc[c]); hv[c] = bf16r(ga * sigmoidf(ga)) * bf16r((&up.x)[c]); }
                        const int ao = (b * 4 + (wq & 1) * 2) * 32 + ln;
                        st_rlx(scr->act[ep & 1] + ao, max(movm(pack_bf16(hv[0], hv[1])), 1u)); st_rlx(scr->act[ep & 1] + 32 + ao, max(movm(pack_bf16(hv[2], hv[3])), 1u));
                        __syncwarp();
                        if (ln == 0) red_add(&scr->cnt[b / 14][0]);
                        st_rlx(scr->act[~ep & 1] + ao, 0); st_rlx(scr->act[~ep & 1] + 32 + ao, 0);
                    }
                } else {
#pragma unroll
                    for (int c = 0; c < 4; c++) st_rlx(&scr->ypart[kc][2 * (ln & 3) + (c & 1)][c2 * 64 + wq * 16 + (c >> 1) * 8 + (ln >> 2)], (__float_as_uint(acc[c]) & ~1u) | (ep & 1));
                }
                TSC(ta == 0, 22 + ph);
            }
            const int ln = lane + (left >> 30);
            if (ph == 0) {
                if ((ta & 126) == 64) mbar_arrive(bars + 8 * B_F1DONE);
                key = poll_all(&scr->sel[ln & 7], 31u, ep & 31, left);
            }
        }
        {
            const int row = 2047 - ((key >> 5) & 2047);
            const float sig = bf16r(sigmoidf(__uint_as_float(((int)key < 0 ? key & 0x7fffffffu : ~key) & 0xffff0000u)));
            uint32_t own = __ballot_sync(0xffffffffu, (row & 1) == par && (row >> 8) == (mt & 3) * 2 + rh) & 255;
            if (wq & 2) own &= own - 1;
            mbar_wait(bars + 8 * B_ZERO, 0, left);
#pragma unroll 1
            for (; own; own &= own - 1, own &= own - 1) {
                const int j = __ffs(own) - 1, col = cb * 128 + (wq & 1) * 64 + (lane & 15) * 4;
                const uint32_t* src = &scr->ypart[lane >> 4][j][col];
                uint4 v[4]; int tries = BUDGET;
#pragma unroll 1
                do {
#pragma unroll
                    for (int m = 0; m < 4; m++) v[m] = ld_rlx4(src + m * 2 * 8192);
                } while ((((v[0].x ^ ep) | (v[1].x ^ ep) | (v[2].x ^ ep) | (v[3].x ^ ep)) & 1) && --tries > 0);
                __syncwarp();
                float a[4];
                const float sj = __shfl_sync(0xffffffffu, sig, j);
                const int rj = __shfl_sync(0xffffffffu, row, j);
#pragma unroll
                for (int c = 0; c < 4; c++) {
                    a[c] = (__uint_as_float((&v[0].x)[c]) + __uint_as_float((&v[1].x)[c])) + (__uint_as_float((&v[2].x)[c]) + __uint_as_float((&v[3].x)[c]));
                    a[c] = bf16r(a[c] + __shfl_xor_sync(0xffffffffu, a[c], 16)) * sj;
                }
                if (lane < 16) asm volatile("red.relaxed.gpu.global.add.noftz.v2.bf16x2 [%0], {%1, %2};" ::"l"(pf.out + (size_t)rj * 2048 + col * 2), "r"(pack_bf16(a[0], a[1])), "r"(pack_bf16(a[2], a[3])) : "memory");
            }
        }
        TSC(ta == 0, 24);
    } else {
        reg_inc<224>();
        const int w = warp >> 2, wi = warp & 3, g = lane >> 2, t = lane & 3;
        const bool elect = (tid & 127) == 0;
        const uint32_t mad = (lane & 15) * 128 + (((lane >> 4) ^ (lane & 7)) << 4);
        float acc[64];
        const uint32_t ring = sb + w * OFF_X1, ofull = bars + 8 * (B_OFULL + w * 6), oempty = mapa(bars + 8 * B_OEMPTY, w);
        const int r0 = rh * 128 + wi * 32 + (1 - w) * 16 + g;
        {
            float acc0[96], acc1[96];
            const uint32_t sta = sb + OFF_STAT + (8 + w * 128 + wi * 32) * 8;
            {
                const uint32_t xfull = bars + 8 * (B_XFULL + w * 6 + 5), xempty = mapa(bars + 8 * B_XEMPTY, w), dx0 = sd + dlo(w * OFF_X1, 16);
                uint32_t s8 = 16, ps8 = 0, ph = 0;
                cluster_wait();
#pragma unroll 1
                for (int k = 0; k < 16; k++) {
                    const uint32_t dx = dx0 + s8 * (2 * BOX >> 7), dw = sd + dlo(OFF_W, BOX) + s8 * (W_BYTES >> 7);
                    mbar_wait(bars + 8 * B_WFULL + s8, ph, budget);
                    mbar_wait(xfull - 2 * s8, ph, budget);
                    TSC(elect && k == 0, 1 + 8 * w);
                    TSC(TIMING % 10 == 1 && tid == 0, 32 + k);
                    wg_wait<0>();
                    wg_fence();
#pragma unroll
                    for (int kk = 0; kk < 4; kk++) wgmma_n192<0, 1>(acc1, mkdesc(dx + kk * 2, dhi(1024, 1)), mkdesc(dw + kk * 128, dhi(1024, 1)), kk ? 1 : k);
                    wg_commit();
                    TSC(TIMING % 10 == 6 && elect, 32 + 16 * w + k);
                    if (elect && k > 0) {
                        mbar_arrive(bars + 8 * B_WEMPTY + ps8);
                        if (k <= 13) { mbar_expect_tx(xfull - 2 * ps8 - 8, BOX); mbar_arrive_at(xempty + 2 * ps8 + 8); }
                    }
                    if (k == 15) {
                        mbar_wait(bars + 8 * B_AUX, 0, budget);
                        const uint32_t zero = budget >> 30, pm = t & 1 ? 0x4432 : 0x3232, ra = sta + ((t >> 1) * 16 + g) * 8;
                        const uint32_t a0 = __byte_perm(lds1(ra), 0, pm), a1 = __byte_perm(lds1(ra + 64), 0, pm), a2 = a0 & zero, a3 = a1 & zero;
                        wg_fence();
                        wgmma_rs_n192(acc1, a0, a1, a2, a3, mkdesc(sd + dlo(OFF_CS, 0), dhi(128, 0)));
                        wgmma_rs_n192(acc0, a0, a1, a2, a3, mkdesc(sd + dlo(OFF_CS + 64, 0), dhi(128, 0)));
                        wg_commit();
                    }
                    mbar_wait(xfull - 2 * s8 - 8, ph, budget);
                    wg_wait<0>();
                    wg_fence();
#pragma unroll
                    for (int kk = 0; kk < 4; kk++) wgmma_n192<0, 1>(acc0, mkdesc(dx + 512 + kk * 2, dhi(1024, 1)), mkdesc(dw + kk * 128, dhi(1024, 1)), kk ? 1 : k);
                    wg_commit();
                    if (elect && k <= 12) { mbar_expect_tx(xfull - 2 * s8, BOX); mbar_arrive_at(xempty + 2 * s8); }
                    ps8 = s8;
                    s8 = s8 == 16 ? 0 : s8 + 8;
                    if (s8 == 16) ph ^= 1;
                }
            }
            const uint32_t zero = budget >> 30;
            const bool u0 = 2 * t > g, u1 = 2 * t + 1 > g;
            uint32_t mU = (u0 ? 0xffffu : 0u) | (u1 ? 0xffff0000u : 0u);
            uint32_t ka0 = sta + (2 * t - (u0 ? 8 : 0)) * 8 + 4, ka1 = sta + (2 * t + 1 - (u1 ? 8 : 0)) * 8 + 4;
            float rk[2][4], fu[2][4], fn[2][4];
            auto factors = [&](int h) {
#pragma unroll
                for (int n = 0; n < 4; n += 2) {
                    const float rq = lds1f(sta + (16 * h + 4 * n + g) * 8 + 4) * (0.17677669529663687f * 1.4426950408889634f);
                    rk[h][n] = lds1f(ka0 + h * 128 + n * 32); rk[h][n + 1] = lds1f(ka1 + h * 128 + n * 32);
                    const float f0 = rq * rk[h][n], f1 = rq * rk[h][n + 1];
                    fu[h][n] = u0 ? f0 : 0.f; fn[h][n] = f0 - fu[h][n]; fu[h][n + 1] = u1 ? f1 : 0.f; fn[h][n + 1] = f1 - fu[h][n + 1];
                }
#pragma unroll
                for (int n = 0; n < 4; n++) asm volatile("" : "+f"(fu[h][n]), "+f"(fn[h][n]));
            };
            uint8_t* og = scr->o + ((size_t)(mt * 4 + w * 2) * 16 + nt) * BOX + wi * 256 + lane * 4;
            TSC(elect, 19 + w);
            uint32_t pk0[48], pk1[48], o[16] = {};
#pragma unroll
            for (int j = 0; j < 48; j++) if (j < 16 || (j & 1)) pk1[j] = pack_here(acc1[2 * j], acc1[2 * j + 1]);
            if (warp < 7) {
#pragma unroll
                for (int c = 0; c < 4; c++) stsm4(ring + 4 * BOX + wi * 2048 + c * 512 + lane * 16, pk1[17 + 8 * c], pk1[19 + 8 * c], pk1[21 + 8 * c], pk1[23 + 8 * c]);
                bar_arrive(1 + warp, 64);
            } else if (j0 != 768) {
#pragma unroll
                for (int c = 0; c < 4; c++) {
                    pk1[17 + 8 * c] = max(pk1[17 + 8 * c], 1u);
                    st_rlx4(&scr->halo[b][c * 128 + lane * 4], pk1[17 + 8 * c], pk1[19 + 8 * c], pk1[21 + 8 * c], pk1[23 + 8 * c]);
                }
            }
            TSC(tid == 224, 28);
#pragma unroll
            for (int j = 16; j < 48; j += 2) pk1[j] = pack_here(acc1[2 * j], acc1[2 * j + 1]);
            factors(1);
            uint32_t od = sb + 2 * BOX + wi * 256 + (lane >> 4) * 1024 + (lane & 15) * 16, g1peer = mapa(bars + 8 * B_G1DONE, hp ^ 1);
            uint32_t ha = sb + (warp == 0 ? OFF_HIN : warp <= 4 ? 4 * BOX - 2048 : OFF_X1 + 4 * BOX - 5 * 2048) + warp * 2048 + lane * 16;
            const bool first = warp == 0 && j0 == 0;
            float bias0 = first && u0 ? -INFINITY : 0.f, bias1 = first && u1 ? -INFINITY : 0.f;
            asm volatile("" : "+l"(og), "+r"(mU), "+r"(od), "+r"(ha), "+f"(bias0), "+f"(bias1));
            mbar_wait(bars + 8 * B_XT, 0, budget);
            mbar_wait(bars + 8 * (B_WEMPTY + 1), 0, budget);
            TSC(elect, 12 + 2 * w);
            wg_wait<0>();
            if (elect) { mbar_arrive(bars + 8 * B_G1DONE); mbar_arrive_at(g1peer); }
            TSC(elect, 2 + 8 * w);
            float ci[4];
#pragma unroll
            for (int n = 0; n < 4; n++) ci[n] = __uint_as_float((0x03800000u + n) | (budget >> 30));
            auto hand_over = [&](int v) {
                asm volatile("{\n.reg .pred p;\nsetp.ne.b32 p, %17, 0;\n"
                             "@p stmatrix.sync.aligned.m8n8.x4.shared.b16 [%16], {%0,%1,%2,%3};\n@p stmatrix.sync.aligned.m8n8.x4.shared.b16 [%16 + 2048], {%4,%5,%6,%7};\n"
                             "@p stmatrix.sync.aligned.m8n8.x4.shared.b16 [%16 + 4096], {%8,%9,%10,%11};\n@p stmatrix.sync.aligned.m8n8.x4.shared.b16 [%16 + 6144], {%12,%13,%14,%15};\n"
                             FENCE_PRED "fence.proxy.async.shared::cta;\n}"
                             ::"r"(o[0]), "r"(o[1]), "r"(o[2]), "r"(o[3]), "r"(o[4]), "r"(o[5]), "r"(o[6]), "r"(o[7]), "r"(o[8]), "r"(o[9]), "r"(o[10]), "r"(o[11]),
                               "r"(o[12]), "r"(o[13]), "r"(o[14]), "r"(o[15]), "r"(od + v * OFF_X1), "r"((int)(w == rh)) : "memory");
                TSC(tid == 0, v ? 27 : 5);
#pragma unroll
                for (int i = 0; i < 16; i++) asm volatile("st.global.u32 [%0], %1;" ::"l"(og + (1 - v) * 16 * BOX + (i >> 1) * 1024 + (i & 1) * 128), "r"(o[i]) : "memory");
                __syncwarp();
                if (lane == 0) mbar_arrive(bars + 8 * (B_STAGED + v));
            };
#pragma unroll
            for (int j = 32; j < 48; j++) pk1[j] = movm(pk1[j]);
#pragma unroll
            for (int j = EARLY_PK; j < 48; j++) if (j >= 32 || (j & 1) || EARLY_PK < 17) pk0[j] = pack_here(acc0[2 * j], acc0[2 * j + 1]);
#pragma unroll
            for (int j = 32; j < 48; j++) pk0[j] = movm(pk0[j]);
            factors(0);
            attn_pair<2>(pk1, pk1 + 16, pk1 + 32, pk0 + 17, pk0 + 33, fu[1], fn[1], rk[1], 0.f, 0.f, mU, zero, ci, o);
            hand_over(0);
            TSC(elect, 3 + 8 * w);
#pragma unroll
            for (int j = 0; j < 32; j++) if (j < EARLY_PK || (!(j & 1) && EARLY_PK == 17)) pk0[j] = pack_here(acc0[2 * j], acc0[2 * j + 1]);
            bar_sync(warp ? warp : 11, 64);
            uint32_t hl[16];
            ldsm4(hl, ha); ldsm4(hl + 4, ha + 512); ldsm4t(hl + 8, ha + 1024); ldsm4t(hl + 12, ha + 1536);
            __syncwarp();
            if (lane == 0) mbar_arrive(bars + 8 * B_FREED);
            attn_pair<1>(pk0, pk0 + 16, pk0 + 32, hl, hl + 8, fu[0], fn[0], rk[0], bias0, bias1, mU, zero, ci, o);
            const float2 s0 = lds2f(sb + OFF_STAT + (8 + r0) * 8), s1 = lds2f(sb + OFF_STAT + (16 + r0) * 8);
            const float m0 = s0.x * s0.y, f0 = 1.f + s0.y, m1 = s1.x * s1.y, f1 = 1.f + s1.y;
            uint32_t xt[32];
#pragma unroll
            for (int j = 0; j < 8; j++) ldsm4(xt + 4 * j, ((ring + wi * 2048 + mad) ^ ((j & 3) * 32)) + (j >> 2) * BOX);
            hand_over(1);
#pragma unroll
            for (int j = 0; j < 32; j++) {
                acc[2 * j] = fmaf(bf_lo(xt[j]), j & 1 ? f1 : f0, j & 1 ? m1 : m0); acc[2 * j + 1] = fmaf(bf_hi(xt[j]), j & 1 ? f1 : f0, j & 1 ? m1 : m0);
            }
        }
        TSC(tid == 0, 4);
        {
            const uint32_t da0 = sd + dlo(w * OFF_X1, 1024), db0 = sd + dlo(OFF_WO, BOX);
            const uint32_t chk = ring + wi * 256 + (lane >> 3) * 1032 + (lane & 7) * 32 + (lane & 4);
            uint32_t s8 = 16, ps8 = 0, ph = 0;
            mbar_wait(ofull + s8, 0, budget);
            mbar_wait(bars + 8 * B_WOFULL + s8, 0, budget);
            TSC(TIMING % 10 == 2 && elect, 32 + w * 16);
            const uint32_t ahi = dhi(128, 0) | (budget >> 30), bhi = dhi(1024, 1) | (budget >> 30);
            const int last = w ? HOLD : 16;
            uint32_t rel = elect ? 0x7fe : 0;
#pragma unroll 1
            for (int i = 1;;) {
                const uint32_t da = da0 + s8 * (BOX >> 7), db = db0 + s8 * (BOX >> 6);
                wg_fence();
#pragma unroll
                for (int kk = 0; kk < 4; kk++) {
                    wgmma_n128<0, 1>(acc, mkdesc(da + kk * 128, ahi), mkdesc(db + kk * 128, bhi), 1);
                    if (kk & 1) wg_commit();
                }
                wg_wait<2>();
                if (rel & 1) { mbar_expect_tx(ofull + ps8, BOX); mbar_arrive_at(oempty + ps8); mbar_arrive(bars + 8 * B_WOEMPTY + ps8); }
                if (i == 16) break;
                rel >>= 1;
                ps8 = s8;
#pragma unroll 1
                do {
                    s8 = s8 == 40 ? 0 : s8 + 8;
                    if (s8 == 16) ph ^= 1;
                    uint32_t bad;
                    asm volatile("{\n.reg .pred p, q, r;\n.reg .u32 u, v;\nmbarrier.try_wait.parity.shared::cta.b64 q, [%2], %3;\nmbarrier.try_wait.parity.shared::cta.b64 p, [%1], %3;\n"
                                 "setp.ne.and.u32 r, %5, 1, p;\nmov.u32 u, 1;\nmov.u32 v, 1;\n@r ld.shared.u32 u, [%4];\n@r ld.shared.u32 v, [%4 + 4096];\n"
                                 "and.pred p, p, q;\nmin.u32 u, u, v;\nsetp.eq.or.u32 p, u, 0, !p;\nvote.sync.any.pred p, p, 0xffffffff;\nselp.u32 %0, 1, 0, p;\n}"
                                 : "=r"(bad) : "r"(ofull + s8), "r"(bars + 8 * B_WOFULL + s8), "r"(ph), "r"(chk + s8 * (BOX / 8)), "r"(i) : "memory");
                    if (__builtin_expect(bad, 0)) {
                        mbar_wait(ofull + s8, ph, budget);
                        mbar_wait(bars + 8 * B_WOFULL + s8, ph, budget);
                        if (__any_sync(0xffffffffu, min(lds1(chk + s8 * (BOX / 8)), lds1(chk + s8 * (BOX / 8) + 4096)) == 0)) {
                            const uint32_t at = wi * 256 + (lane >> 4) * 1024 + (lane & 15) * 16;
                            const uint8_t* src = scr->o + ((size_t)((mt * 2 + rh) * 2 + 1 - w) * 16 + ((2 * p + (i < 2 ? i ^ hp : i)) & 15)) * BOX + at;
#pragma unroll 1
                            for (int n = 0; n < 8192; n += 2048) {
                                uint4 v; int tries = 4096;
#pragma unroll 1
                                do { v = ld_rlx4(src + n); } while (v.x == 0 && --tries > 0);
                                sts4(ring + s8 * (BOX / 8) + at + n, v.x, v.y, v.z, v.w);
                            }
                            NRETRY();
                            fence_async_smem();
                            __syncwarp();
                        }
                    }
                    TSC(TIMING % 10 == 1 && tid == 0, 48 + i);
                    TSC(TIMING % 10 == 2 && elect, 32 + w * 16 + i);
                } while (++i > last && i < 16);
                if (i > last) break;
                wg_wait<1>();
            }
            if (w) {
                bar_sync(9, 256);
#pragma unroll 1
                for (int i = HOLD - 10; i < 6; i++) {
                    wg_fence();
#pragma unroll
                    for (int kk = 0; kk < 4; kk++) wgmma_n128<0, 1>(acc, mkdesc(da0 + i * 512 + kk * 128, ahi), mkdesc(db0 + i * 1024 + kk * 128, bhi), 1);
                    wg_commit();
                }
            } else bar_arrive(9, 256);
            const bool add = (__shfl_sync(0xffffffffu, lds1(sb + OFF_SEL), 0) >> (wi * 2 + 1 - w)) & 1;
            wg_wait<0>();
            TSC(elect, 7 + 9 * w);
            const uint32_t os0 = ring + wi * 4096;
#pragma unroll
            for (int hf = 0; hf < OUT_PARTS; hf++) {
#pragma unroll
                for (int j = hf * (8 / OUT_PARTS); j < (hf + 1) * (8 / OUT_PARTS); j++)
                    stsm4(((os0 + mad) ^ ((j & 3) * 32)) + (j >> 2) * 2048, pack_here(acc[8 * j], acc[8 * j + 1]), pack_here(acc[8 * j + 2], acc[8 * j + 3]),
                          pack_here(acc[8 * j + 4], acc[8 * j + 5]), pack_here(acc[8 * j + 6], acc[8 * j + 7]));
                fence_async_smem();
                __syncwarp();
                if (elect_one())
                    asm volatile("{\n.reg .pred p;\nsetp.ne.b32 p, %6, 0;\n@!p cp.async.bulk.tensor.5d.global.shared::cta.bulk_group [%0, {%2, %2, %3, %4, %5}], [%1];\n"
                                 "@p cp.reduce.async.bulk.tensor.5d.global.shared::cta.add.bulk_group [%0, {%2, %2, %3, %4, %5}], [%1];\n}"
                                 ::"l"(&mout), "r"(os0 + hf * 2048), "r"(0), "r"(((j0 + rh * 128) >> 5) + wi), "r"(1 - w), "r"(par * 16 + cb * 2 + hf), "r"((int)add) : "memory");
            }
            asm volatile("cp.async.bulk.commit_group;\ncp.async.bulk.wait_group.read 0;" ::: "memory");
            if (b == 0 && tid == 0) st_rlx(&scr->epoch[0], lds1(sb + OFF_EP));
            TSC(elect, 8 - 2 * w);
            TS_END();
        }
    }
}

typedef CUresult (*EncodeFn)(CUtensorMap*, CUtensorMapDataType, cuuint32_t, void*, const cuuint64_t*, const cuuint64_t*, const cuuint32_t*,
                             const cuuint32_t*, CUtensorMapInterleave, CUtensorMapSwizzle, CUtensorMapL2promotion, CUtensorMapFloatOOBfill);

CUtensorMap make_map(EncodeFn fn, const void* base, int rank, const cuuint64_t* dims, const cuuint64_t* strides, const cuuint32_t* box,
                     CUtensorMapSwizzle swz = CU_TENSOR_MAP_SWIZZLE_128B, CUtensorMapL2promotion pro = CU_TENSOR_MAP_L2_PROMOTION_L2_256B) {
    CUtensorMap m;
    cuuint32_t es[5] = {1, 1, 1, 1, 1};
    fn(&m, CU_TENSOR_MAP_DATA_TYPE_BFLOAT16, rank, (void*)base, dims, strides, box, es, CU_TENSOR_MAP_INTERLEAVE_NONE,
       swz, pro, CU_TENSOR_MAP_FLOAT_OOB_FILL_NONE);
    return m;
}

}

extern "C" void kernel_launch(void* const* d_in, const int* in_sizes, int n_in, void* d_out, int out_size) {
    (void)in_sizes; (void)n_in; (void)out_size;
    const __nv_bfloat16* x = (const __nv_bfloat16*)d_in[0];
    const __nv_bfloat16* wqkv = (const __nv_bfloat16*)d_in[1];
    const __nv_bfloat16* wo = (const __nv_bfloat16*)d_in[2];
    const __nv_bfloat16* wr = (const __nv_bfloat16*)d_in[4];
    const __nv_bfloat16* wg = (const __nv_bfloat16*)d_in[5];
    const __nv_bfloat16* wu = (const __nv_bfloat16*)d_in[6];
    const __nv_bfloat16* wd = (const __nv_bfloat16*)d_in[7];
    static EncodeFn fn = nullptr;
    static Scratch* scr = nullptr;
    if (!fn) {
        void* p = nullptr; cudaDriverEntryPointQueryResult q;
        cudaGetDriverEntryPoint("cuTensorMapEncodeTiled", &p, cudaEnableDefault, &q);
        fn = (EncodeFn)p;
        cudaFuncSetAttribute(fused_kernel, cudaFuncAttributeMaxDynamicSharedMemorySize, SMEM_LAUNCH);
        cudaGetSymbolAddress((void**)&scr, g_scr);
    }
    const cuuint64_t xd[4] = {2048, 16, 32, 2}, xs[4] = {4096, 131072, 65536, 128}, od[5] = {64, 16, 32, 2, 32};
    const cuuint32_t xb[4] = {64, 16, 4, 1}, ob[5] = {64, 16, 1, 1, 2 / OUT_PARTS};
    const cuuint64_t wdm[3] = {1024, 1024, 3}, wst[2] = {6144, 2048};
    const cuuint32_t wb[3] = {64, 64, 3};
    const cuuint64_t wod[3] = {64, 1024, 16}, wdd[3] = {64, 3584, 16}, wos[2] = {2048, 128};
    const cuuint32_t wob[3] = {64, 64, 2}, wdb[3] = {64, 64, 1};
    CUtensorMap mx = make_map(fn, x, 4, xd, xs, xb), mw = make_map(fn, wqkv, 3, wdm, wst, wb);
    CUtensorMap mwo = make_map(fn, wo, 3, wod, wos, wob), mout = make_map(fn, d_out, 5, od, xs, ob);
    const int swap_gu = wu < wg;
    const cuuint64_t gd[3] = {3584, 1024, 2}, gst[2] = {7168, (cuuint64_t)(swap_gu ? (const char*)wg - (const char*)wu : (const char*)wu - (const char*)wg)};
    const cuuint32_t gb[3] = {32, 64, 2};
    CUtensorMap mgu = make_map(fn, swap_gu ? wu : wg, 3, gd, gst, gb, CU_TENSOR_MAP_SWIZZLE_64B, CU_TENSOR_MAP_L2_PROMOTION_L2_128B);
    CUtensorMap mwd = make_map(fn, wd, 3, wdd, wos, wdb, CU_TENSOR_MAP_SWIZZLE_128B, CU_TENSOR_MAP_L2_PROMOTION_L2_128B);
    const cuuint64_t md[2] = {64, 32768}, ms[1] = {128};
    const cuuint32_t mb[2] = {64, 64};
    CUtensorMap mo = make_map(fn, scr, 2, md, ms, mb, CU_TENSOR_MAP_SWIZZLE_NONE, CU_TENSOR_MAP_L2_PROMOTION_NONE);
    cudaLaunchConfig_t cfg = {};
    cfg.gridDim = dim3(132); cfg.blockDim = dim3(512); cfg.dynamicSmemBytes = SMEM_LAUNCH; cfg.stream = cudaStreamPerThread;
    cudaLaunchAttribute at[1];
    at[0].id = cudaLaunchAttributeClusterDimension; at[0].val.clusterDim.x = 2; at[0].val.clusterDim.y = 1; at[0].val.clusterDim.z = 1;
    cfg.attrs = at; cfg.numAttrs = 1;
    cudaLaunchKernelEx(&cfg, fused_kernel, mx, mw, mwo, mout, mgu, mwd, mo, x, wr, scr, swap_gu, Weights{(const char*)wqkv, (const char*)wo, (const char*)wg, (const char*)wu, (const char*)wd, (char*)d_out});
}
```

```cpp
#include <cuda_runtime.h>
#include <cuda.h>
#include <cuda_bf16.h>
#include <stdint.h>

namespace {

constexpr int BOX = 8192, W_BYTES = 3 * BOX;
constexpr int OFF_X1 = 6 * BOX, OFF_FR = 12 * BOX, OFF_E = 16 * BOX, OFF_W = 19 * BOX;
constexpr int OFF_WO = OFF_E;
constexpr int OFF_HIN = OFF_FR + 2048, OFF_GU = OFF_HIN + 2048, OFF_FS = OFF_GU + 1024;
constexpr int F_BYTES = 9216;
constexpr int CS_BYTES = 3136;
constexpr int OFF_CS = OFF_FS + 5 * F_BYTES;
constexpr int OFF_STAT = 28 * BOX;
constexpr int OFF_SEL = OFF_STAT + 2112;
constexpr int OFF_EP = OFF_SEL + 32;
constexpr int OFF_BAR = OFF_EP + 16;
constexpr int B_WFULL = 0, B_XFULL = 3, B_AUX = 15, B_XT = 16, B_ROW = 17, B_WOFULL = 18, B_OFULL = 24, B_FFULL = 36, B_ZERO = 41;
constexpr int B_WEMPTY = 42, B_F1DONE = 45, B_XEMPTY = 46, B_WOEMPTY = 52, B_OEMPTY = 58;
constexpr int B_G1DONE = 66, B_FEMPTY = 67, B_STAGED = 72, B_RDONE = 75, B_FREED = 76, NBAR = 78;
constexpr int SMEM_BYTES = OFF_BAR + NBAR * 8;
static_assert(OFF_FS + 3 * F_BYTES == OFF_E && OFF_CS + CS_BYTES <= OFF_W && SMEM_BYTES + 256 <= 232448 && OFF_BAR % 8 == 0, "smem");
#define POLL_NS 30
#define PF_RATE 9
#define PF_START 7
#define ZF_NS 100
#define FFN2_GATE (B_STAGED + 1)
#define PF_NW 4
#define EARLY_PK 17
#define FENCE_PRED "@p "
#define ZF_GATE B_ROW
#define HOLD 12
#define F1_DEPTH 1
#define F2_DEPTH 0
#define F1_HOLD 2
#define F1_GATE B_G1DONE
#define OUT_PARTS 2
#define Y_NS 200
#define ROWS_AT 11
constexpr int BUDGET = 1 << 18;

struct Scratch {
    uint8_t o[2048 * 1024 * 2];
    uint32_t ypart[8][8][1024];
    uint32_t halo[128][512];
    uint32_t act[2][14336 + 4096];
    uint2 row[2048];
    uint4 cs[16][3][24];
    uint32_t oflag[16][32];
    uint32_t cnt[9][32];
    uint32_t sel[32], epoch[32];
};
__device__ __align__(1024) Scratch g_scr;
struct Weights { const char *wqkv, *wo, *wg, *wu, *wd; char* out; };

#define TS(i) do {} while (0)
#define TS_END() do {} while (0)
#define TSC(c, i) do {} while (0)
#define NRETRY() do {} while (0)
constexpr int SMEM_LAUNCH = SMEM_BYTES;
__device__ __forceinline__ uint32_t smem_u32(const void* p) { return (uint32_t)__cvta_generic_to_shared(p); }
__device__ __forceinline__ void mbar_init(uint32_t bar, uint32_t cnt) { asm volatile("mbarrier.init.shared::cta.b64 [%0], %1;" ::"r"(bar), "r"(cnt) : "memory"); }
__device__ __forceinline__ void mbar_expect_tx(uint32_t bar, uint32_t bytes) { asm volatile("mbarrier.arrive.expect_tx.shared::cta.b64 _, [%0], %1;" ::"r"(bar), "r"(bytes) : "memory"); }
__device__ __forceinline__ void mbar_arrive(uint32_t bar) { asm volatile("mbarrier.arrive.shared::cta.b64 _, [%0];" ::"r"(bar) : "memory"); }
__device__ __forceinline__ uint32_t mapa(uint32_t a, uint32_t cta) { uint32_t r; asm("mapa.shared::cluster.u32 %0, %1, %2;" : "=r"(r) : "r"(a), "r"(cta)); return r; }
__device__ __forceinline__ void mbar_arrive_at(uint32_t cbar) { asm volatile("mbarrier.arrive.shared::cluster.b64 _, [%0];" ::"r"(cbar) : "memory"); }
__device__ __forceinline__ void mbar_wait(uint32_t bar, uint32_t parity, int& budget) {
    asm volatile("{\n.reg .pred p;\nLAB_WAIT:\nmbarrier.try_wait.parity.shared::cta.b64 p, [%1], %2;\n"
                 "add.s32 %0, %0, -1;\nsetp.gt.and.s32 p, %0, 0, !p;\n@p bra LAB_WAIT;\n}" : "+r"(budget) : "r"(bar), "r"(parity) : "memory");
}
__device__ __forceinline__ void mbar_wait_hot(uint32_t bar, uint32_t parity, int& budget) {
    asm volatile("{\n.reg .pred p;\nmbarrier.try_wait.parity.shared::cta.b64 p, [%1], %2;\n@p bra LAB_DONE;\nLAB_WAIT:\nmbarrier.try_wait.parity.shared::cta.b64 p, [%1], %2;\n"
                 "add.s32 %0, %0, -1;\nsetp.gt.and.s32 p, %0, 0, !p;\n@p bra LAB_WAIT;\nLAB_DONE:\n}" : "+r"(budget) : "r"(bar), "r"(parity) : "memory");
}
__device__ __forceinline__ void tma_2d_mc(uint32_t dst, const CUtensorMap* m, uint32_t bar, int c0, int c1) {
    asm volatile("cp.async.bulk.tensor.2d.shared::cluster.global.mbarrier::complete_tx::bytes.multicast::cluster [%0], [%1, {%3, %4}], [%2], %5;" ::"r"(dst), "l"(m), "r"(bar), "r"(c0), "r"(c1), "h"((uint16_t)3) : "memory");
}
__device__ __forceinline__ void tma_3d(uint32_t dst, const CUtensorMap* m, uint32_t bar, int c0, int c1, int c2) {
    asm volatile("cp.async.bulk.tensor.3d.shared::cluster.global.mbarrier::complete_tx::bytes [%0], [%1, {%3, %4, %5}], [%2];" ::"r"(dst), "l"(m), "r"(bar), "r"(c0), "r"(c1), "r"(c2) : "memory");
}
__device__ __forceinline__ void tma_4d(uint32_t dst, const CUtensorMap* m, uint32_t bar, int c0, int c1, int c2, int c3) {
    asm volatile("cp.async.bulk.tensor.4d.shared::cluster.global.mbarrier::complete_tx::bytes [%0], [%1, {%3, %4, %5, %6}], [%2];" ::"r"(dst), "l"(m), "r"(bar), "r"(c0), "r"(c1), "r"(c2), "r"(c3) : "memory");
}
__device__ __forceinline__ void tma_4d_mc(uint32_t dst, const CUtensorMap* m, uint32_t bar, int c0, int c1, int c2, int c3) {
    asm volatile("cp.async.bulk.tensor.4d.shared::cluster.global.mbarrier::complete_tx::bytes.multicast::cluster [%0], [%1, {%3, %4, %5, %6}], [%2], %7;" ::"r"(dst), "l"(m), "r"(bar), "r"(c0), "r"(c1), "r"(c2), "r"(c3), "h"((uint16_t)3) : "memory");
}
__device__ __forceinline__ void bulk_pf(const void* p, uint32_t bytes) { asm volatile("cp.async.bulk.prefetch.L2.global [%0], %1;" ::"l"(p), "r"(bytes) : "memory"); }
__device__ __forceinline__ void bulk_g2s(uint32_t dst, const void* src, uint32_t bytes, uint32_t bar) {
    asm volatile("cp.async.bulk.shared::cluster.global.mbarrier::complete_tx::bytes [%0], [%1], %2, [%3];" ::"r"(dst), "l"(src), "r"(bytes), "r"(bar) : "memory");
}
__device__ __forceinline__ void bulk_s2c(uint32_t cdst, uint32_t src, uint32_t bytes, uint32_t cbar) {
    asm volatile("cp.async.bulk.shared::cluster.shared::cta.mbarrier::complete_tx::bytes [%0], [%1], %2, [%3];" ::"r"(cdst), "r"(src), "r"(bytes), "r"(cbar) : "memory");
}
__device__ __forceinline__ void cluster_wait() { asm volatile("barrier.cluster.wait.aligned;" ::: "memory"); }
__device__ __forceinline__ void fence_gpu() { asm volatile("fence.acq_rel.gpu;" ::: "memory"); }
__device__ __forceinline__ void fence_async_smem() { asm volatile("fence.proxy.async.shared::cta;" ::: "memory"); }
__device__ __forceinline__ void wg_fence() { asm volatile("wgmma.fence.sync.aligned;" ::: "memory"); }
__device__ __forceinline__ void wg_commit() { asm volatile("wgmma.commit_group.sync.aligned;" ::: "memory"); }
template <int N> __device__ __forceinline__ void wg_wait() { asm volatile("wgmma.wait_group.sync.aligned %0;" ::"n"(N) : "memory"); }
__device__ __forceinline__ uint64_t mkdesc(uint32_t lo, uint32_t hi) { return ((uint64_t)hi << 32) | lo; }
__host__ __device__ constexpr uint32_t dhi(uint32_t sbo, uint32_t mode) { return (sbo >> 4) | (mode << 30); }
__host__ __device__ constexpr uint32_t dlo(uint32_t off, uint32_t lbo) { return (off >> 4) + ((lbo >> 4) << 16); }
__device__ __forceinline__ bool elect_one() {
    uint32_t e;
    asm volatile("{\n.reg .pred p;\nelect.sync _|p, 0xffffffff;\nselp.u32 %0, 1, 0, p;\n}" : "=r"(e));
    return e;
}
template <int R> __device__ __forceinline__ void reg_inc() { asm volatile("setmaxnreg.inc.sync.aligned.u32 %0;" ::"n"(R)); }
template <int R> __device__ __forceinline__ void reg_dec() { asm volatile("setmaxnreg.dec.sync.aligned.u32 %0;" ::"n"(R)); }
__device__ __forceinline__ void bar_sync(int id, int n) { asm volatile("bar.sync %0, %1;" ::"r"(id), "r"(n) : "memory"); }
__device__ __forceinline__ void bar_arrive(int id, int n) { asm volatile("bar.arrive %0, %1;" ::"r"(id), "r"(n) : "memory"); }
__device__ __forceinline__ uint32_t pack_bf16(float lo, float hi) { uint32_t r; asm("cvt.rn.bf16x2.f32 %0, %1, %2;" : "=r"(r) : "f"(hi), "f"(lo)); return r; }
__device__ __forceinline__ uint32_t pack_here(float lo, float hi) { uint32_t r; asm volatile("cvt.rn.bf16x2.f32 %0, %1, %2;" : "=r"(r) : "f"(hi), "f"(lo)); return r; }
__device__ __forceinline__ float bf_lo(uint32_t u) { return __uint_as_float(u << 16); }
__device__ __forceinline__ float bf_hi(uint32_t u) { return __uint_as_float(u & 0xffff0000u); }
__device__ __forceinline__ float bf16r(float v) { return bf_lo(pack_bf16(v, 0.f)); }
__device__ __forceinline__ float rcp(float x) { float r; asm("rcp.approx.ftz.f32 %0, %1;" : "=f"(r) : "f"(x)); return r; }
__device__ __forceinline__ float ex2(float x) { float r; asm("ex2.approx.ftz.f32 %0, %1;" : "=f"(r) : "f"(x)); return r; }
__device__ __forceinline__ float sigmoidf(float v) { return rcp(1.f + ex2(v * -1.4426950408889634f)); }
__device__ __forceinline__ uint32_t movm(uint32_t a) { uint32_t d; asm volatile("movmatrix.sync.aligned.m8n8.trans.b16 %0, %1;" : "=r"(d) : "r"(a)); return d; }
__device__ __forceinline__ void mma16816(float (&c)[4], uint32_t a0, uint32_t a1, uint32_t a2, uint32_t a3, uint32_t b0, uint32_t b1) {
    asm volatile("mma.sync.aligned.m16n8k16.row.col.f32.bf16.bf16.f32 {%0,%1,%2,%3}, {%4,%5,%6,%7}, {%8,%9}, {%0,%1,%2,%3};"
                 : "+f"(c[0]), "+f"(c[1]), "+f"(c[2]), "+f"(c[3]) : "r"(a0), "r"(a1), "r"(a2), "r"(a3), "r"(b0), "r"(b1));
}
__device__ __forceinline__ void mma1688(float (&c)[4], uint32_t a0, uint32_t a1, uint32_t b0) {
    asm volatile("mma.sync.aligned.m16n8k8.row.col.f32.bf16.bf16.f32 {%0,%1,%2,%3}, {%4,%5}, {%6}, {%0,%1,%2,%3};"
                 : "+f"(c[0]), "+f"(c[1]), "+f"(c[2]), "+f"(c[3]) : "r"(a0), "r"(a1), "r"(b0));
}
__device__ __forceinline__ void stsm4(uint32_t a, uint32_t r0, uint32_t r1, uint32_t r2, uint32_t r3) {
    asm volatile("stmatrix.sync.aligned.m8n8.x4.shared.b16 [%0], {%1,%2,%3,%4};" ::"r"(a), "r"(r0), "r"(r1), "r"(r2), "r"(r3) : "memory");
}
__device__ __forceinline__ void ldsm4(uint32_t* r, uint32_t a) {
    asm volatile("ldmatrix.sync.aligned.m8n8.x4.shared.b16 {%0,%1,%2,%3}, [%4];" : "=r"(r[0]), "=r"(r[1]), "=r"(r[2]), "=r"(r[3]) : "r"(a) : "memory");
}
__device__ __forceinline__ void ldsm4t(uint32_t* r, uint32_t a) {
    asm volatile("ldmatrix.sync.aligned.m8n8.x4.trans.shared.b16 {%0,%1,%2,%3}, [%4];" : "=r"(r[0]), "=r"(r[1]), "=r"(r[2]), "=r"(r[3]) : "r"(a) : "memory");
}
__device__ __forceinline__ uint32_t ld_rlx(const void* p) { uint32_t v; asm volatile("ld.relaxed.gpu.global.u32 %0, [%1];" : "=r"(v) : "l"(p) : "memory"); return v; }
__device__ __forceinline__ uint32_t ld_acq(const void* p) { uint32_t v; asm volatile("ld.acquire.gpu.global.u32 %0, [%1];" : "=r"(v) : "l"(p) : "memory"); return v; }
__device__ __forceinline__ uint2 ld_rlx2(const void* p) { uint2 v; asm volatile("ld.relaxed.gpu.global.v2.u32 {%0,%1}, [%2];" : "=r"(v.x), "=r"(v.y) : "l"(p) : "memory"); return v; }
__device__ __forceinline__ uint4 ld_rlx4(const void* p) { uint4 v; asm volatile("ld.relaxed.gpu.global.v4.u32 {%0,%1,%2,%3}, [%4];" : "=r"(v.x), "=r"(v.y), "=r"(v.z), "=r"(v.w) : "l"(p) : "memory"); return v; }
__device__ __forceinline__ void st_rlx(void* p, uint32_t v) { asm volatile("st.relaxed.gpu.global.u32 [%0], %1;" ::"l"(p), "r"(v) : "memory"); }
__device__ __forceinline__ void st_rlx2(void* p, uint32_t a, uint32_t b) { asm volatile("st.relaxed.gpu.global.v2.u32 [%0], {%1,%2};" ::"l"(p), "r"(a), "r"(b) : "memory"); }
__device__ __forceinline__ void st_rlx4(void* p, uint32_t a, uint32_t b, uint32_t c, uint32_t d) { asm volatile("st.relaxed.gpu.global.v4.u32 [%0], {%1,%2,%3,%4};" ::"l"(p), "r"(a), "r"(b), "r"(c), "r"(d) : "memory"); }
__device__ __forceinline__ void red_add(uint32_t* p) { asm volatile("red.relaxed.gpu.global.add.u32 [%0], 1;" ::"l"(p) : "memory"); }
__device__ __forceinline__ uint4 ldg_nc(const void* p) { uint4 v; asm volatile("ld.global.nc.v4.u32 {%0,%1,%2,%3}, [%4];" : "=r"(v.x), "=r"(v.y), "=r"(v.z), "=r"(v.w) : "l"(p)); return v; }
__device__ __forceinline__ void sts4(uint32_t a, uint32_t x, uint32_t y, uint32_t z, uint32_t w) { asm volatile("st.shared.v4.u32 [%0], {%1,%2,%3,%4};" ::"r"(a), "r"(x), "r"(y), "r"(z), "r"(w) : "memory"); }
__device__ __forceinline__ void sts2(uint32_t a, uint32_t x, uint32_t y) { asm volatile("st.shared.v2.u32 [%0], {%1,%2};" ::"r"(a), "r"(x), "r"(y) : "memory"); }
__device__ __forceinline__ void sts1(uint32_t a, uint32_t v) { asm volatile("st.shared.u32 [%0], %1;" ::"r"(a), "r"(v) : "memory"); }
__device__ __forceinline__ uint4 lds4(uint32_t a) { uint4 v; asm volatile("ld.shared.v4.u32 {%0,%1,%2,%3}, [%4];" : "=r"(v.x), "=r"(v.y), "=r"(v.z), "=r"(v.w) : "r"(a) : "memory"); return v; }
__device__ __forceinline__ float4 lds4f(uint32_t a) { float4 v; asm volatile("ld.shared.v4.f32 {%0,%1,%2,%3}, [%4];" : "=f"(v.x), "=f"(v.y), "=f"(v.z), "=f"(v.w) : "r"(a) : "memory"); return v; }
__device__ __forceinline__ float2 lds2f(uint32_t a) { float2 v; asm volatile("ld.shared.v2.f32 {%0,%1}, [%2];" : "=f"(v.x), "=f"(v.y) : "r"(a) : "memory"); return v; }
__device__ __forceinline__ float lds1f(uint32_t a) { float v; asm volatile("ld.shared.f32 %0, [%1];" : "=f"(v) : "r"(a) : "memory"); return v; }
__device__ __forceinline__ uint32_t lds1(uint32_t a) { uint32_t v; asm volatile("ld.shared.u32 %0, [%1];" : "=r"(v) : "r"(a) : "memory"); return v; }
__device__ __forceinline__ uint32_t redux_max(uint32_t v) { uint32_t r; asm volatile("redux.sync.max.u32 %0, %1, 0xffffffff;" : "=r"(r) : "r"(v)); return r; }
__device__ __forceinline__ uint32_t poll_all(const uint32_t* p, uint32_t mask, uint32_t want, int& budget) {
    uint32_t v;
#pragma unroll 1
    while (v = ld_acq(p), !__all_sync(0xffffffffu, (v & mask) == want) && --budget > 0) __nanosleep(POLL_NS);
    return v;
}

template <int TA, int TB>
__device__ __forceinline__ void wgmma_n192(float (&d)[96], uint64_t da, uint64_t db, int keep) {
    asm volatile("{\n.reg .pred p;\nsetp.ne.b32 p, %98, 0;\n"
        "wgmma.mma_async.sync.aligned.m64n192k16.f32.bf16.bf16 "
        "{%0, %1, %2, %3, %4, %5, %6, %7, %8, %9, %10, %11, %12, %13, %14, %15, "
        "%16, %17, %18, %19, %20, %21, %22, %23, %24, %25, %26, %27, %28, %29, %30, %31, "
        "%32, %33, %34, %35, %36, %37, %38, %39, %40, %41, %42, %43, %44, %45, %46, %47, "
        "%48, %49, %50, %51, %52, %53, %54, %55, %56, %57, %58, %59, %60, %61, %62, %63, "
        "%64, %65, %66, %67, %68, %69, %70, %71, %72, %73, %74, %75, %76, %77, %78, %79, "
        "%80, %81, %82, %83, %84, %85, %86, %87, %88, %89, %90, %91, %92, %93, %94, %95}, "
        "%96, %97, p, 1, 1, %99, %100;\n}\n"
        : "+f"(d[0]), "+f"(d[1]), "+f"(d[2]), "+f"(d[3]), "+f"(d[4]), "+f"(d[5]), "+f"(d[6]), "+f"(d[7]),
          "+f"(d[8]), "+f"(d[9]), "+f"(d[10]), "+f"(d[11]), "+f"(d[12]), "+f"(d[13]), "+f"(d[14]), "+f"(d[15]),
          "+f"(d[16]), "+f"(d[17]), "+f"(d[18]), "+f"(d[19]), "+f"(d[20]), "+f"(d[21]), "+f"(d[22]), "+f"(d[23]),
          "+f"(d[24]), "+f"(d[25]), "+f"(d[26]), "+f"(d[27]), "+f"(d[28]), "+f"(d[29]), "+f"(d[30]), "+f"(d[31]),
          "+f"(d[32]), "+f"(d[33]), "+f"(d[34]), "+f"(d[35]), "+f"(d[36]), "+f"(d[37]), "+f"(d[38]), "+f"(d[39]),
          "+f"(d[40]), "+f"(d[41]), "+f"(d[42]), "+f"(d[43]), "+f"(d[44]), "+f"(d[45]), "+f"(d[46]), "+f"(d[47]),
          "+f"(d[48]), "+f"(d[49]), "+f"(d[50]), "+f"(d[51]), "+f"(d[52]), "+f"(d[53]), "+f"(d[54]), "+f"(d[55]),
          "+f"(d[56]), "+f"(d[57]), "+f"(d[58]), "+f"(d[59]), "+f"(d[60]), "+f"(d[61]), "+f"(d[62]), "+f"(d[63]),
          "+f"(d[64]), "+f"(d[65]), "+f"(d[66]), "+f"(d[67]), "+f"(d[68]), "+f"(d[69]), "+f"(d[70]), "+f"(d[71]),
          "+f"(d[72]), "+f"(d[73]), "+f"(d[74]), "+f"(d[75]), "+f"(d[76]), "+f"(d[77]), "+f"(d[78]), "+f"(d[79]),
          "+f"(d[80]), "+f"(d[81]), "+f"(d[82]), "+f"(d[83]), "+f"(d[84]), "+f"(d[85]), "+f"(d[86]), "+f"(d[87]),
          "+f"(d[88]), "+f"(d[89]), "+f"(d[90]), "+f"(d[91]), "+f"(d[92]), "+f"(d[93]), "+f"(d[94]), "+f"(d[95])
        : "l"(da), "l"(db), "r"(keep), "n"(TA), "n"(TB));
}
template <int TA, int TB>
__device__ __forceinline__ void wgmma_n128(float (&d)[64], uint64_t da, uint64_t db, int keep) {
    asm volatile("{\n.reg .pred p;\nsetp.ne.b32 p, %66, 0;\n"
        "wgmma.mma_async.sync.aligned.m64n128k16.f32.bf16.bf16 "
        "{%0, %1, %2, %3, %4, %5, %6, %7, %8, %9, %10, %11, %12, %13, %14, %15, "
        "%16, %17, %18, %19, %20, %21, %22, %23, %24, %25, %26, %27, %28, %29, %30, %31, "
        "%32, %33, %34, %35, %36, %37, %38, %39, %40, %41, %42, %43, %44, %45, %46, %47, "
        "%48, %49, %50, %51, %52, %53, %54, %55, %56, %57, %58, %59, %60, %61, %62, %63}, "
        "%64, %65, p, 1, 1, %67, %68;\n}\n"
        : "+f"(d[0]), "+f"(d[1]), "+f"(d[2]), "+f"(d[3]), "+f"(d[4]), "+f"(d[5]), "+f"(d[6]), "+f"(d[7]),
          "+f"(d[8]), "+f"(d[9]), "+f"(d[10]), "+f"(d[11]), "+f"(d[12]), "+f"(d[13]), "+f"(d[14]), "+f"(d[15]),
          "+f"(d[16]), "+f"(d[17]), "+f"(d[18]), "+f"(d[19]), "+f"(d[20]), "+f"(d[21]), "+f"(d[22]), "+f"(d[23]),
          "+f"(d[24]), "+f"(d[25]), "+f"(d[26]), "+f"(d[27]), "+f"(d[28]), "+f"(d[29]), "+f"(d[30]), "+f"(d[31]),
          "+f"(d[32]), "+f"(d[33]), "+f"(d[34]), "+f"(d[35]), "+f"(d[36]), "+f"(d[37]), "+f"(d[38]), "+f"(d[39]),
          "+f"(d[40]), "+f"(d[41]), "+f"(d[42]), "+f"(d[43]), "+f"(d[44]), "+f"(d[45]), "+f"(d[46]), "+f"(d[47]),
          "+f"(d[48]), "+f"(d[49]), "+f"(d[50]), "+f"(d[51]), "+f"(d[52]), "+f"(d[53]), "+f"(d[54]), "+f"(d[55]),
          "+f"(d[56]), "+f"(d[57]), "+f"(d[58]), "+f"(d[59]), "+f"(d[60]), "+f"(d[61]), "+f"(d[62]), "+f"(d[63])
        : "l"(da), "l"(db), "r"(keep), "n"(TA), "n"(TB));
}
template <int TA, int TB>
__device__ __forceinline__ void wgmma_n8(float (&d)[4], uint64_t da, uint64_t db, int keep) {
    asm volatile("{\n.reg .pred p;\nsetp.ne.b32 p, %6, 0;\n"
        "wgmma.mma_async.sync.aligned.m64n8k16.f32.bf16.bf16 "
        "{%0, %1, %2, %3}, "
        "%4, %5, p, 1, 1, %7, %8;\n}\n"
        : "+f"(d[0]), "+f"(d[1]), "+f"(d[2]), "+f"(d[3])
        : "l"(da), "l"(db), "r"(keep), "n"(TA), "n"(TB));
}
__device__ __forceinline__ void wgmma_rs_n192(float (&d)[96], uint32_t a0, uint32_t a1, uint32_t a2, uint32_t a3, uint64_t db) {
    asm volatile("{\n.reg .pred p;\nsetp.ne.b32 p, 1, 0;\n"
        "wgmma.mma_async.sync.aligned.m64n192k16.f32.bf16.bf16 "
        "{%0, %1, %2, %3, %4, %5, %6, %7, %8, %9, %10, %11, %12, %13, %14, %15, "
        "%16, %17, %18, %19, %20, %21, %22, %23, %24, %25, %26, %27, %28, %29, %30, %31, "
        "%32, %33, %34, %35, %36, %37, %38, %39, %40, %41, %42, %43, %44, %45, %46, %47, "
        "%48, %49, %50, %51, %52, %53, %54, %55, %56, %57, %58, %59, %60, %61, %62, %63, "
        "%64, %65, %66, %67, %68, %69, %70, %71, %72, %73, %74, %75, %76, %77, %78, %79, "
        "%80, %81, %82, %83, %84, %85, %86, %87, %88, %89, %90, %91, %92, %93, %94, %95}, "
        "{%96, %97, %98, %99}, %100, p, 1, 1, 1;\n}\n"
        : "+f"(d[0]), "+f"(d[1]), "+f"(d[2]), "+f"(d[3]), "+f"(d[4]), "+f"(d[5]), "+f"(d[6]), "+f"(d[7]),
          "+f"(d[8]), "+f"(d[9]), "+f"(d[10]), "+f"(d[11]), "+f"(d[12]), "+f"(d[13]), "+f"(d[14]), "+f"(d[15]),
          "+f"(d[16]), "+f"(d[17]), "+f"(d[18]), "+f"(d[19]), "+f"(d[20]), "+f"(d[21]), "+f"(d[22]), "+f"(d[23]),
          "+f"(d[24]), "+f"(d[25]), "+f"(d[26]), "+f"(d[27]), "+f"(d[28]), "+f"(d[29]), "+f"(d[30]), "+f"(d[31]),
          "+f"(d[32]), "+f"(d[33]), "+f"(d[34]), "+f"(d[35]), "+f"(d[36]), "+f"(d[37]), "+f"(d[38]), "+f"(d[39]),
          "+f"(d[40]), "+f"(d[41]), "+f"(d[42]), "+f"(d[43]), "+f"(d[44]), "+f"(d[45]), "+f"(d[46]), "+f"(d[47]),
          "+f"(d[48]), "+f"(d[49]), "+f"(d[50]), "+f"(d[51]), "+f"(d[52]), "+f"(d[53]), "+f"(d[54]), "+f"(d[55]),
          "+f"(d[56]), "+f"(d[57]), "+f"(d[58]), "+f"(d[59]), "+f"(d[60]), "+f"(d[61]), "+f"(d[62]), "+f"(d[63]),
          "+f"(d[64]), "+f"(d[65]), "+f"(d[66]), "+f"(d[67]), "+f"(d[68]), "+f"(d[69]), "+f"(d[70]), "+f"(d[71]),
          "+f"(d[72]), "+f"(d[73]), "+f"(d[74]), "+f"(d[75]), "+f"(d[76]), "+f"(d[77]), "+f"(d[78]), "+f"(d[79]),
          "+f"(d[80]), "+f"(d[81]), "+f"(d[82]), "+f"(d[83]), "+f"(d[84]), "+f"(d[85]), "+f"(d[86]), "+f"(d[87]),
          "+f"(d[88]), "+f"(d[89]), "+f"(d[90]), "+f"(d[91]), "+f"(d[92]), "+f"(d[93]), "+f"(d[94]), "+f"(d[95])
        : "r"(a0), "r"(a1), "r"(a2), "r"(a3), "l"(db));
}

template <int HS>
__device__ __forceinline__ void attn_pair(const uint32_t* q, const uint32_t* k, const uint32_t* v, const uint32_t* kh, const uint32_t* vh,
                                          const float* fu, const float* fn, const float* rk, float bias0, float bias1, uint32_t mU, uint32_t zero, const float* ci, uint32_t* o) {
    float s0[2][4] = {}, s1[2][4] = {}, s2[2][4] = {};
#pragma unroll
    for (int n = 0; n < 4; n++) {
        const int hd = n & 1, a = 8 * hd + 2 * (n & 2);
        mma16816(s1[hd], q[a], q[a + 1], q[a + 2], q[a + 3], k[a], k[a + 2]);
        mma16816(s2[hd], q[a], q[a + 1], q[a + 2], q[a + 3], k[a + 1], k[a + 3]);
    }
#pragma unroll
    for (int n = 0; n < 4; n++) {
        const int hd = n & 1, a = 8 * hd + 2 * (n & 2);
        mma16816(s0[hd], q[a], q[a + 1], q[a + 2], q[a + 3], kh[HS * (a / 2)], kh[HS * (a / 2 + 1)]);
    }
    float e[2][4], m[2][2];
#pragma unroll
    for (int hd = 0; hd < 2; hd++) {
        e[hd][2] = fmaf(s1[hd][2], fu[2], s2[hd][2] * fn[2]); e[hd][3] = fmaf(s1[hd][3], fu[3], s2[hd][3] * fn[3]);
        e[hd][0] = fmaf(s0[hd][0], fu[0], fmaf(s1[hd][0], fn[0], bias0)); e[hd][1] = fmaf(s0[hd][1], fu[1], fmaf(s1[hd][1], fn[1], bias1));
        m[hd][1] = fmaxf(e[hd][2], e[hd][3]); m[hd][0] = fmaxf(e[hd][0], e[hd][1]);
    }
#pragma unroll
    for (int x = 1; x < 3; x++)
#pragma unroll
        for (int n = 0; n < 4; n++) m[n & 1][1 - (n >> 1)] = fmaxf(m[n & 1][1 - (n >> 1)], __shfl_xor_sync(0xffffffffu, m[n & 1][1 - (n >> 1)], x));
#pragma unroll
    for (int hd = 0; hd < 2; hd++) {
#pragma unroll
        for (int n = 0; n < 4; n++) e[hd][n] = ex2(e[hd][n] - m[hd][n >> 1]);
        float sum[4] = {};
        mma1688(sum, pack_bf16(e[hd][0], e[hd][1]), pack_bf16(e[hd][2], e[hd][3]), 0x3f803f80u);
        const float i0 = rcp(sum[0]), i1 = rcp(sum[2]);
        const uint32_t plo = pack_bf16(e[hd][0] * rk[0] * i0, e[hd][1] * rk[1] * i0), phi = pack_bf16(e[hd][2] * rk[2] * i1, e[hd][3] * rk[3] * i1);
        const uint32_t z0 = plo & zero, z1 = phi & zero;
        const uint32_t a0 = plo & ~mU, a1 = phi & mU, a3 = phi & ~mU, b0 = plo & mU;
#pragma unroll
        for (int jj = 0; jj < 4; jj++) {
            float c[4];
            asm volatile("mma.sync.aligned.m16n8k16.row.col.f32.bf16.bf16.f32 {%0,%1,%2,%3}, {%4,%5,%6,%7}, {%8,%9}, {%10,%11,%12,%13};"
                         : "=f"(c[0]), "=f"(c[1]), "=f"(c[2]), "=f"(c[3])
                         : "r"(a0), "r"(a1), "r"(z0), "r"(a3), "r"(v[8 * hd + 2 * jj]), "r"(v[8 * hd + 2 * jj + 1]), "f"(ci[0]), "f"(ci[1]), "f"(ci[2]), "f"(ci[3]));
            mma1688(c, b0, z1, vh[HS * (4 * hd + jj)]);
            o[8 * hd + 2 * jj] = pack_bf16(c[0], c[1]); o[8 * hd + 2 * jj + 1] = pack_bf16(c[2], c[3]);
        }
    }
}

__device__ __forceinline__ uint32_t norm_pair(uint32_t u, float m, float rinv) {
    const uint32_t d = pack_bf16(bf_lo(u) - m, bf_hi(u) - m);
    return max(pack_bf16(bf_lo(d) * rinv, bf_hi(d) * rinv), 1u);
}

__global__ void __launch_bounds__(512, 1)
fused_kernel(const __grid_constant__ CUtensorMap mx, const __grid_constant__ CUtensorMap mw, const __grid_constant__ CUtensorMap mwo,
             const __grid_constant__ CUtensorMap mout, const __grid_constant__ CUtensorMap mgu, const __grid_constant__ CUtensorMap mwd,
             const __grid_constant__ CUtensorMap mo,
             const __nv_bfloat16* __restrict__ x, const __nv_bfloat16* __restrict__ wr, Scratch* __restrict__ scr, int swap_gu, const Weights pf) {
    extern __shared__ __align__(1024) uint8_t smem[];
    const uint32_t sb = smem_u32(smem);
    const uint32_t bars = sb + OFF_BAR;
    const int tid = threadIdx.x, lane = tid & 31, warp = __shfl_sync(0xffffffffu, tid >> 5, 0);
    const uint32_t sd = (sb & 0x3FFFF) >> 4;
    const int hp = blockIdx.x & 1, cl = blockIdx.x >> 1;
    int pr = cl - 4 + (max(cl - 36, 0) * 37 >> 8);
    asm("{\n.reg .pred p;\nsetp.lt.s32 p, %1, 4;\nselp.s32 %0, %2, %0, p;\n}" : "+r"(pr) : "r"(cl), "r"(39 + 8 * cl));
    const int b = pr * 2 + hp, mt = pr >> 3, p = pr & 7, nt = 2 * p + hp, rh = p & 1, cb = (p & 6) + hp;
    const int par = mt >> 2, j0 = (mt & 3) * 256;
    int budget = BUDGET;

    TSC(tid == 0, 0);
    auto load_w = [&](int k, int s) {
        const uint32_t full = bars + 8 * (B_WFULL + s);
        mbar_expect_tx(full, W_BYTES);
        tma_3d(sb + OFF_W + s * W_BYTES, &mw, full, nt * 64, k * 64, 0);
    };
    auto load_x = [&](int n) {
        const int w = n & 1, j = n < 4 ? (n >> 1) + 4 : (n >> 1) - 2;
        const uint32_t full = bars + 8 * (B_XFULL + w * 6 + 5 - j);
        mbar_expect_tx(full, BOX);
        tma_4d(sb + w * OFF_X1 + j * BOX, &mx, full, par * 1024 + (n >> 2) * 64, 0, (j0 + w * 128) >> 5, (~n >> 1) & 1);
    };
    if (warp < NBAR / 6 && elect_one()) {
        const uint32_t cnt = warp < B_WEMPTY / 6 ? 1 : warp < B_G1DONE / 6 ? 2 : warp < B_STAGED / 6 ? 4 : 8;
#pragma unroll
        for (int i = 0; i < 6; i++) mbar_init(bars + 48 * warp + 8 * i, cnt);
        asm volatile("fence.mbarrier_init.release.cluster;" ::: "memory");
        if (warp == 0 && b < 128) { load_x(0); load_w(0, 2); }
    }
    __syncthreads();

    if (b >= 128) {
        const int hc = b - 128, g = lane >> 2, t = lane & 3;
        const uint32_t ep = ld_rlx(&scr->epoch[0]) + 1;
        if (warp < 12) {
            const int n = warp / 3, part = warp - 3 * n;
            auto load = [&](int k) {
                const uint32_t full = bars + 8 * (2 * n + (k & 1));
                mbar_expect_tx(full, W_BYTES);
                tma_3d(sb + (2 * n + (k & 1)) * W_BYTES, &mw, full, (4 * hc + n) * 64, k * 64, 0);
            };
            if (part == 0 && elect_one()) { load(0); load(1); }
            __syncwarp();
            float c0[4] = {0.f, 0.f, 0.f, 0.f}, c1[4] = {0.f, 0.f, 0.f, 0.f};
            const uint32_t sel = g == 0 ? 0x3f80u : g == 1 ? 0x3f800000u : 0u;
            const uint32_t a = sb + 2 * n * W_BYTES + part * BOX + t * 256 + ((g ^ (2 * t)) << 4);
#pragma unroll 1
            for (int k = 0; k < 16; k++) {
                mbar_wait(bars + 8 * (2 * n + (k & 1)), (k >> 1) & 1, budget);
                uint4 v[8], u[8];
#pragma unroll
                for (int i = 0; i < 8; i++) { v[i] = lds4(a + (k & 1) * W_BYTES + i * 1024); u[i] = lds4(((a + 128) ^ 16) + (k & 1) * W_BYTES + i * 1024); }
#pragma unroll
                for (int i = 0; i < 8; i++) { mma16816(c0, v[i].x, v[i].y, u[i].x, u[i].y, sel, sel); mma16816(c1, v[i].z, v[i].w, u[i].z, u[i].w, sel, sel); }
                bar_sync(1 + n, 96);
                if (part == 0 && k < 14 && elect_one()) load(k + 2);
                __syncwarp();
            }
            if (t == 0) {
#pragma unroll
                for (int r = 0; r < 3; r++) {
                    const uint32_t q0 = (pack_bf16(c0[0], c0[1]) & ~1u) | (ep & 1), q1 = pack_bf16(c0[2], c0[3]), q2 = pack_bf16(c1[0], c1[1]), q3 = pack_bf16(c1[2], c1[3]);
                    st_rlx4(&scr->cs[4 * hc + n][r][part * 8 + g], q0, q1, q2, q3);
                    c0[0] -= bf_lo(q0); c0[1] -= bf_hi(q0); c0[2] -= bf_lo(q1); c0[3] -= bf_hi(q1);
                    c1[0] -= bf_lo(q2); c1[1] -= bf_hi(q2); c1[2] -= bf_lo(q3); c1[3] -= bf_hi(q3);
                }
            }
            TSC(tid == 0, 19);
        }
        if (warp < 8) TS_END();
        return;
    }
    asm volatile("barrier.cluster.arrive.relaxed.aligned;" ::: "memory");

    const int kc = b >> 4, c2 = b & 15;
    if (warp >= 12) {
        reg_dec<24>();
        if (warp == 12) {
            if (elect_one()) {
#pragma unroll 1
                for (int n = 1; n < 12; n++) {
                    load_x(n);
                    if (n == ROWS_AT) { mbar_expect_tx(bars + 8 * B_ROW, 4 * BOX); bulk_g2s(sb + OFF_FR, x + (size_t)b * 16 * 1024, 4 * BOX, bars + 8 * B_ROW); }
                    if (n == 3 || n == 7) load_w((n + 1) >> 2, n >> 2);
                }
                int s = 2; uint32_t ph = 0;
#pragma unroll 1
                for (int k = 3; k < 16; k++) {
                    mbar_wait(bars + 8 * (B_WEMPTY + s), ph, budget);
                    load_w(k, s);
                    if (++s == 3) s = 0;
                    if (s == 2) ph ^= 1;
                }
                s = 2;
#pragma unroll 1
                for (int i = 0; i < 16; i++) {
                    mbar_wait(bars + 8 * (i < 2 ? B_WEMPTY + i : i < 4 ? B_G1DONE : i < 6 ? B_F1DONE : B_WOEMPTY + s), i >= 12, budget);
                    if (i == 0) {
                        mbar_expect_tx(bars + 8 * B_XT, 4 * BOX);
#pragma unroll 1
                        for (int n = 0; n < 4; n++)
                            tma_4d(sb + (n >> 1) * OFF_X1 + (n & 1) * BOX, &mx, bars + 8 * B_XT, par * 1024 + cb * 128 + (n & 1) * 64, 0, (j0 + rh * 128) >> 5, 1 - (n >> 1));
                    }
                    const uint32_t full = bars + 8 * (B_WOFULL + s);
                    mbar_expect_tx(full, 2 * BOX);
                    tma_3d(sb + OFF_WO + s * 2 * BOX, &mwo, full, 0, ((2 * p + (i < 2 ? i ^ hp : i)) & 15) * 64, cb * 2);
                    TSC(TIMING % 10 == 4, 48 + i);
                    if (++s == 6) s = 0;
                }
            }
        } else {
            bar_sync(8, 224);
            const uint32_t ep = __shfl_sync(0xffffffffu, lds1(sb + OFF_EP), 0);
            if (warp == 13) {
                cluster_wait();
                if (elect_one()) {
                    int j = 4, q = 0, left = BUDGET; uint32_t ph = 0;
#pragma unroll 1
                    for (int n = 6; n < 32; n++) {
                        mbar_wait(bars + 8 * (B_XEMPTY + j), ph, left);
                        tma_4d_mc(sb + hp * OFF_X1 + j * BOX, &mx, bars + 8 * (B_XFULL + hp * 6 + 5 - j), par * 1024 + (n >> 1) * 64, 0, (j0 + hp * 128) >> 5, ~n & 1);
                        if (++j == 6) j = 0;
                        if (j == 4) ph ^= 1;
#pragma unroll 1
                        for (; q < (PF_RATE * (n - PF_START) >> 3) && q < 18 + PF_NW; q++) {
                            const int u = q - PF_NW;
                            if (u < 0) bulk_pf(pf.wqkv + (size_t)(1024 + 128 * u + b) * 6144, 6144);
                            else if (u < 16) bulk_pf((b < 64 ? pf.wg : pf.wu) + (size_t)(u * 64 + (b & 63)) * 7168, 7168);
                            else bulk_pf(pf.wo + (size_t)((u - 16) * 128 + b) * 8192, 8192);
                        }
                    }
                }
                __syncwarp();
                uint32_t* hs = &scr->halo[b - 16][lane * 4];
                uint4 v[4] = {};
                if (j0) {
#pragma unroll 1
                    do {
#pragma unroll
                        for (int c = 0; c < 4; c++) v[c] = ld_rlx4(hs + c * 128);
                    } while (__any_sync(0xffffffffu, min(min(v[0].x, v[1].x), min(v[2].x, v[3].x)) == 0) && --budget > 0);
                }
#pragma unroll
                for (int c = 0; c < 4; c++) stsm4(sb + OFF_HIN + c * 512 + lane * 16, v[c].x, v[c].y, v[c].z, v[c].w);
                bar_arrive(11, 64);
                if (j0) {
#pragma unroll
                    for (int c = 0; c < 4; c++) st_rlx(hs + c * 128, 0);
                }
                TSC(lane == 0, 31);
                const int src = ((mt * 2 + rh) * 2 + 1 - hp) * 1024;
                if (elect_one()) {
                    const uint32_t* fl = &scr->oflag[mt * 2 + 1 - hp][0];
                    const uint32_t inv = (ep & 1) - 1;
                    uint32_t ready = 0, ph = 0;
                    int s = 4;
#pragma unroll 1
                    for (int i = 2; i < 16; i++) {
                        const int kb = (2 * p + i) & 15;
#pragma unroll 1
                        while (!((ready >> kb) & 1) && --budget > 0) ready = ld_rlx(fl) ^ inv;
                        TSC(i == 2, 30);
                        mbar_wait(bars + 8 * (B_OEMPTY + s), ph, budget);
                        tma_2d_mc(sb + hp * OFF_X1 + s * BOX, &mo, bars + 8 * (B_OFULL + hp * 6 + s), 0, src + kb * 64);
                        TSC(TIMING % 10 == 4 && hp == 0, 32 + i);
                        if (++s == 6) s = 0;
                        if (s == 4) ph ^= 1;
                    }
                }
            } else if (warp == 14) {
                if (elect_one()) {
                    uint32_t s8 = 0, ph = 0;
                    int tries = BUDGET;
                    const uint32_t* act = scr->act[ep & 1];
                    auto counted = [&](int c, uint32_t n) {
#pragma unroll 1
                        while (ld_rlx(&scr->cnt[c][0]) != ep * n && --tries > 0) __nanosleep(POLL_NS);
                    };
                    auto weights = [&](const CUtensorMap* m, int c0, int c1, int c2_) {
                        mbar_wait(bars + 8 * B_FEMPTY + s8, ph, budget);
                        mbar_expect_tx(bars + 8 * B_FFULL + s8, F_BYTES);
                        tma_3d(sb + OFF_FS + s8 * (F_BYTES / 8), m, bars + 8 * B_FFULL + s8, c0, c1, c2_);
                    };
                    if (b < 112) {
                        counted(8, 32);
                        TS(26);
#pragma unroll 1
                        for (int q = 0; q < 16; q++) {
                            weights(&mgu, b * 32, q * 64, 0);
                            bulk_g2s(sb + OFF_FS + BOX + s8 * (F_BYTES / 8), act + 14336 + q * 256, 1024, bars + 8 * B_FFULL + s8);
                            TSC(TIMING % 10 == 5, 32 + q);
                            if (q >= 8) bulk_pf(pf.wd + (size_t)((q - 8) * 112 + b) * 8192, 8192);
                            s8 += 8;
                            if (s8 == 40) { s8 = 0; ph ^= 1; }
                        }
                    }
#pragma unroll 1
                    for (int q = -3; q < 7; q++) {
                        if (q == 0) { counted(kc, 28); TS(29); }
                        if ((unsigned)q >= 3) weights(&mwd, 0, kc * 448 + (q < 0 ? q + 3 : q) * 64, c2);
                        if (q >= 0) bulk_g2s(sb + OFF_FS + BOX + s8 * (F_BYTES / 8), act + (kc * 7 + q) * 256, 1024, bars + 8 * B_FFULL + s8);
                        TSC(TIMING % 10 == 5, 51 + q);
                        s8 += 8;
                        if (s8 == 24) { s8 = 0; if ((unsigned)q >= 3) ph ^= 1; }
                    }
                }
            } else {
#pragma unroll 1
                for (int i = lane * 16; i < CS_BYTES; i += 512) sts4(sb + OFF_CS + i, 0, 0, 0, 0);
                mbar_wait(bars + 8 * ZF_GATE, 0, budget);
                uint8_t* oz = scr->o + ((size_t)mt * 64 + nt) * BOX + lane * 16;
#pragma unroll 1
                for (int i = 0; i < 16; i++, oz += 512) {
#pragma unroll
                    for (int n = 0; n < 4; n++) st_rlx4(oz + n * 16 * BOX, 0, 0, 0, 0);
                    __nanosleep(ZF_NS);
                }
                __syncwarp();
                fence_gpu();
                mbar_wait(bars + 8 * B_RDONE, 0, budget);
                int tries = BUDGET;
#pragma unroll 1
                for (int i = lane; i < 88; i += 32) {
                    const uint2* rp = &scr->row[2 * (j0 - 8 + i) + par];
                    uint2 v0, v1, v2;
#pragma unroll 1
                    do { v0 = ld_rlx2(rp + (j0 + i < 8 ? 16 : 0)); v1 = ld_rlx2(rp + 176); v2 = ld_rlx2(rp + 352); } while ((((v0.y ^ ep) | (v1.y ^ ep) | (v2.y ^ ep)) & 31) && --tries > 0);
                    sts2(sb + OFF_STAT + i * 8, (v0.x << 16) ^ 0x80000000u, __float_as_uint(rcp(bf_hi(v0.x))));
                    sts2(sb + OFF_STAT + i * 8 + 704, (v1.x << 16) ^ 0x80000000u, __float_as_uint(rcp(bf_hi(v1.x))));
                    sts2(sb + OFF_STAT + i * 8 + 1408, (v2.x << 16) ^ 0x80000000u, __float_as_uint(rcp(bf_hi(v2.x))));
                }
                __syncwarp();
                {
                    const int row = 2047 - ((poll_all(&scr->sel[lane & 7], 31u, ep & 31, budget) >> 5) & 2047), jj = (row >> 1) - j0 - rh * 128;
                    uint32_t boxes = __reduce_or_sync(0xffffffffu, (row & 1) == par && (unsigned)jj < 128 ? 1u << (jj >> 4) : 0u);
                    sts1(sb + OFF_SEL, boxes);
#pragma unroll 1
                    for (int i = 0; boxes; i += 2) {
                        if (boxes & 1) st_rlx4(pf.out + (size_t)(2 * (j0 + rh * 128 + i + (lane >> 4)) + par) * 2048 + cb * 256 + (lane & 15) * 16, 0, 0, 0, 0);
                        else i += 14;
                        if ((i & 14) == 14) boxes >>= 1;
                    }
                }
                if (lane < 24) {
                    uint4 v[3];
#pragma unroll 1
                    while (v[0] = ld_rlx4(&scr->cs[nt][0][lane]), v[1] = ld_rlx4(&scr->cs[nt][1][lane]), v[2] = ld_rlx4(&scr->cs[nt][2][lane]),
                           (((v[0].x ^ ep) | (v[1].x ^ ep) | (v[2].x ^ ep)) & 1) && --tries > 0) __nanosleep(100);
#pragma unroll
                    for (int r = 0; r < 3; r++) sts4(sb + OFF_CS + 64 + lane * 128 + r * 16, v[r].x, v[r].y, v[r].z, v[r].w);
                }
                fence_async_smem();
                __syncwarp();
                if (elect_one()) {
                    mbar_arrive(bars + 8 * B_AUX);
                    TS(21);
                    if (lds1(sb + OFF_SEL)) { fence_gpu(); asm volatile("fence.proxy.async.global;" ::: "memory"); }
                    mbar_arrive(bars + 8 * B_ZERO);
                    TS(25);
                    mbar_expect_tx(bars + 8 * (B_OFULL + 3), BOX); mbar_expect_tx(bars + 8 * (B_OFULL + 9), BOX);
#pragma unroll 1
                    for (int v = 0; v < 2; v++) {
                        const uint32_t ring = sb + v * OFF_X1 + 2 * BOX, fb = bars + 8 * (B_OFULL + v * 6 + 2);
                        mbar_wait(bars + 8 * (B_STAGED + v), 0, budget);
                        asm volatile("red.relaxed.gpu.global.xor.b32 [%0], %1;" ::"l"(&scr->oflag[mt * 2 + 1 - v][0]), "r"(1u << nt) : "memory");
                        TS(13 + 2 * v);
                        mbar_arrive(fb);
                        mbar_wait(bars + 8 * B_G1DONE, 0, budget);
                        bulk_s2c(mapa(ring + BOX, hp ^ 1), ring, BOX, mapa(fb + 8, hp ^ 1));
                        if (v == 0) mbar_wait(bars + 8 * B_FREED, 0, budget);
#pragma unroll
                        for (int n = 0; n < 4; n++) {
                            mbar_expect_tx(bars + 8 * (B_OFULL + (n >> 1) * 6 + 4 + (n & 1)) - v * 32, BOX);
                            mbar_arrive_at(mapa(bars + 8 * B_OEMPTY, n >> 1) + (4 + (n & 1)) * 8 - v * 32);
                        }
                    }
                }
            }
        }
    } else if (warp >= 8) {
        reg_dec<40>();
        const int wq = warp - 8, ta = tid - 256;
        const uint32_t rbuf = sb + OFF_FR + wq * BOX, rbar = bars + 8 * B_ROW;
        const uint4 wv = ldg_nc(wr + ta * 8);
        if (ta == 0) sts1(sb + OFF_EP, ld_rlx(&scr->epoch[0]) + 1);
        sts4(sb + OFF_STAT + ta * 16, wv.x, wv.y, wv.z, wv.w);
        bar_sync(8, 224);
        const uint32_t ep = __shfl_sync(0xffffffffu, lds1(sb + OFF_EP), 0);
        {
            const int s = b * 16 + wq * 4 + (lane >> 3);
            if ((lane & 7) == 0) st_rlx2(&scr->row[s], 0, ep - 1);
            float sw = 0.f;
#pragma unroll 1
            for (int i = 0; i < 16; i++) { const uint32_t q = lds1(sb + OFF_STAT + i * 128 + lane * 4); sw += bf_lo(q) + bf_hi(q); }
#pragma unroll 1
            for (int o = 16; o > 0; o >>= 1) sw += __shfl_xor_sync(0xffffffffu, sw, o);
            float s1 = 0.f, s2 = 0.f, sr = 0.f;
            const uint32_t xa = rbuf + (lane >> 3) * 2048 + (lane & 7) * 16, wa = sb + OFF_STAT + (lane & 7) * 16;
            mbar_wait(rbar, 0, budget);
            TSC(ta == 0, 17);
            {
                float s1b = 0.f, s2b = 0.f, srb = 0.f;
                const uint32_t xb = rbuf + (lane >> 4) * 4096 + (lane & 15) * 16, wb = sb + OFF_STAT + (lane & 15) * 16;
                uint4 w4 = lds4(wb), u = lds4(xb), v = lds4(xb + 2048);
#pragma unroll 1
                for (int i = 1; i <= 8; i++) {
                    const uint32_t o = (i * 256) & 2047;
                    float wf[8];
#pragma unroll
                    for (int c = 0; c < 4; c++) { wf[2 * c] = bf_lo((&w4.x)[c]); wf[2 * c + 1] = bf_hi((&w4.x)[c]); }
                    w4 = lds4(wb + o);
#pragma unroll
                    for (int c = 0; c < 4; c++) {
                        const float a0 = bf_lo((&u.x)[c]), a1 = bf_hi((&u.x)[c]);
                        s1 += a0; s2 = fmaf(a0, a0, s2); sr = fmaf(a0, wf[2 * c], sr);
                        s1 += a1; s2 = fmaf(a1, a1, s2); sr = fmaf(a1, wf[2 * c + 1], sr);
                    }
                    u = lds4(xb + o);
#pragma unroll
                    for (int c = 0; c < 4; c++) {
                        const float a0 = bf_lo((&v.x)[c]), a1 = bf_hi((&v.x)[c]);
                        s1b += a0; s2b = fmaf(a0, a0, s2b); srb = fmaf(a0, wf[2 * c], srb);
                        s1b += a1; s2b = fmaf(a1, a1, s2b); srb = fmaf(a1, wf[2 * c + 1], srb);
                    }
                    v = lds4(xb + 2048 + o);
                }
                const bool up = lane & 8;
                s1 = (up ? s1b : s1) + __shfl_xor_sync(0xffffffffu, up ? s1 : s1b, 8);
                s2 = (up ? s2b : s2) + __shfl_xor_sync(0xffffffffu, up ? s2 : s2b, 8);
                sr = (up ? srb : sr) + __shfl_xor_sync(0xffffffffu, up ? sr : srb, 8);
            }
#pragma unroll
            for (int o = 1; o < 8; o <<= 1) {
                s1 += __shfl_xor_sync(0xffffffffu, s1, o); s2 += __shfl_xor_sync(0xffffffffu, s2, o); sr += __shfl_xor_sync(0xffffffffu, sr, o);
            }
            const float mean = s1 * (1.f / 1024.f), mb = bf16r(mean);
            float var = fmaf(-mean, mean, s2 * (1.f / 1024.f));
            sr = fmaf(-mb, sw, sr);
            if (__builtin_expect(__any_sync(0xffffffffu, mean * mean > 256.f * var), 0)) {
                float a2 = 0.f, ar = 0.f;
#pragma unroll 1
                for (int i = 0; i < 64; i++) {
                    const uint32_t o = (i >> 2) * 128 + (i & 3) * 4, q1 = lds1(xa + o), q2 = lds1(wa + o);
                    a2 = fmaf(bf_lo(q1) - mean, bf_lo(q1) - mean, fmaf(bf_hi(q1) - mean, bf_hi(q1) - mean, a2));
                    ar = fmaf(bf_lo(q1) - mb, bf_lo(q2), fmaf(bf_hi(q1) - mb, bf_hi(q2), ar));
                }
#pragma unroll 1
                for (int o = 1; o < 8; o <<= 1) { a2 += __shfl_xor_sync(0xffffffffu, a2, o); ar += __shfl_xor_sync(0xffffffffu, ar, o); }
                var = a2 * (1.f / 1024.f); sr = ar;
            }
            float den;
            asm("sqrt.approx.f32 %0, %1;" : "=f"(den) : "f"(bf16r(bf16r(var) + 1e-5f)));
            const uint32_t st = pack_bf16(mb, den);
            const uint32_t rb = pack_bf16(0.f, sr * rcp(bf_hi(st)) + 0.f);
            uint32_t ord = (int)rb < 0 ? ~rb & 0xffff0000u : rb | 0x80000000u;
            if ((rb & 0x7fffffffu) > 0x7f800000u) ord = 0;
            if ((lane & 7) == 0) st_rlx2(&scr->row[s], st, ord | ((2047 - s) << 5) | (ep & 31));
            __syncwarp();
            if (lane < 7) mbar_arrive(bars + 8 * (lane < 5 ? B_FEMPTY + lane : B_RDONE));
        }
        TSC(ta == 0, 18);
        if ((b >> 3) == 14) {
            const uint32_t gm = sb + OFF_E, cnt = gm + 64, res = gm + 80, list = gm + 128;
            uint32_t kv[16];
            int tries = BUDGET;
#pragma unroll 1
            do {
                uint32_t bad = 0;
#pragma unroll
                for (int n = 0; n < 16; n++) kv[n] = ld_rlx(&scr->row[n * 128 + ta].y);
#pragma unroll
                for (int n = 0; n < 16; n++) bad |= kv[n] ^ ep;
                if ((bad & 31) == 0) break;
            } while (--tries > 0);
            __syncwarp();
            TSC(ta == 0, 26);
            uint32_t m = 0;
#pragma unroll
            for (int n = 0; n < 16; n++) m = max(m, kv[n]);
            uint32_t gmax = m;
#pragma unroll
            for (int o = 1; o < 8; o <<= 1) gmax = max(gmax, __shfl_xor_sync(0xffffffffu, gmax, o));
            sts1(gm + (ta >> 3) * 4, gmax);
            sts1(cnt, 0);
            bar_sync(12, 128);
            const uint32_t c = lds1(gm + (lane & 15) * 4);
            int rank = 0;
#pragma unroll
            for (int i = 0; i < 2; i++) { const uint4 q = lds4(gm + (lane >> 4) * 32 + i * 16); rank += (q.x > c) + (q.y > c) + (q.z > c) + (q.w > c); }
            rank += __shfl_xor_sync(0xffffffffu, rank, 16);
            const uint32_t thr = redux_max(rank == 7 ? c : 0u);
#pragma unroll 1
            while (m >= thr) {
                uint32_t at, m2 = 0;
                asm volatile("atom.shared.add.u32 %0, [%1], 1;" : "=r"(at) : "r"(cnt) : "memory");
#pragma unroll
                for (int n = 0; n < 16; n++) m2 = max(m2, kv[n] < m ? kv[n] : 0u);
                sts1(list + at * 4, m);
                if (m2 == 0) break;
                m = m2;
            }
            bar_sync(12, 128);
            const int nc = lds1(cnt);
#pragma unroll 1
            for (int i = ta >> 3; i < ((nc + 3) & ~3); i += 16) {
                const uint32_t ki = lds1(list + i * 4);
                int r = 0;
#pragma unroll 1
                for (int n = lane & 7; n < nc; n += 8) r += lds1(list + n * 4) > ki;
                __syncwarp();
#pragma unroll
                for (int o = 1; o < 8; o <<= 1) r += __shfl_xor_sync(0xffffffffu, r, o);
                if (r == (b & 7) && i < nc) sts1(res, ki);
            }
            bar_sync(12, 128);
            const uint32_t k0 = lds1(res);
            const int r0 = 2047 - ((k0 >> 5) & 2047);
            TSC(ta == 0, 22);
            if (ta == 0) st_rlx(&scr->sel[b & 7], k0);
            const uint4 v0 = ldg_nc(x + (size_t)r0 * 1024 + ta * 8);
            const uint32_t s0 = ld_rlx(&scr->row[r0]);
            const float m0 = bf_lo(s0), i0 = rcp(bf_hi(s0));
            const int ao = 14336 + (ta >> 3) * 256 + (b & 7) * 32 + ((ta ^ b) & 7) * 4;
            st_rlx4(scr->act[ep & 1] + ao, norm_pair(v0.x, m0, i0), norm_pair(v0.y, m0, i0), norm_pair(v0.z, m0, i0), norm_pair(v0.w, m0, i0));
            __syncwarp();
            if (lane == 0) red_add(&scr->cnt[8][tries >> 30]);
            st_rlx4(scr->act[~ep & 1] + ao, 0, 0, 0, 0);
        }
        uint32_t s8 = 0, fph = 0, key = 0;
        const uint32_t chk = __shfl_sync(0xffffffffu, sb + OFF_FS + BOX + lane * 32 + (lane & 28), lane);
        int left = BUDGET;
#pragma unroll 1
        for (int ph = 0; ph < 2; ph++) {
            if (ph || b < 112) {
                float acc[4] = {0.f, 0.f, 0.f, 0.f};
                const uint32_t alo = sd + (ph ? dlo(OFF_FS, 8192) : dlo(OFF_FS, 4096)), ahi = ph ? dhi(1024, 1) : dhi(512, 2), astep = ph ? 128 : 64;
                const uint32_t bhi = ph ? dhi(128, 0) : dhi(1024, 1), bstep = ph ? 16 : 2, wrap = ph ? 24 : 40;
                uint32_t prev = 0, prev2 = 0;
#pragma unroll 1
                for (int q = ph ? 7 : 16; q > 0; q--) {
                    const uint32_t da = alo + s8 * (F_BYTES >> 7), db = sd + dlo(OFF_FS + BOX, 128) + s8 * (F_BYTES >> 7);
                    if (q == (ph ? 7 : F1_HOLD)) {
                        wg_wait<0>();
                        if (prev) mbar_arrive(prev);
                        prev = 0;
                        mbar_wait(bars + 8 * (ph ? FFN2_GATE : F1_GATE), 0, left);
                    }
                    mbar_wait_hot(bars + 8 * B_FFULL + s8, fph, left);
                    if (__builtin_expect(__any_sync(0xffffffffu, lds1(chk + s8 * (F_BYTES / 8)) == 0), 0)) {
                        int tries = BUDGET;
#pragma unroll 1
                        for (int n = lane * 4 + (left >> 30); n < 256; n += 128) {
                            uint4 v;
#pragma unroll 1
                            do { v = ld_rlx4(scr->act[ep & 1] + ((ph ? kc * 7 + 7 : 72) - q) * 256 + n); } while (v.x == 0 && --tries > 0);
                            __syncwarp();
                            sts4(sb + OFF_FS + BOX + s8 * (F_BYTES / 8) + n * 4, v.x, v.y, v.z, v.w);
                        }
                        NRETRY();
                        fence_async_smem();
                        __syncwarp();
                    }
                    TSC(TIMING % 10 == 3 && ta == 0, 32 + (ph ? 23 : 16) - q);
                    wg_fence();
#pragma unroll
                    for (int j = 0; j < 4; j++) wgmma_n8<1, 0>(acc, mkdesc(da + j * astep, ahi), mkdesc(db + j * bstep, bhi), 1);
                    wg_commit();
                    uint32_t done = F1_DEPTH == 2 ? prev2 : prev;
                    prev2 = prev;
                    if (lane == 0) prev = bars + 8 * B_FEMPTY + s8;
                    wg_wait<F1_DEPTH>();
                    if (ph) { wg_wait<F2_DEPTH>(); done = F2_DEPTH ? prev2 : prev; }
                    if (done) mbar_arrive(done);
                    s8 += 8;
                    if (s8 == wrap) { s8 = 0; fph ^= 1; }
                }
                wg_wait<0>();
                const int ln = lane + (left >> 30);
                if (ph == 0) {
                    if (prev) mbar_arrive(prev);
                    const bool second = (wq >= 2) != (swap_gu != 0);
                    const uint32_t xa = sb + OFF_GU + ((wq & 1) * 32 + ln) * 16;
                    if (second) sts4(xa, __float_as_uint(acc[0]), __float_as_uint(acc[1]), __float_as_uint(acc[2]), __float_as_uint(acc[3]));
                    bar_sync(12, 128);
                    if (!second) {
                        const float4 up = lds4f(xa);
                        float hv[4];
#pragma unroll
                        for (int c = 0; c < 4; c++) { const float ga = bf16r(acc[c]); hv[c] = bf16r(ga * sigmoidf(ga)) * bf16r((&up.x)[c]); }
                        const int ao = (b * 4 + (wq & 1) * 2) * 32 + ln;
                        st_rlx(scr->act[ep & 1] + ao, max(movm(pack_bf16(hv[0], hv[1])), 1u)); st_rlx(scr->act[ep & 1] + 32 + ao, max(movm(pack_bf16(hv[2], hv[3])), 1u));
                        __syncwarp();
                        if (ln == 0) red_add(&scr->cnt[b / 14][0]);
                        st_rlx(scr->act[~ep & 1] + ao, 0); st_rlx(scr->act[~ep & 1] + 32 + ao, 0);
                    }
                } else {
#pragma unroll
                    for (int c = 0; c < 4; c++) st_rlx(&scr->ypart[kc][2 * (ln & 3) + (c & 1)][c2 * 64 + wq * 16 + (c >> 1) * 8 + (ln >> 2)], (__float_as_uint(acc[c]) & ~1u) | (ep & 1));
                }
                TSC(ta == 0, 22 + ph);
            }
            const int ln = lane + (left >> 30);
            if (ph == 0) {
                if ((ta & 126) == 64) mbar_arrive(bars + 8 * B_F1DONE);
                key = poll_all(&scr->sel[ln & 7], 31u, ep & 31, left);
            }
        }
        {
            const int row = 2047 - ((key >> 5) & 2047);
            const float sig = bf16r(sigmoidf(__uint_as_float(((int)key < 0 ? key & 0x7fffffffu : ~key) & 0xffff0000u)));
            uint32_t own = __ballot_sync(0xffffffffu, (row & 1) == par && (row >> 8) == (mt & 3) * 2 + rh) & 255;
            if (wq & 2) own &= own - 1;
            mbar_wait(bars + 8 * B_ZERO, 0, left);
#pragma unroll 1
            for (; own; own &= own - 1, own &= own - 1) {
                const int j = __ffs(own) - 1, col = cb * 128 + (wq & 1) * 64 + (lane & 15) * 4;
                const uint32_t* src = &scr->ypart[lane >> 4][j][col];
                uint4 v[4]; int tries = BUDGET;
#pragma unroll 1
                do {
#pragma unroll
                    for (int m = 0; m < 4; m++) v[m] = ld_rlx4(src + m * 2 * 8192);
                } while ((((v[0].x ^ ep) | (v[1].x ^ ep) | (v[2].x ^ ep) | (v[3].x ^ ep)) & 1) && --tries > 0 && (__nanosleep(Y_NS), true));
                __syncwarp();
                float a[4];
                const float sj = __shfl_sync(0xffffffffu, sig, j);
                const int rj = __shfl_sync(0xffffffffu, row, j);
#pragma unroll
                for (int c = 0; c < 4; c++) {
                    a[c] = (__uint_as_float((&v[0].x)[c]) + __uint_as_float((&v[1].x)[c])) + (__uint_as_float((&v[2].x)[c]) + __uint_as_float((&v[3].x)[c]));
                    a[c] = bf16r(a[c] + __shfl_xor_sync(0xffffffffu, a[c], 16)) * sj;
                }
                if (lane < 16) asm volatile("red.relaxed.gpu.global.add.noftz.v2.bf16x2 [%0], {%1, %2};" ::"l"(pf.out + (size_t)rj * 2048 + col * 2), "r"(pack_bf16(a[0], a[1])), "r"(pack_bf16(a[2], a[3])) : "memory");
            }
        }
        TSC(ta == 0, 24);
    } else {
        reg_inc<224>();
        const int w = warp >> 2, wi = warp & 3, g = lane >> 2, t = lane & 3;
        const bool elect = (tid & 127) == 0;
        const uint32_t mad = (lane & 15) * 128 + (((lane >> 4) ^ (lane & 7)) << 4);
        float acc[64];
        const uint32_t ring = sb + w * OFF_X1, ofull = bars + 8 * (B_OFULL + w * 6), oempty = mapa(bars + 8 * B_OEMPTY, w);
        const int r0 = rh * 128 + wi * 32 + (1 - w) * 16 + g;
        {
            float acc0[96], acc1[96];
            const uint32_t sta = sb + OFF_STAT + (8 + w * 128 + wi * 32) * 8;
            {
                const uint32_t xfull = bars + 8 * (B_XFULL + w * 6 + 5), xempty = mapa(bars + 8 * B_XEMPTY, w), dx0 = sd + dlo(w * OFF_X1, 16);
                uint32_t s8 = 16, ps8 = 0, ph = 0;
                cluster_wait();
#pragma unroll 1
                for (int k = 0; k < 16; k++) {
                    const uint32_t dx = dx0 + s8 * (2 * BOX >> 7), dw = sd + dlo(OFF_W, BOX) + s8 * (W_BYTES >> 7);
                    mbar_wait(bars + 8 * B_WFULL + s8, ph, budget);
                    mbar_wait(xfull - 2 * s8, ph, budget);
                    TSC(elect && k == 0, 1 + 8 * w);
                    TSC(TIMING % 10 == 1 && tid == 0, 32 + k);
                    wg_wait<0>();
                    wg_fence();
#pragma unroll
                    for (int kk = 0; kk < 4; kk++) wgmma_n192<0, 1>(acc1, mkdesc(dx + kk * 2, dhi(1024, 1)), mkdesc(dw + kk * 128, dhi(1024, 1)), kk ? 1 : k);
                    wg_commit();
                    TSC(TIMING % 10 == 6 && elect, 32 + 16 * w + k);
                    if (elect && k > 0) {
                        mbar_arrive(bars + 8 * B_WEMPTY + ps8);
                        if (k <= 13) { mbar_expect_tx(xfull - 2 * ps8 - 8, BOX); mbar_arrive_at(xempty + 2 * ps8 + 8); }
                    }
                    if (k == 15) {
                        mbar_wait(bars + 8 * B_AUX, 0, budget);
                        const uint32_t zero = budget >> 30, pm = t & 1 ? 0x4432 : 0x3232, ra = sta + ((t >> 1) * 16 + g) * 8;
                        const uint32_t a0 = __byte_perm(lds1(ra), 0, pm), a1 = __byte_perm(lds1(ra + 64), 0, pm), a2 = a0 & zero, a3 = a1 & zero;
                        wg_fence();
                        wgmma_rs_n192(acc1, a0, a1, a2, a3, mkdesc(sd + dlo(OFF_CS, 0), dhi(128, 0)));
                        wgmma_rs_n192(acc0, a0, a1, a2, a3, mkdesc(sd + dlo(OFF_CS + 64, 0), dhi(128, 0)));
                        wg_commit();
                    }
                    mbar_wait(xfull - 2 * s8 - 8, ph, budget);
                    wg_wait<0>();
                    wg_fence();
#pragma unroll
                    for (int kk = 0; kk < 4; kk++) wgmma_n192<0, 1>(acc0, mkdesc(dx + 512 + kk * 2, dhi(1024, 1)), mkdesc(dw + kk * 128, dhi(1024, 1)), kk ? 1 : k);
                    wg_commit();
                    if (elect && k <= 12) { mbar_expect_tx(xfull - 2 * s8, BOX); mbar_arrive_at(xempty + 2 * s8); }
                    ps8 = s8;
                    s8 = s8 == 16 ? 0 : s8 + 8;
                    if (s8 == 16) ph ^= 1;
                }
            }
            const uint32_t zero = budget >> 30;
            const bool u0 = 2 * t > g, u1 = 2 * t + 1 > g;
            uint32_t mU = (u0 ? 0xffffu : 0u) | (u1 ? 0xffff0000u : 0u);
            uint32_t ka0 = sta + (2 * t - (u0 ? 8 : 0)) * 8 + 4, ka1 = sta + (2 * t + 1 - (u1 ? 8 : 0)) * 8 + 4;
            float rk[2][4], fu[2][4], fn[2][4];
            auto factors = [&](int h) {
#pragma unroll
                for (int n = 0; n < 4; n += 2) {
                    const float rq = lds1f(sta + (16 * h + 4 * n + g) * 8 + 4) * (0.17677669529663687f * 1.4426950408889634f);
                    rk[h][n] = lds1f(ka0 + h * 128 + n * 32); rk[h][n + 1] = lds1f(ka1 + h * 128 + n * 32);
                    const float f0 = rq * rk[h][n], f1 = rq * rk[h][n + 1];
                    fu[h][n] = u0 ? f0 : 0.f; fn[h][n] = f0 - fu[h][n]; fu[h][n + 1] = u1 ? f1 : 0.f; fn[h][n + 1] = f1 - fu[h][n + 1];
                }
#pragma unroll
                for (int n = 0; n < 4; n++) asm volatile("" : "+f"(fu[h][n]), "+f"(fn[h][n]));
            };
            uint8_t* og = scr->o + ((size_t)(mt * 4 + w * 2) * 16 + nt) * BOX + wi * 256 + lane * 4;
            TSC(elect, 19 + w);
            uint32_t pk0[48], pk1[48], o[16] = {};
#pragma unroll
            for (int j = 0; j < 48; j++) if (j < 16 || (j & 1)) pk1[j] = pack_here(acc1[2 * j], acc1[2 * j + 1]);
            if (warp < 7) {
#pragma unroll
                for (int c = 0; c < 4; c++) stsm4(ring + 4 * BOX + wi * 2048 + c * 512 + lane * 16, pk1[17 + 8 * c], pk1[19 + 8 * c], pk1[21 + 8 * c], pk1[23 + 8 * c]);
                bar_arrive(1 + warp, 64);
            } else if (j0 != 768) {
#pragma unroll
                for (int c = 0; c < 4; c++) {
                    pk1[17 + 8 * c] = max(pk1[17 + 8 * c], 1u);
                    st_rlx4(&scr->halo[b][c * 128 + lane * 4], pk1[17 + 8 * c], pk1[19 + 8 * c], pk1[21 + 8 * c], pk1[23 + 8 * c]);
                }
            }
            TSC(tid == 224, 28);
#pragma unroll
            for (int j = 16; j < 48; j += 2) pk1[j] = pack_here(acc1[2 * j], acc1[2 * j + 1]);
            factors(1);
            uint32_t od = sb + 2 * BOX + wi * 256 + (lane >> 4) * 1024 + (lane & 15) * 16, g1peer = mapa(bars + 8 * B_G1DONE, hp ^ 1);
            uint32_t ha = sb + (warp == 0 ? OFF_HIN : warp <= 4 ? 4 * BOX - 2048 : OFF_X1 + 4 * BOX - 5 * 2048) + warp * 2048 + lane * 16;
            const bool first = warp == 0 && j0 == 0;
            float bias0 = first && u0 ? -INFINITY : 0.f, bias1 = first && u1 ? -INFINITY : 0.f;
            asm volatile("" : "+l"(og), "+r"(mU), "+r"(od), "+r"(ha), "+f"(bias0), "+f"(bias1));
            mbar_wait(bars + 8 * B_XT, 0, budget);
            mbar_wait(bars + 8 * (B_WEMPTY + 1), 0, budget);
            TSC(elect, 12 + 2 * w);
            wg_wait<0>();
            if (elect) { mbar_arrive(bars + 8 * B_G1DONE); mbar_arrive_at(g1peer); }
            TSC(elect, 2 + 8 * w);
            float ci[4];
#pragma unroll
            for (int n = 0; n < 4; n++) ci[n] = __uint_as_float((0x03800000u + n) | (budget >> 30));
            auto hand_over = [&](int v) {
                asm volatile("{\n.reg .pred p;\nsetp.ne.b32 p, %17, 0;\n"
                             "@p stmatrix.sync.aligned.m8n8.x4.shared.b16 [%16], {%0,%1,%2,%3};\n@p stmatrix.sync.aligned.m8n8.x4.shared.b16 [%16 + 2048], {%4,%5,%6,%7};\n"
                             "@p stmatrix.sync.aligned.m8n8.x4.shared.b16 [%16 + 4096], {%8,%9,%10,%11};\n@p stmatrix.sync.aligned.m8n8.x4.shared.b16 [%16 + 6144], {%12,%13,%14,%15};\n"
                             FENCE_PRED "fence.proxy.async.shared::cta;\n}"
                             ::"r"(o[0]), "r"(o[1]), "r"(o[2]), "r"(o[3]), "r"(o[4]), "r"(o[5]), "r"(o[6]), "r"(o[7]), "r"(o[8]), "r"(o[9]), "r"(o[10]), "r"(o[11]),
                               "r"(o[12]), "r"(o[13]), "r"(o[14]), "r"(o[15]), "r"(od + v * OFF_X1), "r"((int)(w == rh)) : "memory");
                TSC(tid == 0, v ? 27 : 5);
#pragma unroll
                for (int i = 0; i < 16; i++) asm volatile("st.global.u32 [%0], %1;" ::"l"(og + (1 - v) * 16 * BOX + (i >> 1) * 1024 + (i & 1) * 128), "r"(o[i]) : "memory");
                __syncwarp();
                if (lane == 0) mbar_arrive(bars + 8 * (B_STAGED + v));
            };
#pragma unroll
            for (int j = 32; j < 48; j++) pk1[j] = movm(pk1[j]);
#pragma unroll
            for (int j = EARLY_PK; j < 48; j++) if (j >= 32 || (j & 1) || EARLY_PK < 17) pk0[j] = pack_here(acc0[2 * j], acc0[2 * j + 1]);
#pragma unroll
            for (int j = 32; j < 48; j++) pk0[j] = movm(pk0[j]);
            factors(0);
            attn_pair<2>(pk1, pk1 + 16, pk1 + 32, pk0 + 17, pk0 + 33, fu[1], fn[1], rk[1], 0.f, 0.f, mU, zero, ci, o);
            hand_over(0);
            TSC(elect, 3 + 8 * w);
#pragma unroll
            for (int j = 0; j < 32; j++) if (j < EARLY_PK || (!(j & 1) && EARLY_PK == 17)) pk0[j] = pack_here(acc0[2 * j], acc0[2 * j + 1]);
            bar_sync(warp ? warp : 11, 64);
            uint32_t hl[16];
            ldsm4(hl, ha); ldsm4(hl + 4, ha + 512); ldsm4t(hl + 8, ha + 1024); ldsm4t(hl + 12, ha + 1536);
            __syncwarp();
            if (lane == 0) mbar_arrive(bars + 8 * B_FREED);
            attn_pair<1>(pk0, pk0 + 16, pk0 + 32, hl, hl + 8, fu[0], fn[0], rk[0], bias0, bias1, mU, zero, ci, o);
            const float2 s0 = lds2f(sb + OFF_STAT + (8 + r0) * 8), s1 = lds2f(sb + OFF_STAT + (16 + r0) * 8);
            const float m0 = s0.x * s0.y, f0 = 1.f + s0.y, m1 = s1.x * s1.y, f1 = 1.f + s1.y;
            uint32_t xt[32];
#pragma unroll
            for (int j = 0; j < 8; j++) ldsm4(xt + 4 * j, ((ring + wi * 2048 + mad) ^ ((j & 3) * 32)) + (j >> 2) * BOX);
            hand_over(1);
#pragma unroll
            for (int j = 0; j < 32; j++) {
                acc[2 * j] = fmaf(bf_lo(xt[j]), j & 1 ? f1 : f0, j & 1 ? m1 : m0); acc[2 * j + 1] = fmaf(bf_hi(xt[j]), j & 1 ? f1 : f0, j & 1 ? m1 : m0);
            }
        }
        TSC(tid == 0, 4);
        {
            const uint32_t da0 = sd + dlo(w * OFF_X1, 1024), db0 = sd + dlo(OFF_WO, BOX);
            const uint32_t chk = ring + wi * 256 + (lane >> 3) * 1032 + (lane & 7) * 32 + (lane & 4);
            uint32_t s8 = 16, ps8 = 0, ph = 0;
            mbar_wait(ofull + s8, 0, budget);
            mbar_wait(bars + 8 * B_WOFULL + s8, 0, budget);
            TSC(TIMING % 10 == 2 && elect, 32 + w * 16);
            const uint32_t ahi = dhi(128, 0) | (budget >> 30), bhi = dhi(1024, 1) | (budget >> 30);
            const int last = w ? HOLD : 16;
            uint32_t rel = elect ? 0x7fe : 0;
#pragma unroll 1
            for (int i = 1;;) {
                const uint32_t da = da0 + s8 * (BOX >> 7), db = db0 + s8 * (BOX >> 6);
                wg_fence();
#pragma unroll
                for (int kk = 0; kk < 4; kk++) {
                    wgmma_n128<0, 1>(acc, mkdesc(da + kk * 128, ahi), mkdesc(db + kk * 128, bhi), 1);
                    if (kk & 1) wg_commit();
                }
                wg_wait<2>();
                if (rel & 1) { mbar_expect_tx(ofull + ps8, BOX); mbar_arrive_at(oempty + ps8); mbar_arrive(bars + 8 * B_WOEMPTY + ps8); }
                if (i == 16) break;
                rel >>= 1;
                ps8 = s8;
#pragma unroll 1
                do {
                    s8 = s8 == 40 ? 0 : s8 + 8;
                    if (s8 == 16) ph ^= 1;
                    uint32_t bad;
                    asm volatile("{\n.reg .pred p, q, r;\n.reg .u32 u, v;\nmbarrier.try_wait.parity.shared::cta.b64 q, [%2], %3;\nmbarrier.try_wait.parity.shared::cta.b64 p, [%1], %3;\n"
                                 "setp.ne.and.u32 r, %5, 1, p;\nmov.u32 u, 1;\nmov.u32 v, 1;\n@r ld.shared.u32 u, [%4];\n@r ld.shared.u32 v, [%4 + 4096];\n"
                                 "and.pred p, p, q;\nmin.u32 u, u, v;\nsetp.eq.or.u32 p, u, 0, !p;\nvote.sync.any.pred p, p, 0xffffffff;\nselp.u32 %0, 1, 0, p;\n}"
                                 : "=r"(bad) : "r"(ofull + s8), "r"(bars + 8 * B_WOFULL + s8), "r"(ph), "r"(chk + s8 * (BOX / 8)), "r"(i) : "memory");
                    if (__builtin_expect(bad, 0)) {
                        mbar_wait(ofull + s8, ph, budget);
                        mbar_wait(bars + 8 * B_WOFULL + s8, ph, budget);
                        if (__any_sync(0xffffffffu, min(lds1(chk + s8 * (BOX / 8)), lds1(chk + s8 * (BOX / 8) + 4096)) == 0)) {
                            const uint32_t at = wi * 256 + (lane >> 4) * 1024 + (lane & 15) * 16;
                            const uint8_t* src = scr->o + ((size_t)((mt * 2 + rh) * 2 + 1 - w) * 16 + ((2 * p + (i < 2 ? i ^ hp : i)) & 15)) * BOX + at;
#pragma unroll 1
                            for (int n = 0; n < 8192; n += 2048) {
                                uint4 v; int tries = 4096;
#pragma unroll 1
                                do { v = ld_rlx4(src + n); } while (v.x == 0 && --tries > 0);
                                sts4(ring + s8 * (BOX / 8) + at + n, v.x, v.y, v.z, v.w);
                            }
                            NRETRY();
                            fence_async_smem();
                            __syncwarp();
                        }
                    }
                    TSC(TIMING % 10 == 1 && tid == 0, 48 + i);
                    TSC(TIMING % 10 == 2 && elect, 32 + w * 16 + i);
                } while (++i > last && i < 16);
                if (i > last) break;
                wg_wait<1>();
            }
            if (w) {
                bar_sync(9, 256);
#pragma unroll 1
                for (int i = HOLD - 10; i < 6; i++) {
                    wg_fence();
#pragma unroll
                    for (int kk = 0; kk < 4; kk++) wgmma_n128<0, 1>(acc, mkdesc(da0 + i * 512 + kk * 128, ahi), mkdesc(db0 + i * 1024 + kk * 128, bhi), 1);
                    wg_commit();
                }
            } else bar_arrive(9, 256);
            const bool add = (__shfl_sync(0xffffffffu, lds1(sb + OFF_SEL), 0) >> (wi * 2 + 1 - w)) & 1;
            wg_wait<0>();
            TSC(elect, 7 + 9 * w);
            const uint32_t os0 = ring + wi * 4096;
#pragma unroll
            for (int hf = 0; hf < OUT_PARTS; hf++) {
#pragma unroll
                for (int j = hf * (8 / OUT_PARTS); j < (hf + 1) * (8 / OUT_PARTS); j++)
                    stsm4(((os0 + mad) ^ ((j & 3) * 32)) + (j >> 2) * 2048, pack_here(acc[8 * j], acc[8 * j + 1]), pack_here(acc[8 * j + 2], acc[8 * j + 3]),
                          pack_here(acc[8 * j + 4], acc[8 * j + 5]), pack_here(acc[8 * j + 6], acc[8 * j + 7]));
                fence_async_smem();
                __syncwarp();
                if (elect_one())
                    asm volatile("{\n.reg .pred p;\nsetp.ne.b32 p, %6, 0;\n@!p cp.async.bulk.tensor.5d.global.shared::cta.bulk_group [%0, {%2, %2, %3, %4, %5}], [%1];\n"
                                 "@p cp.reduce.async.bulk.tensor.5d.global.shared::cta.add.bulk_group [%0, {%2, %2, %3, %4, %5}], [%1];\n}"
                                 ::"l"(&mout), "r"(os0 + hf * 2048), "r"(0), "r"(((j0 + rh * 128) >> 5) + wi), "r"(1 - w), "r"(par * 16 + cb * 2 + hf), "r"((int)add) : "memory");
            }
            asm volatile("cp.async.bulk.commit_group;\ncp.async.bulk.wait_group.read 0;" ::: "memory");
            if (b == 0 && tid == 0) st_rlx(&scr->epoch[0], lds1(sb + OFF_EP));
            TSC(elect, 8 - 2 * w);
            TS_END();
        }
    }
}

typedef CUresult (*EncodeFn)(CUtensorMap*, CUtensorMapDataType, cuuint32_t, void*, const cuuint64_t*, const cuuint64_t*, const cuuint32_t*,
                             const cuuint32_t*, CUtensorMapInterleave, CUtensorMapSwizzle, CUtensorMapL2promotion, CUtensorMapFloatOOBfill);

CUtensorMap make_map(EncodeFn fn, const void* base, int rank, const cuuint64_t* dims, const cuuint64_t* strides, const cuuint32_t* box,
                     CUtensorMapSwizzle swz = CU_TENSOR_MAP_SWIZZLE_128B, CUtensorMapL2promotion pro = CU_TENSOR_MAP_L2_PROMOTION_L2_256B) {
    CUtensorMap m;
    cuuint32_t es[5] = {1, 1, 1, 1, 1};
    fn(&m, CU_TENSOR_MAP_DATA_TYPE_BFLOAT16, rank, (void*)base, dims, strides, box, es, CU_TENSOR_MAP_INTERLEAVE_NONE,
       swz, pro, CU_TENSOR_MAP_FLOAT_OOB_FILL_NONE);
    return m;
}

}

extern "C" void kernel_launch(void* const* d_in, const int* in_sizes, int n_in, void* d_out, int out_size) {
    (void)in_sizes; (void)n_in; (void)out_size;
    const __nv_bfloat16* x = (const __nv_bfloat16*)d_in[0];
    const __nv_bfloat16* wqkv = (const __nv_bfloat16*)d_in[1];
    const __nv_bfloat16* wo = (const __nv_bfloat16*)d_in[2];
    const __nv_bfloat16* wr = (const __nv_bfloat16*)d_in[4];
    const __nv_bfloat16* wg = (const __nv_bfloat16*)d_in[5];
    const __nv_bfloat16* wu = (const __nv_bfloat16*)d_in[6];
    const __nv_bfloat16* wd = (const __nv_bfloat16*)d_in[7];
    static EncodeFn fn = nullptr;
    static Scratch* scr = nullptr;
    if (!fn) {
        void* p = nullptr; cudaDriverEntryPointQueryResult q;
        cudaGetDriverEntryPoint("cuTensorMapEncodeTiled", &p, cudaEnableDefault, &q);
        fn = (EncodeFn)p;
        cudaFuncSetAttribute(fused_kernel, cudaFuncAttributeMaxDynamicSharedMemorySize, SMEM_LAUNCH);
        cudaGetSymbolAddress((void**)&scr, g_scr);
    }
    const cuuint64_t xd[4] = {2048, 16, 32, 2}, xs[4] = {4096, 131072, 65536, 128}, od[5] = {64, 16, 32, 2, 32};
    const cuuint32_t xb[4] = {64, 16, 4, 1}, ob[5] = {64, 16, 1, 1, 2 / OUT_PARTS};
    const cuuint64_t wdm[3] = {1024, 1024, 3}, wst[2] = {6144, 2048};
    const cuuint32_t wb[3] = {64, 64, 3};
    const cuuint64_t wod[3] = {64, 1024, 16}, wdd[3] = {64, 3584, 16}, wos[2] = {2048, 128};
    const cuuint32_t wob[3] = {64, 64, 2}, wdb[3] = {64, 64, 1};
    CUtensorMap mx = make_map(fn, x, 4, xd, xs, xb), mw = make_map(fn, wqkv, 3, wdm, wst, wb);
    CUtensorMap mwo = make_map(fn, wo, 3, wod, wos, wob), mout = make_map(fn, d_out, 5, od, xs, ob);
    const int swap_gu = wu < wg;
    const cuuint64_t gd[3] = {3584, 1024, 2}, gst[2] = {7168, (cuuint64_t)(swap_gu ? (const char*)wg - (const char*)wu : (const char*)wu - (const char*)wg)};
    const cuuint32_t gb[3] = {32, 64, 2};
    CUtensorMap mgu = make_map(fn, swap_gu ? wu : wg, 3, gd, gst, gb, CU_TENSOR_MAP_SWIZZLE_64B, CU_TENSOR_MAP_L2_PROMOTION_L2_128B);
    CUtensorMap mwd = make_map(fn, wd, 3, wdd, wos, wdb, CU_TENSOR_MAP_SWIZZLE_128B, CU_TENSOR_MAP_L2_PROMOTION_L2_128B);
    const cuuint64_t md[2] = {64, 32768}, ms[1] = {128};
    const cuuint32_t mb[2] = {64, 64};
    CUtensorMap mo = make_map(fn, scr, 2, md, ms, mb, CU_TENSOR_MAP_SWIZZLE_NONE, CU_TENSOR_MAP_L2_PROMOTION_NONE);
    cudaLaunchConfig_t cfg = {};
    cfg.gridDim = dim3(132); cfg.blockDim = dim3(512); cfg.dynamicSmemBytes = SMEM_LAUNCH; cfg.stream = cudaStreamPerThread;
    cudaLaunchAttribute at[1];
    at[0].id = cudaLaunchAttributeClusterDimension; at[0].val.clusterDim.x = 2; at[0].val.clusterDim.y = 1; at[0].val.clusterDim.z = 1;
    cfg.attrs = at; cfg.numAttrs = 1;
    cudaLaunchKernelEx(&cfg, fused_kernel, mx, mw, mwo, mout, mgu, mwd, mo, x, wr, scr, swap_gu, Weights{(const char*)wqkv, (const char*)wo, (const char*)wg, (const char*)wu, (const char*)wd, (char*)d_out});
}
```

```cpp
#include <cuda_runtime.h>
#include <cuda.h>
#include <cuda_bf16.h>
#include <stdint.h>

namespace {

constexpr int BOX = 8192, W_BYTES = 3 * BOX;
constexpr int OFF_X1 = 6 * BOX, OFF_FR = 12 * BOX, OFF_E = 16 * BOX, OFF_W = 19 * BOX;
constexpr int OFF_WO = OFF_E;
constexpr int OFF_HIN = OFF_FR + 2048, OFF_GU = OFF_HIN + 2048, OFF_FS = OFF_GU + 1024;
constexpr int F_BYTES = 9216;
constexpr int CS_BYTES = 3136;
constexpr int OFF_CS = OFF_FS + 5 * F_BYTES;
constexpr int OFF_STAT = 28 * BOX;
constexpr int OFF_SEL = OFF_STAT + 2112;
constexpr int OFF_EP = OFF_SEL + 32;
constexpr int OFF_BAR = OFF_EP + 16;
constexpr int B_WFULL = 0, B_XFULL = 3, B_AUX = 15, B_XT = 16, B_ROW = 17, B_WOFULL = 18, B_OFULL = 24, B_FFULL = 36, B_ZERO = 41;
constexpr int B_WEMPTY = 42, B_F1DONE = 45, B_XEMPTY = 46, B_WOEMPTY = 52, B_OEMPTY = 58;
constexpr int B_G1DONE = 66, B_FEMPTY = 67, B_STAGED = 72, B_RDONE = 75, B_FREED = 76, NBAR = 78;
constexpr int SMEM_BYTES = OFF_BAR + NBAR * 8;
static_assert(OFF_FS + 3 * F_BYTES == OFF_E && OFF_CS + CS_BYTES <= OFF_W && SMEM_BYTES + 256 <= 232448 && OFF_BAR % 8 == 0, "smem");
#define POLL_NS 30
#define PF_RATE 10
#define PF_START 7
#define ZF_NS 100
#define FFN2_GATE (B_STAGED + 1)
#define PF_NW 6
#define EARLY_PK 17
#define ZF_GATE B_ROW
#define HOLD 12
#define F1_DEPTH 1
#define F2_DEPTH 0
#define F1_HOLD 2
#define F1_GATE B_G1DONE
#define OUT_PARTS 2
#define Y_NS 200
#define PF_D 8
#define ROWS_AT 11
constexpr int BUDGET = 1 << 18;

struct Scratch {
    uint8_t o[2048 * 1024 * 2];
    uint32_t ypart[8][8][1024];
    uint32_t halo[128][512];
    uint32_t act[2][14336 + 4096];
    uint2 row[2048];
    uint4 cs[16][3][24];
    uint32_t oflag[16][32];
    uint32_t cnt[9][32];
    uint32_t sel[32], epoch[32];
};
__device__ __align__(1024) Scratch g_scr;
struct Weights { const char *wqkv, *wo, *wg, *wu, *wd; char* out; };

#define TS(i) do {} while (0)
#define TS_END() do {} while (0)
#define TSC(c, i) do {} while (0)
#define NRETRY() do {} while (0)
constexpr int SMEM_LAUNCH = SMEM_BYTES;
__device__ __forceinline__ uint32_t smem_u32(const void* p) { return (uint32_t)__cvta_generic_to_shared(p); }
__device__ __forceinline__ void mbar_init(uint32_t bar, uint32_t cnt) { asm volatile("mbarrier.init.shared::cta.b64 [%0], %1;" ::"r"(bar), "r"(cnt) : "memory"); }
__device__ __forceinline__ void mbar_expect_tx(uint32_t bar, uint32_t bytes) { asm volatile("mbarrier.arrive.expect_tx.shared::cta.b64 _, [%0], %1;" ::"r"(bar), "r"(bytes) : "memory"); }
__device__ __forceinline__ void mbar_arrive(uint32_t bar) { asm volatile("mbarrier.arrive.shared::cta.b64 _, [%0];" ::"r"(bar) : "memory"); }
__device__ __forceinline__ uint32_t mapa(uint32_t a, uint32_t cta) { uint32_t r; asm("mapa.shared::cluster.u32 %0, %1, %2;" : "=r"(r) : "r"(a), "r"(cta)); return r; }
__device__ __forceinline__ void mbar_arrive_at(uint32_t cbar) { asm volatile("mbarrier.arrive.shared::cluster.b64 _, [%0];" ::"r"(cbar) : "memory"); }
__device__ __forceinline__ void mbar_wait(uint32_t bar, uint32_t parity, int& budget) {
    asm volatile("{\n.reg .pred p;\nLAB_WAIT:\nmbarrier.try_wait.parity.shared::cta.b64 p, [%1], %2;\n"
                 "add.s32 %0, %0, -1;\nsetp.gt.and.s32 p, %0, 0, !p;\n@p bra LAB_WAIT;\n}" : "+r"(budget) : "r"(bar), "r"(parity) : "memory");
}
__device__ __forceinline__ void mbar_wait_hot(uint32_t bar, uint32_t parity, int& budget) {
    asm volatile("{\n.reg .pred p;\nmbarrier.try_wait.parity.shared::cta.b64 p, [%1], %2;\n@p bra LAB_DONE;\nLAB_WAIT:\nmbarrier.try_wait.parity.shared::cta.b64 p, [%1], %2;\n"
                 "add.s32 %0, %0, -1;\nsetp.gt.and.s32 p, %0, 0, !p;\n@p bra LAB_WAIT;\nLAB_DONE:\n}" : "+r"(budget) : "r"(bar), "r"(parity) : "memory");
}
__device__ __forceinline__ void tma_2d_mc(uint32_t dst, const CUtensorMap* m, uint32_t bar, int c0, int c1) {
    asm volatile("cp.async.bulk.tensor.2d.shared::cluster.global.mbarrier::complete_tx::bytes.multicast::cluster [%0], [%1, {%3, %4}], [%2], %5;" ::"r"(dst), "l"(m), "r"(bar), "r"(c0), "r"(c1), "h"((uint16_t)3) : "memory");
}
__device__ __forceinline__ void tma_3d(uint32_t dst, const CUtensorMap* m, uint32_t bar, int c0, int c1, int c2) {
    asm volatile("cp.async.bulk.tensor.3d.shared::cluster.global.mbarrier::complete_tx::bytes [%0], [%1, {%3, %4, %5}], [%2];" ::"r"(dst), "l"(m), "r"(bar), "r"(c0), "r"(c1), "r"(c2) : "memory");
}
__device__ __forceinline__ void tma_4d(uint32_t dst, const CUtensorMap* m, uint32_t bar, int c0, int c1, int c2, int c3) {
    asm volatile("cp.async.bulk.tensor.4d.shared::cluster.global.mbarrier::complete_tx::bytes [%0], [%1, {%3, %4, %5, %6}], [%2];" ::"r"(dst), "l"(m), "r"(bar), "r"(c0), "r"(c1), "r"(c2), "r"(c3) : "memory");
}
__device__ __forceinline__ void tma_4d_mc(uint32_t dst, const CUtensorMap* m, uint32_t bar, int c0, int c1, int c2, int c3) {
    asm volatile("cp.async.bulk.tensor.4d.shared::cluster.global.mbarrier::complete_tx::bytes.multicast::cluster [%0], [%1, {%3, %4, %5, %6}], [%2], %7;" ::"r"(dst), "l"(m), "r"(bar), "r"(c0), "r"(c1), "r"(c2), "r"(c3), "h"((uint16_t)3) : "memory");
}
__device__ __forceinline__ void bulk_pf(const void* p, uint32_t bytes) { asm volatile("cp.async.bulk.prefetch.L2.global [%0], %1;" ::"l"(p), "r"(bytes) : "memory"); }
__device__ __forceinline__ void bulk_g2s(uint32_t dst, const void* src, uint32_t bytes, uint32_t bar) {
    asm volatile("cp.async.bulk.shared::cluster.global.mbarrier::complete_tx::bytes [%0], [%1], %2, [%3];" ::"r"(dst), "l"(src), "r"(bytes), "r"(bar) : "memory");
}
__device__ __forceinline__ void bulk_s2c(uint32_t cdst, uint32_t src, uint32_t bytes, uint32_t cbar) {
    asm volatile("cp.async.bulk.shared::cluster.shared::cta.mbarrier::complete_tx::bytes [%0], [%1], %2, [%3];" ::"r"(cdst), "r"(src), "r"(bytes), "r"(cbar) : "memory");
}
__device__ __forceinline__ void cluster_wait() { asm volatile("barrier.cluster.wait.aligned;" ::: "memory"); }
__device__ __forceinline__ void fence_gpu() { asm volatile("fence.acq_rel.gpu;" ::: "memory"); }
__device__ __forceinline__ void fence_async_smem() { asm volatile("fence.proxy.async.shared::cta;" ::: "memory"); }
__device__ __forceinline__ void wg_fence() { asm volatile("wgmma.fence.sync.aligned;" ::: "memory"); }
__device__ __forceinline__ void wg_commit() { asm volatile("wgmma.commit_group.sync.aligned;" ::: "memory"); }
template <int N> __device__ __forceinline__ void wg_wait() { asm volatile("wgmma.wait_group.sync.aligned %0;" ::"n"(N) : "memory"); }
__device__ __forceinline__ uint64_t mkdesc(uint32_t lo, uint32_t hi) { return ((uint64_t)hi << 32) | lo; }
__host__ __device__ constexpr uint32_t dhi(uint32_t sbo, uint32_t mode) { return (sbo >> 4) | (mode << 30); }
__host__ __device__ constexpr uint32_t dlo(uint32_t off, uint32_t lbo) { return (off >> 4) + ((lbo >> 4) << 16); }
__device__ __forceinline__ bool elect_one() {
    uint32_t e;
    asm volatile("{\n.reg .pred p;\nelect.sync _|p, 0xffffffff;\nselp.u32 %0, 1, 0, p;\n}" : "=r"(e));
    return e;
}
template <int R> __device__ __forceinline__ void reg_inc() { asm volatile("setmaxnreg.inc.sync.aligned.u32 %0;" ::"n"(R)); }
template <int R> __device__ __forceinline__ void reg_dec() { asm volatile("setmaxnreg.dec.sync.aligned.u32 %0;" ::"n"(R)); }
__device__ __forceinline__ void bar_sync(int id, int n) { asm volatile("bar.sync %0, %1;" ::"r"(id), "r"(n) : "memory"); }
__device__ __forceinline__ void bar_arrive(int id, int n) { asm volatile("bar.arrive %0, %1;" ::"r"(id), "r"(n) : "memory"); }
__device__ __forceinline__ uint32_t pack_bf16(float lo, float hi) { uint32_t r; asm("cvt.rn.bf16x2.f32 %0, %1, %2;" : "=r"(r) : "f"(hi), "f"(lo)); return r; }
__device__ __forceinline__ uint32_t pack_here(float lo, float hi) { uint32_t r; asm volatile("cvt.rn.bf16x2.f32 %0, %1, %2;" : "=r"(r) : "f"(hi), "f"(lo)); return r; }
__device__ __forceinline__ float bf_lo(uint32_t u) { return __uint_as_float(u << 16); }
__device__ __forceinline__ float bf_hi(uint32_t u) { return __uint_as_float(u & 0xffff0000u); }
__device__ __forceinline__ float bf16r(float v) { return bf_lo(pack_bf16(v, 0.f)); }
__device__ __forceinline__ float rcp(float x) { float r; asm("rcp.approx.ftz.f32 %0, %1;" : "=f"(r) : "f"(x)); return r; }
__device__ __forceinline__ float ex2(float x) { float r; asm("ex2.approx.ftz.f32 %0, %1;" : "=f"(r) : "f"(x)); return r; }
__device__ __forceinline__ float sigmoidf(float v) { return rcp(1.f + ex2(v * -1.4426950408889634f)); }
__device__ __forceinline__ uint32_t movm(uint32_t a) { uint32_t d; asm volatile("movmatrix.sync.aligned.m8n8.trans.b16 %0, %1;" : "=r"(d) : "r"(a)); return d; }
__device__ __forceinline__ void mma16816(float (&c)[4], uint32_t a0, uint32_t a1, uint32_t a2, uint32_t a3, uint32_t b0, uint32_t b1) {
    asm volatile("mma.sync.aligned.m16n8k16.row.col.f32.bf16.bf16.f32 {%0,%1,%2,%3}, {%4,%5,%6,%7}, {%8,%9}, {%0,%1,%2,%3};"
                 : "+f"(c[0]), "+f"(c[1]), "+f"(c[2]), "+f"(c[3]) : "r"(a0), "r"(a1), "r"(a2), "r"(a3), "r"(b0), "r"(b1));
}
__device__ __forceinline__ void mma1688(float (&c)[4], uint32_t a0, uint32_t a1, uint32_t b0) {
    asm volatile("mma.sync.aligned.m16n8k8.row.col.f32.bf16.bf16.f32 {%0,%1,%2,%3}, {%4,%5}, {%6}, {%0,%1,%2,%3};"
                 : "+f"(c[0]), "+f"(c[1]), "+f"(c[2]), "+f"(c[3]) : "r"(a0), "r"(a1), "r"(b0));
}
__device__ __forceinline__ void stsm4(uint32_t a, uint32_t r0, uint32_t r1, uint32_t r2, uint32_t r3) {
    asm volatile("stmatrix.sync.aligned.m8n8.x4.shared.b16 [%0], {%1,%2,%3,%4};" ::"r"(a), "r"(r0), "r"(r1), "r"(r2), "r"(r3) : "memory");
}
__device__ __forceinline__ void ldsm4(uint32_t* r, uint32_t a) {
    asm volatile("ldmatrix.sync.aligned.m8n8.x4.shared.b16 {%0,%1,%2,%3}, [%4];" : "=r"(r[0]), "=r"(r[1]), "=r"(r[2]), "=r"(r[3]) : "r"(a) : "memory");
}
__device__ __forceinline__ void ldsm4t(uint32_t* r, uint32_t a) {
    asm volatile("ldmatrix.sync.aligned.m8n8.x4.trans.shared.b16 {%0,%1,%2,%3}, [%4];" : "=r"(r[0]), "=r"(r[1]), "=r"(r[2]), "=r"(r[3]) : "r"(a) : "memory");
}
__device__ __forceinline__ uint32_t ld_rlx(const void* p) { uint32_t v; asm volatile("ld.relaxed.gpu.global.u32 %0, [%1];" : "=r"(v) : "l"(p) : "memory"); return v; }
__device__ __forceinline__ uint32_t ld_acq(const void* p) { uint32_t v; asm volatile("ld.acquire.gpu.global.u32 %0, [%1];" : "=r"(v) : "l"(p) : "memory"); return v; }
__device__ __forceinline__ uint2 ld_rlx2(const void* p) { uint2 v; asm volatile("ld.relaxed.gpu.global.v2.u32 {%0,%1}, [%2];" : "=r"(v.x), "=r"(v.y) : "l"(p) : "memory"); return v; }
__device__ __forceinline__ uint4 ld_rlx4(const void* p) { uint4 v; asm volatile("ld.relaxed.gpu.global.v4.u32 {%0,%1,%2,%3}, [%4];" : "=r"(v.x), "=r"(v.y), "=r"(v.z), "=r"(v.w) : "l"(p) : "memory"); return v; }
__device__ __forceinline__ void st_rlx(void* p, uint32_t v) { asm volatile("st.relaxed.gpu.global.u32 [%0], %1;" ::"l"(p), "r"(v) : "memory"); }
__device__ __forceinline__ void st_rlx2(void* p, uint32_t a, uint32_t b) { asm volatile("st.relaxed.gpu.global.v2.u32 [%0], {%1,%2};" ::"l"(p), "r"(a), "r"(b) : "memory"); }
__device__ __forceinline__ void st_rlx4(void* p, uint32_t a, uint32_t b, uint32_t c, uint32_t d) { asm volatile("st.relaxed.gpu.global.v4.u32 [%0], {%1,%2,%3,%4};" ::"l"(p), "r"(a), "r"(b), "r"(c), "r"(d) : "memory"); }
__device__ __forceinline__ void red_add(uint32_t* p) { asm volatile("red.relaxed.gpu.global.add.u32 [%0], 1;" ::"l"(p) : "memory"); }
__device__ __forceinline__ uint4 ldg_nc(const void* p) { uint4 v; asm volatile("ld.global.nc.v4.u32 {%0,%1,%2,%3}, [%4];" : "=r"(v.x), "=r"(v.y), "=r"(v.z), "=r"(v.w) : "l"(p)); return v; }
__device__ __forceinline__ void sts4(uint32_t a, uint32_t x, uint32_t y, uint32_t z, uint32_t w) { asm volatile("st.shared.v4.u32 [%0], {%1,%2,%3,%4};" ::"r"(a), "r"(x), "r"(y), "r"(z), "r"(w) : "memory"); }
__device__ __forceinline__ void sts2(uint32_t a, uint32_t x, uint32_t y) { asm volatile("st.shared.v2.u32 [%0], {%1,%2};" ::"r"(a), "r"(x), "r"(y) : "memory"); }
__device__ __forceinline__ void sts1(uint32_t a, uint32_t v) { asm volatile("st.shared.u32 [%0], %1;" ::"r"(a), "r"(v) : "memory"); }
__device__ __forceinline__ uint4 lds4(uint32_t a) { uint4 v; asm volatile("ld.shared.v4.u32 {%0,%1,%2,%3}, [%4];" : "=r"(v.x), "=r"(v.y), "=r"(v.z), "=r"(v.w) : "r"(a) : "memory"); return v; }
__device__ __forceinline__ float4 lds4f(uint32_t a) { float4 v; asm volatile("ld.shared.v4.f32 {%0,%1,%2,%3}, [%4];" : "=f"(v.x), "=f"(v.y), "=f"(v.z), "=f"(v.w) : "r"(a) : "memory"); return v; }
__device__ __forceinline__ float2 lds2f(uint32_t a) { float2 v; asm volatile("ld.shared.v2.f32 {%0,%1}, [%2];" : "=f"(v.x), "=f"(v.y) : "r"(a) : "memory"); return v; }
__device__ __forceinline__ float lds1f(uint32_t a) { float v; asm volatile("ld.shared.f32 %0, [%1];" : "=f"(v) : "r"(a) : "memory"); return v; }
__device__ __forceinline__ uint32_t lds1(uint32_t a) { uint32_t v; asm volatile("ld.shared.u32 %0, [%1];" : "=r"(v) : "r"(a) : "memory"); return v; }
__device__ __forceinline__ uint32_t redux_max(uint32_t v) { uint32_t r; asm volatile("redux.sync.max.u32 %0, %1, 0xffffffff;" : "=r"(r) : "r"(v)); return r; }
__device__ __forceinline__ uint32_t poll_all(const uint32_t* p, uint32_t mask, uint32_t want, int& budget) {
    uint32_t v;
#pragma unroll 1
    while (v = ld_acq(p), !__all_sync(0xffffffffu, (v & mask) == want) && --budget > 0) __nanosleep(POLL_NS);
    return v;
}

template <int TA, int TB>
__device__ __forceinline__ void wgmma_n192(float (&d)[96], uint64_t da, uint64_t db, int keep) {
    asm volatile("{\n.reg .pred p;\nsetp.ne.b32 p, %98, 0;\n"
        "wgmma.mma_async.sync.aligned.m64n192k16.f32.bf16.bf16 "
        "{%0, %1, %2, %3, %4, %5, %6, %7, %8, %9, %10, %11, %12, %13, %14, %15, "
        "%16, %17, %18, %19, %20, %21, %22, %23, %24, %25, %26, %27, %28, %29, %30, %31, "
        "%32, %33, %34, %35, %36, %37, %38, %39, %40, %41, %42, %43, %44, %45, %46, %47, "
        "%48, %49, %50, %51, %52, %53, %54, %55, %56, %57, %58, %59, %60, %61, %62, %63, "
        "%64, %65, %66, %67, %68, %69, %70, %71, %72, %73, %74, %75, %76, %77, %78, %79, "
        "%80, %81, %82, %83, %84, %85, %86, %87, %88, %89, %90, %91, %92, %93, %94, %95}, "
        "%96, %97, p, 1, 1, %99, %100;\n}\n"
        : "+f"(d[0]), "+f"(d[1]), "+f"(d[2]), "+f"(d[3]), "+f"(d[4]), "+f"(d[5]), "+f"(d[6]), "+f"(d[7]),
          "+f"(d[8]), "+f"(d[9]), "+f"(d[10]), "+f"(d[11]), "+f"(d[12]), "+f"(d[13]), "+f"(d[14]), "+f"(d[15]),
          "+f"(d[16]), "+f"(d[17]), "+f"(d[18]), "+f"(d[19]), "+f"(d[20]), "+f"(d[21]), "+f"(d[22]), "+f"(d[23]),
          "+f"(d[24]), "+f"(d[25]), "+f"(d[26]), "+f"(d[27]), "+f"(d[28]), "+f"(d[29]), "+f"(d[30]), "+f"(d[31]),
          "+f"(d[32]), "+f"(d[33]), "+f"(d[34]), "+f"(d[35]), "+f"(d[36]), "+f"(d[37]), "+f"(d[38]), "+f"(d[39]),
          "+f"(d[40]), "+f"(d[41]), "+f"(d[42]), "+f"(d[43]), "+f"(d[44]), "+f"(d[45]), "+f"(d[46]), "+f"(d[47]),
          "+f"(d[48]), "+f"(d[49]), "+f"(d[50]), "+f"(d[51]), "+f"(d[52]), "+f"(d[53]), "+f"(d[54]), "+f"(d[55]),
          "+f"(d[56]), "+f"(d[57]), "+f"(d[58]), "+f"(d[59]), "+f"(d[60]), "+f"(d[61]), "+f"(d[62]), "+f"(d[63]),
          "+f"(d[64]), "+f"(d[65]), "+f"(d[66]), "+f"(d[67]), "+f"(d[68]), "+f"(d[69]), "+f"(d[70]), "+f"(d[71]),
          "+f"(d[72]), "+f"(d[73]), "+f"(d[74]), "+f"(d[75]), "+f"(d[76]), "+f"(d[77]), "+f"(d[78]), "+f"(d[79]),
          "+f"(d[80]), "+f"(d[81]), "+f"(d[82]), "+f"(d[83]), "+f"(d[84]), "+f"(d[85]), "+f"(d[86]), "+f"(d[87]),
          "+f"(d[88]), "+f"(d[89]), "+f"(d[90]), "+f"(d[91]), "+f"(d[92]), "+f"(d[93]), "+f"(d[94]), "+f"(d[95])
        : "l"(da), "l"(db), "r"(keep), "n"(TA), "n"(TB));
}
template <int TA, int TB>
__device__ __forceinline__ void wgmma_n128(float (&d)[64], uint64_t da, uint64_t db, int keep) {
    asm volatile("{\n.reg .pred p;\nsetp.ne.b32 p, %66, 0;\n"
        "wgmma.mma_async.sync.aligned.m64n128k16.f32.bf16.bf16 "
        "{%0, %1, %2, %3, %4, %5, %6, %7, %8, %9, %10, %11, %12, %13, %14, %15, "
        "%16, %17, %18, %19, %20, %21, %22, %23, %24, %25, %26, %27, %28, %29, %30, %31, "
        "%32, %33, %34, %35, %36, %37, %38, %39, %40, %41, %42, %43, %44, %45, %46, %47, "
        "%48, %49, %50, %51, %52, %53, %54, %55, %56, %57, %58, %59, %60, %61, %62, %63}, "
        "%64, %65, p, 1, 1, %67, %68;\n}\n"
        : "+f"(d[0]), "+f"(d[1]), "+f"(d[2]), "+f"(d[3]), "+f"(d[4]), "+f"(d[5]), "+f"(d[6]), "+f"(d[7]),
          "+f"(d[8]), "+f"(d[9]), "+f"(d[10]), "+f"(d[11]), "+f"(d[12]), "+f"(d[13]), "+f"(d[14]), "+f"(d[15]),
          "+f"(d[16]), "+f"(d[17]), "+f"(d[18]), "+f"(d[19]), "+f"(d[20]), "+f"(d[21]), "+f"(d[22]), "+f"(d[23]),
          "+f"(d[24]), "+f"(d[25]), "+f"(d[26]), "+f"(d[27]), "+f"(d[28]), "+f"(d[29]), "+f"(d[30]), "+f"(d[31]),
          "+f"(d[32]), "+f"(d[33]), "+f"(d[34]), "+f"(d[35]), "+f"(d[36]), "+f"(d[37]), "+f"(d[38]), "+f"(d[39]),
          "+f"(d[40]), "+f"(d[41]), "+f"(d[42]), "+f"(d[43]), "+f"(d[44]), "+f"(d[45]), "+f"(d[46]), "+f"(d[47]),
          "+f"(d[48]), "+f"(d[49]), "+f"(d[50]), "+f"(d[51]), "+f"(d[52]), "+f"(d[53]), "+f"(d[54]), "+f"(d[55]),
          "+f"(d[56]), "+f"(d[57]), "+f"(d[58]), "+f"(d[59]), "+f"(d[60]), "+f"(d[61]), "+f"(d[62]), "+f"(d[63])
        : "l"(da), "l"(db), "r"(keep), "n"(TA), "n"(TB));
}
template <int TA, int TB>
__device__ __forceinline__ void wgmma_n8(float (&d)[4], uint64_t da, uint64_t db, int keep) {
    asm volatile("{\n.reg .pred p;\nsetp.ne.b32 p, %6, 0;\n"
        "wgmma.mma_async.sync.aligned.m64n8k16.f32.bf16.bf16 "
        "{%0, %1, %2, %3}, "
        "%4, %5, p, 1, 1, %7, %8;\n}\n"
        : "+f"(d[0]), "+f"(d[1]), "+f"(d[2]), "+f"(d[3])
        : "l"(da), "l"(db), "r"(keep), "n"(TA), "n"(TB));
}
__device__ __forceinline__ void wgmma_rs_n192(float (&d)[96], uint32_t a0, uint32_t a1, uint32_t a2, uint32_t a3, uint64_t db) {
    asm volatile("{\n.reg .pred p;\nsetp.ne.b32 p, 1, 0;\n"
        "wgmma.mma_async.sync.aligned.m64n192k16.f32.bf16.bf16 "
        "{%0, %1, %2, %3, %4, %5, %6, %7, %8, %9, %10, %11, %12, %13, %14, %15, "
        "%16, %17, %18, %19, %20, %21, %22, %23, %24, %25, %26, %27, %28, %29, %30, %31, "
        "%32, %33, %34, %35, %36, %37, %38, %39, %40, %41, %42, %43, %44, %45, %46, %47, "
        "%48, %49, %50, %51, %52, %53, %54, %55, %56, %57, %58, %59, %60, %61, %62, %63, "
        "%64, %65, %66, %67, %68, %69, %70, %71, %72, %73, %74, %75, %76, %77, %78, %79, "
        "%80, %81, %82, %83, %84, %85, %86, %87, %88, %89, %90, %91, %92, %93, %94, %95}, "
        "{%96, %97, %98, %99}, %100, p, 1, 1, 1;\n}\n"
        : "+f"(d[0]), "+f"(d[1]), "+f"(d[2]), "+f"(d[3]), "+f"(d[4]), "+f"(d[5]), "+f"(d[6]), "+f"(d[7]),
          "+f"(d[8]), "+f"(d[9]), "+f"(d[10]), "+f"(d[11]), "+f"(d[12]), "+f"(d[13]), "+f"(d[14]), "+f"(d[15]),
          "+f"(d[16]), "+f"(d[17]), "+f"(d[18]), "+f"(d[19]), "+f"(d[20]), "+f"(d[21]), "+f"(d[22]), "+f"(d[23]),
          "+f"(d[24]), "+f"(d[25]), "+f"(d[26]), "+f"(d[27]), "+f"(d[28]), "+f"(d[29]), "+f"(d[30]), "+f"(d[31]),
          "+f"(d[32]), "+f"(d[33]), "+f"(d[34]), "+f"(d[35]), "+f"(d[36]), "+f"(d[37]), "+f"(d[38]), "+f"(d[39]),
          "+f"(d[40]), "+f"(d[41]), "+f"(d[42]), "+f"(d[43]), "+f"(d[44]), "+f"(d[45]), "+f"(d[46]), "+f"(d[47]),
          "+f"(d[48]), "+f"(d[49]), "+f"(d[50]), "+f"(d[51]), "+f"(d[52]), "+f"(d[53]), "+f"(d[54]), "+f"(d[55]),
          "+f"(d[56]), "+f"(d[57]), "+f"(d[58]), "+f"(d[59]), "+f"(d[60]), "+f"(d[61]), "+f"(d[62]), "+f"(d[63]),
          "+f"(d[64]), "+f"(d[65]), "+f"(d[66]), "+f"(d[67]), "+f"(d[68]), "+f"(d[69]), "+f"(d[70]), "+f"(d[71]),
          "+f"(d[72]), "+f"(d[73]), "+f"(d[74]), "+f"(d[75]), "+f"(d[76]), "+f"(d[77]), "+f"(d[78]), "+f"(d[79]),
          "+f"(d[80]), "+f"(d[81]), "+f"(d[82]), "+f"(d[83]), "+f"(d[84]), "+f"(d[85]), "+f"(d[86]), "+f"(d[87]),
          "+f"(d[88]), "+f"(d[89]), "+f"(d[90]), "+f"(d[91]), "+f"(d[92]), "+f"(d[93]), "+f"(d[94]), "+f"(d[95])
        : "r"(a0), "r"(a1), "r"(a2), "r"(a3), "l"(db));
}

template <int HS>
__device__ __forceinline__ void attn_pair(const uint32_t* q, const uint32_t* k, const uint32_t* v, const uint32_t* kh, const uint32_t* vh,
                                          const float* fu, const float* fn, const float* rk, float bias0, float bias1, uint32_t mU, uint32_t zero, const float* ci, uint32_t* o) {
    float s0[2][4] = {}, s1[2][4] = {}, s2[2][4] = {};
#pragma unroll
    for (int n = 0; n < 4; n++) {
        const int hd = n & 1, a = 8 * hd + 2 * (n & 2);
        mma16816(s1[hd], q[a], q[a + 1], q[a + 2], q[a + 3], k[a], k[a + 2]);
        mma16816(s2[hd], q[a], q[a + 1], q[a + 2], q[a + 3], k[a + 1], k[a + 3]);
    }
#pragma unroll
    for (int n = 0; n < 4; n++) {
        const int hd = n & 1, a = 8 * hd + 2 * (n & 2);
        mma16816(s0[hd], q[a], q[a + 1], q[a + 2], q[a + 3], kh[HS * (a / 2)], kh[HS * (a / 2 + 1)]);
    }
    float e[2][4], m[2][2];
#pragma unroll
    for (int hd = 0; hd < 2; hd++) {
        e[hd][2] = fmaf(s1[hd][2], fu[2], s2[hd][2] * fn[2]); e[hd][3] = fmaf(s1[hd][3], fu[3], s2[hd][3] * fn[3]);
        e[hd][0] = fmaf(s0[hd][0], fu[0], fmaf(s1[hd][0], fn[0], bias0)); e[hd][1] = fmaf(s0[hd][1], fu[1], fmaf(s1[hd][1], fn[1], bias1));
        m[hd][1] = fmaxf(e[hd][2], e[hd][3]); m[hd][0] = fmaxf(e[hd][0], e[hd][1]);
    }
#pragma unroll
    for (int x = 1; x < 3; x++)
#pragma unroll
        for (int n = 0; n < 4; n++) m[n & 1][1 - (n >> 1)] = fmaxf(m[n & 1][1 - (n >> 1)], __shfl_xor_sync(0xffffffffu, m[n & 1][1 - (n >> 1)], x));
#pragma unroll
    for (int hd = 0; hd < 2; hd++) {
#pragma unroll
        for (int n = 0; n < 4; n++) e[hd][n] = ex2(e[hd][n] - m[hd][n >> 1]);
        float sum[4] = {};
        mma1688(sum, pack_bf16(e[hd][0], e[hd][1]), pack_bf16(e[hd][2], e[hd][3]), 0x3f803f80u);
        const float i0 = rcp(sum[0]), i1 = rcp(sum[2]);
        const uint32_t plo = pack_bf16(e[hd][0] * rk[0] * i0, e[hd][1] * rk[1] * i0), phi = pack_bf16(e[hd][2] * rk[2] * i1, e[hd][3] * rk[3] * i1);
        const uint32_t z0 = plo & zero, z1 = phi & zero;
        const uint32_t a0 = plo & ~mU, a1 = phi & mU, a3 = phi & ~mU, b0 = plo & mU;
#pragma unroll
        for (int jj = 0; jj < 4; jj++) {
            float c[4];
            asm volatile("mma.sync.aligned.m16n8k16.row.col.f32.bf16.bf16.f32 {%0,%1,%2,%3}, {%4,%5,%6,%7}, {%8,%9}, {%10,%11,%12,%13};"
                         : "=f"(c[0]), "=f"(c[1]), "=f"(c[2]), "=f"(c[3])
                         : "r"(a0), "r"(a1), "r"(z0), "r"(a3), "r"(v[8 * hd + 2 * jj]), "r"(v[8 * hd + 2 * jj + 1]), "f"(ci[0]), "f"(ci[1]), "f"(ci[2]), "f"(ci[3]));
            mma1688(c, b0, z1, vh[HS * (4 * hd + jj)]);
            o[8 * hd + 2 * jj] = pack_bf16(c[0], c[1]); o[8 * hd + 2 * jj + 1] = pack_bf16(c[2], c[3]);
        }
    }
}

__device__ __forceinline__ uint32_t norm_pair(uint32_t u, float m, float rinv) {
    const uint32_t d = pack_bf16(bf_lo(u) - m, bf_hi(u) - m);
    return max(pack_bf16(bf_lo(d) * rinv, bf_hi(d) * rinv), 1u);
}

__global__ void __launch_bounds__(512, 1)
fused_kernel(const __grid_constant__ CUtensorMap mx, const __grid_constant__ CUtensorMap mw, const __grid_constant__ CUtensorMap mwo,
             const __grid_constant__ CUtensorMap mout, const __grid_constant__ CUtensorMap mgu, const __grid_constant__ CUtensorMap mwd,
             const __grid_constant__ CUtensorMap mo,
             const __nv_bfloat16* __restrict__ x, const __nv_bfloat16* __restrict__ wr, Scratch* __restrict__ scr, int swap_gu, const Weights pf) {
    extern __shared__ __align__(1024) uint8_t smem[];
    const uint32_t sb = smem_u32(smem);
    const uint32_t bars = sb + OFF_BAR;
    const int tid = threadIdx.x, lane = tid & 31, warp = __shfl_sync(0xffffffffu, tid >> 5, 0);
    const uint32_t sd = (sb & 0x3FFFF) >> 4;
    const int hp = blockIdx.x & 1, cl = blockIdx.x >> 1;
    int pr = cl - 4 + (max(cl - 36, 0) * 37 >> 8);
    asm("{\n.reg .pred p;\nsetp.lt.s32 p, %1, 4;\nselp.s32 %0, %2, %0, p;\n}" : "+r"(pr) : "r"(cl), "r"(39 + 8 * cl));
    const int b = pr * 2 + hp, mt = pr >> 3, p = pr & 7, nt = 2 * p + hp, rh = p & 1, cb = (p & 6) + hp;
    const int par = mt >> 2, j0 = (mt & 3) * 256;
    int budget = BUDGET;

    TSC(tid == 0, 0);
    auto load_w = [&](int k, int s) {
        const uint32_t full = bars + 8 * (B_WFULL + s);
        mbar_expect_tx(full, W_BYTES);
        tma_3d(sb + OFF_W + s * W_BYTES, &mw, full, nt * 64, k * 64, 0);
    };
    auto load_x = [&](int n) {
        const int w = n & 1, j = n < 4 ? (n >> 1) + 4 : (n >> 1) - 2;
        const uint32_t full = bars + 8 * (B_XFULL + w * 6 + 5 - j);
        mbar_expect_tx(full, BOX);
        tma_4d(sb + w * OFF_X1 + j * BOX, &mx, full, par * 1024 + (n >> 2) * 64, 0, (j0 + w * 128) >> 5, (~n >> 1) & 1);
    };
    if (warp < NBAR / 6 && elect_one()) {
        const uint32_t cnt = warp < B_WEMPTY / 6 ? 1 : warp < B_G1DONE / 6 ? 2 : warp < B_STAGED / 6 ? 4 : 8;
#pragma unroll
        for (int i = 0; i < 6; i++) mbar_init(bars + 48 * warp + 8 * i, cnt);
        asm volatile("fence.mbarrier_init.release.cluster;" ::: "memory");
        if (warp == 0 && b < 128) { load_x(0); load_w(0, 2); }
    }
    __syncthreads();

    if (b >= 128) {
        const int hc = b - 128, g = lane >> 2, t = lane & 3;
        const uint32_t ep = ld_rlx(&scr->epoch[0]) + 1;
        if (warp < 12) {
            const int n = warp / 3, part = warp - 3 * n;
            auto load = [&](int k) {
                const uint32_t full = bars + 8 * (2 * n + (k & 1));
                mbar_expect_tx(full, W_BYTES);
                tma_3d(sb + (2 * n + (k & 1)) * W_BYTES, &mw, full, (4 * hc + n) * 64, k * 64, 0);
            };
            if (part == 0 && elect_one()) { load(0); load(1); }
            __syncwarp();
            float c0[4] = {0.f, 0.f, 0.f, 0.f}, c1[4] = {0.f, 0.f, 0.f, 0.f};
            const uint32_t sel = g == 0 ? 0x3f80u : g == 1 ? 0x3f800000u : 0u;
            const uint32_t a = sb + 2 * n * W_BYTES + part * BOX + t * 256 + ((g ^ (2 * t)) << 4);
#pragma unroll 1
            for (int k = 0; k < 16; k++) {
                mbar_wait(bars + 8 * (2 * n + (k & 1)), (k >> 1) & 1, budget);
                uint4 v[8], u[8];
#pragma unroll
                for (int i = 0; i < 8; i++) { v[i] = lds4(a + (k & 1) * W_BYTES + i * 1024); u[i] = lds4(((a + 128) ^ 16) + (k & 1) * W_BYTES + i * 1024); }
#pragma unroll
                for (int i = 0; i < 8; i++) { mma16816(c0, v[i].x, v[i].y, u[i].x, u[i].y, sel, sel); mma16816(c1, v[i].z, v[i].w, u[i].z, u[i].w, sel, sel); }
                bar_sync(1 + n, 96);
                if (part == 0 && k < 14 && elect_one()) load(k + 2);
                __syncwarp();
            }
            if (t == 0) {
#pragma unroll
                for (int r = 0; r < 3; r++) {
                    const uint32_t q0 = (pack_bf16(c0[0], c0[1]) & ~1u) | (ep & 1), q1 = pack_bf16(c0[2], c0[3]), q2 = pack_bf16(c1[0], c1[1]), q3 = pack_bf16(c1[2], c1[3]);
                    st_rlx4(&scr->cs[4 * hc + n][r][part * 8 + g], q0, q1, q2, q3);
                    c0[0] -= bf_lo(q0); c0[1] -= bf_hi(q0); c0[2] -= bf_lo(q1); c0[3] -= bf_hi(q1);
                    c1[0] -= bf_lo(q2); c1[1] -= bf_hi(q2); c1[2] -= bf_lo(q3); c1[3] -= bf_hi(q3);
                }
            }
            TSC(tid == 0, 19);
        }
        if (warp < 8) TS_END();
        return;
    }
    asm volatile("barrier.cluster.arrive.relaxed.aligned;" ::: "memory");

    const int kc = b >> 4, c2 = b & 15;
    if (warp >= 12) {
        reg_dec<24>();
        if (warp == 12) {
            if (elect_one()) {
#pragma unroll 1
                for (int n = 1; n < 12; n++) {
                    load_x(n);
                    if (n == ROWS_AT) { mbar_expect_tx(bars + 8 * B_ROW, 4 * BOX); bulk_g2s(sb + OFF_FR, x + (size_t)b * 16 * 1024, 4 * BOX, bars + 8 * B_ROW); }
                    if (n == 3 || n == 7) load_w((n + 1) >> 2, n >> 2);
                }
                int s = 2; uint32_t ph = 0;
#pragma unroll 1
                for (int k = 3; k < 16; k++) {
                    mbar_wait(bars + 8 * (B_WEMPTY + s), ph, budget);
                    load_w(k, s);
                    if (++s == 3) s = 0;
                    if (s == 2) ph ^= 1;
                }
                s = 2;
#pragma unroll 1
                for (int i = 0; i < 16; i++) {
                    mbar_wait(bars + 8 * (i < 2 ? B_WEMPTY + i : i < 4 ? B_G1DONE : i < 6 ? B_F1DONE : B_WOEMPTY + s), i >= 12, budget);
                    if (i == 0) {
                        mbar_expect_tx(bars + 8 * B_XT, 4 * BOX);
#pragma unroll 1
                        for (int n = 0; n < 4; n++)
                            tma_4d(sb + (n >> 1) * OFF_X1 + (n & 1) * BOX, &mx, bars + 8 * B_XT, par * 1024 + cb * 128 + (n & 1) * 64, 0, (j0 + rh * 128) >> 5, 1 - (n >> 1));
                    }
                    const uint32_t full = bars + 8 * (B_WOFULL + s);
                    mbar_expect_tx(full, 2 * BOX);
                    tma_3d(sb + OFF_WO + s * 2 * BOX, &mwo, full, 0, ((2 * p + (i < 2 ? i ^ hp : i)) & 15) * 64, cb * 2);
                    TSC(TIMING % 10 == 4, 48 + i);
                    if (++s == 6) s = 0;
                }
            }
        } else {
            bar_sync(8, 224);
            const uint32_t ep = __shfl_sync(0xffffffffu, lds1(sb + OFF_EP), 0);
            if (warp == 13) {
                cluster_wait();
                if (elect_one()) {
                    int j = 4, q = 0, left = BUDGET; uint32_t ph = 0;
#pragma unroll 1
                    for (int n = 6; n < 32; n++) {
                        mbar_wait(bars + 8 * (B_XEMPTY + j), ph, left);
                        tma_4d_mc(sb + hp * OFF_X1 + j * BOX, &mx, bars + 8 * (B_XFULL + hp * 6 + 5 - j), par * 1024 + (n >> 1) * 64, 0, (j0 + hp * 128) >> 5, ~n & 1);
                        if (++j == 6) j = 0;
                        if (j == 4) ph ^= 1;
#pragma unroll 1
                        for (; q < (PF_RATE * (n - PF_START) >> 3) && q < 18 + PF_NW; q++) {
                            const int u = q - PF_NW;
                            if (u < 0) bulk_pf(pf.wqkv + (size_t)(1024 + 128 * u + b) * 6144, 6144);
                            else if (u < 16) bulk_pf((b < 64 ? pf.wg : pf.wu) + (size_t)(u * 64 + (b & 63)) * 7168, 7168);
                            else bulk_pf(pf.wo + (size_t)((u - 16) * 128 + b) * 8192, 8192);
                        }
                    }
                }
                __syncwarp();
                uint32_t* hs = &scr->halo[b - 16][lane * 4];
                uint4 v[4] = {};
                if (j0) {
#pragma unroll 1
                    do {
#pragma unroll
                        for (int c = 0; c < 4; c++) v[c] = ld_rlx4(hs + c * 128);
                    } while (__any_sync(0xffffffffu, min(min(v[0].x, v[1].x), min(v[2].x, v[3].x)) == 0) && --budget > 0);
                }
#pragma unroll
                for (int c = 0; c < 4; c++) stsm4(sb + OFF_HIN + c * 512 + lane * 16, v[c].x, v[c].y, v[c].z, v[c].w);
                bar_arrive(11, 64);
                if (j0) {
#pragma unroll
                    for (int c = 0; c < 4; c++) st_rlx(hs + c * 128, 0);
                }
                TSC(lane == 0, 31);
                const int src = ((mt * 2 + rh) * 2 + 1 - hp) * 1024;
                if (elect_one()) {
                    const uint32_t* fl = &scr->oflag[mt * 2 + 1 - hp][0];
                    const uint32_t inv = (ep & 1) - 1;
                    uint32_t ready = 0, ph = 0;
                    int s = 4;
#pragma unroll 1
                    for (int i = 2; i < 16; i++) {
                        const int kb = (2 * p + i) & 15;
#pragma unroll 1
                        while (!((ready >> kb) & 1) && --budget > 0) ready = ld_rlx(fl) ^ inv;
                        TSC(i == 2, 30);
                        mbar_wait(bars + 8 * (B_OEMPTY + s), ph, budget);
                        tma_2d_mc(sb + hp * OFF_X1 + s * BOX, &mo, bars + 8 * (B_OFULL + hp * 6 + s), 0, src + kb * 64);
                        TSC(TIMING % 10 == 4 && hp == 0, 32 + i);
                        if (++s == 6) s = 0;
                        if (s == 4) ph ^= 1;
                    }
                }
            } else if (warp == 14) {
                if (elect_one()) {
                    uint32_t s8 = 0, ph = 0;
                    int tries = BUDGET;
                    const uint32_t* act = scr->act[ep & 1];
                    auto counted = [&](int c, uint32_t n) {
#pragma unroll 1
                        while (ld_rlx(&scr->cnt[c][0]) != ep * n && --tries > 0) __nanosleep(POLL_NS);
                    };
                    auto weights = [&](const CUtensorMap* m, int c0, int c1, int c2_) {
                        mbar_wait(bars + 8 * B_FEMPTY + s8, ph, budget);
                        mbar_expect_tx(bars + 8 * B_FFULL + s8, F_BYTES);
                        tma_3d(sb + OFF_FS + s8 * (F_BYTES / 8), m, bars + 8 * B_FFULL + s8, c0, c1, c2_);
                    };
                    if (b < 112) {
                        counted(8, 32);
                        TS(26);
#pragma unroll 1
                        for (int q = 0; q < 16; q++) {
                            weights(&mgu, b * 32, q * 64, 0);
                            bulk_g2s(sb + OFF_FS + BOX + s8 * (F_BYTES / 8), act + 14336 + q * 256, 1024, bars + 8 * B_FFULL + s8);
                            TSC(TIMING % 10 == 5, 32 + q);
                            if (q >= PF_D && q < PF_D + 8) bulk_pf(pf.wd + (size_t)((q - PF_D) * 112 + b) * 8192, 8192);
                            s8 += 8;
                            if (s8 == 40) { s8 = 0; ph ^= 1; }
                        }
                    }
#pragma unroll 1
                    for (int q = -3; q < 7; q++) {
                        if (q == 0) { counted(kc, 28); TS(29); }
                        if ((unsigned)q >= 3) weights(&mwd, 0, kc * 448 + (q < 0 ? q + 3 : q) * 64, c2);
                        if (q >= 0) bulk_g2s(sb + OFF_FS + BOX + s8 * (F_BYTES / 8), act + (kc * 7 + q) * 256, 1024, bars + 8 * B_FFULL + s8);
                        TSC(TIMING % 10 == 5, 51 + q);
                        s8 += 8;
                        if (s8 == 24) { s8 = 0; if ((unsigned)q >= 3) ph ^= 1; }
                    }
                }
            } else {
#pragma unroll 1
                for (int i = lane * 16; i < CS_BYTES; i += 512) sts4(sb + OFF_CS + i, 0, 0, 0, 0);
                mbar_wait(bars + 8 * ZF_GATE, 0, budget);
                uint8_t* oz = scr->o + ((size_t)mt * 64 + nt) * BOX + lane * 16;
#pragma unroll 1
                for (int i = 0; i < 16; i++, oz += 512) {
#pragma unroll
                    for (int n = 0; n < 4; n++) st_rlx4(oz + n * 16 * BOX, 0, 0, 0, 0);
                    __nanosleep(ZF_NS);
                }
                __syncwarp();
                fence_gpu();
                mbar_wait(bars + 8 * B_RDONE, 0, budget);
                int tries = BUDGET;
#pragma unroll 1
                for (int i = lane; i < 88; i += 32) {
                    const uint2* rp = &scr->row[2 * (j0 - 8 + i) + par];
                    uint2 v0, v1, v2;
#pragma unroll 1
                    do { v0 = ld_rlx2(rp + (j0 + i < 8 ? 16 : 0)); v1 = ld_rlx2(rp + 176); v2 = ld_rlx2(rp + 352); } while ((((v0.y ^ ep) | (v1.y ^ ep) | (v2.y ^ ep)) & 31) && --tries > 0);
                    sts2(sb + OFF_STAT + i * 8, (v0.x << 16) ^ 0x80000000u, __float_as_uint(rcp(bf_hi(v0.x))));
                    sts2(sb + OFF_STAT + i * 8 + 704, (v1.x << 16) ^ 0x80000000u, __float_as_uint(rcp(bf_hi(v1.x))));
                    sts2(sb + OFF_STAT + i * 8 + 1408, (v2.x << 16) ^ 0x80000000u, __float_as_uint(rcp(bf_hi(v2.x))));
                }
                __syncwarp();
                {
                    const int row = 2047 - ((poll_all(&scr->sel[lane & 7], 31u, ep & 31, budget) >> 5) & 2047), jj = (row >> 1) - j0 - rh * 128;
                    uint32_t boxes = __reduce_or_sync(0xffffffffu, (row & 1) == par && (unsigned)jj < 128 ? 1u << (jj >> 4) : 0u);
                    sts1(sb + OFF_SEL, boxes);
#pragma unroll 1
                    for (int i = 0; boxes; i += 2) {
                        if (boxes & 1) st_rlx4(pf.out + (size_t)(2 * (j0 + rh * 128 + i + (lane >> 4)) + par) * 2048 + cb * 256 + (lane & 15) * 16, 0, 0, 0, 0);
                        else i += 14;
                        if ((i & 14) == 14) boxes >>= 1;
                    }
                }
                if (lane < 24) {
                    uint4 v[3];
#pragma unroll 1
                    while (v[0] = ld_rlx4(&scr->cs[nt][0][lane]), v[1] = ld_rlx4(&scr->cs[nt][1][lane]), v[2] = ld_rlx4(&scr->cs[nt][2][lane]),
                           (((v[0].x ^ ep) | (v[1].x ^ ep) | (v[2].x ^ ep)) & 1) && --tries > 0) __nanosleep(100);
#pragma unroll
                    for (int r = 0; r < 3; r++) sts4(sb + OFF_CS + 64 + lane * 128 + r * 16, v[r].x, v[r].y, v[r].z, v[r].w);
                }
                fence_async_smem();
                __syncwarp();
                if (elect_one()) {
                    mbar_arrive(bars + 8 * B_AUX);
                    TS(21);
                    if (lds1(sb + OFF_SEL)) { fence_gpu(); asm volatile("fence.proxy.async.global;" ::: "memory"); }
                    mbar_arrive(bars + 8 * B_ZERO);
                    TS(25);
                    mbar_expect_tx(bars + 8 * (B_OFULL + 3), BOX); mbar_expect_tx(bars + 8 * (B_OFULL + 9), BOX);
#pragma unroll 1
                    for (int v = 0; v < 2; v++) {
                        const uint32_t ring = sb + v * OFF_X1 + 2 * BOX, fb = bars + 8 * (B_OFULL + v * 6 + 2);
                        mbar_wait(bars + 8 * (B_STAGED + v), 0, budget);
                        asm volatile("red.relaxed.gpu.global.xor.b32 [%0], %1;" ::"l"(&scr->oflag[mt * 2 + 1 - v][0]), "r"(1u << nt) : "memory");
                        TS(13 + 2 * v);
                        mbar_arrive(fb);
                        mbar_wait(bars + 8 * B_G1DONE, 0, budget);
                        bulk_s2c(mapa(ring + BOX, hp ^ 1), ring, BOX, mapa(fb + 8, hp ^ 1));
                        if (v == 0) mbar_wait(bars + 8 * B_FREED, 0, budget);
#pragma unroll
                        for (int n = 0; n < 4; n++) {
                            mbar_expect_tx(bars + 8 * (B_OFULL + (n >> 1) * 6 + 4 + (n & 1)) - v * 32, BOX);
                            mbar_arrive_at(mapa(bars + 8 * B_OEMPTY, n >> 1) + (4 + (n & 1)) * 8 - v * 32);
                        }
                    }
                }
            }
        }
    } else if (warp >= 8) {
        reg_dec<40>();
        const int wq = warp - 8, ta = tid - 256;
        const uint32_t rbuf = sb + OFF_FR + wq * BOX, rbar = bars + 8 * B_ROW;
        const uint4 wv = ldg_nc(wr + ta * 8);
        if (ta == 0) sts1(sb + OFF_EP, ld_rlx(&scr->epoch[0]) + 1);
        sts4(sb + OFF_STAT + ta * 16, wv.x, wv.y, wv.z, wv.w);
        bar_sync(8, 224);
        const uint32_t ep = __shfl_sync(0xffffffffu, lds1(sb + OFF_EP), 0);
        {
            const int s = b * 16 + wq * 4 + (lane >> 3);
            if ((lane & 7) == 0) st_rlx2(&scr->row[s], 0, ep - 1);
            float sw = 0.f;
#pragma unroll 1
            for (int i = 0; i < 16; i++) { const uint32_t q = lds1(sb + OFF_STAT + i * 128 + lane * 4); sw += bf_lo(q) + bf_hi(q); }
#pragma unroll 1
            for (int o = 16; o > 0; o >>= 1) sw += __shfl_xor_sync(0xffffffffu, sw, o);
            float s1 = 0.f, s2 = 0.f, sr = 0.f;
            const uint32_t xa = rbuf + (lane >> 3) * 2048 + (lane & 7) * 16, wa = sb + OFF_STAT + (lane & 7) * 16;
            mbar_wait(rbar, 0, budget);
            TSC(ta == 0, 17);
            {
                float s1b = 0.f, s2b = 0.f, srb = 0.f;
                const uint32_t xb = rbuf + (lane >> 4) * 4096 + (lane & 15) * 16, wb = sb + OFF_STAT + (lane & 15) * 16;
                uint4 w4 = lds4(wb), u = lds4(xb), v = lds4(xb + 2048);
#pragma unroll 1
                for (int i = 1; i <= 8; i++) {
                    const uint32_t o = (i * 256) & 2047;
                    float wf[8];
#pragma unroll
                    for (int c = 0; c < 4; c++) { wf[2 * c] = bf_lo((&w4.x)[c]); wf[2 * c + 1] = bf_hi((&w4.x)[c]); }
                    w4 = lds4(wb + o);
#pragma unroll
                    for (int c = 0; c < 4; c++) {
                        const float a0 = bf_lo((&u.x)[c]), a1 = bf_hi((&u.x)[c]);
                        s1 += a0; s2 = fmaf(a0, a0, s2); sr = fmaf(a0, wf[2 * c], sr);
                        s1 += a1; s2 = fmaf(a1, a1, s2); sr = fmaf(a1, wf[2 * c + 1], sr);
                    }
                    u = lds4(xb + o);
#pragma unroll
                    for (int c = 0; c < 4; c++) {
                        const float a0 = bf_lo((&v.x)[c]), a1 = bf_hi((&v.x)[c]);
                        s1b += a0; s2b = fmaf(a0, a0, s2b); srb = fmaf(a0, wf[2 * c], srb);
                        s1b += a1; s2b = fmaf(a1, a1, s2b); srb = fmaf(a1, wf[2 * c + 1], srb);
                    }
                    v = lds4(xb + 2048 + o);
                }
                const bool up = lane & 8;
                s1 = (up ? s1b : s1) + __shfl_xor_sync(0xffffffffu, up ? s1 : s1b, 8);
                s2 = (up ? s2b : s2) + __shfl_xor_sync(0xffffffffu, up ? s2 : s2b, 8);
                sr = (up ? srb : sr) + __shfl_xor_sync(0xffffffffu, up ? sr : srb, 8);
            }
#pragma unroll
            for (int o = 1; o < 8; o <<= 1) {
                s1 += __shfl_xor_sync(0xffffffffu, s1, o); s2 += __shfl_xor_sync(0xffffffffu, s2, o); sr += __shfl_xor_sync(0xffffffffu, sr, o);
            }
            const float mean = s1 * (1.f / 1024.f), mb = bf16r(mean);
            float var = fmaf(-mean, mean, s2 * (1.f / 1024.f));
            sr = fmaf(-mb, sw, sr);
            if (__builtin_expect(__any_sync(0xffffffffu, mean * mean > 256.f * var), 0)) {
                float a2 = 0.f, ar = 0.f;
#pragma unroll 1
                for (int i = 0; i < 64; i++) {
                    const uint32_t o = (i >> 2) * 128 + (i & 3) * 4, q1 = lds1(xa + o), q2 = lds1(wa + o);
                    a2 = fmaf(bf_lo(q1) - mean, bf_lo(q1) - mean, fmaf(bf_hi(q1) - mean, bf_hi(q1) - mean, a2));
                    ar = fmaf(bf_lo(q1) - mb, bf_lo(q2), fmaf(bf_hi(q1) - mb, bf_hi(q2), ar));
                }
#pragma unroll 1
                for (int o = 1; o < 8; o <<= 1) { a2 += __shfl_xor_sync(0xffffffffu, a2, o); ar += __shfl_xor_sync(0xffffffffu, ar, o); }
                var = a2 * (1.f / 1024.f); sr = ar;
            }
            float den;
            asm("sqrt.approx.f32 %0, %1;" : "=f"(den) : "f"(bf16r(bf16r(var) + 1e-5f)));
            const uint32_t st = pack_bf16(mb, den);
            const uint32_t rb = pack_bf16(0.f, sr * rcp(bf_hi(st)) + 0.f);
            uint32_t ord = (int)rb < 0 ? ~rb & 0xffff0000u : rb | 0x80000000u;
            if ((rb & 0x7fffffffu) > 0x7f800000u) ord = 0;
            if ((lane & 7) == 0) st_rlx2(&scr->row[s], st, ord | ((2047 - s) << 5) | (ep & 31));
            __syncwarp();
            if (lane < 7) mbar_arrive(bars + 8 * (lane < 5 ? B_FEMPTY + lane : B_RDONE));
        }
        TSC(ta == 0, 18);
        if ((b >> 3) == 14) {
            const uint32_t gm = sb + OFF_E, cnt = gm + 64, res = gm + 80, list = gm + 128;
            uint32_t kv[16];
            int tries = BUDGET;
#pragma unroll 1
            do {
                uint32_t bad = 0;
#pragma unroll
                for (int n = 0; n < 16; n++) kv[n] = ld_rlx(&scr->row[n * 128 + ta].y);
#pragma unroll
                for (int n = 0; n < 16; n++) bad |= kv[n] ^ ep;
                if ((bad & 31) == 0) break;
            } while (--tries > 0);
            __syncwarp();
            TSC(ta == 0, 26);
            uint32_t m = 0;
#pragma unroll
            for (int n = 0; n < 16; n++) m = max(m, kv[n]);
            uint32_t gmax = m;
#pragma unroll
            for (int o = 1; o < 8; o <<= 1) gmax = max(gmax, __shfl_xor_sync(0xffffffffu, gmax, o));
            sts1(gm + (ta >> 3) * 4, gmax);
            sts1(cnt, 0);
            bar_sync(12, 128);
            const uint32_t c = lds1(gm + (lane & 15) * 4);
            int rank = 0;
#pragma unroll
            for (int i = 0; i < 2; i++) { const uint4 q = lds4(gm + (lane >> 4) * 32 + i * 16); rank += (q.x > c) + (q.y > c) + (q.z > c) + (q.w > c); }
            rank += __shfl_xor_sync(0xffffffffu, rank, 16);
            const uint32_t thr = redux_max(rank == 7 ? c : 0u);
#pragma unroll 1
            while (m >= thr) {
                uint32_t at, m2 = 0;
                asm volatile("atom.shared.add.u32 %0, [%1], 1;" : "=r"(at) : "r"(cnt) : "memory");
#pragma unroll
                for (int n = 0; n < 16; n++) m2 = max(m2, kv[n] < m ? kv[n] : 0u);
                sts1(list + at * 4, m);
                if (m2 == 0) break;
                m = m2;
            }
            bar_sync(12, 128);
            const int nc = lds1(cnt);
#pragma unroll 1
            for (int i = ta >> 3; i < ((nc + 3) & ~3); i += 16) {
                const uint32_t ki = lds1(list + i * 4);
                int r = 0;
#pragma unroll 1
                for (int n = lane & 7; n < nc; n += 8) r += lds1(list + n * 4) > ki;
                __syncwarp();
#pragma unroll
                for (int o = 1; o < 8; o <<= 1) r += __shfl_xor_sync(0xffffffffu, r, o);
                if (r == (b & 7) && i < nc) sts1(res, ki);
            }
            bar_sync(12, 128);
            const uint32_t k0 = lds1(res);
            const int r0 = 2047 - ((k0 >> 5) & 2047);
            TSC(ta == 0, 22);
            if (ta == 0) st_rlx(&scr->sel[b & 7], k0);
            const uint4 v0 = ldg_nc(x + (size_t)r0 * 1024 + ta * 8);
            const uint32_t s0 = ld_rlx(&scr->row[r0]);
            const float m0 = bf_lo(s0), i0 = rcp(bf_hi(s0));
            const int ao = 14336 + (ta >> 3) * 256 + (b & 7) * 32 + ((ta ^ b) & 7) * 4;
            st_rlx4(scr->act[ep & 1] + ao, norm_pair(v0.x, m0, i0), norm_pair(v0.y, m0, i0), norm_pair(v0.z, m0, i0), norm_pair(v0.w, m0, i0));
            __syncwarp();
            if (lane == 0) red_add(&scr->cnt[8][tries >> 30]);
            st_rlx4(scr->act[~ep & 1] + ao, 0, 0, 0, 0);
        }
        uint32_t s8 = 0, fph = 0, key = 0;
        const uint32_t chk = __shfl_sync(0xffffffffu, sb + OFF_FS + BOX + lane * 32 + (lane & 28), lane);
        int left = BUDGET;
#pragma unroll 1
        for (int ph = 0; ph < 2; ph++) {
            if (ph || b < 112) {
                float acc[4] = {0.f, 0.f, 0.f, 0.f};
                const uint32_t alo = sd + (ph ? dlo(OFF_FS, 8192) : dlo(OFF_FS, 4096)), ahi = ph ? dhi(1024, 1) : dhi(512, 2), astep = ph ? 128 : 64;
                const uint32_t bhi = ph ? dhi(128, 0) : dhi(1024, 1), bstep = ph ? 16 : 2, wrap = ph ? 24 : 40;
                uint32_t prev = 0, prev2 = 0;
#pragma unroll 1
                for (int q = ph ? 7 : 16; q > 0; q--) {
                    const uint32_t da = alo + s8 * (F_BYTES >> 7), db = sd + dlo(OFF_FS + BOX, 128) + s8 * (F_BYTES >> 7);
                    if (q == (ph ? 7 : F1_HOLD)) {
                        wg_wait<0>();
                        if (prev) mbar_arrive(prev);
                        prev = 0;
                        mbar_wait(bars + 8 * (ph ? FFN2_GATE : F1_GATE), 0, left);
                    }
                    mbar_wait_hot(bars + 8 * B_FFULL + s8, fph, left);
                    if (__builtin_expect(__any_sync(0xffffffffu, lds1(chk + s8 * (F_BYTES / 8)) == 0), 0)) {
                        int tries = BUDGET;
#pragma unroll 1
                        for (int n = lane * 4 + (left >> 30); n < 256; n += 128) {
                            uint4 v;
#pragma unroll 1
                            do { v = ld_rlx4(scr->act[ep & 1] + ((ph ? kc * 7 + 7 : 72) - q) * 256 + n); } while (v.x == 0 && --tries > 0);
                            __syncwarp();
                            sts4(sb + OFF_FS + BOX + s8 * (F_BYTES / 8) + n * 4, v.x, v.y, v.z, v.w);
                        }
                        NRETRY();
                        fence_async_smem();
                        __syncwarp();
                    }
                    TSC(TIMING % 10 == 3 && ta == 0, 32 + (ph ? 23 : 16) - q);
                    wg_fence();
#pragma unroll
                    for (int j = 0; j < 4; j++) wgmma_n8<1, 0>(acc, mkdesc(da + j * astep, ahi), mkdesc(db + j * bstep, bhi), 1);
                    wg_commit();
                    uint32_t done = F1_DEPTH == 2 ? prev2 : prev;
                    prev2 = prev;
                    if (lane == 0) prev = bars + 8 * B_FEMPTY + s8;
                    wg_wait<F1_DEPTH>();
                    if (ph) { wg_wait<F2_DEPTH>(); done = F2_DEPTH ? prev2 : prev; }
                    if (done) mbar_arrive(done);
                    s8 += 8;
                    if (s8 == wrap) { s8 = 0; fph ^= 1; }
                }
                wg_wait<0>();
                const int ln = lane + (left >> 30);
                if (ph == 0) {
                    if (prev) mbar_arrive(prev);
                    const bool second = (wq >= 2) != (swap_gu != 0);
                    const uint32_t xa = sb + OFF_GU + ((wq & 1) * 32 + ln) * 16;
                    if (second) sts4(xa, __float_as_uint(acc[0]), __float_as_uint(acc[1]), __float_as_uint(acc[2]), __float_as_uint(acc[3]));
                    bar_sync(12, 128);
                    if (!second) {
                        const float4 up = lds4f(xa);
                        float hv[4];
#pragma unroll
                        for (int c = 0; c < 4; c++) { const float ga = bf16r(acc[c]); hv[c] = bf16r(ga * sigmoidf(ga)) * bf16r((&up.x)[c]); }
                        const int ao = (b * 4 + (wq & 1) * 2) * 32 + ln;
                        st_rlx(scr->act[ep & 1] + ao, max(movm(pack_bf16(hv[0], hv[1])), 1u)); st_rlx(scr->act[ep & 1] + 32 + ao, max(movm(pack_bf16(hv[2], hv[3])), 1u));
                        __syncwarp();
                        if (ln == 0) red_add(&scr->cnt[b / 14][0]);
                        st_rlx(scr->act[~ep & 1] + ao, 0); st_rlx(scr->act[~ep & 1] + 32 + ao, 0);
                    }
                } else {
#pragma unroll
                    for (int c = 0; c < 4; c++) st_rlx(&scr->ypart[kc][2 * (ln & 3) + (c & 1)][c2 * 64 + wq * 16 + (c >> 1) * 8 + (ln >> 2)], (__float_as_uint(acc[c]) & ~1u) | (ep & 1));
                }
                TSC(ta == 0, 22 + ph);
            }
            const int ln = lane + (left >> 30);
            if (ph == 0) {
                if ((ta & 126) == 64) mbar_arrive(bars + 8 * B_F1DONE);
                key = poll_all(&scr->sel[ln & 7], 31u, ep & 31, left);
            }
        }
        {
            const int row = 2047 - ((key >> 5) & 2047);
            const float sig = bf16r(sigmoidf(__uint_as_float(((int)key < 0 ? key & 0x7fffffffu : ~key) & 0xffff0000u)));
            uint32_t own = __ballot_sync(0xffffffffu, (row & 1) == par && (row >> 8) == (mt & 3) * 2 + rh) & 255;
            if (wq & 2) own &= own - 1;
            mbar_wait(bars + 8 * B_ZERO, 0, left);
#pragma unroll 1
            for (; own; own &= own - 1, own &= own - 1) {
                const int j = __ffs(own) - 1, col = cb * 128 + (wq & 1) * 64 + (lane & 15) * 4;
                const uint32_t* src = &scr->ypart[lane >> 4][j][col];
                uint4 v[4]; int tries = BUDGET;
#pragma unroll 1
                do {
#pragma unroll
                    for (int m = 0; m < 4; m++) v[m] = ld_rlx4(src + m * 2 * 8192);
                } while ((((v[0].x ^ ep) | (v[1].x ^ ep) | (v[2].x ^ ep) | (v[3].x ^ ep)) & 1) && --tries > 0 && (__nanosleep(Y_NS), true));
                __syncwarp();
                float a[4];
                const float sj = __shfl_sync(0xffffffffu, sig, j);
                const int rj = __shfl_sync(0xffffffffu, row, j);
#pragma unroll
                for (int c = 0; c < 4; c++) {
                    a[c] = (__uint_as_float((&v[0].x)[c]) + __uint_as_float((&v[1].x)[c])) + (__uint_as_float((&v[2].x)[c]) + __uint_as_float((&v[3].x)[c]));
                    a[c] = bf16r(a[c] + __shfl_xor_sync(0xffffffffu, a[c], 16)) * sj;
                }
                if (lane < 16) asm volatile("red.relaxed.gpu.global.add.noftz.v2.bf16x2 [%0], {%1, %2};" ::"l"(pf.out + (size_t)rj * 2048 + col * 2), "r"(pack_bf16(a[0], a[1])), "r"(pack_bf16(a[2], a[3])) : "memory");
            }
        }
        TSC(ta == 0, 24);
    } else {
        reg_inc<224>();
        const int w = warp >> 2, wi = warp & 3, g = lane >> 2, t = lane & 3;
        const bool elect = (tid & 127) == 0;
        const uint32_t mad = (lane & 15) * 128 + (((lane >> 4) ^ (lane & 7)) << 4);
        float acc[64];
        const uint32_t ring = sb + w * OFF_X1, ofull = bars + 8 * (B_OFULL + w * 6), oempty = mapa(bars + 8 * B_OEMPTY, w);
        const int r0 = rh * 128 + wi * 32 + (1 - w) * 16 + g;
        {
            float acc0[96], acc1[96];
            const uint32_t sta = sb + OFF_STAT + (8 + w * 128 + wi * 32) * 8;
            {
                const uint32_t xfull = bars + 8 * (B_XFULL + w * 6 + 5), xempty = mapa(bars + 8 * B_XEMPTY, w), dx0 = sd + dlo(w * OFF_X1, 16);
                uint32_t s8 = 16, ps8 = 0, ph = 0;
                cluster_wait();
#pragma unroll 1
                for (int k = 0; k < 16; k++) {
                    const uint32_t dx = dx0 + s8 * (2 * BOX >> 7), dw = sd + dlo(OFF_W, BOX) + s8 * (W_BYTES >> 7);
                    mbar_wait(bars + 8 * B_WFULL + s8, ph, budget);
                    mbar_wait(xfull - 2 * s8, ph, budget);
                    TSC(elect && k == 0, 1 + 8 * w);
                    TSC(TIMING % 10 == 1 && tid == 0, 32 + k);
                    wg_wait<0>();
                    wg_fence();
#pragma unroll
                    for (int kk = 0; kk < 4; kk++) wgmma_n192<0, 1>(acc1, mkdesc(dx + kk * 2, dhi(1024, 1)), mkdesc(dw + kk * 128, dhi(1024, 1)), kk ? 1 : k);
                    wg_commit();
                    TSC(TIMING % 10 == 6 && elect, 32 + 16 * w + k);
                    if (elect && k > 0) {
                        mbar_arrive(bars + 8 * B_WEMPTY + ps8);
                        if (k <= 13) { mbar_expect_tx(xfull - 2 * ps8 - 8, BOX); mbar_arrive_at(xempty + 2 * ps8 + 8); }
                    }
                    if (k == 15) {
                        mbar_wait(bars + 8 * B_AUX, 0, budget);
                        const uint32_t zero = budget >> 30, pm = t & 1 ? 0x4432 : 0x3232, ra = sta + ((t >> 1) * 16 + g) * 8;
                        const uint32_t a0 = __byte_perm(lds1(ra), 0, pm), a1 = __byte_perm(lds1(ra + 64), 0, pm), a2 = a0 & zero, a3 = a1 & zero;
                        wg_fence();
                        wgmma_rs_n192(acc1, a0, a1, a2, a3, mkdesc(sd + dlo(OFF_CS, 0), dhi(128, 0)));
                        wgmma_rs_n192(acc0, a0, a1, a2, a3, mkdesc(sd + dlo(OFF_CS + 64, 0), dhi(128, 0)));
                        wg_commit();
                    }
                    mbar_wait(xfull - 2 * s8 - 8, ph, budget);
                    wg_wait<0>();
                    wg_fence();
#pragma unroll
                    for (int kk = 0; kk < 4; kk++) wgmma_n192<0, 1>(acc0, mkdesc(dx + 512 + kk * 2, dhi(1024, 1)), mkdesc(dw + kk * 128, dhi(1024, 1)), kk ? 1 : k);
                    wg_commit();
                    if (elect && k <= 12) { mbar_expect_tx(xfull - 2 * s8, BOX); mbar_arrive_at(xempty + 2 * s8); }
                    ps8 = s8;
                    s8 = s8 == 16 ? 0 : s8 + 8;
                    if (s8 == 16) ph ^= 1;
                }
            }
            const uint32_t zero = budget >> 30;
            const bool u0 = 2 * t > g, u1 = 2 * t + 1 > g;
            uint32_t mU = (u0 ? 0xffffu : 0u) | (u1 ? 0xffff0000u : 0u);
            uint32_t ka0 = sta + (2 * t - (u0 ? 8 : 0)) * 8 + 4, ka1 = sta + (2 * t + 1 - (u1 ? 8 : 0)) * 8 + 4;
            float rk[2][4], fu[2][4], fn[2][4];
            auto factors = [&](int h) {
#pragma unroll
                for (int n = 0; n < 4; n += 2) {
                    const float rq = lds1f(sta + (16 * h + 4 * n + g) * 8 + 4) * (0.17677669529663687f * 1.4426950408889634f);
                    rk[h][n] = lds1f(ka0 + h * 128 + n * 32); rk[h][n + 1] = lds1f(ka1 + h * 128 + n * 32);
                    const float f0 = rq * rk[h][n], f1 = rq * rk[h][n + 1];
                    fu[h][n] = u0 ? f0 : 0.f; fn[h][n] = f0 - fu[h][n]; fu[h][n + 1] = u1 ? f1 : 0.f; fn[h][n + 1] = f1 - fu[h][n + 1];
                }
#pragma unroll
                for (int n = 0; n < 4; n++) asm volatile("" : "+f"(fu[h][n]), "+f"(fn[h][n]));
            };
            uint8_t* og = scr->o + ((size_t)(mt * 4 + w * 2) * 16 + nt) * BOX + wi * 256 + lane * 4;
            TSC(elect, 19 + w);
            uint32_t pk0[48], pk1[48], o[16] = {};
#pragma unroll
            for (int j = 0; j < 48; j++) if (j < 16 || (j & 1)) pk1[j] = pack_here(acc1[2 * j], acc1[2 * j + 1]);
            if (warp < 7) {
#pragma unroll
                for (int c = 0; c < 4; c++) stsm4(ring + 4 * BOX + wi * 2048 + c * 512 + lane * 16, pk1[17 + 8 * c], pk1[19 + 8 * c], pk1[21 + 8 * c], pk1[23 + 8 * c]);
                bar_arrive(1 + warp, 64);
            } else if (j0 != 768) {
#pragma unroll
                for (int c = 0; c < 4; c++) {
                    pk1[17 + 8 * c] = max(pk1[17 + 8 * c], 1u);
                    st_rlx4(&scr->halo[b][c * 128 + lane * 4], pk1[17 + 8 * c], pk1[19 + 8 * c], pk1[21 + 8 * c], pk1[23 + 8 * c]);
                }
            }
            TSC(tid == 224, 28);
#pragma unroll
            for (int j = 16; j < 48; j += 2) pk1[j] = pack_here(acc1[2 * j], acc1[2 * j + 1]);
            factors(1);
            uint32_t od = sb + 2 * BOX + wi * 256 + (lane >> 4) * 1024 + (lane & 15) * 16, g1peer = mapa(bars + 8 * B_G1DONE, hp ^ 1);
            uint32_t ha = sb + (warp == 0 ? OFF_HIN : warp <= 4 ? 4 * BOX - 2048 : OFF_X1 + 4 * BOX - 5 * 2048) + warp * 2048 + lane * 16;
            const bool first = warp == 0 && j0 == 0;
            float bias0 = first && u0 ? -INFINITY : 0.f, bias1 = first && u1 ? -INFINITY : 0.f;
            asm volatile("" : "+l"(og), "+r"(mU), "+r"(od), "+r"(ha), "+f"(bias0), "+f"(bias1));
            mbar_wait(bars + 8 * B_XT, 0, budget);
            mbar_wait(bars + 8 * (B_WEMPTY + 1), 0, budget);
            TSC(elect, 12 + 2 * w);
            wg_wait<0>();
            if (elect) { mbar_arrive(bars + 8 * B_G1DONE); mbar_arrive_at(g1peer); }
            TSC(elect, 2 + 8 * w);
            float ci[4];
#pragma unroll
            for (int n = 0; n < 4; n++) ci[n] = __uint_as_float((0x03800000u + n) | (budget >> 30));
            auto hand_over = [&](int v) {
                asm volatile("{\n.reg .pred p;\nsetp.ne.b32 p, %17, 0;\n"
                             "@p stmatrix.sync.aligned.m8n8.x4.shared.b16 [%16], {%0,%1,%2,%3};\n@p stmatrix.sync.aligned.m8n8.x4.shared.b16 [%16 + 2048], {%4,%5,%6,%7};\n"
                             "@p stmatrix.sync.aligned.m8n8.x4.shared.b16 [%16 + 4096], {%8,%9,%10,%11};\n@p stmatrix.sync.aligned.m8n8.x4.shared.b16 [%16 + 6144], {%12,%13,%14,%15};\n"
                             "fence.proxy.async.shared::cta;\n}"
                             ::"r"(o[0]), "r"(o[1]), "r"(o[2]), "r"(o[3]), "r"(o[4]), "r"(o[5]), "r"(o[6]), "r"(o[7]), "r"(o[8]), "r"(o[9]), "r"(o[10]), "r"(o[11]),
                               "r"(o[12]), "r"(o[13]), "r"(o[14]), "r"(o[15]), "r"(od + v * OFF_X1), "r"((int)(w == rh)) : "memory");
                TSC(tid == 0, v ? 27 : 5);
#pragma unroll
                for (int i = 0; i < 16; i++) asm volatile("st.global.u32 [%0], %1;" ::"l"(og + (1 - v) * 16 * BOX + (i >> 1) * 1024 + (i & 1) * 128), "r"(o[i]) : "memory");
                __syncwarp();
                if (lane == 0) mbar_arrive(bars + 8 * (B_STAGED + v));
            };
#pragma unroll
            for (int j = 32; j < 48; j++) pk1[j] = movm(pk1[j]);
#pragma unroll
            for (int j = EARLY_PK; j < 48; j++) if (j >= 32 || (j & 1) || EARLY_PK < 17) pk0[j] = pack_here(acc0[2 * j], acc0[2 * j + 1]);
#pragma unroll
            for (int j = 32; j < 48; j++) pk0[j] = movm(pk0[j]);
            attn_pair<2>(pk1, pk1 + 16, pk1 + 32, pk0 + 17, pk0 + 33, fu[1], fn[1], rk[1], 0.f, 0.f, mU, zero, ci, o);
            hand_over(0);
            TSC(elect, 3 + 8 * w);
#pragma unroll
            for (int j = 0; j < 32; j++) if (j < EARLY_PK || (!(j & 1) && EARLY_PK == 17)) pk0[j] = pack_here(acc0[2 * j], acc0[2 * j + 1]);
            factors(0);
            bar_sync(warp ? warp : 11, 64);
            uint32_t hl[16];
            ldsm4(hl, ha); ldsm4(hl + 4, ha + 512); ldsm4t(hl + 8, ha + 1024); ldsm4t(hl + 12, ha + 1536);
            __syncwarp();
            if (lane == 0) mbar_arrive(bars + 8 * B_FREED);
            attn_pair<1>(pk0, pk0 + 16, pk0 + 32, hl, hl + 8, fu[0], fn[0], rk[0], bias0, bias1, mU, zero, ci, o);
            const float2 s0 = lds2f(sb + OFF_STAT + (8 + r0) * 8), s1 = lds2f(sb + OFF_STAT + (16 + r0) * 8);
            const float m0 = s0.x * s0.y, f0 = 1.f + s0.y, m1 = s1.x * s1.y, f1 = 1.f + s1.y;
            uint32_t xt[32];
#pragma unroll
            for (int j = 0; j < 8; j++) ldsm4(xt + 4 * j, ((ring + wi * 2048 + mad) ^ ((j & 3) * 32)) + (j >> 2) * BOX);
            hand_over(1);
#pragma unroll
            for (int j = 0; j < 32; j++) {
                acc[2 * j] = fmaf(bf_lo(xt[j]), j & 1 ? f1 : f0, j & 1 ? m1 : m0); acc[2 * j + 1] = fmaf(bf_hi(xt[j]), j & 1 ? f1 : f0, j & 1 ? m1 : m0);
            }
        }
        TSC(tid == 0, 4);
        {
            const uint32_t da0 = sd + dlo(w * OFF_X1, 1024), db0 = sd + dlo(OFF_WO, BOX);
            const uint32_t chk = ring + wi * 256 + (lane >> 3) * 1032 + (lane & 7) * 32 + (lane & 4);
            uint32_t s8 = 16, ps8 = 0, ph = 0;
            mbar_wait(ofull + s8, 0, budget);
            mbar_wait(bars + 8 * B_WOFULL + s8, 0, budget);
            TSC(TIMING % 10 == 2 && elect, 32 + w * 16);
            const uint32_t ahi = dhi(128, 0) | (budget >> 30), bhi = dhi(1024, 1) | (budget >> 30);
            const int last = w ? HOLD : 16;
            uint32_t rel = elect ? 0x7fe : 0;
#pragma unroll 1
            for (int i = 1;;) {
                const uint32_t da = da0 + s8 * (BOX >> 7), db = db0 + s8 * (BOX >> 6);
                wg_fence();
#pragma unroll
                for (int kk = 0; kk < 4; kk++) {
                    wgmma_n128<0, 1>(acc, mkdesc(da + kk * 128, ahi), mkdesc(db + kk * 128, bhi), 1);
                    if (kk & 1) wg_commit();
                }
                wg_wait<2>();
                if (rel & 1) { mbar_expect_tx(ofull + ps8, BOX); mbar_arrive_at(oempty + ps8); mbar_arrive(bars + 8 * B_WOEMPTY + ps8); }
                if (i == 16) break;
                rel >>= 1;
                ps8 = s8;
#pragma unroll 1
                do {
                    s8 = s8 == 40 ? 0 : s8 + 8;
                    if (s8 == 16) ph ^= 1;
                    uint32_t bad;
                    asm volatile("{\n.reg .pred p, q, r;\n.reg .u32 u, v;\nmbarrier.try_wait.parity.shared::cta.b64 q, [%2], %3;\nmbarrier.try_wait.parity.shared::cta.b64 p, [%1], %3;\n"
                                 "setp.ne.and.u32 r, %5, 1, p;\nmov.u32 u, 1;\nmov.u32 v, 1;\n@r ld.shared.u32 u, [%4];\n@r ld.shared.u32 v, [%4 + 4096];\n"
                                 "and.pred p, p, q;\nmin.u32 u, u, v;\nsetp.eq.or.u32 p, u, 0, !p;\nvote.sync.any.pred p, p, 0xffffffff;\nselp.u32 %0, 1, 0, p;\n}"
                                 : "=r"(bad) : "r"(ofull + s8), "r"(bars + 8 * B_WOFULL + s8), "r"(ph), "r"(chk + s8 * (BOX / 8)), "r"(i) : "memory");
                    if (__builtin_expect(bad, 0)) {
                        mbar_wait(ofull + s8, ph, budget);
                        mbar_wait(bars + 8 * B_WOFULL + s8, ph, budget);
                        if (__any_sync(0xffffffffu, min(lds1(chk + s8 * (BOX / 8)), lds1(chk + s8 * (BOX / 8) + 4096)) == 0)) {
                            const uint32_t at = wi * 256 + (lane >> 4) * 1024 + (lane & 15) * 16;
                            const uint8_t* src = scr->o + ((size_t)((mt * 2 + rh) * 2 + 1 - w) * 16 + ((2 * p + (i < 2 ? i ^ hp : i)) & 15)) * BOX + at;
#pragma unroll 1
                            for (int n = 0; n < 8192; n += 2048) {
                                uint4 v; int tries = 4096;
#pragma unroll 1
                                do { v = ld_rlx4(src + n); } while (v.x == 0 && --tries > 0);
                                sts4(ring + s8 * (BOX / 8) + at + n, v.x, v.y, v.z, v.w);
                            }
                            NRETRY();
                            fence_async_smem();
                            __syncwarp();
                        }
                    }
                    TSC(TIMING % 10 == 1 && tid == 0, 48 + i);
                    TSC(TIMING % 10 == 2 && elect, 32 + w * 16 + i);
                } while (++i > last && i < 16);
                if (i > last) break;
                wg_wait<1>();
            }
            if (w) {
                bar_sync(9, 256);
#pragma unroll 1
                for (int i = HOLD - 10; i < 6; i++) {
                    wg_fence();
#pragma unroll
                    for (int kk = 0; kk < 4; kk++) wgmma_n128<0, 1>(acc, mkdesc(da0 + i * 512 + kk * 128, ahi), mkdesc(db0 + i * 1024 + kk * 128, bhi), 1);
                    wg_commit();
                }
            } else bar_arrive(9, 256);
            const bool add = (__shfl_sync(0xffffffffu, lds1(sb + OFF_SEL), 0) >> (wi * 2 + 1 - w)) & 1;
            wg_wait<0>();
            TSC(elect, 7 + 9 * w);
            const uint32_t os0 = ring + wi * 4096;
#pragma unroll
            for (int hf = 0; hf < OUT_PARTS; hf++) {
#pragma unroll
                for (int j = hf * (8 / OUT_PARTS); j < (hf + 1) * (8 / OUT_PARTS); j++)
                    stsm4(((os0 + mad) ^ ((j & 3) * 32)) + (j >> 2) * 2048, pack_here(acc[8 * j], acc[8 * j + 1]), pack_here(acc[8 * j + 2], acc[8 * j + 3]),
                          pack_here(acc[8 * j + 4], acc[8 * j + 5]), pack_here(acc[8 * j + 6], acc[8 * j + 7]));
                fence_async_smem();
                __syncwarp();
                if (elect_one())
                    asm volatile("{\n.reg .pred p;\nsetp.ne.b32 p, %6, 0;\n@!p cp.async.bulk.tensor.5d.global.shared::cta.bulk_group [%0, {%2, %2, %3, %4, %5}], [%1];\n"
                                 "@p cp.reduce.async.bulk.tensor.5d.global.shared::cta.add.bulk_group [%0, {%2, %2, %3, %4, %5}], [%1];\n}"
                                 ::"l"(&mout), "r"(os0 + hf * 2048), "r"(0), "r"(((j0 + rh * 128) >> 5) + wi), "r"(1 - w), "r"(par * 16 + cb * 2 + hf), "r"((int)add) : "memory");
            }
            asm volatile("cp.async.bulk.commit_group;\ncp.async.bulk.wait_group.read 0;" ::: "memory");
            if (b == 0 && tid == 0) st_rlx(&scr->epoch[0], lds1(sb + OFF_EP));
            TSC(elect, 8 - 2 * w);
            TS_END();
        }
    }
}

typedef CUresult (*EncodeFn)(CUtensorMap*, CUtensorMapDataType, cuuint32_t, void*, const cuuint64_t*, const cuuint64_t*, const cuuint32_t*,
                             const cuuint32_t*, CUtensorMapInterleave, CUtensorMapSwizzle, CUtensorMapL2promotion, CUtensorMapFloatOOBfill);

CUtensorMap make_map(EncodeFn fn, const void* base, int rank, const cuuint64_t* dims, const cuuint64_t* strides, const cuuint32_t* box,
                     CUtensorMapSwizzle swz = CU_TENSOR_MAP_SWIZZLE_128B, CUtensorMapL2promotion pro = CU_TENSOR_MAP_L2_PROMOTION_L2_256B) {
    CUtensorMap m;
    cuuint32_t es[5] = {1, 1, 1, 1, 1};
    fn(&m, CU_TENSOR_MAP_DATA_TYPE_BFLOAT16, rank, (void*)base, dims, strides, box, es, CU_TENSOR_MAP_INTERLEAVE_NONE,
       swz, pro, CU_TENSOR_MAP_FLOAT_OOB_FILL_NONE);
    return m;
}

}

extern "C" void kernel_launch(void* const* d_in, const int* in_sizes, int n_in, void* d_out, int out_size) {
    (void)in_sizes; (void)n_in; (void)out_size;
    const __nv_bfloat16* x = (const __nv_bfloat16*)d_in[0];
    const __nv_bfloat16* wqkv = (const __nv_bfloat16*)d_in[1];
    const __nv_bfloat16* wo = (const __nv_bfloat16*)d_in[2];
    const __nv_bfloat16* wr = (const __nv_bfloat16*)d_in[4];
    const __nv_bfloat16* wg = (const __nv_bfloat16*)d_in[5];
    const __nv_bfloat16* wu = (const __nv_bfloat16*)d_in[6];
    const __nv_bfloat16* wd = (const __nv_bfloat16*)d_in[7];
    static EncodeFn fn = nullptr;
    static Scratch* scr = nullptr;
    if (!fn) {
        void* p = nullptr; cudaDriverEntryPointQueryResult q;
        cudaGetDriverEntryPoint("cuTensorMapEncodeTiled", &p, cudaEnableDefault, &q);
        fn = (EncodeFn)p;
        cudaFuncSetAttribute(fused_kernel, cudaFuncAttributeMaxDynamicSharedMemorySize, SMEM_LAUNCH);
        cudaGetSymbolAddress((void**)&scr, g_scr);
    }
    const cuuint64_t xd[4] = {2048, 16, 32, 2}, xs[4] = {4096, 131072, 65536, 128}, od[5] = {64, 16, 32, 2, 32};
    const cuuint32_t xb[4] = {64, 16, 4, 1}, ob[5] = {64, 16, 1, 1, 2 / OUT_PARTS};
    const cuuint64_t wdm[3] = {1024, 1024, 3}, wst[2] = {6144, 2048};
    const cuuint32_t wb[3] = {64, 64, 3};
    const cuuint64_t wod[3] = {64, 1024, 16}, wdd[3] = {64, 3584, 16}, wos[2] = {2048, 128};
    const cuuint32_t wob[3] = {64, 64, 2}, wdb[3] = {64, 64, 1};
    CUtensorMap mx = make_map(fn, x, 4, xd, xs, xb), mw = make_map(fn, wqkv, 3, wdm, wst, wb);
    CUtensorMap mwo = make_map(fn, wo, 3, wod, wos, wob), mout = make_map(fn, d_out, 5, od, xs, ob);
    const int swap_gu = wu < wg;
    const cuuint64_t gd[3] = {3584, 1024, 2}, gst[2] = {7168, (cuuint64_t)(swap_gu ? (const char*)wg - (const char*)wu : (const char*)wu - (const char*)wg)};
    const cuuint32_t gb[3] = {32, 64, 2};
    CUtensorMap mgu = make_map(fn, swap_gu ? wu : wg, 3, gd, gst, gb, CU_TENSOR_MAP_SWIZZLE_64B, CU_TENSOR_MAP_L2_PROMOTION_L2_128B);
    CUtensorMap mwd = make_map(fn, wd, 3, wdd, wos, wdb, CU_TENSOR_MAP_SWIZZLE_128B, CU_TENSOR_MAP_L2_PROMOTION_L2_128B);
    const cuuint64_t md[2] = {64, 32768}, ms[1] = {128};
    const cuuint32_t mb[2] = {64, 64};
    CUtensorMap mo = make_map(fn, scr, 2, md, ms, mb, CU_TENSOR_MAP_SWIZZLE_NONE, CU_TENSOR_MAP_L2_PROMOTION_NONE);
    cudaLaunchConfig_t cfg = {};
    cfg.gridDim = dim3(132); cfg.blockDim = dim3(512); cfg.dynamicSmemBytes = SMEM_LAUNCH; cfg.stream = cudaStreamPerThread;
    cudaLaunchAttribute at[1];
    at[0].id = cudaLaunchAttributeClusterDimension; at[0].val.clusterDim.x = 2; at[0].val.clusterDim.y = 1; at[0].val.clusterDim.z = 1;
    cfg.attrs = at; cfg.numAttrs = 1;
    cudaLaunchKernelEx(&cfg, fused_kernel, mx, mw, mwo, mout, mgu, mwd, mo, x, wr, scr, swap_gu, Weights{(const char*)wqkv, (const char*)wo, (const char*)wg, (const char*)wu, (const char*)wd, (char*)d_out});
}
```

```cpp
#include <cuda_runtime.h>
#include <cuda.h>
#include <cuda_bf16.h>
#include <stdint.h>

namespace {

constexpr int BOX = 8192, W_BYTES = 3 * BOX;
constexpr int OFF_X1 = 6 * BOX, OFF_FR = 12 * BOX, OFF_E = 16 * BOX, OFF_W = 19 * BOX;
constexpr int OFF_WO = OFF_E;
constexpr int OFF_HIN = OFF_FR + 2048, OFF_GU = OFF_HIN + 2048, OFF_FS = OFF_GU + 1024;
constexpr int F_BYTES = 9216;
constexpr int CS_BYTES = 3136;
constexpr int OFF_CS = OFF_FS + 5 * F_BYTES;
constexpr int OFF_STAT = 28 * BOX;
constexpr int OFF_SEL = OFF_STAT + 2112, OFF_EP = OFF_SEL + 4;
constexpr int OFF_BAR = OFF_SEL + 16;
constexpr int B_WFULL = 0, B_XFULL = 3, B_AUX = 15, B_XT = 16, B_ZERO = 17, B_WOFULL = 18, B_OFULL = 24, B_FFULL = 36, B_ROW = 41;
constexpr int B_WEMPTY = 48, B_F1DONE = 51, B_XEMPTY = 52, B_WOEMPTY = 58, B_OEMPTY = 64;
constexpr int B_G1DONE = 72, B_FEMPTY = 73, B_STAGED = 78, B_RDONE = 80, B_FREED = 81, NBAR = 84;
constexpr int SMEM_BYTES = OFF_BAR + NBAR * 8;
static_assert(OFF_FS + 3 * F_BYTES == OFF_E && OFF_CS + CS_BYTES <= OFF_W && SMEM_BYTES + 256 <= 232448 && OFF_BAR % 8 == 0, "smem");
#define POLL_NS 30
#define PF_RATE 10
#define PF_START 7
#define ZF_NS 100
#define FFN2_GATE (B_STAGED + 1)
#define PF_NW 6
#define EARLY_PK 17
#define ZF_GATE (B_ROW + 3)
#define HOLD 12
#define F1_DEPTH 1
#define F2_DEPTH 0
#define OUT_PARTS 2
#define Y_NS 200
#define PF_D 8
#define F_PACE 0
#define X_NW 4
#define ROWS_AT 0x280
constexpr int BUDGET = 1 << 18;

struct Scratch {
    uint8_t o[2048 * 1024 * 2];
    uint32_t ypart[8][8][1024];
    uint32_t halo[128][512];
    uint32_t act[2][14336 + 4096];
    uint2 row[2048];
    uint4 cs[16][3][24];
    uint32_t oflag[16][32];
    uint32_t cnt[9][32];
    uint32_t sel[32], epoch[32];
};
__device__ __align__(1024) Scratch g_scr;
struct Weights { const char *wqkv, *wo, *wg, *wu, *wd; char* out; };

#define TS(i) do {} while (0)
#define TS_END() do {} while (0)
#define TSC(c, i) do {} while (0)
#define NRETRY() do {} while (0)
constexpr int SMEM_LAUNCH = SMEM_BYTES;
__device__ __forceinline__ uint32_t smem_u32(const void* p) { return (uint32_t)__cvta_generic_to_shared(p); }
__device__ __forceinline__ void mbar_init(uint32_t bar, uint32_t cnt) { asm volatile("mbarrier.init.shared::cta.b64 [%0], %1;" ::"r"(bar), "r"(cnt) : "memory"); }
__device__ __forceinline__ void mbar_expect_tx(uint32_t bar, uint32_t bytes) { asm volatile("mbarrier.arrive.expect_tx.shared::cta.b64 _, [%0], %1;" ::"r"(bar), "r"(bytes) : "memory"); }
__device__ __forceinline__ void mbar_arrive(uint32_t bar) { asm volatile("mbarrier.arrive.shared::cta.b64 _, [%0];" ::"r"(bar) : "memory"); }
__device__ __forceinline__ uint32_t mapa(uint32_t a, uint32_t cta) { uint32_t r; asm("mapa.shared::cluster.u32 %0, %1, %2;" : "=r"(r) : "r"(a), "r"(cta)); return r; }
__device__ __forceinline__ void mbar_arrive_at(uint32_t cbar) { asm volatile("mbarrier.arrive.shared::cluster.b64 _, [%0];" ::"r"(cbar) : "memory"); }
__device__ __forceinline__ void mbar_wait(uint32_t bar, uint32_t parity, int& budget) {
    asm volatile("{\n.reg .pred p;\nLAB_WAIT:\nmbarrier.try_wait.parity.shared::cta.b64 p, [%1], %2;\n"
                 "add.s32 %0, %0, -1;\nsetp.gt.and.s32 p, %0, 0, !p;\n@p bra LAB_WAIT;\n}" : "+r"(budget) : "r"(bar), "r"(parity) : "memory");
}
__device__ __forceinline__ void mbar_wait_hot(uint32_t bar, uint32_t parity, int& budget) {
    asm volatile("{\n.reg .pred p;\nmbarrier.try_wait.parity.shared::cta.b64 p, [%1], %2;\n@p bra LAB_DONE;\nLAB_WAIT:\nmbarrier.try_wait.parity.shared::cta.b64 p, [%1], %2;\n"
                 "add.s32 %0, %0, -1;\nsetp.gt.and.s32 p, %0, 0, !p;\n@p bra LAB_WAIT;\nLAB_DONE:\n}" : "+r"(budget) : "r"(bar), "r"(parity) : "memory");
}
__device__ __forceinline__ void tma_2d(uint32_t dst, const CUtensorMap* m, uint32_t bar, int c0, int c1) {
    asm volatile("cp.async.bulk.tensor.2d.shared::cluster.global.mbarrier::complete_tx::bytes [%0], [%1, {%3, %4}], [%2];" ::"r"(dst), "l"(m), "r"(bar), "r"(c0), "r"(c1) : "memory");
}
__device__ __forceinline__ void tma_2d_mc(uint32_t dst, const CUtensorMap* m, uint32_t bar, int c0, int c1) {
    asm volatile("cp.async.bulk.tensor.2d.shared::cluster.global.mbarrier::complete_tx::bytes.multicast::cluster [%0], [%1, {%3, %4}], [%2], %5;" ::"r"(dst), "l"(m), "r"(bar), "r"(c0), "r"(c1), "h"((uint16_t)3) : "memory");
}
__device__ __forceinline__ void tma_3d(uint32_t dst, const CUtensorMap* m, uint32_t bar, int c0, int c1, int c2) {
    asm volatile("cp.async.bulk.tensor.3d.shared::cluster.global.mbarrier::complete_tx::bytes [%0], [%1, {%3, %4, %5}], [%2];" ::"r"(dst), "l"(m), "r"(bar), "r"(c0), "r"(c1), "r"(c2) : "memory");
}
__device__ __forceinline__ void tma_4d(uint32_t dst, const CUtensorMap* m, uint32_t bar, int c0, int c1, int c2, int c3) {
    asm volatile("cp.async.bulk.tensor.4d.shared::cluster.global.mbarrier::complete_tx::bytes [%0], [%1, {%3, %4, %5, %6}], [%2];" ::"r"(dst), "l"(m), "r"(bar), "r"(c0), "r"(c1), "r"(c2), "r"(c3) : "memory");
}
__device__ __forceinline__ void tma_4d_mc(uint32_t dst, const CUtensorMap* m, uint32_t bar, int c0, int c1, int c2, int c3) {
    asm volatile("cp.async.bulk.tensor.4d.shared::cluster.global.mbarrier::complete_tx::bytes.multicast::cluster [%0], [%1, {%3, %4, %5, %6}], [%2], %7;" ::"r"(dst), "l"(m), "r"(bar), "r"(c0), "r"(c1), "r"(c2), "r"(c3), "h"((uint16_t)3) : "memory");
}
__device__ __forceinline__ void bulk_pf(const void* p, uint32_t bytes) { asm volatile("cp.async.bulk.prefetch.L2.global [%0], %1;" ::"l"(p), "r"(bytes) : "memory"); }
__device__ __forceinline__ void bulk_g2s(uint32_t dst, const void* src, uint32_t bytes, uint32_t bar) {
    asm volatile("cp.async.bulk.shared::cluster.global.mbarrier::complete_tx::bytes [%0], [%1], %2, [%3];" ::"r"(dst), "l"(src), "r"(bytes), "r"(bar) : "memory");
}
__device__ __forceinline__ void bulk_s2c(uint32_t cdst, uint32_t src, uint32_t bytes, uint32_t cbar) {
    asm volatile("cp.async.bulk.shared::cluster.shared::cta.mbarrier::complete_tx::bytes [%0], [%1], %2, [%3];" ::"r"(cdst), "r"(src), "r"(bytes), "r"(cbar) : "memory");
}
__device__ __forceinline__ void cluster_wait() { asm volatile("barrier.cluster.wait.aligned;" ::: "memory"); }
__device__ __forceinline__ void fence_gpu() { asm volatile("fence.acq_rel.gpu;" ::: "memory"); }
__device__ __forceinline__ void fence_async_smem() { asm volatile("fence.proxy.async.shared::cta;" ::: "memory"); }
__device__ __forceinline__ void wg_fence() { asm volatile("wgmma.fence.sync.aligned;" ::: "memory"); }
__device__ __forceinline__ void wg_commit() { asm volatile("wgmma.commit_group.sync.aligned;" ::: "memory"); }
template <int N> __device__ __forceinline__ void wg_wait() { asm volatile("wgmma.wait_group.sync.aligned %0;" ::"n"(N) : "memory"); }
__device__ __forceinline__ uint64_t mkdesc(uint32_t lo, uint32_t hi) { return ((uint64_t)hi << 32) | lo; }
__host__ __device__ constexpr uint32_t dhi(uint32_t sbo, uint32_t mode) { return (sbo >> 4) | (mode << 30); }
__host__ __device__ constexpr uint32_t dlo(uint32_t off, uint32_t lbo) { return (off >> 4) + ((lbo >> 4) << 16); }
__device__ __forceinline__ bool elect_one() {
    uint32_t e;
    asm volatile("{\n.reg .pred p;\nelect.sync _|p, 0xffffffff;\nselp.u32 %0, 1, 0, p;\n}" : "=r"(e));
    return e;
}
template <int R> __device__ __forceinline__ void reg_inc() { asm volatile("setmaxnreg.inc.sync.aligned.u32 %0;" ::"n"(R)); }
template <int R> __device__ __forceinline__ void reg_dec() { asm volatile("setmaxnreg.dec.sync.aligned.u32 %0;" ::"n"(R)); }
__device__ __forceinline__ void bar_sync(int id, int n) { asm volatile("bar.sync %0, %1;" ::"r"(id), "r"(n) : "memory"); }
__device__ __forceinline__ void bar_arrive(int id, int n) { asm volatile("bar.arrive %0, %1;" ::"r"(id), "r"(n) : "memory"); }
__device__ __forceinline__ uint32_t pack_bf16(float lo, float hi) { uint32_t r; asm("cvt.rn.bf16x2.f32 %0, %1, %2;" : "=r"(r) : "f"(hi), "f"(lo)); return r; }
__device__ __forceinline__ uint32_t pack_here(float lo, float hi) { uint32_t r; asm volatile("cvt.rn.bf16x2.f32 %0, %1, %2;" : "=r"(r) : "f"(hi), "f"(lo)); return r; }
__device__ __forceinline__ float bf_lo(uint32_t u) { return __uint_as_float(u << 16); }
__device__ __forceinline__ float bf_hi(uint32_t u) { return __uint_as_float(u & 0xffff0000u); }
__device__ __forceinline__ float bf16r(float v) { return bf_lo(pack_bf16(v, 0.f)); }
__device__ __forceinline__ float rcp(float x) { float r; asm("rcp.approx.ftz.f32 %0, %1;" : "=f"(r) : "f"(x)); return r; }
__device__ __forceinline__ float ex2(float x) { float r; asm("ex2.approx.ftz.f32 %0, %1;" : "=f"(r) : "f"(x)); return r; }
__device__ __forceinline__ float sigmoidf(float v) { return rcp(1.f + ex2(v * -1.4426950408889634f)); }
__device__ __forceinline__ uint32_t movm(uint32_t a) { uint32_t d; asm volatile("movmatrix.sync.aligned.m8n8.trans.b16 %0, %1;" : "=r"(d) : "r"(a)); return d; }
__device__ __forceinline__ void mma16816(float (&c)[4], uint32_t a0, uint32_t a1, uint32_t a2, uint32_t a3, uint32_t b0, uint32_t b1) {
    asm volatile("mma.sync.aligned.m16n8k16.row.col.f32.bf16.bf16.f32 {%0,%1,%2,%3}, {%4,%5,%6,%7}, {%8,%9}, {%0,%1,%2,%3};"
                 : "+f"(c[0]), "+f"(c[1]), "+f"(c[2]), "+f"(c[3]) : "r"(a0), "r"(a1), "r"(a2), "r"(a3), "r"(b0), "r"(b1));
}
__device__ __forceinline__ void mma1688(float (&c)[4], uint32_t a0, uint32_t a1, uint32_t b0) {
    asm volatile("mma.sync.aligned.m16n8k8.row.col.f32.bf16.bf16.f32 {%0,%1,%2,%3}, {%4,%5}, {%6}, {%0,%1,%2,%3};"
                 : "+f"(c[0]), "+f"(c[1]), "+f"(c[2]), "+f"(c[3]) : "r"(a0), "r"(a1), "r"(b0));
}
__device__ __forceinline__ void stsm4(uint32_t a, uint32_t r0, uint32_t r1, uint32_t r2, uint32_t r3) {
    asm volatile("stmatrix.sync.aligned.m8n8.x4.shared.b16 [%0], {%1,%2,%3,%4};" ::"r"(a), "r"(r0), "r"(r1), "r"(r2), "r"(r3) : "memory");
}
__device__ __forceinline__ void ldsm4(uint32_t* r, uint32_t a) {
    asm volatile("ldmatrix.sync.aligned.m8n8.x4.shared.b16 {%0,%1,%2,%3}, [%4];" : "=r"(r[0]), "=r"(r[1]), "=r"(r[2]), "=r"(r[3]) : "r"(a) : "memory");
}
__device__ __forceinline__ void ldsm4t(uint32_t* r, uint32_t a) {
    asm volatile("ldmatrix.sync.aligned.m8n8.x4.trans.shared.b16 {%0,%1,%2,%3}, [%4];" : "=r"(r[0]), "=r"(r[1]), "=r"(r[2]), "=r"(r[3]) : "r"(a) : "memory");
}
__device__ __forceinline__ uint32_t ld_rlx(const void* p) { uint32_t v; asm volatile("ld.relaxed.gpu.global.u32 %0, [%1];" : "=r"(v) : "l"(p) : "memory"); return v; }
__device__ __forceinline__ uint32_t ld_acq(const void* p) { uint32_t v; asm volatile("ld.acquire.gpu.global.u32 %0, [%1];" : "=r"(v) : "l"(p) : "memory"); return v; }
__device__ __forceinline__ uint2 ld_rlx2(const void* p) { uint2 v; asm volatile("ld.relaxed.gpu.global.v2.u32 {%0,%1}, [%2];" : "=r"(v.x), "=r"(v.y) : "l"(p) : "memory"); return v; }
__device__ __forceinline__ uint4 ld_rlx4(const void* p) { uint4 v; asm volatile("ld.relaxed.gpu.global.v4.u32 {%0,%1,%2,%3}, [%4];" : "=r"(v.x), "=r"(v.y), "=r"(v.z), "=r"(v.w) : "l"(p) : "memory"); return v; }
__device__ __forceinline__ void st_rlx(void* p, uint32_t v) { asm volatile("st.relaxed.gpu.global.u32 [%0], %1;" ::"l"(p), "r"(v) : "memory"); }
__device__ __forceinline__ void st_rlx2(void* p, uint32_t a, uint32_t b) { asm volatile("st.relaxed.gpu.global.v2.u32 [%0], {%1,%2};" ::"l"(p), "r"(a), "r"(b) : "memory"); }
__device__ __forceinline__ void st_rlx4(void* p, uint32_t a, uint32_t b, uint32_t c, uint32_t d) { asm volatile("st.relaxed.gpu.global.v4.u32 [%0], {%1,%2,%3,%4};" ::"l"(p), "r"(a), "r"(b), "r"(c), "r"(d) : "memory"); }
__device__ __forceinline__ void red_add(uint32_t* p) { asm volatile("red.relaxed.gpu.global.add.u32 [%0], 1;" ::"l"(p) : "memory"); }
__device__ __forceinline__ uint4 ldg_nc(const void* p) { uint4 v; asm volatile("ld.global.nc.v4.u32 {%0,%1,%2,%3}, [%4];" : "=r"(v.x), "=r"(v.y), "=r"(v.z), "=r"(v.w) : "l"(p)); return v; }
__device__ __forceinline__ void sts4(uint32_t a, uint32_t x, uint32_t y, uint32_t z, uint32_t w) { asm volatile("st.shared.v4.u32 [%0], {%1,%2,%3,%4};" ::"r"(a), "r"(x), "r"(y), "r"(z), "r"(w) : "memory"); }
__device__ __forceinline__ void sts2(uint32_t a, uint32_t x, uint32_t y) { asm volatile("st.shared.v2.u32 [%0], {%1,%2};" ::"r"(a), "r"(x), "r"(y) : "memory"); }
__device__ __forceinline__ void sts1(uint32_t a, uint32_t v) { asm volatile("st.shared.u32 [%0], %1;" ::"r"(a), "r"(v) : "memory"); }
__device__ __forceinline__ uint4 lds4(uint32_t a) { uint4 v; asm volatile("ld.shared.v4.u32 {%0,%1,%2,%3}, [%4];" : "=r"(v.x), "=r"(v.y), "=r"(v.z), "=r"(v.w) : "r"(a) : "memory"); return v; }
__device__ __forceinline__ float4 lds4f(uint32_t a) { float4 v; asm volatile("ld.shared.v4.f32 {%0,%1,%2,%3}, [%4];" : "=f"(v.x), "=f"(v.y), "=f"(v.z), "=f"(v.w) : "r"(a) : "memory"); return v; }
__device__ __forceinline__ float2 lds2f(uint32_t a) { float2 v; asm volatile("ld.shared.v2.f32 {%0,%1}, [%2];" : "=f"(v.x), "=f"(v.y) : "r"(a) : "memory"); return v; }
__device__ __forceinline__ float lds1f(uint32_t a) { float v; asm volatile("ld.shared.f32 %0, [%1];" : "=f"(v) : "r"(a) : "memory"); return v; }
__device__ __forceinline__ uint32_t lds1(uint32_t a) { uint32_t v; asm volatile("ld.shared.u32 %0, [%1];" : "=r"(v) : "r"(a) : "memory"); return v; }
__device__ __forceinline__ uint32_t redux_max(uint32_t v) { uint32_t r; asm volatile("redux.sync.max.u32 %0, %1, 0xffffffff;" : "=r"(r) : "r"(v)); return r; }
__device__ __forceinline__ uint32_t poll_all(const uint32_t* p, uint32_t mask, uint32_t want, int& budget) {
    uint32_t v;
#pragma unroll 1
    while (v = ld_acq(p), !__all_sync(0xffffffffu, (v & mask) == want) && --budget > 0) __nanosleep(POLL_NS);
    return v;
}

template <int TA, int TB>
__device__ __forceinline__ void wgmma_n192(float (&d)[96], uint64_t da, uint64_t db, int keep) {
    asm volatile("{\n.reg .pred p;\nsetp.ne.b32 p, %98, 0;\n"
        "wgmma.mma_async.sync.aligned.m64n192k16.f32.bf16.bf16 "
        "{%0, %1, %2, %3, %4, %5, %6, %7, %8, %9, %10, %11, %12, %13, %14, %15, "
        "%16, %17, %18, %19, %20, %21, %22, %23, %24, %25, %26, %27, %28, %29, %30, %31, "
        "%32, %33, %34, %35, %36, %37, %38, %39, %40, %41, %42, %43, %44, %45, %46, %47, "
        "%48, %49, %50, %51, %52, %53, %54, %55, %56, %57, %58, %59, %60, %61, %62, %63, "
        "%64, %65, %66, %67, %68, %69, %70, %71, %72, %73, %74, %75, %76, %77, %78, %79, "
        "%80, %81, %82, %83, %84, %85, %86, %87, %88, %89, %90, %91, %92, %93, %94, %95}, "
        "%96, %97, p, 1, 1, %99, %100;\n}\n"
        : "+f"(d[0]), "+f"(d[1]), "+f"(d[2]), "+f"(d[3]), "+f"(d[4]), "+f"(d[5]), "+f"(d[6]), "+f"(d[7]),
          "+f"(d[8]), "+f"(d[9]), "+f"(d[10]), "+f"(d[11]), "+f"(d[12]), "+f"(d[13]), "+f"(d[14]), "+f"(d[15]),
          "+f"(d[16]), "+f"(d[17]), "+f"(d[18]), "+f"(d[19]), "+f"(d[20]), "+f"(d[21]), "+f"(d[22]), "+f"(d[23]),
          "+f"(d[24]), "+f"(d[25]), "+f"(d[26]), "+f"(d[27]), "+f"(d[28]), "+f"(d[29]), "+f"(d[30]), "+f"(d[31]),
          "+f"(d[32]), "+f"(d[33]), "+f"(d[34]), "+f"(d[35]), "+f"(d[36]), "+f"(d[37]), "+f"(d[38]), "+f"(d[39]),
          "+f"(d[40]), "+f"(d[41]), "+f"(d[42]), "+f"(d[43]), "+f"(d[44]), "+f"(d[45]), "+f"(d[46]), "+f"(d[47]),
          "+f"(d[48]), "+f"(d[49]), "+f"(d[50]), "+f"(d[51]), "+f"(d[52]), "+f"(d[53]), "+f"(d[54]), "+f"(d[55]),
          "+f"(d[56]), "+f"(d[57]), "+f"(d[58]), "+f"(d[59]), "+f"(d[60]), "+f"(d[61]), "+f"(d[62]), "+f"(d[63]),
          "+f"(d[64]), "+f"(d[65]), "+f"(d[66]), "+f"(d[67]), "+f"(d[68]), "+f"(d[69]), "+f"(d[70]), "+f"(d[71]),
          "+f"(d[72]), "+f"(d[73]), "+f"(d[74]), "+f"(d[75]), "+f"(d[76]), "+f"(d[77]), "+f"(d[78]), "+f"(d[79]),
          "+f"(d[80]), "+f"(d[81]), "+f"(d[82]), "+f"(d[83]), "+f"(d[84]), "+f"(d[85]), "+f"(d[86]), "+f"(d[87]),
          "+f"(d[88]), "+f"(d[89]), "+f"(d[90]), "+f"(d[91]), "+f"(d[92]), "+f"(d[93]), "+f"(d[94]), "+f"(d[95])
        : "l"(da), "l"(db), "r"(keep), "n"(TA), "n"(TB));
}
template <int TA, int TB>
__device__ __forceinline__ void wgmma_n128(float (&d)[64], uint64_t da, uint64_t db, int keep) {
    asm volatile("{\n.reg .pred p;\nsetp.ne.b32 p, %66, 0;\n"
        "wgmma.mma_async.sync.aligned.m64n128k16.f32.bf16.bf16 "
        "{%0, %1, %2, %3, %4, %5, %6, %7, %8, %9, %10, %11, %12, %13, %14, %15, "
        "%16, %17, %18, %19, %20, %21, %22, %23, %24, %25, %26, %27, %28, %29, %30, %31, "
        "%32, %33, %34, %35, %36, %37, %38, %39, %40, %41, %42, %43, %44, %45, %46, %47, "
        "%48, %49, %50, %51, %52, %53, %54, %55, %56, %57, %58, %59, %60, %61, %62, %63}, "
        "%64, %65, p, 1, 1, %67, %68;\n}\n"
        : "+f"(d[0]), "+f"(d[1]), "+f"(d[2]), "+f"(d[3]), "+f"(d[4]), "+f"(d[5]), "+f"(d[6]), "+f"(d[7]),
          "+f"(d[8]), "+f"(d[9]), "+f"(d[10]), "+f"(d[11]), "+f"(d[12]), "+f"(d[13]), "+f"(d[14]), "+f"(d[15]),
          "+f"(d[16]), "+f"(d[17]), "+f"(d[18]), "+f"(d[19]), "+f"(d[20]), "+f"(d[21]), "+f"(d[22]), "+f"(d[23]),
          "+f"(d[24]), "+f"(d[25]), "+f"(d[26]), "+f"(d[27]), "+f"(d[28]), "+f"(d[29]), "+f"(d[30]), "+f"(d[31]),
          "+f"(d[32]), "+f"(d[33]), "+f"(d[34]), "+f"(d[35]), "+f"(d[36]), "+f"(d[37]), "+f"(d[38]), "+f"(d[39]),
          "+f"(d[40]), "+f"(d[41]), "+f"(d[42]), "+f"(d[43]), "+f"(d[44]), "+f"(d[45]), "+f"(d[46]), "+f"(d[47]),
          "+f"(d[48]), "+f"(d[49]), "+f"(d[50]), "+f"(d[51]), "+f"(d[52]), "+f"(d[53]), "+f"(d[54]), "+f"(d[55]),
          "+f"(d[56]), "+f"(d[57]), "+f"(d[58]), "+f"(d[59]), "+f"(d[60]), "+f"(d[61]), "+f"(d[62]), "+f"(d[63])
        : "l"(da), "l"(db), "r"(keep), "n"(TA), "n"(TB));
}
template <int TA, int TB>
__device__ __forceinline__ void wgmma_n8(float (&d)[4], uint64_t da, uint64_t db, int keep) {
    asm volatile("{\n.reg .pred p;\nsetp.ne.b32 p, %6, 0;\n"
        "wgmma.mma_async.sync.aligned.m64n8k16.f32.bf16.bf16 "
        "{%0, %1, %2, %3}, "
        "%4, %5, p, 1, 1, %7, %8;\n}\n"
        : "+f"(d[0]), "+f"(d[1]), "+f"(d[2]), "+f"(d[3])
        : "l"(da), "l"(db), "r"(keep), "n"(TA), "n"(TB));
}
__device__ __forceinline__ void wgmma_rs_n192(float (&d)[96], uint32_t a0, uint32_t a1, uint32_t a2, uint32_t a3, uint64_t db) {
    asm volatile("{\n.reg .pred p;\nsetp.ne.b32 p, 1, 0;\n"
        "wgmma.mma_async.sync.aligned.m64n192k16.f32.bf16.bf16 "
        "{%0, %1, %2, %3, %4, %5, %6, %7, %8, %9, %10, %11, %12, %13, %14, %15, "
        "%16, %17, %18, %19, %20, %21, %22, %23, %24, %25, %26, %27, %28, %29, %30, %31, "
        "%32, %33, %34, %35, %36, %37, %38, %39, %40, %41, %42, %43, %44, %45, %46, %47, "
        "%48, %49, %50, %51, %52, %53, %54, %55, %56, %57, %58, %59, %60, %61, %62, %63, "
        "%64, %65, %66, %67, %68, %69, %70, %71, %72, %73, %74, %75, %76, %77, %78, %79, "
        "%80, %81, %82, %83, %84, %85, %86, %87, %88, %89, %90, %91, %92, %93, %94, %95}, "
        "{%96, %97, %98, %99}, %100, p, 1, 1, 1;\n}\n"
        : "+f"(d[0]), "+f"(d[1]), "+f"(d[2]), "+f"(d[3]), "+f"(d[4]), "+f"(d[5]), "+f"(d[6]), "+f"(d[7]),
          "+f"(d[8]), "+f"(d[9]), "+f"(d[10]), "+f"(d[11]), "+f"(d[12]), "+f"(d[13]), "+f"(d[14]), "+f"(d[15]),
          "+f"(d[16]), "+f"(d[17]), "+f"(d[18]), "+f"(d[19]), "+f"(d[20]), "+f"(d[21]), "+f"(d[22]), "+f"(d[23]),
          "+f"(d[24]), "+f"(d[25]), "+f"(d[26]), "+f"(d[27]), "+f"(d[28]), "+f"(d[29]), "+f"(d[30]), "+f"(d[31]),
          "+f"(d[32]), "+f"(d[33]), "+f"(d[34]), "+f"(d[35]), "+f"(d[36]), "+f"(d[37]), "+f"(d[38]), "+f"(d[39]),
          "+f"(d[40]), "+f"(d[41]), "+f"(d[42]), "+f"(d[43]), "+f"(d[44]), "+f"(d[45]), "+f"(d[46]), "+f"(d[47]),
          "+f"(d[48]), "+f"(d[49]), "+f"(d[50]), "+f"(d[51]), "+f"(d[52]), "+f"(d[53]), "+f"(d[54]), "+f"(d[55]),
          "+f"(d[56]), "+f"(d[57]), "+f"(d[58]), "+f"(d[59]), "+f"(d[60]), "+f"(d[61]), "+f"(d[62]), "+f"(d[63]),
          "+f"(d[64]), "+f"(d[65]), "+f"(d[66]), "+f"(d[67]), "+f"(d[68]), "+f"(d[69]), "+f"(d[70]), "+f"(d[71]),
          "+f"(d[72]), "+f"(d[73]), "+f"(d[74]), "+f"(d[75]), "+f"(d[76]), "+f"(d[77]), "+f"(d[78]), "+f"(d[79]),
          "+f"(d[80]), "+f"(d[81]), "+f"(d[82]), "+f"(d[83]), "+f"(d[84]), "+f"(d[85]), "+f"(d[86]), "+f"(d[87]),
          "+f"(d[88]), "+f"(d[89]), "+f"(d[90]), "+f"(d[91]), "+f"(d[92]), "+f"(d[93]), "+f"(d[94]), "+f"(d[95])
        : "r"(a0), "r"(a1), "r"(a2), "r"(a3), "l"(db));
}

template <int HS>
__device__ __forceinline__ void attn_pair(const uint32_t* q, const uint32_t* k, const uint32_t* v, const uint32_t* kh, const uint32_t* vh,
                                          const float* fu, const float* fn, const float* rk, float bias0, float bias1, uint32_t mU, uint32_t zero, const float* ci, uint32_t* o) {
    float s0[2][4] = {}, s1[2][4] = {}, s2[2][4] = {};
#pragma unroll
    for (int n = 0; n < 4; n++) {
        const int hd = n & 1, a = 8 * hd + 2 * (n & 2);
        mma16816(s1[hd], q[a], q[a + 1], q[a + 2], q[a + 3], k[a], k[a + 2]);
        mma16816(s2[hd], q[a], q[a + 1], q[a + 2], q[a + 3], k[a + 1], k[a + 3]);
    }
#pragma unroll
    for (int n = 0; n < 4; n++) {
        const int hd = n & 1, a = 8 * hd + 2 * (n & 2);
        mma16816(s0[hd], q[a], q[a + 1], q[a + 2], q[a + 3], kh[HS * (a / 2)], kh[HS * (a / 2 + 1)]);
    }
    float e[2][4], m[2][2];
#pragma unroll
    for (int hd = 0; hd < 2; hd++) {
        e[hd][2] = fmaf(s1[hd][2], fu[2], s2[hd][2] * fn[2]); e[hd][3] = fmaf(s1[hd][3], fu[3], s2[hd][3] * fn[3]);
        e[hd][0] = fmaf(s0[hd][0], fu[0], fmaf(s1[hd][0], fn[0], bias0)); e[hd][1] = fmaf(s0[hd][1], fu[1], fmaf(s1[hd][1], fn[1], bias1));
        m[hd][1] = fmaxf(e[hd][2], e[hd][3]); m[hd][0] = fmaxf(e[hd][0], e[hd][1]);
    }
#pragma unroll
    for (int x = 1; x < 3; x++)
#pragma unroll
        for (int n = 0; n < 4; n++) m[n & 1][1 - (n >> 1)] = fmaxf(m[n & 1][1 - (n >> 1)], __shfl_xor_sync(0xffffffffu, m[n & 1][1 - (n >> 1)], x));
#pragma unroll
    for (int hd = 0; hd < 2; hd++) {
#pragma unroll
        for (int n = 0; n < 4; n++) e[hd][n] = ex2(e[hd][n] - m[hd][n >> 1]);
        float sum[4] = {};
        mma1688(sum, pack_bf16(e[hd][0], e[hd][1]), pack_bf16(e[hd][2], e[hd][3]), 0x3f803f80u);
        const float i0 = rcp(sum[0]), i1 = rcp(sum[2]);
        const uint32_t plo = pack_bf16(e[hd][0] * rk[0] * i0, e[hd][1] * rk[1] * i0), phi = pack_bf16(e[hd][2] * rk[2] * i1, e[hd][3] * rk[3] * i1);
        const uint32_t z0 = plo & zero, z1 = phi & zero;
        const uint32_t a0 = plo & ~mU, a1 = phi & mU, a3 = phi & ~mU, b0 = plo & mU;
#pragma unroll
        for (int jj = 0; jj < 4; jj++) {
            float c[4];
            asm volatile("mma.sync.aligned.m16n8k16.row.col.f32.bf16.bf16.f32 {%0,%1,%2,%3}, {%4,%5,%6,%7}, {%8,%9}, {%10,%11,%12,%13};"
                         : "=f"(c[0]), "=f"(c[1]), "=f"(c[2]), "=f"(c[3])
                         : "r"(a0), "r"(a1), "r"(z0), "r"(a3), "r"(v[8 * hd + 2 * jj]), "r"(v[8 * hd + 2 * jj + 1]), "f"(ci[0]), "f"(ci[1]), "f"(ci[2]), "f"(ci[3]));
            mma1688(c, b0, z1, vh[HS * (4 * hd + jj)]);
            o[8 * hd + 2 * jj] = pack_bf16(c[0], c[1]); o[8 * hd + 2 * jj + 1] = pack_bf16(c[2], c[3]);
        }
    }
}

__device__ __forceinline__ uint32_t norm_pair(uint32_t u, float m, float rinv) {
    const uint32_t d = pack_bf16(bf_lo(u) - m, bf_hi(u) - m);
    return max(pack_bf16(bf_lo(d) * rinv, bf_hi(d) * rinv), 1u);
}

__global__ void __launch_bounds__(512, 1)
fused_kernel(const __grid_constant__ CUtensorMap mx, const __grid_constant__ CUtensorMap mw, const __grid_constant__ CUtensorMap mwo,
             const __grid_constant__ CUtensorMap mout, const __grid_constant__ CUtensorMap mgu, const __grid_constant__ CUtensorMap mwd,
             const __grid_constant__ CUtensorMap mo, const __grid_constant__ CUtensorMap mr,
             const __nv_bfloat16* __restrict__ x, const __nv_bfloat16* __restrict__ wr, Scratch* __restrict__ scr, int swap_gu, const Weights pf) {
    extern __shared__ __align__(1024) uint8_t smem[];
    const uint32_t sb = smem_u32(smem);
    const uint32_t bars = sb + OFF_BAR;
    const int tid = threadIdx.x, lane = tid & 31, warp = __shfl_sync(0xffffffffu, tid >> 5, 0);
    const uint32_t sd = (sb & 0x3FFFF) >> 4;
    const int hp = blockIdx.x & 1, cl = blockIdx.x >> 1;
    int pr = cl - 4 + (max(cl - 36, 0) * 37 >> 8);
    asm("{\n.reg .pred p;\nsetp.lt.s32 p, %1, 4;\nselp.s32 %0, %2, %0, p;\n}" : "+r"(pr) : "r"(cl), "r"(39 + 8 * cl));
    const int b = pr * 2 + hp, mt = pr >> 3, p = pr & 7, nt = 2 * p + hp, rh = p & 1, cb = (p & 6) + hp;
    const int par = mt >> 2, j0 = (mt & 3) * 256;
    int budget = BUDGET;

    TSC(tid == 0, 0);
    auto load_w = [&](int k, int s) {
        const uint32_t full = bars + 8 * (B_WFULL + s);
        mbar_expect_tx(full, W_BYTES);
        tma_3d(sb + OFF_W + s * W_BYTES, &mw, full, nt * 64, k * 64, 0);
    };
    auto load_x = [&](int n) {
        const int w = n & 1, j = n < 4 ? (n >> 1) + 4 : (n >> 1) - 2;
        const uint32_t full = bars + 8 * (B_XFULL + w * 6 + 5 - j);
        mbar_expect_tx(full, BOX);
        tma_4d(sb + w * OFF_X1 + j * BOX, &mx, full, par * 1024 + (n >> 2) * 64, 0, (j0 + w * 128) >> 5, (~n >> 1) & 1);
    };
    if (warp < NBAR / 6 && elect_one()) {
        const uint32_t cnt = warp < B_WEMPTY / 6 ? 1 : warp < B_G1DONE / 6 ? 2 : warp < B_STAGED / 6 ? 4 : 8;
#pragma unroll
        for (int i = 0; i < 6; i++) mbar_init(bars + 48 * warp + 8 * i, cnt);
        asm volatile("fence.mbarrier_init.release.cluster;" ::: "memory");
        if (warp == 0 && b < 128) { load_x(0); load_w(0, 2); }
    }
    __syncthreads();

    if (b >= 128) {
        const int hc = b - 128, g = lane >> 2, t = lane & 3;
        const uint32_t ep = ld_rlx(&scr->epoch[0]) + 1;
        if (warp < 12) {
            const int n = warp / 3, part = warp - 3 * n;
            auto load = [&](int k) {
                const uint32_t full = bars + 8 * (2 * n + (k & 1));
                mbar_expect_tx(full, W_BYTES);
                tma_3d(sb + (2 * n + (k & 1)) * W_BYTES, &mw, full, (4 * hc + n) * 64, k * 64, 0);
            };
            if (part == 0 && elect_one()) { load(0); load(1); }
            __syncwarp();
            float c0[4] = {0.f, 0.f, 0.f, 0.f}, c1[4] = {0.f, 0.f, 0.f, 0.f};
            const uint32_t sel = g == 0 ? 0x3f80u : g == 1 ? 0x3f800000u : 0u;
            const uint32_t a = sb + 2 * n * W_BYTES + part * BOX + t * 256 + ((g ^ (2 * t)) << 4);
#pragma unroll 1
            for (int k = 0; k < 16; k++) {
                mbar_wait(bars + 8 * (2 * n + (k & 1)), (k >> 1) & 1, budget);
                uint4 v[8], u[8];
#pragma unroll
                for (int i = 0; i < 8; i++) { v[i] = lds4(a + (k & 1) * W_BYTES + i * 1024); u[i] = lds4(((a + 128) ^ 16) + (k & 1) * W_BYTES + i * 1024); }
#pragma unroll
                for (int i = 0; i < 8; i++) { mma16816(c0, v[i].x, v[i].y, u[i].x, u[i].y, sel, sel); mma16816(c1, v[i].z, v[i].w, u[i].z, u[i].w, sel, sel); }
                bar_sync(1 + n, 96);
                if (part == 0 && k < 14 && elect_one()) load(k + 2);
                __syncwarp();
            }
            if (t == 0) {
#pragma unroll
                for (int r = 0; r < 3; r++) {
                    const uint32_t q0 = (pack_bf16(c0[0], c0[1]) & ~1u) | (ep & 1), q1 = pack_bf16(c0[2], c0[3]), q2 = pack_bf16(c1[0], c1[1]), q3 = pack_bf16(c1[2], c1[3]);
                    st_rlx4(&scr->cs[4 * hc + n][r][part * 8 + g], q0, q1, q2, q3);
                    c0[0] -= bf_lo(q0); c0[1] -= bf_hi(q0); c0[2] -= bf_lo(q1); c0[3] -= bf_hi(q1);
                    c1[0] -= bf_lo(q2); c1[1] -= bf_hi(q2); c1[2] -= bf_lo(q3); c1[3] -= bf_hi(q3);
                }
            }
            TSC(tid == 0, 19);
        }
        if (warp < 8) TS_END();
        return;
    }
    asm volatile("barrier.cluster.arrive.relaxed.aligned;" ::: "memory");

    const int kc = b >> 4, c2 = b & 15;
    if (warp >= 12) {
        reg_dec<24>();
        if (warp == 12) {
            if (elect_one()) {
                int c = 0;
#pragma unroll 1
                for (int n = 1; n < 12; n++) {
                    load_x(n);
                    #pragma unroll 1
                    for (; c < (n == 11 ? 4 : __popc(ROWS_AT & ((2 << n) - 1))); c++) { mbar_expect_tx(bars + 8 * (B_ROW + c), BOX); tma_2d(sb + OFF_FR + c * BOX, &mr, bars + 8 * (B_ROW + c), c * 256, b * 16); }
                    if (n == 3 || n == 7) load_w((n + 1) >> 2, n >> 2);
                }
                int s = 2; uint32_t ph = 0;
#pragma unroll 1
                for (int k = 3; k < 16; k++) {
                    mbar_wait(bars + 8 * (B_WEMPTY + s), ph, budget);
                    load_w(k, s);
                    if (++s == 3) s = 0;
                    if (s == 2) ph ^= 1;
                }
                s = 2;
#pragma unroll 1
                for (int i = 0; i < 16; i++) {
                    mbar_wait(bars + 8 * (i < 2 ? B_WEMPTY + i : i < 4 ? B_G1DONE : i < 6 ? B_F1DONE : B_WOEMPTY + s), i >= 12, budget);
                    if (i == 0) {
                        mbar_expect_tx(bars + 8 * B_XT, 4 * BOX);
#pragma unroll 1
                        for (int n = 0; n < 4; n++)
                            tma_4d(sb + (n >> 1) * OFF_X1 + (n & 1) * BOX, &mx, bars + 8 * B_XT, par * 1024 + cb * 128 + (n & 1) * 64, 0, (j0 + rh * 128) >> 5, 1 - (n >> 1));
                    }
                    const uint32_t full = bars + 8 * (B_WOFULL + s);
                    mbar_expect_tx(full, 2 * BOX);
                    tma_3d(sb + OFF_WO + s * 2 * BOX, &mwo, full, 0, ((2 * p + (i < 2 ? i ^ hp : i)) & 15) * 64, cb * 2);
                    TSC(TIMING % 10 == 4, 48 + i);
                    if (++s == 6) s = 0;
                }
            }
        } else {
            bar_sync(8, 224);
            const uint32_t ep = __shfl_sync(0xffffffffu, lds1(sb + OFF_EP), 0);
            if (warp == 13) {
                cluster_wait();
                if (elect_one()) {
                    int j = 4, q = 0, left = BUDGET; uint32_t ph = 0;
#pragma unroll 1
                    for (int n = 6; n < 32; n++) {
                        mbar_wait(bars + 8 * (B_XEMPTY + j), ph, left);
                        tma_4d_mc(sb + hp * OFF_X1 + j * BOX, &mx, bars + 8 * (B_XFULL + hp * 6 + 5 - j), par * 1024 + (n >> 1) * 64, 0, (j0 + hp * 128) >> 5, ~n & 1);
                        if (++j == 6) j = 0;
                        if (j == 4) ph ^= 1;
#pragma unroll 1
                        for (; q < (PF_RATE * (n - PF_START) >> 3) && q < 18 + PF_NW; q++) {
                            const int u = q - PF_NW;
                            if (u < 0) bulk_pf(pf.wqkv + (size_t)(1024 + 128 * u + b) * 6144, 6144);
                            else if (u < 16) bulk_pf((b < 64 ? pf.wg : pf.wu) + (size_t)(u * 64 + (b & 63)) * 7168, 7168);
                            else bulk_pf(pf.wo + (size_t)((u - 16) * 128 + b) * 8192, 8192);
                        }
                    }
                }
                __syncwarp();
                uint32_t* hs = &scr->halo[b - 16][lane * 4];
                uint4 v[4] = {};
                if (j0) {
#pragma unroll 1
                    do {
#pragma unroll
                        for (int c = 0; c < 4; c++) v[c] = ld_rlx4(hs + c * 128);
                    } while (__any_sync(0xffffffffu, min(min(v[0].x, v[1].x), min(v[2].x, v[3].x)) == 0) && --budget > 0);
                }
#pragma unroll
                for (int c = 0; c < 4; c++) stsm4(sb + OFF_HIN + c * 512 + lane * 16, v[c].x, v[c].y, v[c].z, v[c].w);
                bar_arrive(11, 64);
                if (j0) {
#pragma unroll
                    for (int c = 0; c < 4; c++) st_rlx(hs + c * 128, 0);
                }
                TSC(lane == 0, 31);
                const int src = ((mt * 2 + rh) * 2 + 1 - hp) * 1024;
                if (elect_one()) {
                    const uint32_t* fl = &scr->oflag[mt * 2 + 1 - hp][0];
                    const uint32_t inv = (ep & 1) - 1;
                    uint32_t ready = 0, ph = 0;
                    int s = 4;
#pragma unroll 1
                    for (int i = 2; i < 16; i++) {
                        const int kb = (2 * p + i) & 15;
#pragma unroll 1
                        while (!((ready >> kb) & 1) && --budget > 0) ready = ld_rlx(fl) ^ inv;
                        TSC(i == 2, 30);
                        mbar_wait(bars + 8 * (B_OEMPTY + s), ph, budget);
                        tma_2d_mc(sb + hp * OFF_X1 + s * BOX, &mo, bars + 8 * (B_OFULL + hp * 6 + s), 0, src + kb * 64);
                        TSC(TIMING % 10 == 4 && hp == 0, 32 + i);
                        if (++s == 6) s = 0;
                        if (s == 4) ph ^= 1;
                    }
                }
            } else if (warp == 14) {
                if (elect_one()) {
                    uint32_t s8 = 0, ph = 0;
                    int tries = BUDGET;
                    const uint32_t* act = scr->act[ep & 1];
                    auto counted = [&](int c, uint32_t n) {
#pragma unroll 1
                        while (ld_rlx(&scr->cnt[c][0]) != ep * n && --tries > 0) __nanosleep(POLL_NS);
                    };
                    auto weights = [&](const CUtensorMap* m, int c0, int c1, int c2_) {
                        mbar_wait(bars + 8 * B_FEMPTY + s8, ph, budget);
                        mbar_expect_tx(bars + 8 * B_FFULL + s8, F_BYTES);
                        tma_3d(sb + OFF_FS + s8 * (F_BYTES / 8), m, bars + 8 * B_FFULL + s8, c0, c1, c2_);
                    };
                    if (b < 112) {
                        counted(8, 32);
                        TS(26);
#pragma unroll 1
                        for (int q = 0; q < 16; q++) {
                            weights(&mgu, b * 32, q * 64, 0);
                            bulk_g2s(sb + OFF_FS + BOX + s8 * (F_BYTES / 8), act + 14336 + q * 256, 1024, bars + 8 * B_FFULL + s8);
                            TSC(TIMING % 10 == 5, 32 + q);
                            if (q >= PF_D && q < PF_D + 8) bulk_pf(pf.wd + (size_t)((q - PF_D) * 112 + b) * 8192, 8192);
                            s8 += 8;
                            if (s8 == 40) { s8 = 0; ph ^= 1; }
                        }
                    }
#pragma unroll 1
                    for (int q = -3; q < 7; q++) {
                        if (q == 0) { counted(kc, 28); TS(29); }
                        if ((unsigned)q >= 3) weights(&mwd, 0, kc * 448 + (q < 0 ? q + 3 : q) * 64, c2);
                        if (q >= 0) bulk_g2s(sb + OFF_FS + BOX + s8 * (F_BYTES / 8), act + (kc * 7 + q) * 256, 1024, bars + 8 * B_FFULL + s8);
                        TSC(TIMING % 10 == 5, 51 + q);
                        s8 += 8;
                        if (s8 == 24) { s8 = 0; if ((unsigned)q >= 3) ph ^= 1; }
                    }
                }
            } else {
#pragma unroll 1
                for (int i = lane * 16; i < CS_BYTES; i += 512) sts4(sb + OFF_CS + i, 0, 0, 0, 0);
                mbar_wait(bars + 8 * ZF_GATE, 0, budget);
                uint8_t* oz = scr->o + ((size_t)mt * 64 + nt) * BOX + lane * 16;
#pragma unroll 1
                for (int i = 0; i < 16; i++, oz += 512) {
#pragma unroll
                    for (int n = 0; n < 4; n++) st_rlx4(oz + n * 16 * BOX, 0, 0, 0, 0);
                    __nanosleep(ZF_NS);
                }
                __syncwarp();
                fence_gpu();
                mbar_wait(bars + 8 * B_RDONE, 0, budget);
                int tries = BUDGET;
#pragma unroll 1
                for (int i = lane; i < 88; i += 32) {
                    const uint2* rp = &scr->row[2 * (j0 - 8 + i) + par];
                    uint2 v0, v1, v2;
#pragma unroll 1
                    do { v0 = ld_rlx2(rp + (j0 + i < 8 ? 16 : 0)); v1 = ld_rlx2(rp + 176); v2 = ld_rlx2(rp + 352); } while ((((v0.y ^ ep) | (v1.y ^ ep) | (v2.y ^ ep)) & 31) && --tries > 0);
                    sts2(sb + OFF_STAT + i * 8, (v0.x << 16) ^ 0x80000000u, __float_as_uint(rcp(bf_hi(v0.x))));
                    sts2(sb + OFF_STAT + i * 8 + 704, (v1.x << 16) ^ 0x80000000u, __float_as_uint(rcp(bf_hi(v1.x))));
                    sts2(sb + OFF_STAT + i * 8 + 1408, (v2.x << 16) ^ 0x80000000u, __float_as_uint(rcp(bf_hi(v2.x))));
                }
                __syncwarp();
                {
                    const int row = 2047 - ((poll_all(&scr->sel[lane & 7], 31u, ep & 31, budget) >> 5) & 2047), jj = (row >> 1) - j0 - rh * 128;
                    uint32_t boxes = __reduce_or_sync(0xffffffffu, (row & 1) == par && (unsigned)jj < 128 ? 1u << (jj >> 4) : 0u);
                    sts1(sb + OFF_SEL, boxes);
#pragma unroll 1
                    for (int i = 0; boxes; i += 2) {
                        if (boxes & 1) st_rlx4(pf.out + (size_t)(2 * (j0 + rh * 128 + i + (lane >> 4)) + par) * 2048 + cb * 256 + (lane & 15) * 16, 0, 0, 0, 0);
                        else i += 14;
                        if ((i & 14) == 14) boxes >>= 1;
                    }
                }
                if (lane < 24) {
                    uint4 v[3];
#pragma unroll 1
                    while (v[0] = ld_rlx4(&scr->cs[nt][0][lane]), v[1] = ld_rlx4(&scr->cs[nt][1][lane]), v[2] = ld_rlx4(&scr->cs[nt][2][lane]),
                           (((v[0].x ^ ep) | (v[1].x ^ ep) | (v[2].x ^ ep)) & 1) && --tries > 0) __nanosleep(100);
#pragma unroll
                    for (int r = 0; r < 3; r++) sts4(sb + OFF_CS + 64 + lane * 128 + r * 16, v[r].x, v[r].y, v[r].z, v[r].w);
                }
                fence_async_smem();
                __syncwarp();
                if (elect_one()) {
                    mbar_arrive(bars + 8 * B_AUX);
                    TS(21);
                    if (lds1(sb + OFF_SEL)) { fence_gpu(); asm volatile("fence.proxy.async.global;" ::: "memory"); }
                    mbar_arrive(bars + 8 * B_ZERO);
                    TS(25);
                    mbar_expect_tx(bars + 8 * (B_OFULL + 3), BOX); mbar_expect_tx(bars + 8 * (B_OFULL + 9), BOX);
#pragma unroll 1
                    for (int v = 0; v < 2; v++) {
                        const uint32_t ring = sb + v * OFF_X1 + 2 * BOX, fb = bars + 8 * (B_OFULL + v * 6 + 2);
                        mbar_wait(bars + 8 * (B_STAGED + v), 0, budget);
                        asm volatile("red.relaxed.gpu.global.xor.b32 [%0], %1;" ::"l"(&scr->oflag[mt * 2 + 1 - v][0]), "r"(1u << nt) : "memory");
                        TS(13 + 2 * v);
                        mbar_arrive(fb);
                        mbar_wait(bars + 8 * B_G1DONE, 0, budget);
                        bulk_s2c(mapa(ring + BOX, hp ^ 1), ring, BOX, mapa(fb + 8, hp ^ 1));
                        if (v == 0) mbar_wait(bars + 8 * B_FREED, 0, budget);
#pragma unroll
                        for (int n = 0; n < 4; n++) {
                            mbar_expect_tx(bars + 8 * (B_OFULL + (n >> 1) * 6 + 4 + (n & 1)) - v * 32, BOX);
                            mbar_arrive_at(mapa(bars + 8 * B_OEMPTY, n >> 1) + (4 + (n & 1)) * 8 - v * 32);
                        }
                    }
                }
            }
        }
    } else if (warp >= 8) {
        reg_dec<40>();
        const int wq = warp - 8, ta = tid - 256;
        const uint32_t rbuf = sb + OFF_FR + wq * 2048;
        const uint4 wv = ldg_nc(wr + ta * 8);
        if (ta == 0) sts1(sb + OFF_EP, ld_rlx(&scr->epoch[0]) + 1);
        sts4(sb + OFF_STAT + ta * 16, wv.x, wv.y, wv.z, wv.w);
        bar_sync(8, 224);
        const uint32_t ep = __shfl_sync(0xffffffffu, lds1(sb + OFF_EP), 0);
        {
            const int s = b * 16 + wq * 4 + (lane >> 3);
            if ((lane & 7) == 0) st_rlx2(&scr->row[s], 0, ep - 1);
            float sw = 0.f;
#pragma unroll 1
            for (int i = 0; i < 16; i++) { const uint32_t q = lds1(sb + OFF_STAT + i * 128 + lane * 4); sw += bf_lo(q) + bf_hi(q); }
#pragma unroll 1
            for (int o = 16; o > 0; o >>= 1) sw += __shfl_xor_sync(0xffffffffu, sw, o);
            float s1 = 0.f, s2 = 0.f, sr = 0.f;
            {
                float s1b = 0.f, s2b = 0.f, srb = 0.f;
                const uint32_t xb = rbuf + (lane >> 4) * 1024 + (lane & 15) * 16, wb = sb + OFF_STAT + (lane & 15) * 16;
#pragma unroll 1
                for (int i = 0; i < 8; i++) {
                    const uint4 w4 = lds4(wb + i * 256);
                    mbar_wait_hot(bars + 8 * (B_ROW + (i >> 1)), 0, budget);
                    TSC(ta == 0 && i == 0, 17);
                    const uint32_t o = (i >> 1) * BOX + (i & 1) * 256;
                    const uint4 u = lds4(xb + o), v = lds4(xb + o + 512);
#pragma unroll
                    for (int c = 0; c < 4; c++) {
                        const float w0 = bf_lo((&w4.x)[c]), w1 = bf_hi((&w4.x)[c]);
                        const float a0 = bf_lo((&u.x)[c]), a1 = bf_hi((&u.x)[c]), b0 = bf_lo((&v.x)[c]), b1 = bf_hi((&v.x)[c]);
                        s1 += a0; s2 = fmaf(a0, a0, s2); sr = fmaf(a0, w0, sr);
                        s1 += a1; s2 = fmaf(a1, a1, s2); sr = fmaf(a1, w1, sr);
                        s1b += b0; s2b = fmaf(b0, b0, s2b); srb = fmaf(b0, w0, srb);
                        s1b += b1; s2b = fmaf(b1, b1, s2b); srb = fmaf(b1, w1, srb);
                    }
                }
                const bool up = lane & 8;
                s1 = (up ? s1b : s1) + __shfl_xor_sync(0xffffffffu, up ? s1 : s1b, 8);
                s2 = (up ? s2b : s2) + __shfl_xor_sync(0xffffffffu, up ? s2 : s2b, 8);
                sr = (up ? srb : sr) + __shfl_xor_sync(0xffffffffu, up ? sr : srb, 8);
            }
#pragma unroll
            for (int o = 1; o < 8; o <<= 1) {
                s1 += __shfl_xor_sync(0xffffffffu, s1, o); s2 += __shfl_xor_sync(0xffffffffu, s2, o); sr += __shfl_xor_sync(0xffffffffu, sr, o);
            }
            const float mean = s1 * (1.f / 1024.f), mb = bf16r(mean);
            float var = fmaf(-mean, mean, s2 * (1.f / 1024.f));
            sr = fmaf(-mb, sw, sr);
            if (__builtin_expect(__any_sync(0xffffffffu, mean * mean > 256.f * var), 0)) {
                float a2 = 0.f, ar = 0.f;
#pragma unroll 1
                for (int i = 0; i < 64; i++) {
                    const uint32_t o = i * 32 + (lane & 7) * 4, q1 = lds1(rbuf + (lane >> 3) * 512 + (o >> 9) * BOX + (o & 511)), q2 = lds1(sb + OFF_STAT + o);
                    a2 = fmaf(bf_lo(q1) - mean, bf_lo(q1) - mean, fmaf(bf_hi(q1) - mean, bf_hi(q1) - mean, a2));
                    ar = fmaf(bf_lo(q1) - mb, bf_lo(q2), fmaf(bf_hi(q1) - mb, bf_hi(q2), ar));
                }
#pragma unroll 1
                for (int o = 1; o < 8; o <<= 1) { a2 += __shfl_xor_sync(0xffffffffu, a2, o); ar += __shfl_xor_sync(0xffffffffu, ar, o); }
                var = a2 * (1.f / 1024.f); sr = ar;
            }
            float den;
            asm("sqrt.approx.f32 %0, %1;" : "=f"(den) : "f"(bf16r(bf16r(var) + 1e-5f)));
            const uint32_t st = pack_bf16(mb, den);
            const uint32_t rb = pack_bf16(0.f, sr * rcp(bf_hi(st)) + 0.f);
            uint32_t ord = (int)rb < 0 ? ~rb & 0xffff0000u : rb | 0x80000000u;
            if ((rb & 0x7fffffffu) > 0x7f800000u) ord = 0;
            if ((lane & 7) == 0) st_rlx2(&scr->row[s], st, ord | ((2047 - s) << 5) | (ep & 31));
            __syncwarp();
            if (lane < 7) mbar_arrive(bars + 8 * (lane < 5 ? B_FEMPTY + lane : B_RDONE));
        }
        TSC(ta == 0, 18);
        if ((b >> 3) == 14) {
            const uint32_t gm = sb + OFF_E, cnt = gm + 64, res = gm + 80, list = gm + 128;
            uint32_t kv[16];
            int tries = BUDGET;
#pragma unroll 1
            do {
                uint32_t bad = 0;
#pragma unroll
                for (int n = 0; n < 16; n++) kv[n] = ld_rlx(&scr->row[n * 128 + ta].y);
#pragma unroll
                for (int n = 0; n < 16; n++) bad |= kv[n] ^ ep;
                if ((bad & 31) == 0) break;
            } while (--tries > 0);
            __syncwarp();
            TSC(ta == 0, 26);
            uint32_t m = 0;
#pragma unroll
            for (int n = 0; n < 16; n++) m = max(m, kv[n]);
            uint32_t gmax = m;
#pragma unroll
            for (int o = 1; o < 8; o <<= 1) gmax = max(gmax, __shfl_xor_sync(0xffffffffu, gmax, o));
            sts1(gm + (ta >> 3) * 4, gmax);
            sts1(cnt, 0);
            bar_sync(12, 128);
            const uint32_t c = lds1(gm + (lane & 15) * 4);
            int rank = 0;
#pragma unroll
            for (int i = 0; i < 2; i++) { const uint4 q = lds4(gm + (lane >> 4) * 32 + i * 16); rank += (q.x > c) + (q.y > c) + (q.z > c) + (q.w > c); }
            rank += __shfl_xor_sync(0xffffffffu, rank, 16);
            const uint32_t thr = redux_max(rank == 7 ? c : 0u);
#pragma unroll 1
            while (m >= thr) {
                uint32_t at, m2 = 0;
                asm volatile("atom.shared.add.u32 %0, [%1], 1;" : "=r"(at) : "r"(cnt) : "memory");
#pragma unroll
                for (int n = 0; n < 16; n++) m2 = max(m2, kv[n] < m ? kv[n] : 0u);
                sts1(list + at * 4, m);
                if (m2 == 0) break;
                m = m2;
            }
            bar_sync(12, 128);
            const int nc = lds1(cnt);
#pragma unroll 1
            for (int i = ta >> 3; i < ((nc + 3) & ~3); i += 16) {
                const uint32_t ki = lds1(list + i * 4);
                int r = 0;
#pragma unroll 1
                for (int n = lane & 7; n < nc; n += 8) r += lds1(list + n * 4) > ki;
                __syncwarp();
#pragma unroll
                for (int o = 1; o < 8; o <<= 1) r += __shfl_xor_sync(0xffffffffu, r, o);
                if (r == (b & 7) && i < nc) sts1(res, ki);
            }
            bar_sync(12, 128);
            const uint32_t k0 = lds1(res);
            const int r0 = 2047 - ((k0 >> 5) & 2047);
            TSC(ta == 0, 22);
            if (ta == 0) st_rlx(&scr->sel[b & 7], k0);
            const uint4 v0 = ldg_nc(x + (size_t)r0 * 1024 + ta * 8);
            const uint32_t s0 = ld_rlx(&scr->row[r0]);
            const float m0 = bf_lo(s0), i0 = rcp(bf_hi(s0));
            const int ao = 14336 + (ta >> 3) * 256 + (b & 7) * 32 + ((ta ^ b) & 7) * 4;
            st_rlx4(scr->act[ep & 1] + ao, norm_pair(v0.x, m0, i0), norm_pair(v0.y, m0, i0), norm_pair(v0.z, m0, i0), norm_pair(v0.w, m0, i0));
            __syncwarp();
            if (lane == 0) red_add(&scr->cnt[8][tries >> 30]);
            st_rlx4(scr->act[~ep & 1] + ao, 0, 0, 0, 0);
        }
        uint32_t s8 = 0, fph = 0, key = 0;
        const uint32_t chk = __shfl_sync(0xffffffffu, sb + OFF_FS + BOX + lane * 32 + (lane & 28), lane);
        int left = BUDGET;
#pragma unroll 1
        for (int ph = 0; ph < 2; ph++) {
            if (ph || b < 112) {
                float acc[4] = {0.f, 0.f, 0.f, 0.f};
                const uint32_t alo = sd + (ph ? dlo(OFF_FS, 8192) : dlo(OFF_FS, 4096)), ahi = ph ? dhi(1024, 1) : dhi(512, 2), astep = ph ? 128 : 64;
                const uint32_t bhi = ph ? dhi(128, 0) : dhi(1024, 1), bstep = ph ? 16 : 2, wrap = ph ? 24 : 40;
                uint32_t prev = 0, prev2 = 0;
                if (ph) mbar_wait(bars + 8 * FFN2_GATE, 0, left);
#pragma unroll 1
                for (int q = ph ? 7 : 16; q > 0; q--) {
                    const uint32_t da = alo + s8 * (F_BYTES >> 7), db = sd + dlo(OFF_FS + BOX, 128) + s8 * (F_BYTES >> 7);
                    mbar_wait_hot(bars + 8 * B_FFULL + s8, fph, left);
                    if (__builtin_expect(__any_sync(0xffffffffu, lds1(chk + s8 * (F_BYTES / 8)) == 0), 0)) {
                        int tries = BUDGET;
#pragma unroll 1
                        for (int n = lane * 4 + (left >> 30); n < 256; n += 128) {
                            uint4 v;
#pragma unroll 1
                            do { v = ld_rlx4(scr->act[ep & 1] + ((ph ? kc * 7 + 7 : 72) - q) * 256 + n); } while (v.x == 0 && --tries > 0);
                            __syncwarp();
                            sts4(sb + OFF_FS + BOX + s8 * (F_BYTES / 8) + n * 4, v.x, v.y, v.z, v.w);
                        }
                        NRETRY();
                        fence_async_smem();
                        __syncwarp();
                    }
                    TSC(TIMING % 10 == 3 && ta == 0, 32 + (ph ? 23 : 16) - q);
                    wg_fence();
#pragma unroll
                    for (int j = 0; j < X_NW; j++) wgmma_n8<1, 0>(acc, mkdesc(da + j * astep, ahi), mkdesc(db + j * bstep, bhi), 1);
                    wg_commit();
                    uint32_t done = F1_DEPTH == 2 ? prev2 : prev;
                    prev2 = prev;
                    if (lane == 0) prev = bars + 8 * B_FEMPTY + s8;
                    wg_wait<F1_DEPTH>();
                    if (ph) { wg_wait<F2_DEPTH>(); done = F2_DEPTH ? prev2 : prev; }
                    if (done) mbar_arrive(done);
                    s8 += 8;
                    if (s8 == wrap) { s8 = 0; fph ^= 1; }
                }
                wg_wait<0>();
                const int ln = lane + (left >> 30);
                if (ph == 0) {
                    if (prev) mbar_arrive(prev);
                    const bool second = (wq >= 2) != (swap_gu != 0);
                    const uint32_t xa = sb + OFF_GU + ((wq & 1) * 32 + ln) * 16;
                    if (second) sts4(xa, __float_as_uint(acc[0]), __float_as_uint(acc[1]), __float_as_uint(acc[2]), __float_as_uint(acc[3]));
                    bar_sync(12, 128);
                    if (!second) {
                        const float4 up = lds4f(xa);
                        float hv[4];
#pragma unroll
                        for (int c = 0; c < 4; c++) { const float ga = bf16r(acc[c]); hv[c] = bf16r(ga * sigmoidf(ga)) * bf16r((&up.x)[c]); }
                        const int ao = (b * 4 + (wq & 1) * 2) * 32 + ln;
                        st_rlx(scr->act[ep & 1] + ao, max(movm(pack_bf16(hv[0], hv[1])), 1u)); st_rlx(scr->act[ep & 1] + 32 + ao, max(movm(pack_bf16(hv[2], hv[3])), 1u));
                        __syncwarp();
                        if (ln == 0) red_add(&scr->cnt[b / 14][0]);
                        st_rlx(scr->act[~ep & 1] + ao, 0); st_rlx(scr->act[~ep & 1] + 32 + ao, 0);
                    }
                } else {
#pragma unroll
                    for (int c = 0; c < 4; c++) st_rlx(&scr->ypart[kc][2 * (ln & 3) + (c & 1)][c2 * 64 + wq * 16 + (c >> 1) * 8 + (ln >> 2)], (__float_as_uint(acc[c]) & ~1u) | (ep & 1));
                }
                TSC(ta == 0, 22 + ph);
            }
            const int ln = lane + (left >> 30);
            if (ph == 0) {
                if ((ta & 126) == 64) mbar_arrive(bars + 8 * B_F1DONE);
                key = poll_all(&scr->sel[ln & 7], 31u, ep & 31, left);
            }
        }
        {
            const int row = 2047 - ((key >> 5) & 2047);
            const float sig = bf16r(sigmoidf(__uint_as_float(((int)key < 0 ? key & 0x7fffffffu : ~key) & 0xffff0000u)));
            uint32_t own = __ballot_sync(0xffffffffu, (row & 1) == par && (row >> 8) == (mt & 3) * 2 + rh) & 255;
            if (wq & 2) own &= own - 1;
            mbar_wait(bars + 8 * B_ZERO, 0, left);
#pragma unroll 1
            for (; own; own &= own - 1, own &= own - 1) {
                const int j = __ffs(own) - 1, col = cb * 128 + (wq & 1) * 64 + (lane & 15) * 4;
                const uint32_t* src = &scr->ypart[lane >> 4][j][col];
                uint4 v[4]; int tries = BUDGET;
#pragma unroll 1
                do {
#pragma unroll
                    for (int m = 0; m < 4; m++) v[m] = ld_rlx4(src + m * 2 * 8192);
                } while ((((v[0].x ^ ep) | (v[1].x ^ ep) | (v[2].x ^ ep) | (v[3].x ^ ep)) & 1) && --tries > 0 && (__nanosleep(Y_NS), true));
                __syncwarp();
                float a[4];
                const float sj = __shfl_sync(0xffffffffu, sig, j);
                const int rj = __shfl_sync(0xffffffffu, row, j);
#pragma unroll
                for (int c = 0; c < 4; c++) {
                    a[c] = (__uint_as_float((&v[0].x)[c]) + __uint_as_float((&v[1].x)[c])) + (__uint_as_float((&v[2].x)[c]) + __uint_as_float((&v[3].x)[c]));
                    a[c] = bf16r(a[c] + __shfl_xor_sync(0xffffffffu, a[c], 16)) * sj;
                }
                if (lane < 16) asm volatile("red.relaxed.gpu.global.add.noftz.v2.bf16x2 [%0], {%1, %2};" ::"l"(pf.out + (size_t)rj * 2048 + col * 2), "r"(pack_bf16(a[0], a[1])), "r"(pack_bf16(a[2], a[3])) : "memory");
            }
        }
        TSC(ta == 0, 24);
    } else {
        reg_inc<224>();
        const int w = warp >> 2, wi = warp & 3, g = lane >> 2, t = lane & 3;
        const bool elect = (tid & 127) == 0;
        const uint32_t mad = (lane & 15) * 128 + (((lane >> 4) ^ (lane & 7)) << 4);
        float acc[64];
        const uint32_t ring = sb + w * OFF_X1, ofull = bars + 8 * (B_OFULL + w * 6), oempty = mapa(bars + 8 * B_OEMPTY, w);
        const int r0 = rh * 128 + wi * 32 + (1 - w) * 16 + g;
        {
            float acc0[96], acc1[96];
            const uint32_t sta = sb + OFF_STAT + (8 + w * 128 + wi * 32) * 8;
            {
                const uint32_t xfull = bars + 8 * (B_XFULL + w * 6 + 5), xempty = mapa(bars + 8 * B_XEMPTY, w), dx0 = sd + dlo(w * OFF_X1, 16);
                uint32_t s8 = 16, ps8 = 0, ph = 0;
                cluster_wait();
#pragma unroll 1
                for (int k = 0; k < 16; k++) {
                    const uint32_t dx = dx0 + s8 * (2 * BOX >> 7), dw = sd + dlo(OFF_W, BOX) + s8 * (W_BYTES >> 7);
                    mbar_wait(bars + 8 * B_WFULL + s8, ph, budget);
                    mbar_wait(xfull - 2 * s8, ph, budget);
                    TSC(elect && k == 0, 1 + 8 * w);
                    TSC(TIMING % 10 == 1 && tid == 0, 32 + k);
                    wg_wait<0>();
                    wg_fence();
#pragma unroll
                    for (int kk = 0; kk < 4; kk++) wgmma_n192<0, 1>(acc1, mkdesc(dx + kk * 2, dhi(1024, 1)), mkdesc(dw + kk * 128, dhi(1024, 1)), kk ? 1 : k);
                    wg_commit();
                    TSC(TIMING % 10 == 6 && elect, 32 + 16 * w + k);
                    if (elect && k > 0) {
                        mbar_arrive(bars + 8 * B_WEMPTY + ps8);
                        if (k <= 13) { mbar_expect_tx(xfull - 2 * ps8 - 8, BOX); mbar_arrive_at(xempty + 2 * ps8 + 8); }
                    }
                    if (k == 15) {
                        mbar_wait(bars + 8 * B_AUX, 0, budget);
                        const uint32_t zero = budget >> 30, pm = t & 1 ? 0x4432 : 0x3232, ra = sta + ((t >> 1) * 16 + g) * 8;
                        const uint32_t a0 = __byte_perm(lds1(ra), 0, pm), a1 = __byte_perm(lds1(ra + 64), 0, pm), a2 = a0 & zero, a3 = a1 & zero;
                        wg_fence();
                        wgmma_rs_n192(acc1, a0, a1, a2, a3, mkdesc(sd + dlo(OFF_CS, 0), dhi(128, 0)));
                        wgmma_rs_n192(acc0, a0, a1, a2, a3, mkdesc(sd + dlo(OFF_CS + 64, 0), dhi(128, 0)));
                        wg_commit();
                    }
                    mbar_wait(xfull - 2 * s8 - 8, ph, budget);
                    wg_wait<0>();
                    wg_fence();
#pragma unroll
                    for (int kk = 0; kk < 4; kk++) wgmma_n192<0, 1>(acc0, mkdesc(dx + 512 + kk * 2, dhi(1024, 1)), mkdesc(dw + kk * 128, dhi(1024, 1)), kk ? 1 : k);
                    wg_commit();
                    if (elect && k <= 12) { mbar_expect_tx(xfull - 2 * s8, BOX); mbar_arrive_at(xempty + 2 * s8); }
                    ps8 = s8;
                    s8 = s8 == 16 ? 0 : s8 + 8;
                    if (s8 == 16) ph ^= 1;
                }
            }
            const uint32_t zero = budget >> 30;
            const bool u0 = 2 * t > g, u1 = 2 * t + 1 > g;
            uint32_t mU = (u0 ? 0xffffu : 0u) | (u1 ? 0xffff0000u : 0u);
            uint32_t ka0 = sta + (2 * t - (u0 ? 8 : 0)) * 8 + 4, ka1 = sta + (2 * t + 1 - (u1 ? 8 : 0)) * 8 + 4;
            float rk[2][4], fu[2][4], fn[2][4];
            auto factors = [&](int h) {
#pragma unroll
                for (int n = 0; n < 4; n += 2) {
                    const float rq = lds1f(sta + (16 * h + 4 * n + g) * 8 + 4) * (0.17677669529663687f * 1.4426950408889634f);
                    rk[h][n] = lds1f(ka0 + h * 128 + n * 32); rk[h][n + 1] = lds1f(ka1 + h * 128 + n * 32);
                    const float f0 = rq * rk[h][n], f1 = rq * rk[h][n + 1];
                    fu[h][n] = u0 ? f0 : 0.f; fn[h][n] = f0 - fu[h][n]; fu[h][n + 1] = u1 ? f1 : 0.f; fn[h][n + 1] = f1 - fu[h][n + 1];
                }
#pragma unroll
                for (int n = 0; n < 4; n++) asm volatile("" : "+f"(fu[h][n]), "+f"(fn[h][n]));
            };
            uint8_t* og = scr->o + ((size_t)(mt * 4 + w * 2) * 16 + nt) * BOX + wi * 256 + lane * 4;
            TSC(elect, 19 + w);
            uint32_t pk0[48], pk1[48], o[16] = {};
#pragma unroll
            for (int j = 0; j < 48; j++) if (j < 16 || (j & 1)) pk1[j] = pack_here(acc1[2 * j], acc1[2 * j + 1]);
            if (warp < 7) {
#pragma unroll
                for (int c = 0; c < 4; c++) stsm4(ring + 4 * BOX + wi * 2048 + c * 512 + lane * 16, pk1[17 + 8 * c], pk1[19 + 8 * c], pk1[21 + 8 * c], pk1[23 + 8 * c]);
                bar_arrive(1 + warp, 64);
            } else if (j0 != 768) {
#pragma unroll
                for (int c = 0; c < 4; c++) {
                    pk1[17 + 8 * c] = max(pk1[17 + 8 * c], 1u);
                    st_rlx4(&scr->halo[b][c * 128 + lane * 4], pk1[17 + 8 * c], pk1[19 + 8 * c], pk1[21 + 8 * c], pk1[23 + 8 * c]);
                }
            }
            TSC(tid == 224, 28);
#pragma unroll
            for (int j = 16; j < 48; j += 2) pk1[j] = pack_here(acc1[2 * j], acc1[2 * j + 1]);
            factors(1);
            uint32_t od = sb + 2 * BOX + wi * 256 + (lane >> 4) * 1024 + (lane & 15) * 16, g1peer = mapa(bars + 8 * B_G1DONE, hp ^ 1);
            uint32_t ha = sb + (warp == 0 ? OFF_HIN : warp <= 4 ? 4 * BOX - 2048 : OFF_X1 + 4 * BOX - 5 * 2048) + warp * 2048 + lane * 16;
            const bool first = warp == 0 && j0 == 0;
            float bias0 = first && u0 ? -INFINITY : 0.f, bias1 = first && u1 ? -INFINITY : 0.f;
            asm volatile("" : "+l"(og), "+r"(mU), "+r"(od), "+r"(ha), "+f"(bias0), "+f"(bias1));
            mbar_wait(bars + 8 * B_XT, 0, budget);
            mbar_wait(bars + 8 * (B_WEMPTY + 1), 0, budget);
            wg_wait<0>();
            if (elect) { mbar_arrive(bars + 8 * B_G1DONE); mbar_arrive_at(g1peer); }
            TSC(elect, 2 + 8 * w);
            float ci[4];
#pragma unroll
            for (int n = 0; n < 4; n++) ci[n] = __uint_as_float((0x03800000u + n) | (budget >> 30));
            auto hand_over = [&](int v) {
                asm volatile("{\n.reg .pred p;\nsetp.ne.b32 p, %17, 0;\n"
                             "@p stmatrix.sync.aligned.m8n8.x4.shared.b16 [%16], {%0,%1,%2,%3};\n@p stmatrix.sync.aligned.m8n8.x4.shared.b16 [%16 + 2048], {%4,%5,%6,%7};\n"
                             "@p stmatrix.sync.aligned.m8n8.x4.shared.b16 [%16 + 4096], {%8,%9,%10,%11};\n@p stmatrix.sync.aligned.m8n8.x4.shared.b16 [%16 + 6144], {%12,%13,%14,%15};\n"
                             "fence.proxy.async.shared::cta;\n}"
                             ::"r"(o[0]), "r"(o[1]), "r"(o[2]), "r"(o[3]), "r"(o[4]), "r"(o[5]), "r"(o[6]), "r"(o[7]), "r"(o[8]), "r"(o[9]), "r"(o[10]), "r"(o[11]),
                               "r"(o[12]), "r"(o[13]), "r"(o[14]), "r"(o[15]), "r"(od + v * OFF_X1), "r"((int)(w == rh)) : "memory");
                TSC(tid == 0, v ? 27 : 5);
#pragma unroll
                for (int i = 0; i < 16; i++) asm volatile("st.global.u32 [%0], %1;" ::"l"(og + (1 - v) * 16 * BOX + (i >> 1) * 1024 + (i & 1) * 128), "r"(o[i]) : "memory");
                __syncwarp();
                if (lane == 0) mbar_arrive(bars + 8 * (B_STAGED + v));
            };
#pragma unroll
            for (int j = 32; j < 48; j++) pk1[j] = movm(pk1[j]);
#pragma unroll
            for (int j = EARLY_PK; j < 48; j++) if (j >= 32 || (j & 1) || EARLY_PK < 17) pk0[j] = pack_here(acc0[2 * j], acc0[2 * j + 1]);
#pragma unroll
            for (int j = 32; j < 48; j++) pk0[j] = movm(pk0[j]);
            attn_pair<2>(pk1, pk1 + 16, pk1 + 32, pk0 + 17, pk0 + 33, fu[1], fn[1], rk[1], 0.f, 0.f, mU, zero, ci, o);
            hand_over(0);
            TSC(elect, 3 + 8 * w);
#pragma unroll
            for (int j = 0; j < 32; j++) if (j < EARLY_PK || (!(j & 1) && EARLY_PK == 17)) pk0[j] = pack_here(acc0[2 * j], acc0[2 * j + 1]);
            factors(0);
            bar_sync(warp ? warp : 11, 64);
            uint32_t hl[16];
            ldsm4(hl, ha); ldsm4(hl + 4, ha + 512); ldsm4t(hl + 8, ha + 1024); ldsm4t(hl + 12, ha + 1536);
            __syncwarp();
            if (lane == 0) mbar_arrive(bars + 8 * B_FREED);
            attn_pair<1>(pk0, pk0 + 16, pk0 + 32, hl, hl + 8, fu[0], fn[0], rk[0], bias0, bias1, mU, zero, ci, o);
            const float2 s0 = lds2f(sb + OFF_STAT + (8 + r0) * 8), s1 = lds2f(sb + OFF_STAT + (16 + r0) * 8);
            const float m0 = s0.x * s0.y, f0 = 1.f + s0.y, m1 = s1.x * s1.y, f1 = 1.f + s1.y;
            uint32_t xt[32];
#pragma unroll
            for (int j = 0; j < 8; j++) ldsm4(xt + 4 * j, ((ring + wi * 2048 + mad) ^ ((j & 3) * 32)) + (j >> 2) * BOX);
            hand_over(1);
#pragma unroll
            for (int j = 0; j < 32; j++) {
                acc[2 * j] = fmaf(bf_lo(xt[j]), j & 1 ? f1 : f0, j & 1 ? m1 : m0); acc[2 * j + 1] = fmaf(bf_hi(xt[j]), j & 1 ? f1 : f0, j & 1 ? m1 : m0);
            }
        }
        TSC(tid == 0, 4);
        {
            const uint32_t da0 = sd + dlo(w * OFF_X1, 1024), db0 = sd + dlo(OFF_WO, BOX);
            const uint32_t chk = ring + wi * 256 + (lane >> 3) * 1032 + (lane & 7) * 32 + (lane & 4);
            uint32_t s8 = 16, ps8 = 0, ph = 0;
            mbar_wait(ofull + s8, 0, budget);
            mbar_wait(bars + 8 * B_WOFULL + s8, 0, budget);
            TSC(TIMING % 10 == 2 && elect, 32 + w * 16);
            const uint32_t ahi = dhi(128, 0) | (budget >> 30), bhi = dhi(1024, 1) | (budget >> 30);
            const int last = w ? HOLD : 16;
            uint32_t rel = elect ? 0x7fe : 0;
#pragma unroll 1
            for (int i = 1;;) {
                const uint32_t da = da0 + s8 * (BOX >> 7), db = db0 + s8 * (BOX >> 6);
                wg_fence();
#pragma unroll
                for (int kk = 0; kk < 4; kk++) {
                    wgmma_n128<0, 1>(acc, mkdesc(da + kk * 128, ahi), mkdesc(db + kk * 128, bhi), 1);
                    if (kk & 1) wg_commit();
                }
                wg_wait<2>();
                if (rel & 1) { mbar_expect_tx(ofull + ps8, BOX); mbar_arrive_at(oempty + ps8); mbar_arrive(bars + 8 * B_WOEMPTY + ps8); }
                if (i == 16) break;
                rel >>= 1;
                ps8 = s8;
#pragma unroll 1
                do {
                    s8 = s8 == 40 ? 0 : s8 + 8;
                    if (s8 == 16) ph ^= 1;
                    uint32_t bad;
                    asm volatile("{\n.reg .pred p, q, r;\n.reg .u32 u, v;\nmbarrier.try_wait.parity.shared::cta.b64 q, [%2], %3;\nmbarrier.try_wait.parity.shared::cta.b64 p, [%1], %3;\n"
                                 "setp.ne.and.u32 r, %5, 1, p;\nmov.u32 u, 1;\nmov.u32 v, 1;\n@r ld.shared.u32 u, [%4];\n@r ld.shared.u32 v, [%4 + 4096];\n"
                                 "and.pred p, p, q;\nmin.u32 u, u, v;\nsetp.eq.or.u32 p, u, 0, !p;\nvote.sync.any.pred p, p, 0xffffffff;\nselp.u32 %0, 1, 0, p;\n}"
                                 : "=r"(bad) : "r"(ofull + s8), "r"(bars + 8 * B_WOFULL + s8), "r"(ph), "r"(chk + s8 * (BOX / 8)), "r"(i) : "memory");
                    if (__builtin_expect(bad, 0)) {
                        mbar_wait(ofull + s8, ph, budget);
                        mbar_wait(bars + 8 * B_WOFULL + s8, ph, budget);
                        if (__any_sync(0xffffffffu, min(lds1(chk + s8 * (BOX / 8)), lds1(chk + s8 * (BOX / 8) + 4096)) == 0)) {
                            const uint32_t at = wi * 256 + (lane >> 4) * 1024 + (lane & 15) * 16;
                            const uint8_t* src = scr->o + ((size_t)((mt * 2 + rh) * 2 + 1 - w) * 16 + ((2 * p + (i < 2 ? i ^ hp : i)) & 15)) * BOX + at;
#pragma unroll 1
                            for (int n = 0; n < 8192; n += 2048) {
                                uint4 v; int tries = 4096;
#pragma unroll 1
                                do { v = ld_rlx4(src + n); } while (v.x == 0 && --tries > 0);
                                sts4(ring + s8 * (BOX / 8) + at + n, v.x, v.y, v.z, v.w);
                            }
                            NRETRY();
                            fence_async_smem();
                            __syncwarp();
                        }
                    }
                    TSC(TIMING % 10 == 1 && tid == 0, 48 + i);
                    TSC(TIMING % 10 == 2 && elect, 32 + w * 16 + i);
                } while (++i > last && i < 16);
                if (i > last) break;
                wg_wait<1>();
            }
            if (w) {
                bar_sync(9, 256);
#pragma unroll 1
                for (int i = HOLD - 10; i < 6; i++) {
                    wg_fence();
#pragma unroll
                    for (int kk = 0; kk < 4; kk++) wgmma_n128<0, 1>(acc, mkdesc(da0 + i * 512 + kk * 128, ahi), mkdesc(db0 + i * 1024 + kk * 128, bhi), 1);
                    wg_commit();
                }
            } else bar_arrive(9, 256);
            const bool add = (__shfl_sync(0xffffffffu, lds1(sb + OFF_SEL), 0) >> (wi * 2 + 1 - w)) & 1;
            wg_wait<0>();
            TSC(elect, 7 + 9 * w);
            const uint32_t os0 = ring + wi * 4096;
#pragma unroll
            for (int hf = 0; hf < OUT_PARTS; hf++) {
#pragma unroll
                for (int j = hf * (8 / OUT_PARTS); j < (hf + 1) * (8 / OUT_PARTS); j++)
                    stsm4(((os0 + mad) ^ ((j & 3) * 32)) + (j >> 2) * 2048, pack_here(acc[8 * j], acc[8 * j + 1]), pack_here(acc[8 * j + 2], acc[8 * j + 3]),
                          pack_here(acc[8 * j + 4], acc[8 * j + 5]), pack_here(acc[8 * j + 6], acc[8 * j + 7]));
                fence_async_smem();
                __syncwarp();
                if (elect_one())
                    asm volatile("{\n.reg .pred p;\nsetp.ne.b32 p, %6, 0;\n@!p cp.async.bulk.tensor.5d.global.shared::cta.bulk_group [%0, {%2, %2, %3, %4, %5}], [%1];\n"
                                 "@p cp.reduce.async.bulk.tensor.5d.global.shared::cta.add.bulk_group [%0, {%2, %2, %3, %4, %5}], [%1];\n}"
                                 ::"l"(&mout), "r"(os0 + hf * 2048), "r"(0), "r"(((j0 + rh * 128) >> 5) + wi), "r"(1 - w), "r"(par * 16 + cb * 2 + hf), "r"((int)add) : "memory");
            }
            asm volatile("cp.async.bulk.commit_group;\ncp.async.bulk.wait_group.read 0;" ::: "memory");
            if (b == 0 && tid == 0) st_rlx(&scr->epoch[0], lds1(sb + OFF_EP));
            TSC(elect, 8 - 2 * w);
            TS_END();
        }
    }
}

typedef CUresult (*EncodeFn)(CUtensorMap*, CUtensorMapDataType, cuuint32_t, void*, const cuuint64_t*, const cuuint64_t*, const cuuint32_t*,
                             const cuuint32_t*, CUtensorMapInterleave, CUtensorMapSwizzle, CUtensorMapL2promotion, CUtensorMapFloatOOBfill);

CUtensorMap make_map(EncodeFn fn, const void* base, int rank, const cuuint64_t* dims, const cuuint64_t* strides, const cuuint32_t* box,
                     CUtensorMapSwizzle swz = CU_TENSOR_MAP_SWIZZLE_128B, CUtensorMapL2promotion pro = CU_TENSOR_MAP_L2_PROMOTION_L2_256B) {
    CUtensorMap m;
    cuuint32_t es[5] = {1, 1, 1, 1, 1};
    fn(&m, CU_TENSOR_MAP_DATA_TYPE_BFLOAT16, rank, (void*)base, dims, strides, box, es, CU_TENSOR_MAP_INTERLEAVE_NONE,
       swz, pro, CU_TENSOR_MAP_FLOAT_OOB_FILL_NONE);
    return m;
}

}

extern "C" void kernel_launch(void* const* d_in, const int* in_sizes, int n_in, void* d_out, int out_size) {
    (void)in_sizes; (void)n_in; (void)out_size;
    const __nv_bfloat16* x = (const __nv_bfloat16*)d_in[0];
    const __nv_bfloat16* wqkv = (const __nv_bfloat16*)d_in[1];
    const __nv_bfloat16* wo = (const __nv_bfloat16*)d_in[2];
    const __nv_bfloat16* wr = (const __nv_bfloat16*)d_in[4];
    const __nv_bfloat16* wg = (const __nv_bfloat16*)d_in[5];
    const __nv_bfloat16* wu = (const __nv_bfloat16*)d_in[6];
    const __nv_bfloat16* wd = (const __nv_bfloat16*)d_in[7];
    static EncodeFn fn = nullptr;
    static Scratch* scr = nullptr;
    if (!fn) {
        void* p = nullptr; cudaDriverEntryPointQueryResult q;
        cudaGetDriverEntryPoint("cuTensorMapEncodeTiled", &p, cudaEnableDefault, &q);
        fn = (EncodeFn)p;
        cudaFuncSetAttribute(fused_kernel, cudaFuncAttributeMaxDynamicSharedMemorySize, SMEM_LAUNCH);
        cudaGetSymbolAddress((void**)&scr, g_scr);
    }
    const cuuint64_t xd[4] = {2048, 16, 32, 2}, xs[4] = {4096, 131072, 65536, 128}, od[5] = {64, 16, 32, 2, 32};
    const cuuint32_t xb[4] = {64, 16, 4, 1}, ob[5] = {64, 16, 1, 1, 2 / OUT_PARTS};
    const cuuint64_t wdm[3] = {1024, 1024, 3}, wst[2] = {6144, 2048};
    const cuuint32_t wb[3] = {64, 64, 3};
    const cuuint64_t wod[3] = {64, 1024, 16}, wdd[3] = {64, 3584, 16}, wos[2] = {2048, 128};
    const cuuint32_t wob[3] = {64, 64, 2}, wdb[3] = {64, 64, 1};
    CUtensorMap mx = make_map(fn, x, 4, xd, xs, xb), mw = make_map(fn, wqkv, 3, wdm, wst, wb);
    CUtensorMap mwo = make_map(fn, wo, 3, wod, wos, wob), mout = make_map(fn, d_out, 5, od, xs, ob);
    const int swap_gu = wu < wg;
    const cuuint64_t gd[3] = {3584, 1024, 2}, gst[2] = {7168, (cuuint64_t)(swap_gu ? (const char*)wg - (const char*)wu : (const char*)wu - (const char*)wg)};
    const cuuint32_t gb[3] = {32, 64, 2};
    CUtensorMap mgu = make_map(fn, swap_gu ? wu : wg, 3, gd, gst, gb, CU_TENSOR_MAP_SWIZZLE_64B, CU_TENSOR_MAP_L2_PROMOTION_L2_128B);
    CUtensorMap mwd = make_map(fn, wd, 3, wdd, wos, wdb, CU_TENSOR_MAP_SWIZZLE_128B, CU_TENSOR_MAP_L2_PROMOTION_L2_128B);
    const cuuint64_t md[2] = {64, 32768}, ms[1] = {128};
    const cuuint32_t mb[2] = {64, 64};
    CUtensorMap mo = make_map(fn, scr, 2, md, ms, mb, CU_TENSOR_MAP_SWIZZLE_NONE, CU_TENSOR_MAP_L2_PROMOTION_NONE);
    const cuuint64_t rd[2] = {1024, 2048};
    const cuuint32_t rb[2] = {256, 16};
    CUtensorMap mr = make_map(fn, x, 2, rd, wos, rb, CU_TENSOR_MAP_SWIZZLE_NONE);
    cudaLaunchConfig_t cfg = {};
    cfg.gridDim = dim3(132); cfg.blockDim = dim3(512); cfg.dynamicSmemBytes = SMEM_LAUNCH; cfg.stream = cudaStreamPerThread;
    cudaLaunchAttribute at[1];
    at[0].id = cudaLaunchAttributeClusterDimension; at[0].val.clusterDim.x = 2; at[0].val.clusterDim.y = 1; at[0].val.clusterDim.z = 1;
    cfg.attrs = at; cfg.numAttrs = 1;
    cudaLaunchKernelEx(&cfg, fused_kernel, mx, mw, mwo, mout, mgu, mwd, mo, mr, x, wr, scr, swap_gu, Weights{(const char*)wqkv, (const char*)wo, (const char*)wg, (const char*)wu, (const char*)wd, (char*)d_out});
}
```

```cpp
#include <cuda_runtime.h>
#include <cuda.h>
#include <cuda_bf16.h>
#include <stdint.h>

namespace {

constexpr int BOX = 8192, W_BYTES = 3 * BOX;
constexpr int OFF_X1 = 6 * BOX, OFF_FR = 12 * BOX, OFF_E = 16 * BOX, OFF_W = 19 * BOX;
constexpr int OFF_WO = OFF_E;
constexpr int OFF_HIN = OFF_FR + 2048, OFF_GU = OFF_HIN + 2048, OFF_FS = OFF_GU + 1024;
constexpr int F_BYTES = 9216;
constexpr int CS_BYTES = 3136;
constexpr int OFF_CS = OFF_FS + 5 * F_BYTES;
constexpr int OFF_STAT = 28 * BOX;
constexpr int OFF_SEL = OFF_STAT + 2112, OFF_EP = OFF_SEL + 4;
constexpr int OFF_BAR = OFF_SEL + 16;
constexpr int B_WFULL = 0, B_XFULL = 3, B_AUX = 15, B_XT = 16, B_ZERO = 17, B_WOFULL = 18, B_OFULL = 24, B_FFULL = 36, B_ROW = 41;
constexpr int B_WEMPTY = 48, B_F1DONE = 51, B_XEMPTY = 52, B_WOEMPTY = 58, B_OEMPTY = 64;
constexpr int B_G1DONE = 72, B_FEMPTY = 73, B_STAGED = 78, B_RDONE = 80, B_FREED = 81, NBAR = 84;
constexpr int SMEM_BYTES = OFF_BAR + NBAR * 8;
static_assert(OFF_FS + 3 * F_BYTES == OFF_E && OFF_CS + CS_BYTES <= OFF_W && SMEM_BYTES + 256 <= 232448 && OFF_BAR % 8 == 0, "smem");
#define POLL_NS 30
#define PF_RATE 10
#define PF_START 7
#define ZF_NS 100
#define FFN2_GATE (B_STAGED + 1)
#define PF_NW 6
#define EARLY_PK 17
#define ZF_GATE (B_ROW + 3)
#define HOLD 12
#define F2_DEPTH 0
#define OUT_PARTS 2
#define PF_D 8
#define NM 4
#define N7 8
#define H_NS 400
#define ROWS_AT 0x280
constexpr int NH = 56 - 7 * NM - N7;
constexpr int BUDGET = 1 << 18;

struct Scratch {
    uint8_t o[2048 * 1024 * 2];
    uint4 ypart[8][16][128];
    uint32_t halo[128][512];
    uint32_t act[2][14336 + 4096];
    uint2 row[2048];
    uint4 cs[16][3][24];
    uint32_t oflag[16][32];
    uint32_t cnt[10][32];
    uint32_t sel[32], zflag[32], epoch[32];
};
__device__ __align__(1024) Scratch g_scr;
struct Weights { const char *wqkv, *wo, *wg, *wu, *wd; char* out; };

#define TS(i) do {} while (0)
#define TS_END() do {} while (0)
#define TSC(c, i) do {} while (0)
#define NRETRY() do {} while (0)
constexpr int SMEM_LAUNCH = SMEM_BYTES;
__device__ __forceinline__ uint32_t smem_u32(const void* p) { return (uint32_t)__cvta_generic_to_shared(p); }
__device__ __forceinline__ void mbar_init(uint32_t bar, uint32_t cnt) { asm volatile("mbarrier.init.shared::cta.b64 [%0], %1;" ::"r"(bar), "r"(cnt) : "memory"); }
__device__ __forceinline__ void mbar_expect_tx(uint32_t bar, uint32_t bytes) { asm volatile("mbarrier.arrive.expect_tx.shared::cta.b64 _, [%0], %1;" ::"r"(bar), "r"(bytes) : "memory"); }
__device__ __forceinline__ void mbar_arrive(uint32_t bar) { asm volatile("mbarrier.arrive.shared::cta.b64 _, [%0];" ::"r"(bar) : "memory"); }
__device__ __forceinline__ uint32_t mapa(uint32_t a, uint32_t cta) { uint32_t r; asm("mapa.shared::cluster.u32 %0, %1, %2;" : "=r"(r) : "r"(a), "r"(cta)); return r; }
__device__ __forceinline__ void mbar_arrive_at(uint32_t cbar) { asm volatile("mbarrier.arrive.shared::cluster.b64 _, [%0];" ::"r"(cbar) : "memory"); }
__device__ __forceinline__ void mbar_wait(uint32_t bar, uint32_t parity, int& budget) {
    asm volatile("{\n.reg .pred p;\nLAB_WAIT:\nmbarrier.try_wait.parity.shared::cta.b64 p, [%1], %2;\n"
                 "add.s32 %0, %0, -1;\nsetp.gt.and.s32 p, %0, 0, !p;\n@p bra LAB_WAIT;\n}" : "+r"(budget) : "r"(bar), "r"(parity) : "memory");
}
__device__ __forceinline__ void mbar_wait_hot(uint32_t bar, uint32_t parity, int& budget) {
    asm volatile("{\n.reg .pred p;\nmbarrier.try_wait.parity.shared::cta.b64 p, [%1], %2;\n@p bra LAB_DONE;\nLAB_WAIT:\nmbarrier.try_wait.parity.shared::cta.b64 p, [%1], %2;\n"
                 "add.s32 %0, %0, -1;\nsetp.gt.and.s32 p, %0, 0, !p;\n@p bra LAB_WAIT;\nLAB_DONE:\n}" : "+r"(budget) : "r"(bar), "r"(parity) : "memory");
}
__device__ __forceinline__ void tma_2d(uint32_t dst, const CUtensorMap* m, uint32_t bar, int c0, int c1) {
    asm volatile("cp.async.bulk.tensor.2d.shared::cluster.global.mbarrier::complete_tx::bytes [%0], [%1, {%3, %4}], [%2];" ::"r"(dst), "l"(m), "r"(bar), "r"(c0), "r"(c1) : "memory");
}
__device__ __forceinline__ void tma_2d_mc(uint32_t dst, const CUtensorMap* m, uint32_t bar, int c0, int c1) {
    asm volatile("cp.async.bulk.tensor.2d.shared::cluster.global.mbarrier::complete_tx::bytes.multicast::cluster [%0], [%1, {%3, %4}], [%2], %5;" ::"r"(dst), "l"(m), "r"(bar), "r"(c0), "r"(c1), "h"((uint16_t)3) : "memory");
}
__device__ __forceinline__ void tma_3d(uint32_t dst, const CUtensorMap* m, uint32_t bar, int c0, int c1, int c2) {
    asm volatile("cp.async.bulk.tensor.3d.shared::cluster.global.mbarrier::complete_tx::bytes [%0], [%1, {%3, %4, %5}], [%2];" ::"r"(dst), "l"(m), "r"(bar), "r"(c0), "r"(c1), "r"(c2) : "memory");
}
__device__ __forceinline__ void tma_4d(uint32_t dst, const CUtensorMap* m, uint32_t bar, int c0, int c1, int c2, int c3) {
    asm volatile("cp.async.bulk.tensor.4d.shared::cluster.global.mbarrier::complete_tx::bytes [%0], [%1, {%3, %4, %5, %6}], [%2];" ::"r"(dst), "l"(m), "r"(bar), "r"(c0), "r"(c1), "r"(c2), "r"(c3) : "memory");
}
__device__ __forceinline__ void tma_4d_mc(uint32_t dst, const CUtensorMap* m, uint32_t bar, int c0, int c1, int c2, int c3) {
    asm volatile("cp.async.bulk.tensor.4d.shared::cluster.global.mbarrier::complete_tx::bytes.multicast::cluster [%0], [%1, {%3, %4, %5, %6}], [%2], %7;" ::"r"(dst), "l"(m), "r"(bar), "r"(c0), "r"(c1), "r"(c2), "r"(c3), "h"((uint16_t)3) : "memory");
}
__device__ __forceinline__ void bulk_pf(const void* p, uint32_t bytes) { asm volatile("cp.async.bulk.prefetch.L2.global [%0], %1;" ::"l"(p), "r"(bytes) : "memory"); }
__device__ __forceinline__ void bulk_g2s(uint32_t dst, const void* src, uint32_t bytes, uint32_t bar) {
    asm volatile("cp.async.bulk.shared::cluster.global.mbarrier::complete_tx::bytes [%0], [%1], %2, [%3];" ::"r"(dst), "l"(src), "r"(bytes), "r"(bar) : "memory");
}
__device__ __forceinline__ void bulk_s2c(uint32_t cdst, uint32_t src, uint32_t bytes, uint32_t cbar) {
    asm volatile("cp.async.bulk.shared::cluster.shared::cta.mbarrier::complete_tx::bytes [%0], [%1], %2, [%3];" ::"r"(cdst), "r"(src), "r"(bytes), "r"(cbar) : "memory");
}
__device__ __forceinline__ void cluster_wait() { asm volatile("barrier.cluster.wait.aligned;" ::: "memory"); }
__device__ __forceinline__ void fence_gpu() { asm volatile("fence.acq_rel.gpu;" ::: "memory"); }
__device__ __forceinline__ void fence_async_smem() { asm volatile("fence.proxy.async.shared::cta;" ::: "memory"); }
__device__ __forceinline__ void wg_fence() { asm volatile("wgmma.fence.sync.aligned;" ::: "memory"); }
__device__ __forceinline__ void wg_commit() { asm volatile("wgmma.commit_group.sync.aligned;" ::: "memory"); }
template <int N> __device__ __forceinline__ void wg_wait() { asm volatile("wgmma.wait_group.sync.aligned %0;" ::"n"(N) : "memory"); }
__device__ __forceinline__ uint64_t mkdesc(uint32_t lo, uint32_t hi) { return ((uint64_t)hi << 32) | lo; }
__host__ __device__ constexpr uint32_t dhi(uint32_t sbo, uint32_t mode) { return (sbo >> 4) | (mode << 30); }
__host__ __device__ constexpr uint32_t dlo(uint32_t off, uint32_t lbo) { return (off >> 4) + ((lbo >> 4) << 16); }
__device__ __forceinline__ bool elect_one() {
    uint32_t e;
    asm volatile("{\n.reg .pred p;\nelect.sync _|p, 0xffffffff;\nselp.u32 %0, 1, 0, p;\n}" : "=r"(e));
    return e;
}
template <int R> __device__ __forceinline__ void reg_inc() { asm volatile("setmaxnreg.inc.sync.aligned.u32 %0;" ::"n"(R)); }
template <int R> __device__ __forceinline__ void reg_dec() { asm volatile("setmaxnreg.dec.sync.aligned.u32 %0;" ::"n"(R)); }
__device__ __forceinline__ void bar_sync(int id, int n) { asm volatile("bar.sync %0, %1;" ::"r"(id), "r"(n) : "memory"); }
__device__ __forceinline__ void bar_arrive(int id, int n) { asm volatile("bar.arrive %0, %1;" ::"r"(id), "r"(n) : "memory"); }
__device__ __forceinline__ uint32_t pack_bf16(float lo, float hi) { uint32_t r; asm("cvt.rn.bf16x2.f32 %0, %1, %2;" : "=r"(r) : "f"(hi), "f"(lo)); return r; }
__device__ __forceinline__ uint32_t pack_here(float lo, float hi) { uint32_t r; asm volatile("cvt.rn.bf16x2.f32 %0, %1, %2;" : "=r"(r) : "f"(hi), "f"(lo)); return r; }
__device__ __forceinline__ float bf_lo(uint32_t u) { return __uint_as_float(u << 16); }
__device__ __forceinline__ float bf_hi(uint32_t u) { return __uint_as_float(u & 0xffff0000u); }
__device__ __forceinline__ float bf16r(float v) { return bf_lo(pack_bf16(v, 0.f)); }
__device__ __forceinline__ float rcp(float x) { float r; asm("rcp.approx.ftz.f32 %0, %1;" : "=f"(r) : "f"(x)); return r; }
__device__ __forceinline__ float ex2(float x) { float r; asm("ex2.approx.ftz.f32 %0, %1;" : "=f"(r) : "f"(x)); return r; }
__device__ __forceinline__ float sigmoidf(float v) { return rcp(1.f + ex2(v * -1.4426950408889634f)); }
__device__ __forceinline__ uint32_t movm(uint32_t a) { uint32_t d; asm volatile("movmatrix.sync.aligned.m8n8.trans.b16 %0, %1;" : "=r"(d) : "r"(a)); return d; }
__device__ __forceinline__ void mma16816(float (&c)[4], uint32_t a0, uint32_t a1, uint32_t a2, uint32_t a3, uint32_t b0, uint32_t b1) {
    asm volatile("mma.sync.aligned.m16n8k16.row.col.f32.bf16.bf16.f32 {%0,%1,%2,%3}, {%4,%5,%6,%7}, {%8,%9}, {%0,%1,%2,%3};"
                 : "+f"(c[0]), "+f"(c[1]), "+f"(c[2]), "+f"(c[3]) : "r"(a0), "r"(a1), "r"(a2), "r"(a3), "r"(b0), "r"(b1));
}
__device__ __forceinline__ void mma1688(float (&c)[4], uint32_t a0, uint32_t a1, uint32_t b0) {
    asm volatile("mma.sync.aligned.m16n8k8.row.col.f32.bf16.bf16.f32 {%0,%1,%2,%3}, {%4,%5}, {%6}, {%0,%1,%2,%3};"
                 : "+f"(c[0]), "+f"(c[1]), "+f"(c[2]), "+f"(c[3]) : "r"(a0), "r"(a1), "r"(b0));
}
__device__ __forceinline__ void stsm4(uint32_t a, uint32_t r0, uint32_t r1, uint32_t r2, uint32_t r3) {
    asm volatile("stmatrix.sync.aligned.m8n8.x4.shared.b16 [%0], {%1,%2,%3,%4};" ::"r"(a), "r"(r0), "r"(r1), "r"(r2), "r"(r3) : "memory");
}
__device__ __forceinline__ void ldsm4(uint32_t* r, uint32_t a) {
    asm volatile("ldmatrix.sync.aligned.m8n8.x4.shared.b16 {%0,%1,%2,%3}, [%4];" : "=r"(r[0]), "=r"(r[1]), "=r"(r[2]), "=r"(r[3]) : "r"(a) : "memory");
}
__device__ __forceinline__ void ldsm4t(uint32_t* r, uint32_t a) {
    asm volatile("ldmatrix.sync.aligned.m8n8.x4.trans.shared.b16 {%0,%1,%2,%3}, [%4];" : "=r"(r[0]), "=r"(r[1]), "=r"(r[2]), "=r"(r[3]) : "r"(a) : "memory");
}
__device__ __forceinline__ uint32_t ld_rlx(const void* p) { uint32_t v; asm volatile("ld.relaxed.gpu.global.u32 %0, [%1];" : "=r"(v) : "l"(p) : "memory"); return v; }
__device__ __forceinline__ uint32_t ld_acq(const void* p) { uint32_t v; asm volatile("ld.acquire.gpu.global.u32 %0, [%1];" : "=r"(v) : "l"(p) : "memory"); return v; }
__device__ __forceinline__ uint2 ld_rlx2(const void* p) { uint2 v; asm volatile("ld.relaxed.gpu.global.v2.u32 {%0,%1}, [%2];" : "=r"(v.x), "=r"(v.y) : "l"(p) : "memory"); return v; }
__device__ __forceinline__ uint4 ld_rlx4(const void* p) { uint4 v; asm volatile("ld.relaxed.gpu.global.v4.u32 {%0,%1,%2,%3}, [%4];" : "=r"(v.x), "=r"(v.y), "=r"(v.z), "=r"(v.w) : "l"(p) : "memory"); return v; }
__device__ __forceinline__ void st_rlx(void* p, uint32_t v) { asm volatile("st.relaxed.gpu.global.u32 [%0], %1;" ::"l"(p), "r"(v) : "memory"); }
__device__ __forceinline__ void st_rlx2(void* p, uint32_t a, uint32_t b) { asm volatile("st.relaxed.gpu.global.v2.u32 [%0], {%1,%2};" ::"l"(p), "r"(a), "r"(b) : "memory"); }
__device__ __forceinline__ void st_rlx4(void* p, uint32_t a, uint32_t b, uint32_t c, uint32_t d) { asm volatile("st.relaxed.gpu.global.v4.u32 [%0], {%1,%2,%3,%4};" ::"l"(p), "r"(a), "r"(b), "r"(c), "r"(d) : "memory"); }
__device__ __forceinline__ void red_add(uint32_t* p) { asm volatile("red.relaxed.gpu.global.add.u32 [%0], 1;" ::"l"(p) : "memory"); }
__device__ __forceinline__ uint4 ldg_nc(const void* p) { uint4 v; asm volatile("ld.global.nc.v4.u32 {%0,%1,%2,%3}, [%4];" : "=r"(v.x), "=r"(v.y), "=r"(v.z), "=r"(v.w) : "l"(p)); return v; }
__device__ __forceinline__ void sts4(uint32_t a, uint32_t x, uint32_t y, uint32_t z, uint32_t w) { asm volatile("st.shared.v4.u32 [%0], {%1,%2,%3,%4};" ::"r"(a), "r"(x), "r"(y), "r"(z), "r"(w) : "memory"); }
__device__ __forceinline__ void sts2(uint32_t a, uint32_t x, uint32_t y) { asm volatile("st.shared.v2.u32 [%0], {%1,%2};" ::"r"(a), "r"(x), "r"(y) : "memory"); }
__device__ __forceinline__ void sts1(uint32_t a, uint32_t v) { asm volatile("st.shared.u32 [%0], %1;" ::"r"(a), "r"(v) : "memory"); }
__device__ __forceinline__ uint4 lds4(uint32_t a) { uint4 v; asm volatile("ld.shared.v4.u32 {%0,%1,%2,%3}, [%4];" : "=r"(v.x), "=r"(v.y), "=r"(v.z), "=r"(v.w) : "r"(a) : "memory"); return v; }
__device__ __forceinline__ float4 lds4f(uint32_t a) { float4 v; asm volatile("ld.shared.v4.f32 {%0,%1,%2,%3}, [%4];" : "=f"(v.x), "=f"(v.y), "=f"(v.z), "=f"(v.w) : "r"(a) : "memory"); return v; }
__device__ __forceinline__ float2 lds2f(uint32_t a) { float2 v; asm volatile("ld.shared.v2.f32 {%0,%1}, [%2];" : "=f"(v.x), "=f"(v.y) : "r"(a) : "memory"); return v; }
__device__ __forceinline__ float lds1f(uint32_t a) { float v; asm volatile("ld.shared.f32 %0, [%1];" : "=f"(v) : "r"(a) : "memory"); return v; }
__device__ __forceinline__ uint32_t lds1(uint32_t a) { uint32_t v; asm volatile("ld.shared.u32 %0, [%1];" : "=r"(v) : "r"(a) : "memory"); return v; }
__device__ __forceinline__ uint32_t redux_max(uint32_t v) { uint32_t r; asm volatile("redux.sync.max.u32 %0, %1, 0xffffffff;" : "=r"(r) : "r"(v)); return r; }
__device__ __forceinline__ uint32_t poll_all(const uint32_t* p, uint32_t mask, uint32_t want, int& budget) {
    uint32_t v;
#pragma unroll 1
    while (v = ld_acq(p), !__all_sync(0xffffffffu, (v & mask) == want) && --budget > 0) __nanosleep(POLL_NS);
    return v;
}

template <int TA, int TB>
__device__ __forceinline__ void wgmma_n192(float (&d)[96], uint64_t da, uint64_t db, int keep) {
    asm volatile("{\n.reg .pred p;\nsetp.ne.b32 p, %98, 0;\n"
        "wgmma.mma_async.sync.aligned.m64n192k16.f32.bf16.bf16 "
        "{%0, %1, %2, %3, %4, %5, %6, %7, %8, %9, %10, %11, %12, %13, %14, %15, "
        "%16, %17, %18, %19, %20, %21, %22, %23, %24, %25, %26, %27, %28, %29, %30, %31, "
        "%32, %33, %34, %35, %36, %37, %38, %39, %40, %41, %42, %43, %44, %45, %46, %47, "
        "%48, %49, %50, %51, %52, %53, %54, %55, %56, %57, %58, %59, %60, %61, %62, %63, "
        "%64, %65, %66, %67, %68, %69, %70, %71, %72, %73, %74, %75, %76, %77, %78, %79, "
        "%80, %81, %82, %83, %84, %85, %86, %87, %88, %89, %90, %91, %92, %93, %94, %95}, "
        "%96, %97, p, 1, 1, %99, %100;\n}\n"
        : "+f"(d[0]), "+f"(d[1]), "+f"(d[2]), "+f"(d[3]), "+f"(d[4]), "+f"(d[5]), "+f"(d[6]), "+f"(d[7]),
          "+f"(d[8]), "+f"(d[9]), "+f"(d[10]), "+f"(d[11]), "+f"(d[12]), "+f"(d[13]), "+f"(d[14]), "+f"(d[15]),
          "+f"(d[16]), "+f"(d[17]), "+f"(d[18]), "+f"(d[19]), "+f"(d[20]), "+f"(d[21]), "+f"(d[22]), "+f"(d[23]),
          "+f"(d[24]), "+f"(d[25]), "+f"(d[26]), "+f"(d[27]), "+f"(d[28]), "+f"(d[29]), "+f"(d[30]), "+f"(d[31]),
          "+f"(d[32]), "+f"(d[33]), "+f"(d[34]), "+f"(d[35]), "+f"(d[36]), "+f"(d[37]), "+f"(d[38]), "+f"(d[39]),
          "+f"(d[40]), "+f"(d[41]), "+f"(d[42]), "+f"(d[43]), "+f"(d[44]), "+f"(d[45]), "+f"(d[46]), "+f"(d[47]),
          "+f"(d[48]), "+f"(d[49]), "+f"(d[50]), "+f"(d[51]), "+f"(d[52]), "+f"(d[53]), "+f"(d[54]), "+f"(d[55]),
          "+f"(d[56]), "+f"(d[57]), "+f"(d[58]), "+f"(d[59]), "+f"(d[60]), "+f"(d[61]), "+f"(d[62]), "+f"(d[63]),
          "+f"(d[64]), "+f"(d[65]), "+f"(d[66]), "+f"(d[67]), "+f"(d[68]), "+f"(d[69]), "+f"(d[70]), "+f"(d[71]),
          "+f"(d[72]), "+f"(d[73]), "+f"(d[74]), "+f"(d[75]), "+f"(d[76]), "+f"(d[77]), "+f"(d[78]), "+f"(d[79]),
          "+f"(d[80]), "+f"(d[81]), "+f"(d[82]), "+f"(d[83]), "+f"(d[84]), "+f"(d[85]), "+f"(d[86]), "+f"(d[87]),
          "+f"(d[88]), "+f"(d[89]), "+f"(d[90]), "+f"(d[91]), "+f"(d[92]), "+f"(d[93]), "+f"(d[94]), "+f"(d[95])
        : "l"(da), "l"(db), "r"(keep), "n"(TA), "n"(TB));
}
template <int TA, int TB>
__device__ __forceinline__ void wgmma_n128(float (&d)[64], uint64_t da, uint64_t db, int keep) {
    asm volatile("{\n.reg .pred p;\nsetp.ne.b32 p, %66, 0;\n"
        "wgmma.mma_async.sync.aligned.m64n128k16.f32.bf16.bf16 "
        "{%0, %1, %2, %3, %4, %5, %6, %7, %8, %9, %10, %11, %12, %13, %14, %15, "
        "%16, %17, %18, %19, %20, %21, %22, %23, %24, %25, %26, %27, %28, %29, %30, %31, "
        "%32, %33, %34, %35, %36, %37, %38, %39, %40, %41, %42, %43, %44, %45, %46, %47, "
        "%48, %49, %50, %51, %52, %53, %54, %55, %56, %57, %58, %59, %60, %61, %62, %63}, "
        "%64, %65, p, 1, 1, %67, %68;\n}\n"
        : "+f"(d[0]), "+f"(d[1]), "+f"(d[2]), "+f"(d[3]), "+f"(d[4]), "+f"(d[5]), "+f"(d[6]), "+f"(d[7]),
          "+f"(d[8]), "+f"(d[9]), "+f"(d[10]), "+f"(d[11]), "+f"(d[12]), "+f"(d[13]), "+f"(d[14]), "+f"(d[15]),
          "+f"(d[16]), "+f"(d[17]), "+f"(d[18]), "+f"(d[19]), "+f"(d[20]), "+f"(d[21]), "+f"(d[22]), "+f"(d[23]),
          "+f"(d[24]), "+f"(d[25]), "+f"(d[26]), "+f"(d[27]), "+f"(d[28]), "+f"(d[29]), "+f"(d[30]), "+f"(d[31]),
          "+f"(d[32]), "+f"(d[33]), "+f"(d[34]), "+f"(d[35]), "+f"(d[36]), "+f"(d[37]), "+f"(d[38]), "+f"(d[39]),
          "+f"(d[40]), "+f"(d[41]), "+f"(d[42]), "+f"(d[43]), "+f"(d[44]), "+f"(d[45]), "+f"(d[46]), "+f"(d[47]),
          "+f"(d[48]), "+f"(d[49]), "+f"(d[50]), "+f"(d[51]), "+f"(d[52]), "+f"(d[53]), "+f"(d[54]), "+f"(d[55]),
          "+f"(d[56]), "+f"(d[57]), "+f"(d[58]), "+f"(d[59]), "+f"(d[60]), "+f"(d[61]), "+f"(d[62]), "+f"(d[63])
        : "l"(da), "l"(db), "r"(keep), "n"(TA), "n"(TB));
}
template <int TA, int TB>
__device__ __forceinline__ void wgmma_n8(float (&d)[4], uint64_t da, uint64_t db, int keep) {
    asm volatile("{\n.reg .pred p;\nsetp.ne.b32 p, %6, 0;\n"
        "wgmma.mma_async.sync.aligned.m64n8k16.f32.bf16.bf16 "
        "{%0, %1, %2, %3}, "
        "%4, %5, p, 1, 1, %7, %8;\n}\n"
        : "+f"(d[0]), "+f"(d[1]), "+f"(d[2]), "+f"(d[3])
        : "l"(da), "l"(db), "r"(keep), "n"(TA), "n"(TB));
}
__device__ __forceinline__ void wgmma_rs_n192(float (&d)[96], uint32_t a0, uint32_t a1, uint32_t a2, uint32_t a3, uint64_t db) {
    asm volatile("{\n.reg .pred p;\nsetp.ne.b32 p, 1, 0;\n"
        "wgmma.mma_async.sync.aligned.m64n192k16.f32.bf16.bf16 "
        "{%0, %1, %2, %3, %4, %5, %6, %7, %8, %9, %10, %11, %12, %13, %14, %15, "
        "%16, %17, %18, %19, %20, %21, %22, %23, %24, %25, %26, %27, %28, %29, %30, %31, "
        "%32, %33, %34, %35, %36, %37, %38, %39, %40, %41, %42, %43, %44, %45, %46, %47, "
        "%48, %49, %50, %51, %52, %53, %54, %55, %56, %57, %58, %59, %60, %61, %62, %63, "
        "%64, %65, %66, %67, %68, %69, %70, %71, %72, %73, %74, %75, %76, %77, %78, %79, "
        "%80, %81, %82, %83, %84, %85, %86, %87, %88, %89, %90, %91, %92, %93, %94, %95}, "
        "{%96, %97, %98, %99}, %100, p, 1, 1, 1;\n}\n"
        : "+f"(d[0]), "+f"(d[1]), "+f"(d[2]), "+f"(d[3]), "+f"(d[4]), "+f"(d[5]), "+f"(d[6]), "+f"(d[7]),
          "+f"(d[8]), "+f"(d[9]), "+f"(d[10]), "+f"(d[11]), "+f"(d[12]), "+f"(d[13]), "+f"(d[14]), "+f"(d[15]),
          "+f"(d[16]), "+f"(d[17]), "+f"(d[18]), "+f"(d[19]), "+f"(d[20]), "+f"(d[21]), "+f"(d[22]), "+f"(d[23]),
          "+f"(d[24]), "+f"(d[25]), "+f"(d[26]), "+f"(d[27]), "+f"(d[28]), "+f"(d[29]), "+f"(d[30]), "+f"(d[31]),
          "+f"(d[32]), "+f"(d[33]), "+f"(d[34]), "+f"(d[35]), "+f"(d[36]), "+f"(d[37]), "+f"(d[38]), "+f"(d[39]),
          "+f"(d[40]), "+f"(d[41]), "+f"(d[42]), "+f"(d[43]), "+f"(d[44]), "+f"(d[45]), "+f"(d[46]), "+f"(d[47]),
          "+f"(d[48]), "+f"(d[49]), "+f"(d[50]), "+f"(d[51]), "+f"(d[52]), "+f"(d[53]), "+f"(d[54]), "+f"(d[55]),
          "+f"(d[56]), "+f"(d[57]), "+f"(d[58]), "+f"(d[59]), "+f"(d[60]), "+f"(d[61]), "+f"(d[62]), "+f"(d[63]),
          "+f"(d[64]), "+f"(d[65]), "+f"(d[66]), "+f"(d[67]), "+f"(d[68]), "+f"(d[69]), "+f"(d[70]), "+f"(d[71]),
          "+f"(d[72]), "+f"(d[73]), "+f"(d[74]), "+f"(d[75]), "+f"(d[76]), "+f"(d[77]), "+f"(d[78]), "+f"(d[79]),
          "+f"(d[80]), "+f"(d[81]), "+f"(d[82]), "+f"(d[83]), "+f"(d[84]), "+f"(d[85]), "+f"(d[86]), "+f"(d[87]),
          "+f"(d[88]), "+f"(d[89]), "+f"(d[90]), "+f"(d[91]), "+f"(d[92]), "+f"(d[93]), "+f"(d[94]), "+f"(d[95])
        : "r"(a0), "r"(a1), "r"(a2), "r"(a3), "l"(db));
}

template <int HS>
__device__ __forceinline__ void attn_pair(const uint32_t* q, const uint32_t* k, const uint32_t* v, const uint32_t* kh, const uint32_t* vh,
                                          const float* fu, const float* fn, const float* rk, float bias0, float bias1, uint32_t mU, uint32_t zero, const float* ci, uint32_t* o) {
    float s0[2][4] = {}, s1[2][4] = {}, s2[2][4] = {};
#pragma unroll
    for (int n = 0; n < 4; n++) {
        const int hd = n & 1, a = 8 * hd + 2 * (n & 2);
        mma16816(s1[hd], q[a], q[a + 1], q[a + 2], q[a + 3], k[a], k[a + 2]);
        mma16816(s2[hd], q[a], q[a + 1], q[a + 2], q[a + 3], k[a + 1], k[a + 3]);
    }
#pragma unroll
    for (int n = 0; n < 4; n++) {
        const int hd = n & 1, a = 8 * hd + 2 * (n & 2);
        mma16816(s0[hd], q[a], q[a + 1], q[a + 2], q[a + 3], kh[HS * (a / 2)], kh[HS * (a / 2 + 1)]);
    }
    float e[2][4], m[2][2];
#pragma unroll
    for (int hd = 0; hd < 2; hd++) {
        e[hd][2] = fmaf(s1[hd][2], fu[2], s2[hd][2] * fn[2]); e[hd][3] = fmaf(s1[hd][3], fu[3], s2[hd][3] * fn[3]);
        e[hd][0] = fmaf(s0[hd][0], fu[0], fmaf(s1[hd][0], fn[0], bias0)); e[hd][1] = fmaf(s0[hd][1], fu[1], fmaf(s1[hd][1], fn[1], bias1));
        m[hd][1] = fmaxf(e[hd][2], e[hd][3]); m[hd][0] = fmaxf(e[hd][0], e[hd][1]);
    }
#pragma unroll
    for (int x = 1; x < 3; x++)
#pragma unroll
        for (int n = 0; n < 4; n++) m[n & 1][1 - (n >> 1)] = fmaxf(m[n & 1][1 - (n >> 1)], __shfl_xor_sync(0xffffffffu, m[n & 1][1 - (n >> 1)], x));
#pragma unroll
    for (int hd = 0; hd < 2; hd++) {
#pragma unroll
        for (int n = 0; n < 4; n++) e[hd][n] = ex2(e[hd][n] - m[hd][n >> 1]);
        float sum[4] = {};
        mma1688(sum, pack_bf16(e[hd][0], e[hd][1]), pack_bf16(e[hd][2], e[hd][3]), 0x3f803f80u);
        const float i0 = rcp(sum[0]), i1 = rcp(sum[2]);
        const uint32_t plo = pack_bf16(e[hd][0] * rk[0] * i0, e[hd][1] * rk[1] * i0), phi = pack_bf16(e[hd][2] * rk[2] * i1, e[hd][3] * rk[3] * i1);
        const uint32_t z0 = plo & zero, z1 = phi & zero;
        const uint32_t a0 = plo & ~mU, a1 = phi & mU, a3 = phi & ~mU, b0 = plo & mU;
#pragma unroll
        for (int jj = 0; jj < 4; jj++) {
            float c[4];
            asm volatile("mma.sync.aligned.m16n8k16.row.col.f32.bf16.bf16.f32 {%0,%1,%2,%3}, {%4,%5,%6,%7}, {%8,%9}, {%10,%11,%12,%13};"
                         : "=f"(c[0]), "=f"(c[1]), "=f"(c[2]), "=f"(c[3])
                         : "r"(a0), "r"(a1), "r"(z0), "r"(a3), "r"(v[8 * hd + 2 * jj]), "r"(v[8 * hd + 2 * jj + 1]), "f"(ci[0]), "f"(ci[1]), "f"(ci[2]), "f"(ci[3]));
            mma1688(c, b0, z1, vh[HS * (4 * hd + jj)]);
            o[8 * hd + 2 * jj] = pack_bf16(c[0], c[1]); o[8 * hd + 2 * jj + 1] = pack_bf16(c[2], c[3]);
        }
    }
}

__device__ __forceinline__ uint32_t norm_pair(uint32_t u, float m, float rinv) {
    const uint32_t d = pack_bf16(bf_lo(u) - m, bf_hi(u) - m);
    return max(pack_bf16(bf_lo(d) * rinv, bf_hi(d) * rinv), 1u);
}

__global__ void __launch_bounds__(512, 1)
fused_kernel(const __grid_constant__ CUtensorMap mx, const __grid_constant__ CUtensorMap mw, const __grid_constant__ CUtensorMap mwo,
             const __grid_constant__ CUtensorMap mout, const __grid_constant__ CUtensorMap mgu, const __grid_constant__ CUtensorMap mwd,
             const __grid_constant__ CUtensorMap mo, const __grid_constant__ CUtensorMap mr,
             const __nv_bfloat16* __restrict__ x, const __nv_bfloat16* __restrict__ wr, Scratch* __restrict__ scr, int swap_gu, const Weights pf) {
    extern __shared__ __align__(1024) uint8_t smem[];
    const uint32_t sb = smem_u32(smem);
    const uint32_t bars = sb + OFF_BAR;
    const int tid = threadIdx.x, lane = tid & 31, warp = __shfl_sync(0xffffffffu, tid >> 5, 0);
    const uint32_t sd = (sb & 0x3FFFF) >> 4;
    const int hp = blockIdx.x & 1, cl = blockIdx.x >> 1;
    int pr = cl - 4 + (max(cl - 36, 0) * 37 >> 8);
    asm("{\n.reg .pred p;\nsetp.lt.s32 p, %1, 4;\nselp.s32 %0, %2, %0, p;\n}" : "+r"(pr) : "r"(cl), "r"(39 + 8 * cl));
    const int b = pr * 2 + hp, mt = pr >> 3, p = pr & 7, nt = 2 * p + hp, rh = p & 1, cb = (p & 6) + hp;
    const int par = mt >> 2, j0 = (mt & 3) * 256;
    int budget = BUDGET;

    TSC(tid == 0, 0);
    auto load_w = [&](int k, int s) {
        const uint32_t full = bars + 8 * (B_WFULL + s);
        mbar_expect_tx(full, W_BYTES);
        tma_3d(sb + OFF_W + s * W_BYTES, &mw, full, nt * 64, k * 64, 0);
    };
    auto load_x = [&](int n) {
        const int w = n & 1, j = n < 4 ? (n >> 1) + 4 : (n >> 1) - 2;
        const uint32_t full = bars + 8 * (B_XFULL + w * 6 + 5 - j);
        mbar_expect_tx(full, BOX);
        tma_4d(sb + w * OFF_X1 + j * BOX, &mx, full, par * 1024 + (n >> 2) * 64, 0, (j0 + w * 128) >> 5, (~n >> 1) & 1);
    };
    if (warp < NBAR / 6 && elect_one()) {
        const uint32_t cnt = warp < B_WEMPTY / 6 ? 1 : warp < B_G1DONE / 6 ? 2 : warp < B_STAGED / 6 ? 4 : 8;
#pragma unroll
        for (int i = 0; i < 6; i++) mbar_init(bars + 48 * warp + 8 * i, cnt);
        asm volatile("fence.mbarrier_init.release.cluster;" ::: "memory");
        if (warp == 0 && b < 128) { load_x(0); load_w(0, 2); }
    }
    __syncthreads();

    if (b >= 128) {
        const int hc = b - 128, g = lane >> 2, t = lane & 3;
        const uint32_t ep = ld_rlx(&scr->epoch[0]) + 1;
        if (warp < 12) {
            const int n = warp / 3, part = warp - 3 * n;
            auto load = [&](int k) {
                const uint32_t full = bars + 8 * (2 * n + (k & 1));
                mbar_expect_tx(full, W_BYTES);
                tma_3d(sb + (2 * n + (k & 1)) * W_BYTES, &mw, full, (4 * hc + n) * 64, k * 64, 0);
            };
            if (part == 0 && elect_one()) { load(0); load(1); }
            __syncwarp();
            float c0[4] = {0.f, 0.f, 0.f, 0.f}, c1[4] = {0.f, 0.f, 0.f, 0.f};
            const uint32_t sel = g == 0 ? 0x3f80u : g == 1 ? 0x3f800000u : 0u;
            const uint32_t a = sb + 2 * n * W_BYTES + part * BOX + t * 256 + ((g ^ (2 * t)) << 4);
#pragma unroll 1
            for (int k = 0; k < 16; k++) {
                mbar_wait(bars + 8 * (2 * n + (k & 1)), (k >> 1) & 1, budget);
                uint4 v[8], u[8];
#pragma unroll
                for (int i = 0; i < 8; i++) { v[i] = lds4(a + (k & 1) * W_BYTES + i * 1024); u[i] = lds4(((a + 128) ^ 16) + (k & 1) * W_BYTES + i * 1024); }
#pragma unroll
                for (int i = 0; i < 8; i++) { mma16816(c0, v[i].x, v[i].y, u[i].x, u[i].y, sel, sel); mma16816(c1, v[i].z, v[i].w, u[i].z, u[i].w, sel, sel); }
                bar_sync(1 + n, 96);
                if (part == 0 && k < 14 && elect_one()) load(k + 2);
                __syncwarp();
            }
            if (t == 0) {
#pragma unroll
                for (int r = 0; r < 3; r++) {
                    const uint32_t q0 = (pack_bf16(c0[0], c0[1]) & ~1u) | (ep & 1), q1 = pack_bf16(c0[2], c0[3]), q2 = pack_bf16(c1[0], c1[1]), q3 = pack_bf16(c1[2], c1[3]);
                    st_rlx4(&scr->cs[4 * hc + n][r][part * 8 + g], q0, q1, q2, q3);
                    c0[0] -= bf_lo(q0); c0[1] -= bf_hi(q0); c0[2] -= bf_lo(q1); c0[3] -= bf_hi(q1);
                    c1[0] -= bf_lo(q2); c1[1] -= bf_hi(q2); c1[2] -= bf_lo(q3); c1[3] -= bf_hi(q3);
                }
            }
            TSC(tid == 0, 19);
        }
        {
            const int wg = warp >> 2, c2 = 4 * hc + wg, tw = tid & 127;
            const uint32_t ring = sb + wg * 6 * BOX, full = bars + 8 * (8 + wg * 6), ha = sb + 24 * BOX;
            const uint32_t* hsrc = scr->act[ep & 1] + (56 - NH) * 256;
            auto load = [&](int q, int s) { mbar_expect_tx(full + 8 * s, BOX); tma_3d(ring + s * BOX, &mwd, full + 8 * s, 0, (56 - NH + q) * 64, c2); };
            __syncthreads();
            const uint32_t key = poll_all(&scr->sel[lane & 7], 31u, ep & 31, budget);
            const int zr = (2047 - ((__shfl_sync(0xffffffffu, key, warp >> 1) >> 5) & 2047)) & ~30;
#pragma unroll
            for (int i = 0; i < 8; i++) st_rlx4(pf.out + (size_t)(zr + (warp & 1) * 16 + 2 * i) * 2048 + hc * 512 + lane * 16, 0, 0, 0, 0);
            __syncthreads();
            if (tid == 64) { fence_gpu(); st_rlx(&scr->zflag[hc], ep); }
            if ((warp & 3) == 0 && elect_one()) {
#pragma unroll 1
                for (int q = 0; q < 6; q++) { load(q, q); __nanosleep(H_NS); }
            }
            if (warp == 1 && elect_one()) {
                int tries = BUDGET;
#pragma unroll 1
                while (ld_rlx(&scr->cnt[8][0]) != ep * (4 * NH) && --tries > 0) {}
                mbar_expect_tx(bars + 8 * 32, NH * 1024);
                bulk_g2s(ha, hsrc, NH * 1024, bars + 8 * 32);
                TS(17);
            }
            __syncwarp();
            mbar_wait(bars + 8 * 32, 0, budget);
#pragma unroll 1
            for (int i = tid; i < NH * 64; i += 512) {
                int tries = BUDGET;
                if (lds1(ha + i * 16) == 0) {
                    uint4 v;
#pragma unroll 1
                    do { v = ld_rlx4(hsrc + i * 4); } while (v.x == 0 && --tries > 0);
                    sts4(ha + i * 16, v.x, v.y, v.z, v.w);
                }
            }
            fence_async_smem();
            __syncthreads();
            float acc[4] = {0.f, 0.f, 0.f, 0.f};
            int s = 0; uint32_t ph = 0;
#pragma unroll 1
            for (int q = 0; q < NH; q++) {
                mbar_wait(full + 8 * s, ph, budget);
                wg_fence();
#pragma unroll
                for (int j = 0; j < 4; j++)
                    wgmma_n8<1, 0>(acc, mkdesc(sd + dlo((wg * 6 + s) * BOX, BOX) + j * 128, dhi(1024, 1)), mkdesc(sd + dlo(24 * BOX + q * 1024, 128) + j * 16, dhi(128, 0)), 1);
                wg_commit();
                wg_wait<0>();
                bar_sync(1 + wg, 128);
                if ((warp & 3) == 0 && q + 6 < NH && elect_one()) load(q + 6, s);
                __syncwarp();
                if (++s == 6) { s = 0; ph ^= 1; }
            }
            TSC(tid == 0, 18);
            uint4 v[8]; uint32_t bad; int tries = BUDGET;
#pragma unroll 1
            do {
                bad = 0;
#pragma unroll
                for (int m = 0; m < 8; m++) v[m] = ld_rlx4(&scr->ypart[m][c2][tw]);
#pragma unroll
                for (int m = 0; m < 8; m++) bad |= v[m].x ^ ep;
            } while ((bad & 1) && --tries > 0);
            __syncwarp();
            const float sig = bf16r(sigmoidf(__uint_as_float(((int)key < 0 ? key & 0x7fffffffu : ~key) & 0xffff0000u)));
#pragma unroll
            for (int c = 0; c < 4; c++) {
#pragma unroll
                for (int m = 0; m < 8; m++) acc[c] += __uint_as_float((&v[m].x)[c]);
                acc[c] = bf16r(acc[c]) * __shfl_sync(0xffffffffu, sig, 2 * t + (c & 1));
            }
            char* dst = pf.out + (size_t)(2047 - ((__shfl_sync(0xffffffffu, key, g) >> 5) & 2047)) * 2048 + c2 * 128 + (warp & 3) * 32 + t * 4;
            asm volatile("red.relaxed.gpu.global.add.noftz.bf16x2 [%0], %1;" ::"l"(dst), "r"(movm(pack_bf16(acc[0], acc[1]))) : "memory");
            asm volatile("red.relaxed.gpu.global.add.noftz.bf16x2 [%0], %1;" ::"l"(dst + 16), "r"(movm(pack_bf16(acc[2], acc[3]))) : "memory");
            TSC(tid == 0, 20);
        }
        if (warp < 8) TS_END();
        return;
    }
    asm volatile("barrier.cluster.arrive.relaxed.aligned;" ::: "memory");

    const int c2 = b & 15, n2 = mt < 7 ? NM : N7;
    if (warp >= 12) {
        reg_dec<24>();
        if (warp == 12) {
            if (elect_one()) {
                int c = 0;
#pragma unroll 1
                for (int n = 1; n < 12; n++) {
                    load_x(n);
                    #pragma unroll 1
                    for (; c < (n == 11 ? 4 : __popc(ROWS_AT & ((2 << n) - 1))); c++) { mbar_expect_tx(bars + 8 * (B_ROW + c), BOX); tma_2d(sb + OFF_FR + c * BOX, &mr, bars + 8 * (B_ROW + c), c * 256, b * 16); }
                    if (n == 3 || n == 7) load_w((n + 1) >> 2, n >> 2);
                }
                int s = 2; uint32_t ph = 0;
#pragma unroll 1
                for (int k = 3; k < 16; k++) {
                    mbar_wait(bars + 8 * (B_WEMPTY + s), ph, budget);
                    load_w(k, s);
                    if (++s == 3) s = 0;
                    if (s == 2) ph ^= 1;
                }
                s = 2;
#pragma unroll 1
                for (int i = 0; i < 16; i++) {
                    mbar_wait(bars + 8 * (i < 2 ? B_WEMPTY + i : i < 4 ? B_G1DONE : i < 6 ? B_F1DONE : B_WOEMPTY + s), i >= 12, budget);
                    if (i == 0) {
                        mbar_expect_tx(bars + 8 * B_XT, 4 * BOX);
#pragma unroll 1
                        for (int n = 0; n < 4; n++)
                            tma_4d(sb + (n >> 1) * OFF_X1 + (n & 1) * BOX, &mx, bars + 8 * B_XT, par * 1024 + cb * 128 + (n & 1) * 64, 0, (j0 + rh * 128) >> 5, 1 - (n >> 1));
                    }
                    const uint32_t full = bars + 8 * (B_WOFULL + s);
                    mbar_expect_tx(full, 2 * BOX);
                    tma_3d(sb + OFF_WO + s * 2 * BOX, &mwo, full, 0, ((2 * p + (i < 2 ? i ^ hp : i)) & 15) * 64, cb * 2);
                    TSC(TIMING % 10 == 4, 48 + i);
                    if (++s == 6) s = 0;
                }
            }
        } else {
            bar_sync(8, 224);
            const uint32_t ep = __shfl_sync(0xffffffffu, lds1(sb + OFF_EP), 0);
            if (warp == 13) {
                cluster_wait();
                if (elect_one()) {
                    int j = 4, q = 0, left = BUDGET; uint32_t ph = 0;
#pragma unroll 1
                    for (int n = 6; n < 32; n++) {
                        mbar_wait(bars + 8 * (B_XEMPTY + j), ph, left);
                        tma_4d_mc(sb + hp * OFF_X1 + j * BOX, &mx, bars + 8 * (B_XFULL + hp * 6 + 5 - j), par * 1024 + (n >> 1) * 64, 0, (j0 + hp * 128) >> 5, ~n & 1);
                        if (++j == 6) j = 0;
                        if (j == 4) ph ^= 1;
#pragma unroll 1
                        for (; q < (PF_RATE * (n - PF_START) >> 3) && q < 18 + PF_NW; q++) {
                            const int u = q - PF_NW;
                            if (u < 0) bulk_pf(pf.wqkv + (size_t)(1024 + 128 * u + b) * 6144, 6144);
                            else if (u < 16) bulk_pf((b < 64 ? pf.wg : pf.wu) + (size_t)(u * 64 + (b & 63)) * 7168, 7168);
                            else bulk_pf(pf.wo + (size_t)((u - 16) * 128 + b) * 8192, 8192);
                        }
                    }
                }
                __syncwarp();
                uint32_t* hs = &scr->halo[b - 16][lane * 4];
                uint4 v[4] = {};
                if (j0) {
#pragma unroll 1
                    do {
#pragma unroll
                        for (int c = 0; c < 4; c++) v[c] = ld_rlx4(hs + c * 128);
                    } while (__any_sync(0xffffffffu, min(min(v[0].x, v[1].x), min(v[2].x, v[3].x)) == 0) && --budget > 0);
                }
#pragma unroll
                for (int c = 0; c < 4; c++) stsm4(sb + OFF_HIN + c * 512 + lane * 16, v[c].x, v[c].y, v[c].z, v[c].w);
                bar_arrive(11, 64);
                if (j0) {
#pragma unroll
                    for (int c = 0; c < 4; c++) st_rlx(hs + c * 128, 0);
                }
                TSC(lane == 0, 31);
                const int src = ((mt * 2 + rh) * 2 + 1 - hp) * 1024;
                if (elect_one()) {
                    const uint32_t* fl = &scr->oflag[mt * 2 + 1 - hp][0];
                    const uint32_t inv = (ep & 1) - 1;
                    uint32_t ready = 0, ph = 0;
                    int s = 4;
#pragma unroll 1
                    for (int i = 2; i < 16; i++) {
                        const int kb = (2 * p + i) & 15;
#pragma unroll 1
                        while (!((ready >> kb) & 1) && --budget > 0) ready = ld_rlx(fl) ^ inv;
                        TSC(i == 2, 30);
                        mbar_wait(bars + 8 * (B_OEMPTY + s), ph, budget);
                        tma_2d_mc(sb + hp * OFF_X1 + s * BOX, &mo, bars + 8 * (B_OFULL + hp * 6 + s), 0, src + kb * 64);
                        TSC(TIMING % 10 == 4 && hp == 0, 32 + i);
                        if (++s == 6) s = 0;
                        if (s == 4) ph ^= 1;
                    }
                }
            } else if (warp == 14) {
                if (elect_one()) {
                    uint32_t s8 = 0, ph = 0;
                    int tries = BUDGET;
                    const uint32_t* act = scr->act[ep & 1];
                    auto counted = [&](int c, uint32_t n) {
#pragma unroll 1
                        while (ld_rlx(&scr->cnt[c][0]) != ep * n && --tries > 0) __nanosleep(POLL_NS);
                    };
                    auto weights = [&](const CUtensorMap* m, int c0, int c1, int c2_) {
                        mbar_wait(bars + 8 * B_FEMPTY + s8, ph, budget);
                        mbar_expect_tx(bars + 8 * B_FFULL + s8, F_BYTES);
                        tma_3d(sb + OFF_FS + s8 * (F_BYTES / 8), m, bars + 8 * B_FFULL + s8, c0, c1, c2_);
                    };
                    if (b < 112) {
                        counted(9, 32);
                        TS(26);
#pragma unroll 1
                        for (int q = 0; q < 16; q++) {
                            weights(&mgu, b * 32, q * 64, 0);
                            bulk_g2s(sb + OFF_FS + BOX + s8 * (F_BYTES / 8), act + 14336 + q * 256, 1024, bars + 8 * B_FFULL + s8);
                            TSC(TIMING % 10 == 5, 32 + q);
                            if (q >= PF_D && q < PF_D + 8) bulk_pf(pf.wd + (size_t)((q - PF_D) * 112 + b) * 8192, 8192);
                            s8 += 8;
                            if (s8 == 40) { s8 = 0; ph ^= 1; }
                        }
                    }
#pragma unroll 1
                    for (int q = -3; q < n2; q++) {
                        if (q == 0) { counted(mt, 4 * n2); TS(29); }
                        if ((unsigned)q >= 3) weights(&mwd, 0, (mt * NM + (q < 0 ? q + 3 : q)) * 64, c2);
                        if (q >= 0) bulk_g2s(sb + OFF_FS + BOX + s8 * (F_BYTES / 8), act + (mt * NM + q) * 256, 1024, bars + 8 * B_FFULL + s8);
                        TSC(TIMING % 10 == 5, 51 + q);
                        s8 += 8;
                        if (s8 == 24) { s8 = 0; if ((unsigned)q >= 3) ph ^= 1; }
                    }
                }
            } else {
#pragma unroll 1
                for (int i = lane * 16; i < CS_BYTES; i += 512) sts4(sb + OFF_CS + i, 0, 0, 0, 0);
                mbar_wait(bars + 8 * ZF_GATE, 0, budget);
                uint8_t* oz = scr->o + ((size_t)mt * 64 + nt) * BOX + lane * 16;
#pragma unroll 1
                for (int i = 0; i < 16; i++, oz += 512) {
#pragma unroll
                    for (int n = 0; n < 4; n++) st_rlx4(oz + n * 16 * BOX, 0, 0, 0, 0);
                    __nanosleep(ZF_NS);
                }
                __syncwarp();
                fence_gpu();
                mbar_wait(bars + 8 * B_RDONE, 0, budget);
                int tries = BUDGET;
#pragma unroll 1
                for (int i = lane; i < 88; i += 32) {
                    const uint2* rp = &scr->row[2 * (j0 - 8 + i) + par];
                    uint2 v0, v1, v2;
#pragma unroll 1
                    do { v0 = ld_rlx2(rp + (j0 + i < 8 ? 16 : 0)); v1 = ld_rlx2(rp + 176); v2 = ld_rlx2(rp + 352); } while ((((v0.y ^ ep) | (v1.y ^ ep) | (v2.y ^ ep)) & 31) && --tries > 0);
                    sts2(sb + OFF_STAT + i * 8, (v0.x << 16) ^ 0x80000000u, __float_as_uint(rcp(bf_hi(v0.x))));
                    sts2(sb + OFF_STAT + i * 8 + 704, (v1.x << 16) ^ 0x80000000u, __float_as_uint(rcp(bf_hi(v1.x))));
                    sts2(sb + OFF_STAT + i * 8 + 1408, (v2.x << 16) ^ 0x80000000u, __float_as_uint(rcp(bf_hi(v2.x))));
                }
                __syncwarp();
                {
                    const int row = 2047 - ((poll_all(&scr->sel[lane & 7], 31u, ep & 31, budget) >> 5) & 2047), jj = (row >> 1) - j0 - rh * 128;
                    sts1(sb + OFF_SEL, __reduce_or_sync(0xffffffffu, (row & 1) == par && (unsigned)jj < 128 ? 1u << (jj >> 4) : 0u));
                }
                if (lane < 24) {
                    uint4 v[3];
#pragma unroll 1
                    while (v[0] = ld_rlx4(&scr->cs[nt][0][lane]), v[1] = ld_rlx4(&scr->cs[nt][1][lane]), v[2] = ld_rlx4(&scr->cs[nt][2][lane]),
                           (((v[0].x ^ ep) | (v[1].x ^ ep) | (v[2].x ^ ep)) & 1) && --tries > 0) __nanosleep(100);
#pragma unroll
                    for (int r = 0; r < 3; r++) sts4(sb + OFF_CS + 64 + lane * 128 + r * 16, v[r].x, v[r].y, v[r].z, v[r].w);
                }
                fence_async_smem();
                __syncwarp();
                if (elect_one()) {
                    mbar_arrive(bars + 8 * B_AUX);
                    TS(21);
                    mbar_expect_tx(bars + 8 * (B_OFULL + 3), BOX); mbar_expect_tx(bars + 8 * (B_OFULL + 9), BOX);
#pragma unroll 1
                    for (int v = 0; v < 2; v++) {
                        const uint32_t ring = sb + v * OFF_X1 + 2 * BOX, fb = bars + 8 * (B_OFULL + v * 6 + 2);
                        mbar_wait(bars + 8 * (B_STAGED + v), 0, budget);
                        asm volatile("red.relaxed.gpu.global.xor.b32 [%0], %1;" ::"l"(&scr->oflag[mt * 2 + 1 - v][0]), "r"(1u << nt) : "memory");
                        TS(13 + 2 * v);
                        mbar_arrive(fb);
                        mbar_wait(bars + 8 * B_G1DONE, 0, budget);
                        bulk_s2c(mapa(ring + BOX, hp ^ 1), ring, BOX, mapa(fb + 8, hp ^ 1));
                        if (v == 0) mbar_wait(bars + 8 * B_FREED, 0, budget);
#pragma unroll
                        for (int n = 0; n < 4; n++) {
                            mbar_expect_tx(bars + 8 * (B_OFULL + (n >> 1) * 6 + 4 + (n & 1)) - v * 32, BOX);
                            mbar_arrive_at(mapa(bars + 8 * B_OEMPTY, n >> 1) + (4 + (n & 1)) * 8 - v * 32);
                        }
                    }
                    if (lds1(sb + OFF_SEL)) {
#pragma unroll 1
                        while (ld_acq(&scr->zflag[p >> 1]) != ep && --tries > 0) {}
                        asm volatile("fence.proxy.async.global;" ::: "memory");
                    }
                    mbar_arrive(bars + 8 * B_ZERO);
                }
            }
        }
    } else if (warp >= 8) {
        reg_dec<40>();
        const int wq = warp - 8, ta = tid - 256;
        const uint32_t rbuf = sb + OFF_FR + wq * 2048;
        const uint4 wv = ldg_nc(wr + ta * 8);
        if (ta == 0) sts1(sb + OFF_EP, ld_rlx(&scr->epoch[0]) + 1);
        sts4(sb + OFF_STAT + ta * 16, wv.x, wv.y, wv.z, wv.w);
        bar_sync(8, 224);
        const uint32_t ep = __shfl_sync(0xffffffffu, lds1(sb + OFF_EP), 0);
        {
            const int s = b * 16 + wq * 4 + (lane >> 3);
            if ((lane & 7) == 0) st_rlx2(&scr->row[s], 0, ep - 1);
            float sw = 0.f;
#pragma unroll 1
            for (int i = 0; i < 16; i++) { const uint32_t q = lds1(sb + OFF_STAT + i * 128 + lane * 4); sw += bf_lo(q) + bf_hi(q); }
#pragma unroll 1
            for (int o = 16; o > 0; o >>= 1) sw += __shfl_xor_sync(0xffffffffu, sw, o);
            float s1 = 0.f, s2 = 0.f, sr = 0.f;
            {
                float s1b = 0.f, s2b = 0.f, srb = 0.f;
                const uint32_t xb = rbuf + (lane >> 4) * 1024 + (lane & 15) * 16, wb = sb + OFF_STAT + (lane & 15) * 16;
#pragma unroll 1
                for (int i = 0; i < 8; i++) {
                    const uint4 w4 = lds4(wb + i * 256);
                    mbar_wait_hot(bars + 8 * (B_ROW + (i >> 1)), 0, budget);
                    TSC(ta == 0 && i == 0, 17);
                    const uint32_t o = (i >> 1) * BOX + (i & 1) * 256;
                    const uint4 u = lds4(xb + o), v = lds4(xb + o + 512);
#pragma unroll
                    for (int c = 0; c < 4; c++) {
                        const float w0 = bf_lo((&w4.x)[c]), w1 = bf_hi((&w4.x)[c]);
                        const float a0 = bf_lo((&u.x)[c]), a1 = bf_hi((&u.x)[c]), b0 = bf_lo((&v.x)[c]), b1 = bf_hi((&v.x)[c]);
                        s1 += a0; s2 = fmaf(a0, a0, s2); sr = fmaf(a0, w0, sr);
                        s1 += a1; s2 = fmaf(a1, a1, s2); sr = fmaf(a1, w1, sr);
                        s1b += b0; s2b = fmaf(b0, b0, s2b); srb = fmaf(b0, w0, srb);
                        s1b += b1; s2b = fmaf(b1, b1, s2b); srb = fmaf(b1, w1, srb);
                    }
                }
                const bool up = lane & 8;
                s1 = (up ? s1b : s1) + __shfl_xor_sync(0xffffffffu, up ? s1 : s1b, 8);
                s2 = (up ? s2b : s2) + __shfl_xor_sync(0xffffffffu, up ? s2 : s2b, 8);
                sr = (up ? srb : sr) + __shfl_xor_sync(0xffffffffu, up ? sr : srb, 8);
            }
#pragma unroll
            for (int o = 1; o < 8; o <<= 1) {
                s1 += __shfl_xor_sync(0xffffffffu, s1, o); s2 += __shfl_xor_sync(0xffffffffu, s2, o); sr += __shfl_xor_sync(0xffffffffu, sr, o);
            }
            const float mean = s1 * (1.f / 1024.f), mb = bf16r(mean);
            float var = fmaf(-mean, mean, s2 * (1.f / 1024.f));
            sr = fmaf(-mb, sw, sr);
            if (__builtin_expect(__any_sync(0xffffffffu, mean * mean > 256.f * var), 0)) {
                float a2 = 0.f, ar = 0.f;
#pragma unroll 1
                for (int i = 0; i < 64; i++) {
                    const uint32_t o = i * 32 + (lane & 7) * 4, q1 = lds1(rbuf + (lane >> 3) * 512 + (o >> 9) * BOX + (o & 511)), q2 = lds1(sb + OFF_STAT + o);
                    a2 = fmaf(bf_lo(q1) - mean, bf_lo(q1) - mean, fmaf(bf_hi(q1) - mean, bf_hi(q1) - mean, a2));
                    ar = fmaf(bf_lo(q1) - mb, bf_lo(q2), fmaf(bf_hi(q1) - mb, bf_hi(q2), ar));
                }
#pragma unroll 1
                for (int o = 1; o < 8; o <<= 1) { a2 += __shfl_xor_sync(0xffffffffu, a2, o); ar += __shfl_xor_sync(0xffffffffu, ar, o); }
                var = a2 * (1.f / 1024.f); sr = ar;
            }
            float den;
            asm("sqrt.approx.f32 %0, %1;" : "=f"(den) : "f"(bf16r(bf16r(var) + 1e-5f)));
            const uint32_t st = pack_bf16(mb, den);
            const uint32_t rb = pack_bf16(0.f, sr * rcp(bf_hi(st)) + 0.f);
            uint32_t ord = (int)rb < 0 ? ~rb & 0xffff0000u : rb | 0x80000000u;
            if ((rb & 0x7fffffffu) > 0x7f800000u) ord = 0;
            if ((lane & 7) == 0) st_rlx2(&scr->row[s], st, ord | ((2047 - s) << 5) | (ep & 31));
            __syncwarp();
            if (lane < 7) mbar_arrive(bars + 8 * (lane < 5 ? B_FEMPTY + lane : B_RDONE));
        }
        TSC(ta == 0, 18);
        if ((b >> 3) == 14) {
            const uint32_t gm = sb + OFF_E, cnt = gm + 64, res = gm + 80, list = gm + 128;
            uint32_t kv[16];
            int tries = BUDGET;
#pragma unroll 1
            do {
                uint32_t bad = 0;
#pragma unroll
                for (int n = 0; n < 16; n++) kv[n] = ld_rlx(&scr->row[n * 128 + ta].y);
#pragma unroll
                for (int n = 0; n < 16; n++) bad |= kv[n] ^ ep;
                if ((bad & 31) == 0) break;
            } while (--tries > 0);
            __syncwarp();
            TSC(ta == 0, 26);
            uint32_t m = 0;
#pragma unroll
            for (int n = 0; n < 16; n++) m = max(m, kv[n]);
            uint32_t gmax = m;
#pragma unroll
            for (int o = 1; o < 8; o <<= 1) gmax = max(gmax, __shfl_xor_sync(0xffffffffu, gmax, o));
            sts1(gm + (ta >> 3) * 4, gmax);
            sts1(cnt, 0);
            bar_sync(12, 128);
            const uint32_t c = lds1(gm + (lane & 15) * 4);
            int rank = 0;
#pragma unroll
            for (int i = 0; i < 2; i++) { const uint4 q = lds4(gm + (lane >> 4) * 32 + i * 16); rank += (q.x > c) + (q.y > c) + (q.z > c) + (q.w > c); }
            rank += __shfl_xor_sync(0xffffffffu, rank, 16);
            const uint32_t thr = redux_max(rank == 7 ? c : 0u);
#pragma unroll 1
            while (m >= thr) {
                uint32_t at, m2 = 0;
                asm volatile("atom.shared.add.u32 %0, [%1], 1;" : "=r"(at) : "r"(cnt) : "memory");
#pragma unroll
                for (int n = 0; n < 16; n++) m2 = max(m2, kv[n] < m ? kv[n] : 0u);
                sts1(list + at * 4, m);
                if (m2 == 0) break;
                m = m2;
            }
            bar_sync(12, 128);
            const int nc = lds1(cnt);
#pragma unroll 1
            for (int i = ta >> 3; i < ((nc + 3) & ~3); i += 16) {
                const uint32_t ki = lds1(list + i * 4);
                int r = 0;
#pragma unroll 1
                for (int n = lane & 7; n < nc; n += 8) r += lds1(list + n * 4) > ki;
                __syncwarp();
#pragma unroll
                for (int o = 1; o < 8; o <<= 1) r += __shfl_xor_sync(0xffffffffu, r, o);
                if (r == (b & 7) && i < nc) sts1(res, ki);
            }
            bar_sync(12, 128);
            const uint32_t k0 = lds1(res);
            const int r0 = 2047 - ((k0 >> 5) & 2047);
            TSC(ta == 0, 22);
            if (ta == 0) st_rlx(&scr->sel[b & 7], k0);
            const uint4 v0 = ldg_nc(x + (size_t)r0 * 1024 + ta * 8);
            const uint32_t s0 = ld_rlx(&scr->row[r0]);
            const float m0 = bf_lo(s0), i0 = rcp(bf_hi(s0));
            const int ao = 14336 + (ta >> 3) * 256 + (b & 7) * 32 + ((ta ^ b) & 7) * 4;
            st_rlx4(scr->act[ep & 1] + ao, norm_pair(v0.x, m0, i0), norm_pair(v0.y, m0, i0), norm_pair(v0.z, m0, i0), norm_pair(v0.w, m0, i0));
            __syncwarp();
            if (lane == 0) red_add(&scr->cnt[9][tries >> 30]);
            st_rlx4(scr->act[~ep & 1] + ao, 0, 0, 0, 0);
        }
        uint32_t s8 = 0, fph = 0;
        const uint32_t chk = __shfl_sync(0xffffffffu, sb + OFF_FS + BOX + lane * 32 + (lane & 28), lane);
        int left = BUDGET;
        if (b >= 112 && ta < 2) mbar_arrive(bars + 8 * B_F1DONE);
#pragma unroll 1
        for (int ph = b >= 112; ph < 2; ph++) {
            {
                float acc[4] = {0.f, 0.f, 0.f, 0.f};
                const uint32_t alo = sd + (ph ? dlo(OFF_FS, 8192) : dlo(OFF_FS, 4096)), ahi = ph ? dhi(1024, 1) : dhi(512, 2), astep = ph ? 128 : 64;
                const uint32_t bhi = ph ? dhi(128, 0) : dhi(1024, 1), bstep = ph ? 16 : 2, wrap = ph ? 24 : 40;
                uint32_t prev = 0;
                if (ph) mbar_wait(bars + 8 * FFN2_GATE, 0, left);
#pragma unroll 1
                for (int q = ph ? n2 : 16; q > 0; q--) {
                    const uint32_t da = alo + s8 * (F_BYTES >> 7), db = sd + dlo(OFF_FS + BOX, 128) + s8 * (F_BYTES >> 7);
                    mbar_wait_hot(bars + 8 * B_FFULL + s8, fph, left);
                    if (__builtin_expect(__any_sync(0xffffffffu, lds1(chk + s8 * (F_BYTES / 8)) == 0), 0)) {
                        int tries = BUDGET;
#pragma unroll 1
                        for (int n = lane * 4 + (left >> 30); n < 256; n += 128) {
                            uint4 v;
#pragma unroll 1
                            do { v = ld_rlx4(scr->act[ep & 1] + ((ph ? mt * NM + n2 : 72) - q) * 256 + n); } while (v.x == 0 && --tries > 0);
                            __syncwarp();
                            sts4(sb + OFF_FS + BOX + s8 * (F_BYTES / 8) + n * 4, v.x, v.y, v.z, v.w);
                        }
                        NRETRY();
                        fence_async_smem();
                        __syncwarp();
                    }
                    TSC(TIMING % 10 == 3 && ta == 0, 32 + (ph ? 16 + n2 : 16) - q);
                    wg_fence();
#pragma unroll
                    for (int j = 0; j < 4; j++) wgmma_n8<1, 0>(acc, mkdesc(da + j * astep, ahi), mkdesc(db + j * bstep, bhi), 1);
                    wg_commit();
                    wg_wait<1>();
                    if (ph) { wg_wait<0>(); if (lane == 0) prev = bars + 8 * B_FEMPTY + s8; }
                    if (prev) mbar_arrive(prev);
                    if (lane == 0) prev = bars + 8 * B_FEMPTY + s8;
                    s8 += 8;
                    if (s8 == wrap) { s8 = 0; fph ^= 1; }
                }
                wg_wait<0>();
                const int ln = lane + (left >> 30);
                if (ph == 0) {
                    if (prev) mbar_arrive(prev);
                    const bool second = (wq >= 2) != (swap_gu != 0);
                    const uint32_t xa = sb + OFF_GU + ((wq & 1) * 32 + ln) * 16;
                    if (second) sts4(xa, __float_as_uint(acc[0]), __float_as_uint(acc[1]), __float_as_uint(acc[2]), __float_as_uint(acc[3]));
                    bar_sync(12, 128);
                    if (second) { if (ln == 0) mbar_arrive(bars + 8 * B_F1DONE); }
                    else {
                        const float4 up = lds4f(xa);
                        float hv[4];
#pragma unroll
                        for (int c = 0; c < 4; c++) { const float ga = bf16r(acc[c]); hv[c] = bf16r(ga * sigmoidf(ga)) * bf16r((&up.x)[c]); }
                        const int ao = (b * 4 + (wq & 1) * 2) * 32 + ln;
                        st_rlx(scr->act[ep & 1] + ao, max(movm(pack_bf16(hv[0], hv[1])), 1u)); st_rlx(scr->act[ep & 1] + 32 + ao, max(movm(pack_bf16(hv[2], hv[3])), 1u));
                        __syncwarp();
                        if (ln == 0) red_add(&scr->cnt[b < 14 * NM ? b / (2 * NM) : b < 14 * NM + 2 * N7 ? 7 : 8][0]);
                        st_rlx(scr->act[~ep & 1] + ao, 0); st_rlx(scr->act[~ep & 1] + 32 + ao, 0);
                    }
                } else {
                    st_rlx4(&scr->ypart[mt][c2][wq * 32 + ln], (__float_as_uint(acc[0]) & ~1u) | (ep & 1), __float_as_uint(acc[1]), __float_as_uint(acc[2]), __float_as_uint(acc[3]));
                }
                TSC(ta == 0, 22 + ph);
            }
        }
        TSC(ta == 0, 24);
    } else {
        reg_inc<224>();
        const int w = warp >> 2, wi = warp & 3, g = lane >> 2, t = lane & 3;
        const bool elect = (tid & 127) == 0;
        const uint32_t mad = (lane & 15) * 128 + (((lane >> 4) ^ (lane & 7)) << 4);
        float acc[64];
        const uint32_t ring = sb + w * OFF_X1, ofull = bars + 8 * (B_OFULL + w * 6), oempty = mapa(bars + 8 * B_OEMPTY, w);
        const int r0 = rh * 128 + wi * 32 + (1 - w) * 16 + g;
        {
            float acc0[96], acc1[96];
            const uint32_t sta = sb + OFF_STAT + (8 + w * 128 + wi * 32) * 8;
            {
                const uint32_t xfull = bars + 8 * (B_XFULL + w * 6 + 5), xempty = mapa(bars + 8 * B_XEMPTY, w), dx0 = sd + dlo(w * OFF_X1, 16);
                uint32_t s8 = 16, ps8 = 0, ph = 0;
                cluster_wait();
#pragma unroll 1
                for (int k = 0; k < 16; k++) {
                    const uint32_t dx = dx0 + s8 * (2 * BOX >> 7), dw = sd + dlo(OFF_W, BOX) + s8 * (W_BYTES >> 7);
                    mbar_wait(bars + 8 * B_WFULL + s8, ph, budget);
                    mbar_wait(xfull - 2 * s8, ph, budget);
                    TSC(elect && k == 0, 1 + 8 * w);
                    TSC(TIMING % 10 == 1 && tid == 0, 32 + k);
                    wg_wait<0>();
                    wg_fence();
#pragma unroll
                    for (int kk = 0; kk < 4; kk++) wgmma_n192<0, 1>(acc1, mkdesc(dx + kk * 2, dhi(1024, 1)), mkdesc(dw + kk * 128, dhi(1024, 1)), kk ? 1 : k);
                    wg_commit();
                    TSC(TIMING % 10 == 6 && elect, 32 + 16 * w + k);
                    if (elect && k > 0) {
                        mbar_arrive(bars + 8 * B_WEMPTY + ps8);
                        if (k <= 13) { mbar_expect_tx(xfull - 2 * ps8 - 8, BOX); mbar_arrive_at(xempty + 2 * ps8 + 8); }
                    }
                    if (k == 15) {
                        mbar_wait(bars + 8 * B_AUX, 0, budget);
                        const uint32_t zero = budget >> 30, pm = t & 1 ? 0x4432 : 0x3232, ra = sta + ((t >> 1) * 16 + g) * 8;
                        const uint32_t a0 = __byte_perm(lds1(ra), 0, pm), a1 = __byte_perm(lds1(ra + 64), 0, pm), a2 = a0 & zero, a3 = a1 & zero;
                        wg_fence();
                        wgmma_rs_n192(acc1, a0, a1, a2, a3, mkdesc(sd + dlo(OFF_CS, 0), dhi(128, 0)));
                        wgmma_rs_n192(acc0, a0, a1, a2, a3, mkdesc(sd + dlo(OFF_CS + 64, 0), dhi(128, 0)));
                        wg_commit();
                    }
                    mbar_wait(xfull - 2 * s8 - 8, ph, budget);
                    wg_wait<0>();
                    wg_fence();
#pragma unroll
                    for (int kk = 0; kk < 4; kk++) wgmma_n192<0, 1>(acc0, mkdesc(dx + 512 + kk * 2, dhi(1024, 1)), mkdesc(dw + kk * 128, dhi(1024, 1)), kk ? 1 : k);
                    wg_commit();
                    if (elect && k <= 12) { mbar_expect_tx(xfull - 2 * s8, BOX); mbar_arrive_at(xempty + 2 * s8); }
                    ps8 = s8;
                    s8 = s8 == 16 ? 0 : s8 + 8;
                    if (s8 == 16) ph ^= 1;
                }
            }
            const uint32_t zero = budget >> 30;
            const bool u0 = 2 * t > g, u1 = 2 * t + 1 > g;
            uint32_t mU = (u0 ? 0xffffu : 0u) | (u1 ? 0xffff0000u : 0u);
            uint32_t ka0 = sta + (2 * t - (u0 ? 8 : 0)) * 8 + 4, ka1 = sta + (2 * t + 1 - (u1 ? 8 : 0)) * 8 + 4;
            float rk[2][4], fu[2][4], fn[2][4];
            auto factors = [&](int h) {
#pragma unroll
                for (int n = 0; n < 4; n += 2) {
                    const float rq = lds1f(sta + (16 * h + 4 * n + g) * 8 + 4) * (0.17677669529663687f * 1.4426950408889634f);
                    rk[h][n] = lds1f(ka0 + h * 128 + n * 32); rk[h][n + 1] = lds1f(ka1 + h * 128 + n * 32);
                    const float f0 = rq * rk[h][n], f1 = rq * rk[h][n + 1];
                    fu[h][n] = u0 ? f0 : 0.f; fn[h][n] = f0 - fu[h][n]; fu[h][n + 1] = u1 ? f1 : 0.f; fn[h][n + 1] = f1 - fu[h][n + 1];
                }
#pragma unroll
                for (int n = 0; n < 4; n++) asm volatile("" : "+f"(fu[h][n]), "+f"(fn[h][n]));
            };
            uint8_t* og = scr->o + ((size_t)(mt * 4 + w * 2) * 16 + nt) * BOX + wi * 256 + lane * 4;
            TSC(elect, 19 + w);
            uint32_t pk0[48], pk1[48], o[16] = {};
#pragma unroll
            for (int j = 0; j < 48; j++) if (j < 16 || (j & 1)) pk1[j] = pack_here(acc1[2 * j], acc1[2 * j + 1]);
            if (warp < 7) {
#pragma unroll
                for (int c = 0; c < 4; c++) stsm4(ring + 4 * BOX + wi * 2048 + c * 512 + lane * 16, pk1[17 + 8 * c], pk1[19 + 8 * c], pk1[21 + 8 * c], pk1[23 + 8 * c]);
                bar_arrive(1 + warp, 64);
            } else if (j0 != 768) {
#pragma unroll
                for (int c = 0; c < 4; c++) {
                    pk1[17 + 8 * c] = max(pk1[17 + 8 * c], 1u);
                    st_rlx4(&scr->halo[b][c * 128 + lane * 4], pk1[17 + 8 * c], pk1[19 + 8 * c], pk1[21 + 8 * c], pk1[23 + 8 * c]);
                }
            }
            TSC(tid == 224, 28);
#pragma unroll
            for (int j = 16; j < 48; j += 2) pk1[j] = pack_here(acc1[2 * j], acc1[2 * j + 1]);
            factors(1);
            uint32_t od = sb + 2 * BOX + wi * 256 + (lane >> 4) * 1024 + (lane & 15) * 16, g1peer = mapa(bars + 8 * B_G1DONE, hp ^ 1);
            uint32_t ha = sb + (warp == 0 ? OFF_HIN : warp <= 4 ? 4 * BOX - 2048 : OFF_X1 + 4 * BOX - 5 * 2048) + warp * 2048 + lane * 16;
            const bool first = warp == 0 && j0 == 0;
            float bias0 = first && u0 ? -INFINITY : 0.f, bias1 = first && u1 ? -INFINITY : 0.f;
            asm volatile("" : "+l"(og), "+r"(mU), "+r"(od), "+r"(ha), "+f"(bias0), "+f"(bias1));
            mbar_wait(bars + 8 * B_XT, 0, budget);
            mbar_wait(bars + 8 * (B_WEMPTY + 1), 0, budget);
            wg_wait<0>();
            if (elect) { mbar_arrive(bars + 8 * B_G1DONE); mbar_arrive_at(g1peer); }
            TSC(elect, 2 + 8 * w);
            float ci[4];
#pragma unroll
            for (int n = 0; n < 4; n++) ci[n] = __uint_as_float((0x03800000u + n) | (budget >> 30));
            auto hand_over = [&](int v) {
                asm volatile("{\n.reg .pred p;\nsetp.ne.b32 p, %17, 0;\n"
                             "@p stmatrix.sync.aligned.m8n8.x4.shared.b16 [%16], {%0,%1,%2,%3};\n@p stmatrix.sync.aligned.m8n8.x4.shared.b16 [%16 + 2048], {%4,%5,%6,%7};\n"
                             "@p stmatrix.sync.aligned.m8n8.x4.shared.b16 [%16 + 4096], {%8,%9,%10,%11};\n@p stmatrix.sync.aligned.m8n8.x4.shared.b16 [%16 + 6144], {%12,%13,%14,%15};\n"
                             "fence.proxy.async.shared::cta;\n}"
                             ::"r"(o[0]), "r"(o[1]), "r"(o[2]), "r"(o[3]), "r"(o[4]), "r"(o[5]), "r"(o[6]), "r"(o[7]), "r"(o[8]), "r"(o[9]), "r"(o[10]), "r"(o[11]),
                               "r"(o[12]), "r"(o[13]), "r"(o[14]), "r"(o[15]), "r"(od + v * OFF_X1), "r"((int)(w == rh)) : "memory");
                TSC(tid == 0, v ? 27 : 5);
#pragma unroll
                for (int i = 0; i < 16; i++) asm volatile("st.global.u32 [%0], %1;" ::"l"(og + (1 - v) * 16 * BOX + (i >> 1) * 1024 + (i & 1) * 128), "r"(o[i]) : "memory");
                __syncwarp();
                if (lane == 0) mbar_arrive(bars + 8 * (B_STAGED + v));
            };
#pragma unroll
            for (int j = 32; j < 48; j++) pk1[j] = movm(pk1[j]);
#pragma unroll
            for (int j = EARLY_PK; j < 48; j++) if (j >= 32 || (j & 1) || EARLY_PK < 17) pk0[j] = pack_here(acc0[2 * j], acc0[2 * j + 1]);
#pragma unroll
            for (int j = 32; j < 48; j++) pk0[j] = movm(pk0[j]);
            attn_pair<2>(pk1, pk1 + 16, pk1 + 32, pk0 + 17, pk0 + 33, fu[1], fn[1], rk[1], 0.f, 0.f, mU, zero, ci, o);
            hand_over(0);
            TSC(elect, 3 + 8 * w);
#pragma unroll
            for (int j = 0; j < 32; j++) if (j < EARLY_PK || (!(j & 1) && EARLY_PK == 17)) pk0[j] = pack_here(acc0[2 * j], acc0[2 * j + 1]);
            factors(0);
            bar_sync(warp ? warp : 11, 64);
            uint32_t hl[16];
            ldsm4(hl, ha); ldsm4(hl + 4, ha + 512); ldsm4t(hl + 8, ha + 1024); ldsm4t(hl + 12, ha + 1536);
            __syncwarp();
            if (lane == 0) mbar_arrive(bars + 8 * B_FREED);
            attn_pair<1>(pk0, pk0 + 16, pk0 + 32, hl, hl + 8, fu[0], fn[0], rk[0], bias0, bias1, mU, zero, ci, o);
            const float2 s0 = lds2f(sb + OFF_STAT + (8 + r0) * 8), s1 = lds2f(sb + OFF_STAT + (16 + r0) * 8);
            const float m0 = s0.x * s0.y, f0 = 1.f + s0.y, m1 = s1.x * s1.y, f1 = 1.f + s1.y;
            uint32_t xt[32];
#pragma unroll
            for (int j = 0; j < 8; j++) ldsm4(xt + 4 * j, ((ring + wi * 2048 + mad) ^ ((j & 3) * 32)) + (j >> 2) * BOX);
            hand_over(1);
#pragma unroll
            for (int j = 0; j < 32; j++) {
                acc[2 * j] = fmaf(bf_lo(xt[j]), j & 1 ? f1 : f0, j & 1 ? m1 : m0); acc[2 * j + 1] = fmaf(bf_hi(xt[j]), j & 1 ? f1 : f0, j & 1 ? m1 : m0);
            }
        }
        TSC(tid == 0, 4);
        {
            const uint32_t da0 = sd + dlo(w * OFF_X1, 1024), db0 = sd + dlo(OFF_WO, BOX);
            const uint32_t chk = ring + wi * 256 + (lane >> 3) * 1032 + (lane & 7) * 32 + (lane & 4);
            uint32_t s8 = 16, ps8 = 0, ph = 0;
            mbar_wait(ofull + s8, 0, budget);
            mbar_wait(bars + 8 * B_WOFULL + s8, 0, budget);
            TSC(TIMING % 10 == 2 && elect, 32 + w * 16);
            const uint32_t ahi = dhi(128, 0) | (budget >> 30), bhi = dhi(1024, 1) | (budget >> 30);
            const int last = w ? HOLD : 16;
            uint32_t rel = elect ? 0x7fe : 0;
#pragma unroll 1
            for (int i = 1;;) {
                const uint32_t da = da0 + s8 * (BOX >> 7), db = db0 + s8 * (BOX >> 6);
                wg_fence();
#pragma unroll
                for (int kk = 0; kk < 4; kk++) {
                    wgmma_n128<0, 1>(acc, mkdesc(da + kk * 128, ahi), mkdesc(db + kk * 128, bhi), 1);
                    if (kk & 1) wg_commit();
                }
                wg_wait<2>();
                if (rel & 1) { mbar_expect_tx(ofull + ps8, BOX); mbar_arrive_at(oempty + ps8); mbar_arrive(bars + 8 * B_WOEMPTY + ps8); }
                if (i == 16) break;
                rel >>= 1;
                ps8 = s8;
#pragma unroll 1
                do {
                    s8 = s8 == 40 ? 0 : s8 + 8;
                    if (s8 == 16) ph ^= 1;
                    uint32_t bad;
                    asm volatile("{\n.reg .pred p, q, r;\n.reg .u32 u, v;\nmbarrier.try_wait.parity.shared::cta.b64 q, [%2], %3;\nmbarrier.try_wait.parity.shared::cta.b64 p, [%1], %3;\n"
                                 "setp.ne.and.u32 r, %5, 1, p;\nmov.u32 u, 1;\nmov.u32 v, 1;\n@r ld.shared.u32 u, [%4];\n@r ld.shared.u32 v, [%4 + 4096];\n"
                                 "and.pred p, p, q;\nmin.u32 u, u, v;\nsetp.eq.or.u32 p, u, 0, !p;\nvote.sync.any.pred p, p, 0xffffffff;\nselp.u32 %0, 1, 0, p;\n}"
                                 : "=r"(bad) : "r"(ofull + s8), "r"(bars + 8 * B_WOFULL + s8), "r"(ph), "r"(chk + s8 * (BOX / 8)), "r"(i) : "memory");
                    if (__builtin_expect(bad, 0)) {
                        mbar_wait(ofull + s8, ph, budget);
                        mbar_wait(bars + 8 * B_WOFULL + s8, ph, budget);
                        if (__any_sync(0xffffffffu, min(lds1(chk + s8 * (BOX / 8)), lds1(chk + s8 * (BOX / 8) + 4096)) == 0)) {
                            const uint32_t at = wi * 256 + (lane >> 4) * 1024 + (lane & 15) * 16;
                            const uint8_t* src = scr->o + ((size_t)((mt * 2 + rh) * 2 + 1 - w) * 16 + ((2 * p + (i < 2 ? i ^ hp : i)) & 15)) * BOX + at;
#pragma unroll 1
                            for (int n = 0; n < 8192; n += 2048) {
                                uint4 v; int tries = 4096;
#pragma unroll 1
                                do { v = ld_rlx4(src + n); } while (v.x == 0 && --tries > 0);
                                sts4(ring + s8 * (BOX / 8) + at + n, v.x, v.y, v.z, v.w);
                            }
                            NRETRY();
                            fence_async_smem();
                            __syncwarp();
                        }
                    }
                    TSC(TIMING % 10 == 1 && tid == 0, 48 + i);
                    TSC(TIMING % 10 == 2 && elect, 32 + w * 16 + i);
                } while (++i > last && i < 16);
                if (i > last) break;
                wg_wait<1>();
            }
            if (w) {
                bar_sync(9, 256);
#pragma unroll 1
                for (int i = HOLD - 10; i < 6; i++) {
                    wg_fence();
#pragma unroll
                    for (int kk = 0; kk < 4; kk++) wgmma_n128<0, 1>(acc, mkdesc(da0 + i * 512 + kk * 128, ahi), mkdesc(db0 + i * 1024 + kk * 128, bhi), 1);
                    wg_commit();
                }
            } else bar_arrive(9, 256);
            mbar_wait(bars + 8 * B_ZERO, 0, budget);
            const bool add = (__shfl_sync(0xffffffffu, lds1(sb + OFF_SEL), 0) >> (wi * 2 + 1 - w)) & 1;
            wg_wait<0>();
            TSC(elect, 7 + 9 * w);
            const uint32_t os0 = ring + wi * 4096;
#pragma unroll
            for (int hf = 0; hf < OUT_PARTS; hf++) {
#pragma unroll
                for (int j = hf * (8 / OUT_PARTS); j < (hf + 1) * (8 / OUT_PARTS); j++)
                    stsm4(((os0 + mad) ^ ((j & 3) * 32)) + (j >> 2) * 2048, pack_here(acc[8 * j], acc[8 * j + 1]), pack_here(acc[8 * j + 2], acc[8 * j + 3]),
                          pack_here(acc[8 * j + 4], acc[8 * j + 5]), pack_here(acc[8 * j + 6], acc[8 * j + 7]));
                fence_async_smem();
                __syncwarp();
                if (elect_one())
                    asm volatile("{\n.reg .pred p;\nsetp.ne.b32 p, %6, 0;\n@!p cp.async.bulk.tensor.5d.global.shared::cta.bulk_group [%0, {%2, %2, %3, %4, %5}], [%1];\n"
                                 "@p cp.reduce.async.bulk.tensor.5d.global.shared::cta.add.bulk_group [%0, {%2, %2, %3, %4, %5}], [%1];\n}"
                                 ::"l"(&mout), "r"(os0 + hf * 2048), "r"(0), "r"(((j0 + rh * 128) >> 5) + wi), "r"(1 - w), "r"(par * 16 + cb * 2 + hf), "r"((int)add) : "memory");
            }
            asm volatile("cp.async.bulk.commit_group;\ncp.async.bulk.wait_group.read 0;" ::: "memory");
            if (b == 0 && tid == 0) st_rlx(&scr->epoch[0], lds1(sb + OFF_EP));
            TSC(elect, 8 - 2 * w);
            TS_END();
        }
    }
}

typedef CUresult (*EncodeFn)(CUtensorMap*, CUtensorMapDataType, cuuint32_t, void*, const cuuint64_t*, const cuuint64_t*, const cuuint32_t*,
                             const cuuint32_t*, CUtensorMapInterleave, CUtensorMapSwizzle, CUtensorMapL2promotion, CUtensorMapFloatOOBfill);

CUtensorMap make_map(EncodeFn fn, const void* base, int rank, const cuuint64_t* dims, const cuuint64_t* strides, const cuuint32_t* box,
                     CUtensorMapSwizzle swz = CU_TENSOR_MAP_SWIZZLE_128B, CUtensorMapL2promotion pro = CU_TENSOR_MAP_L2_PROMOTION_L2_256B) {
    CUtensorMap m;
    cuuint32_t es[5] = {1, 1, 1, 1, 1};
    fn(&m, CU_TENSOR_MAP_DATA_TYPE_BFLOAT16, rank, (void*)base, dims, strides, box, es, CU_TENSOR_MAP_INTERLEAVE_NONE,
       swz, pro, CU_TENSOR_MAP_FLOAT_OOB_FILL_NONE);
    return m;
}

}

extern "C" void kernel_launch(void* const* d_in, const int* in_sizes, int n_in, void* d_out, int out_size) {
    (void)in_sizes; (void)n_in; (void)out_size;
    const __nv_bfloat16* x = (const __nv_bfloat16*)d_in[0];
    const __nv_bfloat16* wqkv = (const __nv_bfloat16*)d_in[1];
    const __nv_bfloat16* wo = (const __nv_bfloat16*)d_in[2];
    const __nv_bfloat16* wr = (const __nv_bfloat16*)d_in[4];
    const __nv_bfloat16* wg = (const __nv_bfloat16*)d_in[5];
    const __nv_bfloat16* wu = (const __nv_bfloat16*)d_in[6];
    const __nv_bfloat16* wd = (const __nv_bfloat16*)d_in[7];
    static EncodeFn fn = nullptr;
    static Scratch* scr = nullptr;
    if (!fn) {
        void* p = nullptr; cudaDriverEntryPointQueryResult q;
        cudaGetDriverEntryPoint("cuTensorMapEncodeTiled", &p, cudaEnableDefault, &q);
        fn = (EncodeFn)p;
        cudaFuncSetAttribute(fused_kernel, cudaFuncAttributeMaxDynamicSharedMemorySize, SMEM_LAUNCH);
        cudaGetSymbolAddress((void**)&scr, g_scr);
    }
    const cuuint64_t xd[4] = {2048, 16, 32, 2}, xs[4] = {4096, 131072, 65536, 128}, od[5] = {64, 16, 32, 2, 32};
    const cuuint32_t xb[4] = {64, 16, 4, 1}, ob[5] = {64, 16, 1, 1, 2 / OUT_PARTS};
    const cuuint64_t wdm[3] = {1024, 1024, 3}, wst[2] = {6144, 2048};
    const cuuint32_t wb[3] = {64, 64, 3};
    const cuuint64_t wod[3] = {64, 1024, 16}, wdd[3] = {64, 3584, 16}, wos[2] = {2048, 128};
    const cuuint32_t wob[3] = {64, 64, 2}, wdb[3] = {64, 64, 1};
    CUtensorMap mx = make_map(fn, x, 4, xd, xs, xb), mw = make_map(fn, wqkv, 3, wdm, wst, wb);
    CUtensorMap mwo = make_map(fn, wo, 3, wod, wos, wob), mout = make_map(fn, d_out, 5, od, xs, ob);
    const int swap_gu = wu < wg;
    const cuuint64_t gd[3] = {3584, 1024, 2}, gst[2] = {7168, (cuuint64_t)(swap_gu ? (const char*)wg - (const char*)wu : (const char*)wu - (const char*)wg)};
    const cuuint32_t gb[3] = {32, 64, 2};
    CUtensorMap mgu = make_map(fn, swap_gu ? wu : wg, 3, gd, gst, gb, CU_TENSOR_MAP_SWIZZLE_64B, CU_TENSOR_MAP_L2_PROMOTION_L2_128B);
    CUtensorMap mwd = make_map(fn, wd, 3, wdd, wos, wdb, CU_TENSOR_MAP_SWIZZLE_128B, CU_TENSOR_MAP_L2_PROMOTION_L2_128B);
    const cuuint64_t md[2] = {64, 32768}, ms[1] = {128};
    const cuuint32_t mb[2] = {64, 64};
    CUtensorMap mo = make_map(fn, scr, 2, md, ms, mb, CU_TENSOR_MAP_SWIZZLE_NONE, CU_TENSOR_MAP_L2_PROMOTION_NONE);
    const cuuint64_t rd[2] = {1024, 2048};
    const cuuint32_t rb[2] = {256, 16};
    CUtensorMap mr = make_map(fn, x, 2, rd, wos, rb, CU_TENSOR_MAP_SWIZZLE_NONE);
    cudaLaunchConfig_t cfg = {};
    cfg.gridDim = dim3(132); cfg.blockDim = dim3(512); cfg.dynamicSmemBytes = SMEM_LAUNCH; cfg.stream = cudaStreamPerThread;
    cudaLaunchAttribute at[1];
    at[0].id = cudaLaunchAttributeClusterDimension; at[0].val.clusterDim.x = 2; at[0].val.clusterDim.y = 1; at[0].val.clusterDim.z = 1;
    cfg.attrs = at; cfg.numAttrs = 1;
    cudaLaunchKernelEx(&cfg, fused_kernel, mx, mw, mwo, mout, mgu, mwd, mo, mr, x, wr, scr, swap_gu, Weights{(const char*)wqkv, (const char*)wo, (const char*)wg, (const char*)wu, (const char*)wd, (char*)d_out});
}
```

```cpp
#include <cuda_runtime.h>
#include <cuda.h>
#include <cuda_bf16.h>
#include <stdint.h>

namespace {

constexpr int BOX = 8192, W_BYTES = 3 * BOX;
constexpr int OFF_X1 = 6 * BOX, OFF_FR = 12 * BOX, OFF_E = 16 * BOX, OFF_W = 19 * BOX;
constexpr int OFF_WO = OFF_E;
constexpr int OFF_HIN = OFF_FR + 2048, OFF_GU = OFF_HIN + 2048, OFF_FS = OFF_GU + 1024;
constexpr int F_BYTES = 9216;
constexpr int CS_BYTES = 3136;
constexpr int OFF_CS = OFF_FS + 5 * F_BYTES;
constexpr int OFF_STAT = 28 * BOX;
constexpr int OFF_SEL = OFF_STAT + 2112, OFF_EP = OFF_SEL + 4;
constexpr int OFF_BAR = OFF_SEL + 16;
constexpr int B_WFULL = 0, B_XFULL = 3, B_AUX = 15, B_XT = 16, B_ZERO = 17, B_WOFULL = 18, B_OFULL = 24, B_FFULL = 36, B_ROW = 41;
constexpr int B_WEMPTY = 48, B_F1DONE = 51, B_XEMPTY = 52, B_WOEMPTY = 58, B_OEMPTY = 64;
constexpr int B_G1DONE = 72, B_FEMPTY = 73, B_STAGED = 78, B_RDONE = 80, B_FREED = 81, NBAR = 84;
constexpr int SMEM_BYTES = OFF_BAR + NBAR * 8;
static_assert(OFF_FS + 3 * F_BYTES == OFF_E && OFF_CS + CS_BYTES <= OFF_W && SMEM_BYTES + 256 <= 232448 && OFF_BAR % 8 == 0, "smem");
#define POLL_NS 30
#define PF_RATE 10
#define PF_START 7
#define ZF_NS 100
#define FFN2_GATE (B_STAGED + 1)
#define PF_NW 6
#define EARLY_PK 17
#define ZF_GATE (B_ROW + 3)
#define HOLD 12
#define F2_DEPTH 0
#define OUT_PARTS 2
#define PF_D 8
#define NM 4
#define N7 8
#define H_NS 0
#define NR 4
#define ROWS_AT 0x280
constexpr int NH = 56 - 7 * NM - N7;
static_assert(NH >= NR + 6 && NH <= 32 && NR < 6, "FFN2 split");
constexpr int BUDGET = 1 << 18;

struct Scratch {
    uint8_t o[2048 * 1024 * 2];
    uint4 ypart[8][16][128];
    uint32_t halo[128][512];
    uint32_t act[2][14336 + 4096];
    uint2 row[2048];
    uint4 cs[16][3][24];
    uint32_t oflag[16][32];
    uint32_t cnt[10][32];
    uint32_t sel[32], zflag[32], epoch[32];
};
__device__ __align__(1024) Scratch g_scr;
struct Weights { const char *wqkv, *wo, *wg, *wu, *wd; char* out; };

#define TS(i) do {} while (0)
#define TS_END() do {} while (0)
#define TSC(c, i) do {} while (0)
#define NRETRY() do {} while (0)
constexpr int SMEM_LAUNCH = SMEM_BYTES;
__device__ __forceinline__ uint32_t smem_u32(const void* p) { return (uint32_t)__cvta_generic_to_shared(p); }
__device__ __forceinline__ void mbar_init(uint32_t bar, uint32_t cnt) { asm volatile("mbarrier.init.shared::cta.b64 [%0], %1;" ::"r"(bar), "r"(cnt) : "memory"); }
__device__ __forceinline__ void mbar_expect_tx(uint32_t bar, uint32_t bytes) { asm volatile("mbarrier.arrive.expect_tx.shared::cta.b64 _, [%0], %1;" ::"r"(bar), "r"(bytes) : "memory"); }
__device__ __forceinline__ void mbar_arrive(uint32_t bar) { asm volatile("mbarrier.arrive.shared::cta.b64 _, [%0];" ::"r"(bar) : "memory"); }
__device__ __forceinline__ uint32_t mapa(uint32_t a, uint32_t cta) { uint32_t r; asm("mapa.shared::cluster.u32 %0, %1, %2;" : "=r"(r) : "r"(a), "r"(cta)); return r; }
__device__ __forceinline__ void mbar_arrive_at(uint32_t cbar) { asm volatile("mbarrier.arrive.shared::cluster.b64 _, [%0];" ::"r"(cbar) : "memory"); }
__device__ __forceinline__ void mbar_wait(uint32_t bar, uint32_t parity, int& budget) {
    asm volatile("{\n.reg .pred p;\nLAB_WAIT:\nmbarrier.try_wait.parity.shared::cta.b64 p, [%1], %2;\n"
                 "add.s32 %0, %0, -1;\nsetp.gt.and.s32 p, %0, 0, !p;\n@p bra LAB_WAIT;\n}" : "+r"(budget) : "r"(bar), "r"(parity) : "memory");
}
__device__ __forceinline__ void mbar_wait_hot(uint32_t bar, uint32_t parity, int& budget) {
    asm volatile("{\n.reg .pred p;\nmbarrier.try_wait.parity.shared::cta.b64 p, [%1], %2;\n@p bra LAB_DONE;\nLAB_WAIT:\nmbarrier.try_wait.parity.shared::cta.b64 p, [%1], %2;\n"
                 "add.s32 %0, %0, -1;\nsetp.gt.and.s32 p, %0, 0, !p;\n@p bra LAB_WAIT;\nLAB_DONE:\n}" : "+r"(budget) : "r"(bar), "r"(parity) : "memory");
}
__device__ __forceinline__ void tma_2d(uint32_t dst, const CUtensorMap* m, uint32_t bar, int c0, int c1) {
    asm volatile("cp.async.bulk.tensor.2d.shared::cluster.global.mbarrier::complete_tx::bytes [%0], [%1, {%3, %4}], [%2];" ::"r"(dst), "l"(m), "r"(bar), "r"(c0), "r"(c1) : "memory");
}
__device__ __forceinline__ void tma_2d_mc(uint32_t dst, const CUtensorMap* m, uint32_t bar, int c0, int c1) {
    asm volatile("cp.async.bulk.tensor.2d.shared::cluster.global.mbarrier::complete_tx::bytes.multicast::cluster [%0], [%1, {%3, %4}], [%2], %5;" ::"r"(dst), "l"(m), "r"(bar), "r"(c0), "r"(c1), "h"((uint16_t)3) : "memory");
}
__device__ __forceinline__ void tma_3d(uint32_t dst, const CUtensorMap* m, uint32_t bar, int c0, int c1, int c2) {
    asm volatile("cp.async.bulk.tensor.3d.shared::cluster.global.mbarrier::complete_tx::bytes [%0], [%1, {%3, %4, %5}], [%2];" ::"r"(dst), "l"(m), "r"(bar), "r"(c0), "r"(c1), "r"(c2) : "memory");
}
__device__ __forceinline__ void tma_4d(uint32_t dst, const CUtensorMap* m, uint32_t bar, int c0, int c1, int c2, int c3) {
    asm volatile("cp.async.bulk.tensor.4d.shared::cluster.global.mbarrier::complete_tx::bytes [%0], [%1, {%3, %4, %5, %6}], [%2];" ::"r"(dst), "l"(m), "r"(bar), "r"(c0), "r"(c1), "r"(c2), "r"(c3) : "memory");
}
__device__ __forceinline__ void tma_4d_mc(uint32_t dst, const CUtensorMap* m, uint32_t bar, int c0, int c1, int c2, int c3) {
    asm volatile("cp.async.bulk.tensor.4d.shared::cluster.global.mbarrier::complete_tx::bytes.multicast::cluster [%0], [%1, {%3, %4, %5, %6}], [%2], %7;" ::"r"(dst), "l"(m), "r"(bar), "r"(c0), "r"(c1), "r"(c2), "r"(c3), "h"((uint16_t)3) : "memory");
}
__device__ __forceinline__ void bulk_pf(const void* p, uint32_t bytes) { asm volatile("cp.async.bulk.prefetch.L2.global [%0], %1;" ::"l"(p), "r"(bytes) : "memory"); }
__device__ __forceinline__ void bulk_g2s(uint32_t dst, const void* src, uint32_t bytes, uint32_t bar) {
    asm volatile("cp.async.bulk.shared::cluster.global.mbarrier::complete_tx::bytes [%0], [%1], %2, [%3];" ::"r"(dst), "l"(src), "r"(bytes), "r"(bar) : "memory");
}
__device__ __forceinline__ void bulk_s2c(uint32_t cdst, uint32_t src, uint32_t bytes, uint32_t cbar) {
    asm volatile("cp.async.bulk.shared::cluster.shared::cta.mbarrier::complete_tx::bytes [%0], [%1], %2, [%3];" ::"r"(cdst), "r"(src), "r"(bytes), "r"(cbar) : "memory");
}
__device__ __forceinline__ void cluster_wait() { asm volatile("barrier.cluster.wait.aligned;" ::: "memory"); }
__device__ __forceinline__ void fence_gpu() { asm volatile("fence.acq_rel.gpu;" ::: "memory"); }
__device__ __forceinline__ void fence_async_smem() { asm volatile("fence.proxy.async.shared::cta;" ::: "memory"); }
__device__ __forceinline__ void wg_fence() { asm volatile("wgmma.fence.sync.aligned;" ::: "memory"); }
__device__ __forceinline__ void wg_commit() { asm volatile("wgmma.commit_group.sync.aligned;" ::: "memory"); }
template <int N> __device__ __forceinline__ void wg_wait() { asm volatile("wgmma.wait_group.sync.aligned %0;" ::"n"(N) : "memory"); }
__device__ __forceinline__ uint64_t mkdesc(uint32_t lo, uint32_t hi) { return ((uint64_t)hi << 32) | lo; }
__host__ __device__ constexpr uint32_t dhi(uint32_t sbo, uint32_t mode) { return (sbo >> 4) | (mode << 30); }
__host__ __device__ constexpr uint32_t dlo(uint32_t off, uint32_t lbo) { return (off >> 4) + ((lbo >> 4) << 16); }
__device__ __forceinline__ bool elect_one() {
    uint32_t e;
    asm volatile("{\n.reg .pred p;\nelect.sync _|p, 0xffffffff;\nselp.u32 %0, 1, 0, p;\n}" : "=r"(e));
    return e;
}
template <int R> __device__ __forceinline__ void reg_inc() { asm volatile("setmaxnreg.inc.sync.aligned.u32 %0;" ::"n"(R)); }
template <int R> __device__ __forceinline__ void reg_dec() { asm volatile("setmaxnreg.dec.sync.aligned.u32 %0;" ::"n"(R)); }
__device__ __forceinline__ void bar_sync(int id, int n) { asm volatile("bar.sync %0, %1;" ::"r"(id), "r"(n) : "memory"); }
__device__ __forceinline__ void bar_arrive(int id, int n) { asm volatile("bar.arrive %0, %1;" ::"r"(id), "r"(n) : "memory"); }
__device__ __forceinline__ uint32_t pack_bf16(float lo, float hi) { uint32_t r; asm("cvt.rn.bf16x2.f32 %0, %1, %2;" : "=r"(r) : "f"(hi), "f"(lo)); return r; }
__device__ __forceinline__ uint32_t pack_here(float lo, float hi) { uint32_t r; asm volatile("cvt.rn.bf16x2.f32 %0, %1, %2;" : "=r"(r) : "f"(hi), "f"(lo)); return r; }
__device__ __forceinline__ float bf_lo(uint32_t u) { return __uint_as_float(u << 16); }
__device__ __forceinline__ float bf_hi(uint32_t u) { return __uint_as_float(u & 0xffff0000u); }
__device__ __forceinline__ float bf16r(float v) { return bf_lo(pack_bf16(v, 0.f)); }
__device__ __forceinline__ float rcp(float x) { float r; asm("rcp.approx.ftz.f32 %0, %1;" : "=f"(r) : "f"(x)); return r; }
__device__ __forceinline__ float ex2(float x) { float r; asm("ex2.approx.ftz.f32 %0, %1;" : "=f"(r) : "f"(x)); return r; }
__device__ __forceinline__ float sigmoidf(float v) { return rcp(1.f + ex2(v * -1.4426950408889634f)); }
__device__ __forceinline__ uint32_t movm(uint32_t a) { uint32_t d; asm volatile("movmatrix.sync.aligned.m8n8.trans.b16 %0, %1;" : "=r"(d) : "r"(a)); return d; }
__device__ __forceinline__ void mma16816(float (&c)[4], uint32_t a0, uint32_t a1, uint32_t a2, uint32_t a3, uint32_t b0, uint32_t b1) {
    asm volatile("mma.sync.aligned.m16n8k16.row.col.f32.bf16.bf16.f32 {%0,%1,%2,%3}, {%4,%5,%6,%7}, {%8,%9}, {%0,%1,%2,%3};"
                 : "+f"(c[0]), "+f"(c[1]), "+f"(c[2]), "+f"(c[3]) : "r"(a0), "r"(a1), "r"(a2), "r"(a3), "r"(b0), "r"(b1));
}
__device__ __forceinline__ void mma1688(float (&c)[4], uint32_t a0, uint32_t a1, uint32_t b0) {
    asm volatile("mma.sync.aligned.m16n8k8.row.col.f32.bf16.bf16.f32 {%0,%1,%2,%3}, {%4,%5}, {%6}, {%0,%1,%2,%3};"
                 : "+f"(c[0]), "+f"(c[1]), "+f"(c[2]), "+f"(c[3]) : "r"(a0), "r"(a1), "r"(b0));
}
__device__ __forceinline__ void stsm4(uint32_t a, uint32_t r0, uint32_t r1, uint32_t r2, uint32_t r3) {
    asm volatile("stmatrix.sync.aligned.m8n8.x4.shared.b16 [%0], {%1,%2,%3,%4};" ::"r"(a), "r"(r0), "r"(r1), "r"(r2), "r"(r3) : "memory");
}
__device__ __forceinline__ void ldsm4(uint32_t* r, uint32_t a) {
    asm volatile("ldmatrix.sync.aligned.m8n8.x4.shared.b16 {%0,%1,%2,%3}, [%4];" : "=r"(r[0]), "=r"(r[1]), "=r"(r[2]), "=r"(r[3]) : "r"(a) : "memory");
}
__device__ __forceinline__ void ldsm4t(uint32_t* r, uint32_t a) {
    asm volatile("ldmatrix.sync.aligned.m8n8.x4.trans.shared.b16 {%0,%1,%2,%3}, [%4];" : "=r"(r[0]), "=r"(r[1]), "=r"(r[2]), "=r"(r[3]) : "r"(a) : "memory");
}
__device__ __forceinline__ uint32_t ld_rlx(const void* p) { uint32_t v; asm volatile("ld.relaxed.gpu.global.u32 %0, [%1];" : "=r"(v) : "l"(p) : "memory"); return v; }
__device__ __forceinline__ uint32_t ld_acq(const void* p) { uint32_t v; asm volatile("ld.acquire.gpu.global.u32 %0, [%1];" : "=r"(v) : "l"(p) : "memory"); return v; }
__device__ __forceinline__ uint2 ld_rlx2(const void* p) { uint2 v; asm volatile("ld.relaxed.gpu.global.v2.u32 {%0,%1}, [%2];" : "=r"(v.x), "=r"(v.y) : "l"(p) : "memory"); return v; }
__device__ __forceinline__ uint4 ld_rlx4(const void* p) { uint4 v; asm volatile("ld.relaxed.gpu.global.v4.u32 {%0,%1,%2,%3}, [%4];" : "=r"(v.x), "=r"(v.y), "=r"(v.z), "=r"(v.w) : "l"(p) : "memory"); return v; }
__device__ __forceinline__ void st_rlx(void* p, uint32_t v) { asm volatile("st.relaxed.gpu.global.u32 [%0], %1;" ::"l"(p), "r"(v) : "memory"); }
__device__ __forceinline__ void st_rlx2(void* p, uint32_t a, uint32_t b) { asm volatile("st.relaxed.gpu.global.v2.u32 [%0], {%1,%2};" ::"l"(p), "r"(a), "r"(b) : "memory"); }
__device__ __forceinline__ void st_rlx4(void* p, uint32_t a, uint32_t b, uint32_t c, uint32_t d) { asm volatile("st.relaxed.gpu.global.v4.u32 [%0], {%1,%2,%3,%4};" ::"l"(p), "r"(a), "r"(b), "r"(c), "r"(d) : "memory"); }
__device__ __forceinline__ void red_add(uint32_t* p) { asm volatile("red.relaxed.gpu.global.add.u32 [%0], 1;" ::"l"(p) : "memory"); }
__device__ __forceinline__ uint4 ldg_nc(const void* p) { uint4 v; asm volatile("ld.global.nc.v4.u32 {%0,%1,%2,%3}, [%4];" : "=r"(v.x), "=r"(v.y), "=r"(v.z), "=r"(v.w) : "l"(p)); return v; }
__device__ __forceinline__ void sts4(uint32_t a, uint32_t x, uint32_t y, uint32_t z, uint32_t w) { asm volatile("st.shared.v4.u32 [%0], {%1,%2,%3,%4};" ::"r"(a), "r"(x), "r"(y), "r"(z), "r"(w) : "memory"); }
__device__ __forceinline__ void sts2(uint32_t a, uint32_t x, uint32_t y) { asm volatile("st.shared.v2.u32 [%0], {%1,%2};" ::"r"(a), "r"(x), "r"(y) : "memory"); }
__device__ __forceinline__ void sts1(uint32_t a, uint32_t v) { asm volatile("st.shared.u32 [%0], %1;" ::"r"(a), "r"(v) : "memory"); }
__device__ __forceinline__ uint4 lds4(uint32_t a) { uint4 v; asm volatile("ld.shared.v4.u32 {%0,%1,%2,%3}, [%4];" : "=r"(v.x), "=r"(v.y), "=r"(v.z), "=r"(v.w) : "r"(a) : "memory"); return v; }
__device__ __forceinline__ float4 lds4f(uint32_t a) { float4 v; asm volatile("ld.shared.v4.f32 {%0,%1,%2,%3}, [%4];" : "=f"(v.x), "=f"(v.y), "=f"(v.z), "=f"(v.w) : "r"(a) : "memory"); return v; }
__device__ __forceinline__ float2 lds2f(uint32_t a) { float2 v; asm volatile("ld.shared.v2.f32 {%0,%1}, [%2];" : "=f"(v.x), "=f"(v.y) : "r"(a) : "memory"); return v; }
__device__ __forceinline__ float lds1f(uint32_t a) { float v; asm volatile("ld.shared.f32 %0, [%1];" : "=f"(v) : "r"(a) : "memory"); return v; }
__device__ __forceinline__ uint32_t lds1(uint32_t a) { uint32_t v; asm volatile("ld.shared.u32 %0, [%1];" : "=r"(v) : "r"(a) : "memory"); return v; }
__device__ __forceinline__ uint32_t redux_max(uint32_t v) { uint32_t r; asm volatile("redux.sync.max.u32 %0, %1, 0xffffffff;" : "=r"(r) : "r"(v)); return r; }
__device__ __forceinline__ uint32_t poll_all(const uint32_t* p, uint32_t mask, uint32_t want, int& budget) {
    uint32_t v;
#pragma unroll 1
    while (v = ld_acq(p), !__all_sync(0xffffffffu, (v & mask) == want) && --budget > 0) __nanosleep(POLL_NS);
    return v;
}

template <int TA, int TB>
__device__ __forceinline__ void wgmma_n192(float (&d)[96], uint64_t da, uint64_t db, int keep) {
    asm volatile("{\n.reg .pred p;\nsetp.ne.b32 p, %98, 0;\n"
        "wgmma.mma_async.sync.aligned.m64n192k16.f32.bf16.bf16 "
        "{%0, %1, %2, %3, %4, %5, %6, %7, %8, %9, %10, %11, %12, %13, %14, %15, "
        "%16, %17, %18, %19, %20, %21, %22, %23, %24, %25, %26, %27, %28, %29, %30, %31, "
        "%32, %33, %34, %35, %36, %37, %38, %39, %40, %41, %42, %43, %44, %45, %46, %47, "
        "%48, %49, %50, %51, %52, %53, %54, %55, %56, %57, %58, %59, %60, %61, %62, %63, "
        "%64, %65, %66, %67, %68, %69, %70, %71, %72, %73, %74, %75, %76, %77, %78, %79, "
        "%80, %81, %82, %83, %84, %85, %86, %87, %88, %89, %90, %91, %92, %93, %94, %95}, "
        "%96, %97, p, 1, 1, %99, %100;\n}\n"
        : "+f"(d[0]), "+f"(d[1]), "+f"(d[2]), "+f"(d[3]), "+f"(d[4]), "+f"(d[5]), "+f"(d[6]), "+f"(d[7]),
          "+f"(d[8]), "+f"(d[9]), "+f"(d[10]), "+f"(d[11]), "+f"(d[12]), "+f"(d[13]), "+f"(d[14]), "+f"(d[15]),
          "+f"(d[16]), "+f"(d[17]), "+f"(d[18]), "+f"(d[19]), "+f"(d[20]), "+f"(d[21]), "+f"(d[22]), "+f"(d[23]),
          "+f"(d[24]), "+f"(d[25]), "+f"(d[26]), "+f"(d[27]), "+f"(d[28]), "+f"(d[29]), "+f"(d[30]), "+f"(d[31]),
          "+f"(d[32]), "+f"(d[33]), "+f"(d[34]), "+f"(d[35]), "+f"(d[36]), "+f"(d[37]), "+f"(d[38]), "+f"(d[39]),
          "+f"(d[40]), "+f"(d[41]), "+f"(d[42]), "+f"(d[43]), "+f"(d[44]), "+f"(d[45]), "+f"(d[46]), "+f"(d[47]),
          "+f"(d[48]), "+f"(d[49]), "+f"(d[50]), "+f"(d[51]), "+f"(d[52]), "+f"(d[53]), "+f"(d[54]), "+f"(d[55]),
          "+f"(d[56]), "+f"(d[57]), "+f"(d[58]), "+f"(d[59]), "+f"(d[60]), "+f"(d[61]), "+f"(d[62]), "+f"(d[63]),
          "+f"(d[64]), "+f"(d[65]), "+f"(d[66]), "+f"(d[67]), "+f"(d[68]), "+f"(d[69]), "+f"(d[70]), "+f"(d[71]),
          "+f"(d[72]), "+f"(d[73]), "+f"(d[74]), "+f"(d[75]), "+f"(d[76]), "+f"(d[77]), "+f"(d[78]), "+f"(d[79]),
          "+f"(d[80]), "+f"(d[81]), "+f"(d[82]), "+f"(d[83]), "+f"(d[84]), "+f"(d[85]), "+f"(d[86]), "+f"(d[87]),
          "+f"(d[88]), "+f"(d[89]), "+f"(d[90]), "+f"(d[91]), "+f"(d[92]), "+f"(d[93]), "+f"(d[94]), "+f"(d[95])
        : "l"(da), "l"(db), "r"(keep), "n"(TA), "n"(TB));
}
template <int TA, int TB>
__device__ __forceinline__ void wgmma_n128(float (&d)[64], uint64_t da, uint64_t db, int keep) {
    asm volatile("{\n.reg .pred p;\nsetp.ne.b32 p, %66, 0;\n"
        "wgmma.mma_async.sync.aligned.m64n128k16.f32.bf16.bf16 "
        "{%0, %1, %2, %3, %4, %5, %6, %7, %8, %9, %10, %11, %12, %13, %14, %15, "
        "%16, %17, %18, %19, %20, %21, %22, %23, %24, %25, %26, %27, %28, %29, %30, %31, "
        "%32, %33, %34, %35, %36, %37, %38, %39, %40, %41, %42, %43, %44, %45, %46, %47, "
        "%48, %49, %50, %51, %52, %53, %54, %55, %56, %57, %58, %59, %60, %61, %62, %63}, "
        "%64, %65, p, 1, 1, %67, %68;\n}\n"
        : "+f"(d[0]), "+f"(d[1]), "+f"(d[2]), "+f"(d[3]), "+f"(d[4]), "+f"(d[5]), "+f"(d[6]), "+f"(d[7]),
          "+f"(d[8]), "+f"(d[9]), "+f"(d[10]), "+f"(d[11]), "+f"(d[12]), "+f"(d[13]), "+f"(d[14]), "+f"(d[15]),
          "+f"(d[16]), "+f"(d[17]), "+f"(d[18]), "+f"(d[19]), "+f"(d[20]), "+f"(d[21]), "+f"(d[22]), "+f"(d[23]),
          "+f"(d[24]), "+f"(d[25]), "+f"(d[26]), "+f"(d[27]), "+f"(d[28]), "+f"(d[29]), "+f"(d[30]), "+f"(d[31]),
          "+f"(d[32]), "+f"(d[33]), "+f"(d[34]), "+f"(d[35]), "+f"(d[36]), "+f"(d[37]), "+f"(d[38]), "+f"(d[39]),
          "+f"(d[40]), "+f"(d[41]), "+f"(d[42]), "+f"(d[43]), "+f"(d[44]), "+f"(d[45]), "+f"(d[46]), "+f"(d[47]),
          "+f"(d[48]), "+f"(d[49]), "+f"(d[50]), "+f"(d[51]), "+f"(d[52]), "+f"(d[53]), "+f"(d[54]), "+f"(d[55]),
          "+f"(d[56]), "+f"(d[57]), "+f"(d[58]), "+f"(d[59]), "+f"(d[60]), "+f"(d[61]), "+f"(d[62]), "+f"(d[63])
        : "l"(da), "l"(db), "r"(keep), "n"(TA), "n"(TB));
}
template <int TA, int TB>
__device__ __forceinline__ void wgmma_n8(float (&d)[4], uint64_t da, uint64_t db, int keep) {
    asm volatile("{\n.reg .pred p;\nsetp.ne.b32 p, %6, 0;\n"
        "wgmma.mma_async.sync.aligned.m64n8k16.f32.bf16.bf16 "
        "{%0, %1, %2, %3}, "
        "%4, %5, p, 1, 1, %7, %8;\n}\n"
        : "+f"(d[0]), "+f"(d[1]), "+f"(d[2]), "+f"(d[3])
        : "l"(da), "l"(db), "r"(keep), "n"(TA), "n"(TB));
}
__device__ __forceinline__ void wgmma_rs_n192(float (&d)[96], uint32_t a0, uint32_t a1, uint32_t a2, uint32_t a3, uint64_t db) {
    asm volatile("{\n.reg .pred p;\nsetp.ne.b32 p, 1, 0;\n"
        "wgmma.mma_async.sync.aligned.m64n192k16.f32.bf16.bf16 "
        "{%0, %1, %2, %3, %4, %5, %6, %7, %8, %9, %10, %11, %12, %13, %14, %15, "
        "%16, %17, %18, %19, %20, %21, %22, %23, %24, %25, %26, %27, %28, %29, %30, %31, "
        "%32, %33, %34, %35, %36, %37, %38, %39, %40, %41, %42, %43, %44, %45, %46, %47, "
        "%48, %49, %50, %51, %52, %53, %54, %55, %56, %57, %58, %59, %60, %61, %62, %63, "
        "%64, %65, %66, %67, %68, %69, %70, %71, %72, %73, %74, %75, %76, %77, %78, %79, "
        "%80, %81, %82, %83, %84, %85, %86, %87, %88, %89, %90, %91, %92, %93, %94, %95}, "
        "{%96, %97, %98, %99}, %100, p, 1, 1, 1;\n}\n"
        : "+f"(d[0]), "+f"(d[1]), "+f"(d[2]), "+f"(d[3]), "+f"(d[4]), "+f"(d[5]), "+f"(d[6]), "+f"(d[7]),
          "+f"(d[8]), "+f"(d[9]), "+f"(d[10]), "+f"(d[11]), "+f"(d[12]), "+f"(d[13]), "+f"(d[14]), "+f"(d[15]),
          "+f"(d[16]), "+f"(d[17]), "+f"(d[18]), "+f"(d[19]), "+f"(d[20]), "+f"(d[21]), "+f"(d[22]), "+f"(d[23]),
          "+f"(d[24]), "+f"(d[25]), "+f"(d[26]), "+f"(d[27]), "+f"(d[28]), "+f"(d[29]), "+f"(d[30]), "+f"(d[31]),
          "+f"(d[32]), "+f"(d[33]), "+f"(d[34]), "+f"(d[35]), "+f"(d[36]), "+f"(d[37]), "+f"(d[38]), "+f"(d[39]),
          "+f"(d[40]), "+f"(d[41]), "+f"(d[42]), "+f"(d[43]), "+f"(d[44]), "+f"(d[45]), "+f"(d[46]), "+f"(d[47]),
          "+f"(d[48]), "+f"(d[49]), "+f"(d[50]), "+f"(d[51]), "+f"(d[52]), "+f"(d[53]), "+f"(d[54]), "+f"(d[55]),
          "+f"(d[56]), "+f"(d[57]), "+f"(d[58]), "+f"(d[59]), "+f"(d[60]), "+f"(d[61]), "+f"(d[62]), "+f"(d[63]),
          "+f"(d[64]), "+f"(d[65]), "+f"(d[66]), "+f"(d[67]), "+f"(d[68]), "+f"(d[69]), "+f"(d[70]), "+f"(d[71]),
          "+f"(d[72]), "+f"(d[73]), "+f"(d[74]), "+f"(d[75]), "+f"(d[76]), "+f"(d[77]), "+f"(d[78]), "+f"(d[79]),
          "+f"(d[80]), "+f"(d[81]), "+f"(d[82]), "+f"(d[83]), "+f"(d[84]), "+f"(d[85]), "+f"(d[86]), "+f"(d[87]),
          "+f"(d[88]), "+f"(d[89]), "+f"(d[90]), "+f"(d[91]), "+f"(d[92]), "+f"(d[93]), "+f"(d[94]), "+f"(d[95])
        : "r"(a0), "r"(a1), "r"(a2), "r"(a3), "l"(db));
}
__device__ __forceinline__ void wgmma_rs_n8(float (&d)[4], uint32_t a0, uint32_t a1, uint32_t a2, uint32_t a3, uint64_t db) {
    asm volatile("{\n.reg .pred p;\nsetp.ne.b32 p, 1, 0;\n"
        "wgmma.mma_async.sync.aligned.m64n8k16.f32.bf16.bf16 "
        "{%0, %1, %2, %3}, "
        "{%4, %5, %6, %7}, %8, p, 1, 1, 0;\n}\n"
        : "+f"(d[0]), "+f"(d[1]), "+f"(d[2]), "+f"(d[3])
        : "r"(a0), "r"(a1), "r"(a2), "r"(a3), "l"(db));
}

template <int HS>
__device__ __forceinline__ void attn_pair(const uint32_t* q, const uint32_t* k, const uint32_t* v, const uint32_t* kh, const uint32_t* vh,
                                          const float* fu, const float* fn, const float* rk, float bias0, float bias1, uint32_t mU, uint32_t zero, const float* ci, uint32_t* o) {
    float s0[2][4] = {}, s1[2][4] = {}, s2[2][4] = {};
#pragma unroll
    for (int n = 0; n < 4; n++) {
        const int hd = n & 1, a = 8 * hd + 2 * (n & 2);
        mma16816(s1[hd], q[a], q[a + 1], q[a + 2], q[a + 3], k[a], k[a + 2]);
        mma16816(s2[hd], q[a], q[a + 1], q[a + 2], q[a + 3], k[a + 1], k[a + 3]);
    }
#pragma unroll
    for (int n = 0; n < 4; n++) {
        const int hd = n & 1, a = 8 * hd + 2 * (n & 2);
        mma16816(s0[hd], q[a], q[a + 1], q[a + 2], q[a + 3], kh[HS * (a / 2)], kh[HS * (a / 2 + 1)]);
    }
    float e[2][4], m[2][2];
#pragma unroll
    for (int hd = 0; hd < 2; hd++) {
        e[hd][2] = fmaf(s1[hd][2], fu[2], s2[hd][2] * fn[2]); e[hd][3] = fmaf(s1[hd][3], fu[3], s2[hd][3] * fn[3]);
        e[hd][0] = fmaf(s0[hd][0], fu[0], fmaf(s1[hd][0], fn[0], bias0)); e[hd][1] = fmaf(s0[hd][1], fu[1], fmaf(s1[hd][1], fn[1], bias1));
        m[hd][1] = fmaxf(e[hd][2], e[hd][3]); m[hd][0] = fmaxf(e[hd][0], e[hd][1]);
    }
#pragma unroll
    for (int x = 1; x < 3; x++)
#pragma unroll
        for (int n = 0; n < 4; n++) m[n & 1][1 - (n >> 1)] = fmaxf(m[n & 1][1 - (n >> 1)], __shfl_xor_sync(0xffffffffu, m[n & 1][1 - (n >> 1)], x));
#pragma unroll
    for (int hd = 0; hd < 2; hd++) {
#pragma unroll
        for (int n = 0; n < 4; n++) e[hd][n] = ex2(e[hd][n] - m[hd][n >> 1]);
        float sum[4] = {};
        mma1688(sum, pack_bf16(e[hd][0], e[hd][1]), pack_bf16(e[hd][2], e[hd][3]), 0x3f803f80u);
        const float i0 = rcp(sum[0]), i1 = rcp(sum[2]);
        const uint32_t plo = pack_bf16(e[hd][0] * rk[0] * i0, e[hd][1] * rk[1] * i0), phi = pack_bf16(e[hd][2] * rk[2] * i1, e[hd][3] * rk[3] * i1);
        const uint32_t z0 = plo & zero, z1 = phi & zero;
        const uint32_t a0 = plo & ~mU, a1 = phi & mU, a3 = phi & ~mU, b0 = plo & mU;
#pragma unroll
        for (int jj = 0; jj < 4; jj++) {
            float c[4];
            asm volatile("mma.sync.aligned.m16n8k16.row.col.f32.bf16.bf16.f32 {%0,%1,%2,%3}, {%4,%5,%6,%7}, {%8,%9}, {%10,%11,%12,%13};"
                         : "=f"(c[0]), "=f"(c[1]), "=f"(c[2]), "=f"(c[3])
                         : "r"(a0), "r"(a1), "r"(z0), "r"(a3), "r"(v[8 * hd + 2 * jj]), "r"(v[8 * hd + 2 * jj + 1]), "f"(ci[0]), "f"(ci[1]), "f"(ci[2]), "f"(ci[3]));
            mma1688(c, b0, z1, vh[HS * (4 * hd + jj)]);
            o[8 * hd + 2 * jj] = pack_bf16(c[0], c[1]); o[8 * hd + 2 * jj + 1] = pack_bf16(c[2], c[3]);
        }
    }
}

__device__ __forceinline__ uint32_t norm_pair(uint32_t u, float m, float rinv) {
    const uint32_t d = pack_bf16(bf_lo(u) - m, bf_hi(u) - m);
    return max(pack_bf16(bf_lo(d) * rinv, bf_hi(d) * rinv), 1u);
}

__global__ void __launch_bounds__(512, 1)
fused_kernel(const __grid_constant__ CUtensorMap mx, const __grid_constant__ CUtensorMap mw, const __grid_constant__ CUtensorMap mwo,
             const __grid_constant__ CUtensorMap mout, const __grid_constant__ CUtensorMap mgu, const __grid_constant__ CUtensorMap mwd,
             const __grid_constant__ CUtensorMap mo, const __grid_constant__ CUtensorMap mr,
             const __nv_bfloat16* __restrict__ x, const __nv_bfloat16* __restrict__ wr, Scratch* __restrict__ scr, int swap_gu, const Weights pf) {
    extern __shared__ __align__(1024) uint8_t smem[];
    const uint32_t sb = smem_u32(smem);
    const uint32_t bars = sb + OFF_BAR;
    const int tid = threadIdx.x, lane = tid & 31, warp = __shfl_sync(0xffffffffu, tid >> 5, 0);
    const uint32_t sd = (sb & 0x3FFFF) >> 4;
    const int hp = blockIdx.x & 1, cl = blockIdx.x >> 1;
    int pr = cl - 4 + (max(cl - 36, 0) * 37 >> 8);
    asm("{\n.reg .pred p;\nsetp.lt.s32 p, %1, 4;\nselp.s32 %0, %2, %0, p;\n}" : "+r"(pr) : "r"(cl), "r"(39 + 8 * cl));
    const int b = pr * 2 + hp, mt = pr >> 3, p = pr & 7, nt = 2 * p + hp, rh = p & 1, cb = (p & 6) + hp;
    const int par = mt >> 2, j0 = (mt & 3) * 256;
    int budget = BUDGET;

    TSC(tid == 0, 0);
    auto load_w = [&](int k, int s) {
        const uint32_t full = bars + 8 * (B_WFULL + s);
        mbar_expect_tx(full, W_BYTES);
        tma_3d(sb + OFF_W + s * W_BYTES, &mw, full, nt * 64, k * 64, 0);
    };
    auto load_x = [&](int n) {
        const int w = n & 1, j = n < 4 ? (n >> 1) + 4 : (n >> 1) - 2;
        const uint32_t full = bars + 8 * (B_XFULL + w * 6 + 5 - j);
        mbar_expect_tx(full, BOX);
        tma_4d(sb + w * OFF_X1 + j * BOX, &mx, full, par * 1024 + (n >> 2) * 64, 0, (j0 + w * 128) >> 5, (~n >> 1) & 1);
    };
    if (warp < NBAR / 6 && elect_one()) {
        const uint32_t cnt = warp < B_WEMPTY / 6 ? 1 : warp < B_G1DONE / 6 ? 2 : warp < B_STAGED / 6 ? 4 : 8;
#pragma unroll
        for (int i = 0; i < 6; i++) mbar_init(bars + 48 * warp + 8 * i, cnt);
        asm volatile("fence.mbarrier_init.release.cluster;" ::: "memory");
        if (warp == 0 && b < 128) { load_x(0); load_w(0, 2); }
    }
    __syncthreads();

    if (b >= 128) {
        const int hc = b - 128, g = lane >> 2, t = lane & 3;
        const uint32_t ep = ld_rlx(&scr->epoch[0]) + 1;
        if (warp < 12) {
            const int n = warp / 3, part = warp - 3 * n;
            auto load = [&](int k) {
                const uint32_t full = bars + 8 * (2 * n + (k & 1));
                mbar_expect_tx(full, W_BYTES);
                tma_3d(sb + (2 * n + (k & 1)) * W_BYTES, &mw, full, (4 * hc + n) * 64, k * 64, 0);
            };
            if (part == 0 && elect_one()) { load(0); load(1); }
            __syncwarp();
            float c0[4] = {0.f, 0.f, 0.f, 0.f}, c1[4] = {0.f, 0.f, 0.f, 0.f};
            const uint32_t sel = g == 0 ? 0x3f80u : g == 1 ? 0x3f800000u : 0u;
            const uint32_t a = sb + 2 * n * W_BYTES + part * BOX + t * 256 + ((g ^ (2 * t)) << 4);
#pragma unroll 1
            for (int k = 0; k < 16; k++) {
                mbar_wait(bars + 8 * (2 * n + (k & 1)), (k >> 1) & 1, budget);
                uint4 v[8], u[8];
#pragma unroll
                for (int i = 0; i < 8; i++) { v[i] = lds4(a + (k & 1) * W_BYTES + i * 1024); u[i] = lds4(((a + 128) ^ 16) + (k & 1) * W_BYTES + i * 1024); }
                bar_sync(1 + n, 96);
                if (part == k % 3 && k < 14 && elect_one()) load(k + 2);
                __syncwarp();
#pragma unroll
                for (int i = 0; i < 8; i++) { mma16816(c0, v[i].x, v[i].y, u[i].x, u[i].y, sel, sel); mma16816(c1, v[i].z, v[i].w, u[i].z, u[i].w, sel, sel); }
            }
            if (t == 0) {
#pragma unroll
                for (int r = 0; r < 3; r++) {
                    const uint32_t q0 = (pack_bf16(c0[0], c0[1]) & ~1u) | (ep & 1), q1 = pack_bf16(c0[2], c0[3]), q2 = pack_bf16(c1[0], c1[1]), q3 = pack_bf16(c1[2], c1[3]);
                    st_rlx4(&scr->cs[4 * hc + n][r][part * 8 + g], q0, q1, q2, q3);
                    c0[0] -= bf_lo(q0); c0[1] -= bf_hi(q0); c0[2] -= bf_lo(q1); c0[3] -= bf_hi(q1);
                    c1[0] -= bf_lo(q2); c1[1] -= bf_hi(q2); c1[2] -= bf_lo(q3); c1[3] -= bf_hi(q3);
                }
            }
            TSC(tid == 0, 19);
        }
        {
            const int wg = warp >> 2, c2 = 4 * hc + wg, tw = tid & 127;
            const uint32_t ring = sb + wg * 6 * BOX, full = bars + 8 * (8 + wg * 6), ha = sb + 24 * BOX;
            const uint32_t* hsrc = scr->act[ep & 1] + (56 - NH) * 256;
            auto load = [&](int q, int s) { mbar_expect_tx(full + 8 * s, BOX); tma_3d(ring + s * BOX, &mwd, full + 8 * s, 0, (56 - NH + q) * 64, c2); };
            const uint32_t key = poll_all(&scr->sel[lane & 7], 31u, ep & 31, budget);
            __syncthreads();
            TSC(tid == 0, 12);
            if ((warp & 3) == 0 && elect_one()) {
#pragma unroll 1
                for (int q = 0; q < 6; q++) { load(q, q); __nanosleep(H_NS); }
            }
            __syncwarp();
            const int zr = (2047 - ((__shfl_sync(0xffffffffu, key, warp >> 1) >> 5) & 2047)) & ~30;
#pragma unroll
            for (int i = 0; i < 8; i++) st_rlx4(pf.out + (size_t)(zr + (warp & 1) * 16 + 2 * i) * 2048 + hc * 512 + lane * 16, 0, 0, 0, 0);
            __syncthreads();
                        __syncwarp();
            uint32_t wa[NR * 16];
#pragma unroll
            for (int q = 0; q < NR; q++) {
                mbar_wait(full + 8 * q, 0, budget);
                TSC(tid == 0, 32 + q);
#pragma unroll
                for (int j = 0; j < 4; j++) ldsm4t(wa + 16 * q + 4 * j, ring + q * BOX + j * 2048 + (lane >> 4) * 1024 + (lane & 7) * 128 + ((((warp & 3) * 2 + ((lane >> 3) & 1)) ^ (lane & 7)) << 4));
                bar_sync(1 + wg, 128);
                if ((warp & 3) == 0 && elect_one()) { load(q + 6, q); __nanosleep(H_NS); }
                __syncwarp();
            }
            if (tid == 64) { fence_gpu(); st_rlx(&scr->zflag[hc], ep); }
            if (warp == 1 && elect_one()) {
                int tries = BUDGET;
#pragma unroll 1
                while (ld_rlx(&scr->cnt[8][0]) != ep * (4 * NH) && --tries > 0) {}
                mbar_expect_tx(bars + 8 * 32, NH * 1024);
                bulk_g2s(ha, hsrc, NH * 1024, bars + 8 * 32);
                TS(17);
            }
            __syncwarp();
            mbar_wait(bars + 8 * 32, 0, budget);
#pragma unroll 1
            for (int i = tid; i < NH * 64; i += 512) {
                int tries = BUDGET;
                if (lds1(ha + i * 16) == 0) {
                    uint4 v;
#pragma unroll 1
                    do { v = ld_rlx4(hsrc + i * 4); } while (v.x == 0 && --tries > 0);
                    sts4(ha + i * 16, v.x, v.y, v.z, v.w);
                }
            }
            fence_async_smem();
            __syncthreads();
            TSC(tid == 0, 5);
            float acc[4] = {0.f, 0.f, 0.f, 0.f};
            int s = NR; uint32_t ph = 0;
#pragma unroll 1
            for (int q = NR; q < NH; q++) {
                mbar_wait(full + 8 * s, ph, budget);
                TSC(tid == 0, 32 + q);
                wg_fence();
#pragma unroll
                for (int j = 0; j < 4; j++)
                    wgmma_n8<1, 0>(acc, mkdesc(sd + dlo((wg * 6 + s) * BOX, BOX) + j * 128, dhi(1024, 1)), mkdesc(sd + dlo(24 * BOX + q * 1024, 128) + j * 16, dhi(128, 0)), 1);
                wg_commit();
                wg_wait<1>();
                if ((warp & 3) == (q & 3) && q > NR && q + 5 < NH && elect_one()) load(q + 5, s ? s - 1 : 5);
                __syncwarp();
                if (++s == 6) { s = 0; ph ^= 1; }
                if (q == NR + 5) {
                    wg_fence();
#pragma unroll
                    for (int j = 0; j < 4 * NR; j++) wgmma_rs_n8(acc, wa[4 * j], wa[4 * j + 1], wa[4 * j + 2], wa[4 * j + 3], mkdesc(sd + dlo(24 * BOX, 128) + j * 16, dhi(128, 0)));
                    wg_commit();
                }
            }
            wg_wait<0>();
            TSC(tid == 0, 18);
            uint4 v[8]; uint32_t bad; int tries = BUDGET;
#pragma unroll 1
            do {
                bad = 0;
#pragma unroll
                for (int m = 0; m < 8; m++) v[m] = ld_rlx4(&scr->ypart[m][c2][tw]);
#pragma unroll
                for (int m = 0; m < 8; m++) bad |= v[m].x ^ ep;
            } while ((bad & 1) && --tries > 0);
            __syncwarp();
            const float sig = bf16r(sigmoidf(__uint_as_float(((int)key < 0 ? key & 0x7fffffffu : ~key) & 0xffff0000u)));
#pragma unroll
            for (int c = 0; c < 4; c++) {
#pragma unroll
                for (int m = 0; m < 8; m++) acc[c] += __uint_as_float((&v[m].x)[c]);
                acc[c] = bf16r(acc[c]) * __shfl_sync(0xffffffffu, sig, 2 * t + (c & 1));
            }
            char* dst = pf.out + (size_t)(2047 - ((__shfl_sync(0xffffffffu, key, g) >> 5) & 2047)) * 2048 + c2 * 128 + (warp & 3) * 32 + t * 4;
            asm volatile("red.relaxed.gpu.global.add.noftz.bf16x2 [%0], %1;" ::"l"(dst), "r"(movm(pack_bf16(acc[0], acc[1]))) : "memory");
            asm volatile("red.relaxed.gpu.global.add.noftz.bf16x2 [%0], %1;" ::"l"(dst + 16), "r"(movm(pack_bf16(acc[2], acc[3]))) : "memory");
            TSC(tid == 0, 20);
        }
        if (warp < 8) TS_END();
        return;
    }
    asm volatile("barrier.cluster.arrive.relaxed.aligned;" ::: "memory");

    const int c2 = b & 15, n2 = mt < 7 ? NM : N7;
    if (warp >= 12) {
        reg_dec<24>();
        if (warp == 12) {
            if (elect_one()) {
                int c = 0;
#pragma unroll 1
                for (int n = 1; n < 12; n++) {
                    load_x(n);
                    #pragma unroll 1
                    for (; c < (n == 11 ? 4 : __popc(ROWS_AT & ((2 << n) - 1))); c++) { mbar_expect_tx(bars + 8 * (B_ROW + c), BOX); tma_2d(sb + OFF_FR + c * BOX, &mr, bars + 8 * (B_ROW + c), c * 256, b * 16); }
                    if (n == 3 || n == 7) load_w((n + 1) >> 2, n >> 2);
                }
                int s = 2; uint32_t ph = 0;
#pragma unroll 1
                for (int k = 3; k < 16; k++) {
                    mbar_wait(bars + 8 * (B_WEMPTY + s), ph, budget);
                    load_w(k, s);
                    if (++s == 3) s = 0;
                    if (s == 2) ph ^= 1;
                }
                s = 2;
#pragma unroll 1
                for (int i = 0; i < 16; i++) {
                    mbar_wait(bars + 8 * (i < 2 ? B_WEMPTY + i : i < 4 ? B_G1DONE : i < 6 ? B_F1DONE : B_WOEMPTY + s), i >= 12, budget);
                    if (i == 0) {
                        mbar_expect_tx(bars + 8 * B_XT, 4 * BOX);
#pragma unroll 1
                        for (int n = 0; n < 4; n++)
                            tma_4d(sb + (n >> 1) * OFF_X1 + (n & 1) * BOX, &mx, bars + 8 * B_XT, par * 1024 + cb * 128 + (n & 1) * 64, 0, (j0 + rh * 128) >> 5, 1 - (n >> 1));
                    }
                    const uint32_t full = bars + 8 * (B_WOFULL + s);
                    mbar_expect_tx(full, 2 * BOX);
                    tma_3d(sb + OFF_WO + s * 2 * BOX, &mwo, full, 0, ((2 * p + (i < 2 ? i ^ hp : i)) & 15) * 64, cb * 2);
                    TSC(TIMING % 10 == 4, 48 + i);
                    if (++s == 6) s = 0;
                }
            }
        } else {
            bar_sync(8, 224);
            const uint32_t ep = __shfl_sync(0xffffffffu, lds1(sb + OFF_EP), 0);
            if (warp == 13) {
                cluster_wait();
                if (elect_one()) {
                    int j = 4, q = 0, left = BUDGET; uint32_t ph = 0;
#pragma unroll 1
                    for (int n = 6; n < 32; n++) {
                        mbar_wait(bars + 8 * (B_XEMPTY + j), ph, left);
                        tma_4d_mc(sb + hp * OFF_X1 + j * BOX, &mx, bars + 8 * (B_XFULL + hp * 6 + 5 - j), par * 1024 + (n >> 1) * 64, 0, (j0 + hp * 128) >> 5, ~n & 1);
                        if (++j == 6) j = 0;
                        if (j == 4) ph ^= 1;
#pragma unroll 1
                        for (; q < (PF_RATE * (n - PF_START) >> 3) && q < 18 + PF_NW; q++) {
                            const int u = q - PF_NW;
                            if (u < 0) bulk_pf(pf.wqkv + (size_t)(1024 + 128 * u + b) * 6144, 6144);
                            else if (u < 16) bulk_pf((b < 64 ? pf.wg : pf.wu) + (size_t)(u * 64 + (b & 63)) * 7168, 7168);
                            else bulk_pf(pf.wo + (size_t)((u - 16) * 128 + b) * 8192, 8192);
                        }
                    }
                }
                __syncwarp();
                uint32_t* hs = &scr->halo[b - 16][lane * 4];
                uint4 v[4] = {};
                if (j0) {
#pragma unroll 1
                    do {
#pragma unroll
                        for (int c = 0; c < 4; c++) v[c] = ld_rlx4(hs + c * 128);
                    } while (__any_sync(0xffffffffu, min(min(v[0].x, v[1].x), min(v[2].x, v[3].x)) == 0) && --budget > 0);
#pragma unroll
                    for (int c = 0; c < 4; c++) st_rlx(hs + c * 128, 0);
                }
#pragma unroll
                for (int c = 0; c < 4; c++) stsm4(sb + OFF_HIN + c * 512 + lane * 16, v[c].x, v[c].y, v[c].z, v[c].w);
                bar_arrive(11, 64);
                TSC(lane == 0, 31);
                const int src = ((mt * 2 + rh) * 2 + 1 - hp) * 1024;
                if (elect_one()) {
                    const uint32_t* fl = &scr->oflag[mt * 2 + 1 - hp][0];
                    const uint32_t inv = (ep & 1) - 1;
                    uint32_t ready = 0, ph = 0;
                    int s = 4;
#pragma unroll 1
                    for (int i = 2; i < 16; i++) {
                        const int kb = (2 * p + i) & 15;
#pragma unroll 1
                        while (!((ready >> kb) & 1) && --budget > 0) ready = ld_rlx(fl) ^ inv;
                        TSC(i == 2, 30);
                        mbar_wait(bars + 8 * (B_OEMPTY + s), ph, budget);
                        tma_2d_mc(sb + hp * OFF_X1 + s * BOX, &mo, bars + 8 * (B_OFULL + hp * 6 + s), 0, src + kb * 64);
                        TSC(TIMING % 10 == 4 && hp == 0, 32 + i);
                        if (++s == 6) s = 0;
                        if (s == 4) ph ^= 1;
                    }
                }
            } else if (warp == 14) {
                if (elect_one()) {
                    uint32_t s8 = 0, ph = 0;
                    int tries = BUDGET;
                    const uint32_t* act = scr->act[ep & 1];
                    auto counted = [&](int c, uint32_t n) {
#pragma unroll 1
                        while (ld_rlx(&scr->cnt[c][0]) != ep * n && --tries > 0) __nanosleep(POLL_NS);
                    };
                    auto weights = [&](const CUtensorMap* m, int c0, int c1, int c2_) {
                        mbar_wait(bars + 8 * B_FEMPTY + s8, ph, budget);
                        mbar_expect_tx(bars + 8 * B_FFULL + s8, F_BYTES);
                        tma_3d(sb + OFF_FS + s8 * (F_BYTES / 8), m, bars + 8 * B_FFULL + s8, c0, c1, c2_);
                    };
                    if (b < 112) {
                        counted(9, 32);
                        TS(26);
#pragma unroll 1
                        for (int q = 0; q < 16; q++) {
                            weights(&mgu, b * 32, q * 64, 0);
                            bulk_g2s(sb + OFF_FS + BOX + s8 * (F_BYTES / 8), act + 14336 + q * 256, 1024, bars + 8 * B_FFULL + s8);
                            TSC(TIMING % 10 == 5, 32 + q);
                            if (q >= PF_D && q < PF_D + 8) bulk_pf(pf.wd + (size_t)((q - PF_D) * 112 + b) * 8192, 8192);
                            s8 += 8;
                            if (s8 == 40) { s8 = 0; ph ^= 1; }
                        }
                    }
#pragma unroll 1
                    for (int q = -3; q < n2; q++) {
                        if (q == 0) { counted(mt, 4 * n2); TS(29); }
                        if ((unsigned)q >= 3) weights(&mwd, 0, (mt * NM + (q < 0 ? q + 3 : q)) * 64, c2);
                        if (q >= 0) bulk_g2s(sb + OFF_FS + BOX + s8 * (F_BYTES / 8), act + (mt * NM + q) * 256, 1024, bars + 8 * B_FFULL + s8);
                        TSC(TIMING % 10 == 5, 51 + q);
                        s8 += 8;
                        if (s8 == 24) { s8 = 0; if ((unsigned)q >= 3) ph ^= 1; }
                    }
                }
            } else {
#pragma unroll 1
                for (int i = lane * 16; i < CS_BYTES; i += 512) sts4(sb + OFF_CS + i, 0, 0, 0, 0);
                mbar_wait(bars + 8 * ZF_GATE, 0, budget);
                uint8_t* oz = scr->o + ((size_t)mt * 64 + nt) * BOX + lane * 16;
#pragma unroll 1
                for (int i = 0; i < 16; i++, oz += 512) {
#pragma unroll
                    for (int n = 0; n < 4; n++) st_rlx4(oz + n * 16 * BOX, 0, 0, 0, 0);
                    __nanosleep(ZF_NS);
                }
                __syncwarp();
                TSC(lane == 0, 5);
                fence_gpu();
                TSC(lane == 0, 12);
                mbar_wait(bars + 8 * B_RDONE, 0, budget);
                int tries = BUDGET;
#pragma unroll 1
                for (int i = lane; i < 88; i += 32) {
                    const uint2* rp = &scr->row[2 * (j0 - 8 + i) + par];
                    uint2 v0, v1, v2;
#pragma unroll 1
                    do { v0 = ld_rlx2(rp + (j0 + i < 8 ? 16 : 0)); v1 = ld_rlx2(rp + 176); v2 = ld_rlx2(rp + 352); } while ((((v0.y ^ ep) | (v1.y ^ ep) | (v2.y ^ ep)) & 31) && --tries > 0);
                    sts2(sb + OFF_STAT + i * 8, (v0.x << 16) ^ 0x80000000u, __float_as_uint(rcp(bf_hi(v0.x))));
                    sts2(sb + OFF_STAT + i * 8 + 704, (v1.x << 16) ^ 0x80000000u, __float_as_uint(rcp(bf_hi(v1.x))));
                    sts2(sb + OFF_STAT + i * 8 + 1408, (v2.x << 16) ^ 0x80000000u, __float_as_uint(rcp(bf_hi(v2.x))));
                }
                __syncwarp();
                {
                    const int row = 2047 - ((poll_all(&scr->sel[lane & 7], 31u, ep & 31, budget) >> 5) & 2047), jj = (row >> 1) - j0 - rh * 128;
                    sts1(sb + OFF_SEL, __reduce_or_sync(0xffffffffu, (row & 1) == par && (unsigned)jj < 128 ? 1u << (jj >> 4) : 0u));
                }
                TSC(lane == 0, 14);
                if (lane < 24) {
                    uint4 v[3];
#pragma unroll 1
                    while (v[0] = ld_rlx4(&scr->cs[nt][0][lane]), v[1] = ld_rlx4(&scr->cs[nt][1][lane]), v[2] = ld_rlx4(&scr->cs[nt][2][lane]),
                           (((v[0].x ^ ep) | (v[1].x ^ ep) | (v[2].x ^ ep)) & 1) && --tries > 0) __nanosleep(100);
#pragma unroll
                    for (int r = 0; r < 3; r++) sts4(sb + OFF_CS + 64 + lane * 128 + r * 16, v[r].x, v[r].y, v[r].z, v[r].w);
                }
                fence_async_smem();
                __syncwarp();
                if (elect_one()) {
                    mbar_arrive(bars + 8 * B_AUX);
                    TS(21);
                    mbar_expect_tx(bars + 8 * (B_OFULL + 3), BOX); mbar_expect_tx(bars + 8 * (B_OFULL + 9), BOX);
#pragma unroll 1
                    for (int v = 0; v < 2; v++) {
                        const uint32_t ring = sb + v * OFF_X1 + 2 * BOX, fb = bars + 8 * (B_OFULL + v * 6 + 2);
                        mbar_wait(bars + 8 * (B_STAGED + v), 0, budget);
                        asm volatile("red.relaxed.gpu.global.xor.b32 [%0], %1;" ::"l"(&scr->oflag[mt * 2 + 1 - v][0]), "r"(1u << nt) : "memory");
                        TS(13 + 2 * v);
                        mbar_arrive(fb);
                        mbar_wait(bars + 8 * B_G1DONE, 0, budget);
                        bulk_s2c(mapa(ring + BOX, hp ^ 1), ring, BOX, mapa(fb + 8, hp ^ 1));
                        if (v == 0) mbar_wait(bars + 8 * B_FREED, 0, budget);
#pragma unroll
                        for (int n = 0; n < 4; n++) {
                            mbar_expect_tx(bars + 8 * (B_OFULL + (n >> 1) * 6 + 4 + (n & 1)) - v * 32, BOX);
                            mbar_arrive_at(mapa(bars + 8 * B_OEMPTY, n >> 1) + (4 + (n & 1)) * 8 - v * 32);
                        }
                    }
                    if (lds1(sb + OFF_SEL)) {
#pragma unroll 1
                        while (ld_acq(&scr->zflag[p >> 1]) != ep && --tries > 0) {}
                        asm volatile("fence.proxy.async.global;" ::: "memory");
                    }
                    mbar_arrive(bars + 8 * B_ZERO);
                }
            }
        }
    } else if (warp >= 8) {
        reg_dec<40>();
        const int wq = warp - 8, ta = tid - 256;
        const uint32_t rbuf = sb + OFF_FR + wq * 2048;
        const uint4 wv = ldg_nc(wr + ta * 8);
        if (ta == 0) sts1(sb + OFF_EP, ld_rlx(&scr->epoch[0]) + 1);
        sts4(sb + OFF_STAT + ta * 16, wv.x, wv.y, wv.z, wv.w);
        bar_sync(8, 224);
        const uint32_t ep = __shfl_sync(0xffffffffu, lds1(sb + OFF_EP), 0);
        {
            const int s = b * 16 + wq * 4 + (lane >> 3);
            if ((lane & 7) == 0) st_rlx2(&scr->row[s], 0, ep - 1);
            float sw = 0.f;
#pragma unroll 1
            for (int i = 0; i < 16; i++) { const uint32_t q = lds1(sb + OFF_STAT + i * 128 + lane * 4); sw += bf_lo(q) + bf_hi(q); }
#pragma unroll 1
            for (int o = 16; o > 0; o >>= 1) sw += __shfl_xor_sync(0xffffffffu, sw, o);
            float s1 = 0.f, s2 = 0.f, sr = 0.f;
            {
                float s1b = 0.f, s2b = 0.f, srb = 0.f;
                const uint32_t xb = rbuf + (lane >> 4) * 1024 + (lane & 15) * 16, wb = sb + OFF_STAT + (lane & 15) * 16;
#pragma unroll 1
                for (int i = 0; i < 8; i++) {
                    const uint4 w4 = lds4(wb + i * 256);
                    mbar_wait_hot(bars + 8 * (B_ROW + (i >> 1)), 0, budget);
                    TSC(ta == 0 && i == 0, 17);
                    const uint32_t o = (i >> 1) * BOX + (i & 1) * 256;
                    const uint4 u = lds4(xb + o), v = lds4(xb + o + 512);
#pragma unroll
                    for (int c = 0; c < 4; c++) {
                        const float w0 = bf_lo((&w4.x)[c]), w1 = bf_hi((&w4.x)[c]);
                        const float a0 = bf_lo((&u.x)[c]), a1 = bf_hi((&u.x)[c]), b0 = bf_lo((&v.x)[c]), b1 = bf_hi((&v.x)[c]);
                        s1 += a0; s2 = fmaf(a0, a0, s2); sr = fmaf(a0, w0, sr);
                        s1 += a1; s2 = fmaf(a1, a1, s2); sr = fmaf(a1, w1, sr);
                        s1b += b0; s2b = fmaf(b0, b0, s2b); srb = fmaf(b0, w0, srb);
                        s1b += b1; s2b = fmaf(b1, b1, s2b); srb = fmaf(b1, w1, srb);
                    }
                }
                const bool up = lane & 8;
                s1 = (up ? s1b : s1) + __shfl_xor_sync(0xffffffffu, up ? s1 : s1b, 8);
                s2 = (up ? s2b : s2) + __shfl_xor_sync(0xffffffffu, up ? s2 : s2b, 8);
                sr = (up ? srb : sr) + __shfl_xor_sync(0xffffffffu, up ? sr : srb, 8);
            }
#pragma unroll
            for (int o = 1; o < 8; o <<= 1) {
                s1 += __shfl_xor_sync(0xffffffffu, s1, o); s2 += __shfl_xor_sync(0xffffffffu, s2, o); sr += __shfl_xor_sync(0xffffffffu, sr, o);
            }
            const float mean = s1 * (1.f / 1024.f), mb = bf16r(mean);
            float var = fmaf(-mean, mean, s2 * (1.f / 1024.f));
            sr = fmaf(-mb, sw, sr);
            if (__builtin_expect(__any_sync(0xffffffffu, mean * mean > 256.f * var), 0)) {
                float a2 = 0.f, ar = 0.f;
#pragma unroll 1
                for (int i = 0; i < 64; i++) {
                    const uint32_t o = i * 32 + (lane & 7) * 4, q1 = lds1(rbuf + (lane >> 3) * 512 + (o >> 9) * BOX + (o & 511)), q2 = lds1(sb + OFF_STAT + o);
                    a2 = fmaf(bf_lo(q1) - mean, bf_lo(q1) - mean, fmaf(bf_hi(q1) - mean, bf_hi(q1) - mean, a2));
                    ar = fmaf(bf_lo(q1) - mb, bf_lo(q2), fmaf(bf_hi(q1) - mb, bf_hi(q2), ar));
                }
#pragma unroll 1
                for (int o = 1; o < 8; o <<= 1) { a2 += __shfl_xor_sync(0xffffffffu, a2, o); ar += __shfl_xor_sync(0xffffffffu, ar, o); }
                var = a2 * (1.f / 1024.f); sr = ar;
            }
            float den;
            asm("sqrt.approx.f32 %0, %1;" : "=f"(den) : "f"(bf16r(bf16r(var) + 1e-5f)));
            const uint32_t st = pack_bf16(mb, den);
            const uint32_t rb = pack_bf16(0.f, sr * rcp(bf_hi(st)) + 0.f);
            uint32_t ord = (int)rb < 0 ? ~rb & 0xffff0000u : rb | 0x80000000u;
            if ((rb & 0x7fffffffu) > 0x7f800000u) ord = 0;
            if ((lane & 7) == 0) st_rlx2(&scr->row[s], st, ord | ((2047 - s) << 5) | (ep & 31));
            __syncwarp();
            if (lane < 7) mbar_arrive(bars + 8 * (lane < 5 ? B_FEMPTY + lane : B_RDONE));
        }
        TSC(ta == 0, 18);
        if ((b >> 3) == 14) {
            const uint32_t gm = sb + OFF_E, cnt = gm + 64, res = gm + 80, list = gm + 128;
            uint32_t kv[16];
            int tries = BUDGET;
#pragma unroll 1
            do {
                uint32_t bad = 0;
#pragma unroll
                for (int n = 0; n < 16; n++) kv[n] = ld_rlx(&scr->row[n * 128 + ta].y);
#pragma unroll
                for (int n = 0; n < 16; n++) bad |= kv[n] ^ ep;
                if ((bad & 31) == 0) break;
            } while (--tries > 0);
            __syncwarp();
            TSC(ta == 0, 26);
            uint32_t m = 0;
#pragma unroll
            for (int n = 0; n < 16; n++) m = max(m, kv[n]);
            uint32_t gmax = m;
#pragma unroll
            for (int o = 1; o < 8; o <<= 1) gmax = max(gmax, __shfl_xor_sync(0xffffffffu, gmax, o));
            sts1(gm + (ta >> 3) * 4, gmax);
            sts1(cnt, 0);
            bar_sync(12, 128);
            const uint32_t c = lds1(gm + (lane & 15) * 4);
            int rank = 0;
#pragma unroll
            for (int i = 0; i < 2; i++) { const uint4 q = lds4(gm + (lane >> 4) * 32 + i * 16); rank += (q.x > c) + (q.y > c) + (q.z > c) + (q.w > c); }
            rank += __shfl_xor_sync(0xffffffffu, rank, 16);
            const uint32_t thr = redux_max(rank == 7 ? c : 0u);
#pragma unroll 1
            while (m >= thr) {
                uint32_t at, m2 = 0;
                asm volatile("atom.shared.add.u32 %0, [%1], 1;" : "=r"(at) : "r"(cnt) : "memory");
#pragma unroll
                for (int n = 0; n < 16; n++) m2 = max(m2, kv[n] < m ? kv[n] : 0u);
                sts1(list + at * 4, m);
                if (m2 == 0) break;
                m = m2;
            }
            bar_sync(12, 128);
            const int nc = lds1(cnt);
#pragma unroll 1
            for (int i = ta >> 3; i < ((nc + 3) & ~3); i += 16) {
                const uint32_t ki = lds1(list + i * 4);
                int r = 0;
#pragma unroll 1
                for (int n = lane & 7; n < nc; n += 8) r += lds1(list + n * 4) > ki;
                __syncwarp();
#pragma unroll
                for (int o = 1; o < 8; o <<= 1) r += __shfl_xor_sync(0xffffffffu, r, o);
                if (r == (b & 7) && i < nc) sts1(res, ki);
            }
            bar_sync(12, 128);
            const uint32_t k0 = lds1(res);
            const int r0 = 2047 - ((k0 >> 5) & 2047);
            TSC(ta == 0, 22);
            if (ta == 0) st_rlx(&scr->sel[b & 7], k0);
            const uint4 v0 = ldg_nc(x + (size_t)r0 * 1024 + ta * 8);
            const uint32_t s0 = ld_rlx(&scr->row[r0]);
            const float m0 = bf_lo(s0), i0 = rcp(bf_hi(s0));
            const int ao = 14336 + (ta >> 3) * 256 + (b & 7) * 32 + ((ta ^ b) & 7) * 4;
            st_rlx4(scr->act[ep & 1] + ao, norm_pair(v0.x, m0, i0), norm_pair(v0.y, m0, i0), norm_pair(v0.z, m0, i0), norm_pair(v0.w, m0, i0));
            __syncwarp();
            if (lane == 0) red_add(&scr->cnt[9][tries >> 30]);
            st_rlx4(scr->act[~ep & 1] + ao, 0, 0, 0, 0);
        }
        uint32_t s8 = 0, fph = 0;
        const uint32_t chk = __shfl_sync(0xffffffffu, sb + OFF_FS + BOX + lane * 32 + (lane & 28), lane);
        int left = BUDGET;
        if (b >= 112 && ta < 2) mbar_arrive(bars + 8 * B_F1DONE);
#pragma unroll 1
        for (int ph = b >= 112; ph < 2; ph++) {
            {
                float acc[4] = {0.f, 0.f, 0.f, 0.f};
                const uint32_t alo = sd + (ph ? dlo(OFF_FS, 8192) : dlo(OFF_FS, 4096)), ahi = ph ? dhi(1024, 1) : dhi(512, 2), astep = ph ? 128 : 64;
                const uint32_t bhi = ph ? dhi(128, 0) : dhi(1024, 1), bstep = ph ? 16 : 2, wrap = ph ? 24 : 40;
                uint32_t prev = 0;
                if (ph) mbar_wait(bars + 8 * FFN2_GATE, 0, left);
#pragma unroll 1
                for (int q = ph ? n2 : 16; q > 0; q--) {
                    const uint32_t da = alo + s8 * (F_BYTES >> 7), db = sd + dlo(OFF_FS + BOX, 128) + s8 * (F_BYTES >> 7);
                    mbar_wait_hot(bars + 8 * B_FFULL + s8, fph, left);
                    if (__builtin_expect(__any_sync(0xffffffffu, lds1(chk + s8 * (F_BYTES / 8)) == 0), 0)) {
                        int tries = BUDGET;
#pragma unroll 1
                        for (int n = lane * 4 + (left >> 30); n < 256; n += 128) {
                            uint4 v;
#pragma unroll 1
                            do { v = ld_rlx4(scr->act[ep & 1] + ((ph ? mt * NM + n2 : 72) - q) * 256 + n); } while (v.x == 0 && --tries > 0);
                            __syncwarp();
                            sts4(sb + OFF_FS + BOX + s8 * (F_BYTES / 8) + n * 4, v.x, v.y, v.z, v.w);
                        }
                        NRETRY();
                        fence_async_smem();
                        __syncwarp();
                    }
                    TSC(TIMING % 10 == 3 && ta == 0, 32 + (ph ? 16 + n2 : 16) - q);
                    wg_fence();
#pragma unroll
                    for (int j = 0; j < 4; j++) wgmma_n8<1, 0>(acc, mkdesc(da + j * astep, ahi), mkdesc(db + j * bstep, bhi), 1);
                    wg_commit();
                    wg_wait<1>();
                    if (ph) { wg_wait<0>(); if (lane == 0) prev = bars + 8 * B_FEMPTY + s8; }
                    if (prev) mbar_arrive(prev);
                    if (lane == 0) prev = bars + 8 * B_FEMPTY + s8;
                    s8 += 8;
                    if (s8 == wrap) { s8 = 0; fph ^= 1; }
                }
                wg_wait<0>();
                const int ln = lane + (left >> 30);
                if (ph == 0) {
                    if (prev) mbar_arrive(prev);
                    const bool second = (wq >= 2) != (swap_gu != 0);
                    const uint32_t xa = sb + OFF_GU + ((wq & 1) * 32 + ln) * 16;
                    if (second) sts4(xa, __float_as_uint(acc[0]), __float_as_uint(acc[1]), __float_as_uint(acc[2]), __float_as_uint(acc[3]));
                    bar_sync(12, 128);
                    if (second) { if (ln == 0) mbar_arrive(bars + 8 * B_F1DONE); }
                    else {
                        const float4 up = lds4f(xa);
                        float hv[4];
#pragma unroll
                        for (int c = 0; c < 4; c++) { const float ga = bf16r(acc[c]); hv[c] = bf16r(ga * sigmoidf(ga)) * bf16r((&up.x)[c]); }
                        const int ao = (b * 4 + (wq & 1) * 2) * 32 + ln;
                        st_rlx(scr->act[ep & 1] + ao, max(movm(pack_bf16(hv[0], hv[1])), 1u)); st_rlx(scr->act[ep & 1] + 32 + ao, max(movm(pack_bf16(hv[2], hv[3])), 1u));
                        __syncwarp();
                        if (ln == 0) red_add(&scr->cnt[b < 14 * NM ? b / (2 * NM) : b < 14 * NM + 2 * N7 ? 7 : 8][0]);
                        st_rlx(scr->act[~ep & 1] + ao, 0); st_rlx(scr->act[~ep & 1] + 32 + ao, 0);
                    }
                } else {
                    st_rlx4(&scr->ypart[mt][c2][wq * 32 + ln], (__float_as_uint(acc[0]) & ~1u) | (ep & 1), __float_as_uint(acc[1]), __float_as_uint(acc[2]), __float_as_uint(acc[3]));
                }
                TSC(ta == 0, 22 + ph);
            }
        }
        TSC(ta == 0, 24);
    } else {
        reg_inc<224>();
        const int w = warp >> 2, wi = warp & 3, g = lane >> 2, t = lane & 3;
        const bool elect = (tid & 127) == 0;
        const uint32_t mad = (lane & 15) * 128 + (((lane >> 4) ^ (lane & 7)) << 4);
        float acc[64];
        const uint32_t ring = sb + w * OFF_X1, ofull = bars + 8 * (B_OFULL + w * 6), oempty = mapa(bars + 8 * B_OEMPTY, w);
        const int r0 = rh * 128 + wi * 32 + (1 - w) * 16 + g;
        {
            float acc0[96], acc1[96];
            const uint32_t sta = sb + OFF_STAT + (8 + w * 128 + wi * 32) * 8;
            {
                const uint32_t xfull = bars + 8 * (B_XFULL + w * 6 + 5), xempty = mapa(bars + 8 * B_XEMPTY, w), dx0 = sd + dlo(w * OFF_X1, 16);
                uint32_t s8 = 16, ps8 = 0, ph = 0;
                cluster_wait();
#pragma unroll 1
                for (int k = 0; k < 16; k++) {
                    const uint32_t dx = dx0 + s8 * (2 * BOX >> 7), dw = sd + dlo(OFF_W, BOX) + s8 * (W_BYTES >> 7);
                    mbar_wait(bars + 8 * B_WFULL + s8, ph, budget);
                    mbar_wait(xfull - 2 * s8, ph, budget);
                    TSC(elect && k == 0, 1 + 8 * w);
                    TSC(TIMING % 10 == 1 && tid == 0, 32 + k);
                    wg_wait<0>();
                    wg_fence();
#pragma unroll
                    for (int kk = 0; kk < 4; kk++) wgmma_n192<0, 1>(acc1, mkdesc(dx + kk * 2, dhi(1024, 1)), mkdesc(dw + kk * 128, dhi(1024, 1)), kk ? 1 : k);
                    wg_commit();
                    TSC(TIMING % 10 == 6 && elect, 32 + 16 * w + k);
                    if (elect && k > 0) {
                        mbar_arrive(bars + 8 * B_WEMPTY + ps8);
                        if (k <= 13) { mbar_expect_tx(xfull - 2 * ps8 - 8, BOX); mbar_arrive_at(xempty + 2 * ps8 + 8); }
                    }
                    if (k == 15) {
                        mbar_wait(bars + 8 * B_AUX, 0, budget);
                        const uint32_t zero = budget >> 30, pm = t & 1 ? 0x4432 : 0x3232, ra = sta + ((t >> 1) * 16 + g) * 8;
                        const uint32_t a0 = __byte_perm(lds1(ra), 0, pm), a1 = __byte_perm(lds1(ra + 64), 0, pm), a2 = a0 & zero, a3 = a1 & zero;
                        wg_fence();
                        wgmma_rs_n192(acc1, a0, a1, a2, a3, mkdesc(sd + dlo(OFF_CS, 0), dhi(128, 0)));
                        wgmma_rs_n192(acc0, a0, a1, a2, a3, mkdesc(sd + dlo(OFF_CS + 64, 0), dhi(128, 0)));
                        wg_commit();
                    }
                    mbar_wait(xfull - 2 * s8 - 8, ph, budget);
                    wg_wait<0>();
                    wg_fence();
#pragma unroll
                    for (int kk = 0; kk < 4; kk++) wgmma_n192<0, 1>(acc0, mkdesc(dx + 512 + kk * 2, dhi(1024, 1)), mkdesc(dw + kk * 128, dhi(1024, 1)), kk ? 1 : k);
                    wg_commit();
                    if (elect && k <= 12) { mbar_expect_tx(xfull - 2 * s8, BOX); mbar_arrive_at(xempty + 2 * s8); }
                    ps8 = s8;
                    s8 = s8 == 16 ? 0 : s8 + 8;
                    if (s8 == 16) ph ^= 1;
                }
            }
            const uint32_t zero = budget >> 30;
            const bool u0 = 2 * t > g, u1 = 2 * t + 1 > g;
            uint32_t mU = (u0 ? 0xffffu : 0u) | (u1 ? 0xffff0000u : 0u);
            uint32_t ka0 = sta + (2 * t - (u0 ? 8 : 0)) * 8 + 4, ka1 = sta + (2 * t + 1 - (u1 ? 8 : 0)) * 8 + 4;
            float rk[2][4], fu[2][4], fn[2][4];
            auto factors = [&](int h) {
#pragma unroll
                for (int n = 0; n < 4; n += 2) {
                    const float rq = lds1f(sta + (16 * h + 4 * n + g) * 8 + 4) * (0.17677669529663687f * 1.4426950408889634f);
                    rk[h][n] = lds1f(ka0 + h * 128 + n * 32); rk[h][n + 1] = lds1f(ka1 + h * 128 + n * 32);
                    const float f0 = rq * rk[h][n], f1 = rq * rk[h][n + 1];
                    fu[h][n] = u0 ? f0 : 0.f; fn[h][n] = f0 - fu[h][n]; fu[h][n + 1] = u1 ? f1 : 0.f; fn[h][n + 1] = f1 - fu[h][n + 1];
                }
#pragma unroll
                for (int n = 0; n < 4; n++) asm volatile("" : "+f"(fu[h][n]), "+f"(fn[h][n]));
            };
            uint8_t* og = scr->o + ((size_t)(mt * 4 + w * 2) * 16 + nt) * BOX + wi * 256 + lane * 4;
            TSC(elect, 19 + w);
            uint32_t pk0[48], pk1[48], o[16] = {};
#pragma unroll
            for (int j = 0; j < 48; j++) if (j < 16 || (j & 1)) pk1[j] = pack_here(acc1[2 * j], acc1[2 * j + 1]);
            if (warp < 7) {
#pragma unroll
                for (int c = 0; c < 4; c++) stsm4(ring + 4 * BOX + wi * 2048 + c * 512 + lane * 16, pk1[17 + 8 * c], pk1[19 + 8 * c], pk1[21 + 8 * c], pk1[23 + 8 * c]);
                bar_arrive(1 + warp, 64);
            } else if (j0 != 768) {
#pragma unroll
                for (int c = 0; c < 4; c++) {
                    pk1[17 + 8 * c] = max(pk1[17 + 8 * c], 1u);
                    st_rlx4(&scr->halo[b][c * 128 + lane * 4], pk1[17 + 8 * c], pk1[19 + 8 * c], pk1[21 + 8 * c], pk1[23 + 8 * c]);
                }
            }
            TSC(tid == 224, 28);
#pragma unroll
            for (int j = 16; j < 48; j += 2) pk1[j] = pack_here(acc1[2 * j], acc1[2 * j + 1]);
            factors(1);
            uint32_t od = sb + 2 * BOX + wi * 256 + (lane >> 4) * 1024 + (lane & 15) * 16, g1peer = mapa(bars + 8 * B_G1DONE, hp ^ 1);
            uint32_t ha = sb + (warp == 0 ? OFF_HIN : warp <= 4 ? 4 * BOX - 2048 : OFF_X1 + 4 * BOX - 5 * 2048) + warp * 2048 + lane * 16;
            const bool first = warp == 0 && j0 == 0;
            float bias0 = first && u0 ? -INFINITY : 0.f, bias1 = first && u1 ? -INFINITY : 0.f;
            asm volatile("" : "+l"(og), "+r"(mU), "+r"(od), "+r"(ha), "+f"(bias0), "+f"(bias1));
            mbar_wait(bars + 8 * B_XT, 0, budget);
            mbar_wait(bars + 8 * (B_WEMPTY + 1), 0, budget);
            wg_wait<0>();
            if (elect) { mbar_arrive(bars + 8 * B_G1DONE); mbar_arrive_at(g1peer); }
            TSC(elect, 2 + 8 * w);
            float ci[4];
#pragma unroll
            for (int n = 0; n < 4; n++) ci[n] = __uint_as_float((0x03800000u + n) | (budget >> 30));
            auto hand_over = [&](int v) {
                asm volatile("{\n.reg .pred p;\nsetp.ne.b32 p, %17, 0;\n"
                             "@p stmatrix.sync.aligned.m8n8.x4.shared.b16 [%16], {%0,%1,%2,%3};\n@p stmatrix.sync.aligned.m8n8.x4.shared.b16 [%16 + 2048], {%4,%5,%6,%7};\n"
                             "@p stmatrix.sync.aligned.m8n8.x4.shared.b16 [%16 + 4096], {%8,%9,%10,%11};\n@p stmatrix.sync.aligned.m8n8.x4.shared.b16 [%16 + 6144], {%12,%13,%14,%15};\n"
                             "fence.proxy.async.shared::cta;\n}"
                             ::"r"(o[0]), "r"(o[1]), "r"(o[2]), "r"(o[3]), "r"(o[4]), "r"(o[5]), "r"(o[6]), "r"(o[7]), "r"(o[8]), "r"(o[9]), "r"(o[10]), "r"(o[11]),
                               "r"(o[12]), "r"(o[13]), "r"(o[14]), "r"(o[15]), "r"(od + v * OFF_X1), "r"((int)(w == rh)) : "memory");
#pragma unroll
                for (int i = 0; i < 16; i++) asm volatile("st.global.u32 [%0], %1;" ::"l"(og + (1 - v) * 16 * BOX + (i >> 1) * 1024 + (i & 1) * 128), "r"(o[i]) : "memory");
                __syncwarp();
                if (lane == 0) mbar_arrive(bars + 8 * (B_STAGED + v));
            };
#pragma unroll
            for (int j = 32; j < 48; j++) pk1[j] = movm(pk1[j]);
#pragma unroll
            for (int j = EARLY_PK; j < 48; j++) if (j >= 32 || (j & 1) || EARLY_PK < 17) pk0[j] = pack_here(acc0[2 * j], acc0[2 * j + 1]);
#pragma unroll
            for (int j = 32; j < 48; j++) pk0[j] = movm(pk0[j]);
            attn_pair<2>(pk1, pk1 + 16, pk1 + 32, pk0 + 17, pk0 + 33, fu[1], fn[1], rk[1], 0.f, 0.f, mU, zero, ci, o);
            hand_over(0);
            TSC(elect, 3 + 8 * w);
#pragma unroll
            for (int j = 0; j < 32; j++) if (j < EARLY_PK || (!(j & 1) && EARLY_PK == 17)) pk0[j] = pack_here(acc0[2 * j], acc0[2 * j + 1]);
            factors(0);
            bar_sync(warp ? warp : 11, 64);
            uint32_t hl[16];
            ldsm4(hl, ha); ldsm4(hl + 4, ha + 512); ldsm4t(hl + 8, ha + 1024); ldsm4t(hl + 12, ha + 1536);
            __syncwarp();
            if (lane == 0) mbar_arrive(bars + 8 * B_FREED);
            attn_pair<1>(pk0, pk0 + 16, pk0 + 32, hl, hl + 8, fu[0], fn[0], rk[0], bias0, bias1, mU, zero, ci, o);
            const float2 s0 = lds2f(sb + OFF_STAT + (8 + r0) * 8), s1 = lds2f(sb + OFF_STAT + (16 + r0) * 8);
            const float m0 = s0.x * s0.y, f0 = 1.f + s0.y, m1 = s1.x * s1.y, f1 = 1.f + s1.y;
            uint32_t xt[32];
#pragma unroll
            for (int j = 0; j < 8; j++) ldsm4(xt + 4 * j, ((ring + wi * 2048 + mad) ^ ((j & 3) * 32)) + (j >> 2) * BOX);
            hand_over(1);
#pragma unroll
            for (int j = 0; j < 32; j++) {
                acc[2 * j] = fmaf(bf_lo(xt[j]), j & 1 ? f1 : f0, j & 1 ? m1 : m0); acc[2 * j + 1] = fmaf(bf_hi(xt[j]), j & 1 ? f1 : f0, j & 1 ? m1 : m0);
            }
        }
        TSC(tid == 0, 4);
        {
            const uint32_t da0 = sd + dlo(w * OFF_X1, 1024), db0 = sd + dlo(OFF_WO, BOX);
            const uint32_t chk = ring + wi * 256 + (lane >> 3) * 1032 + (lane & 7) * 32 + (lane & 4);
            uint32_t s8 = 16, ps8 = 0, ph = 0;
            mbar_wait(ofull + s8, 0, budget);
            mbar_wait(bars + 8 * B_WOFULL + s8, 0, budget);
            TSC(TIMING % 10 == 2 && elect, 32 + w * 16);
            const uint32_t ahi = dhi(128, 0) | (budget >> 30), bhi = dhi(1024, 1) | (budget >> 30);
            const int last = w ? HOLD : 16;
            uint32_t rel = elect ? 0x7fe : 0;
#pragma unroll 1
            for (int i = 1;;) {
                const uint32_t da = da0 + s8 * (BOX >> 7), db = db0 + s8 * (BOX >> 6);
                wg_fence();
#pragma unroll
                for (int kk = 0; kk < 4; kk++) {
                    wgmma_n128<0, 1>(acc, mkdesc(da + kk * 128, ahi), mkdesc(db + kk * 128, bhi), 1);
                    if (kk & 1) wg_commit();
                }
                wg_wait<2>();
                if (rel & 1) { mbar_expect_tx(ofull + ps8, BOX); mbar_arrive_at(oempty + ps8); mbar_arrive(bars + 8 * B_WOEMPTY + ps8); }
                if (i == 16) break;
                rel >>= 1;
                ps8 = s8;
#pragma unroll 1
                do {
                    s8 = s8 == 40 ? 0 : s8 + 8;
                    if (s8 == 16) ph ^= 1;
                    uint32_t bad;
                    asm volatile("{\n.reg .pred p, q, r;\n.reg .u32 u, v;\nmbarrier.try_wait.parity.shared::cta.b64 q, [%2], %3;\nmbarrier.try_wait.parity.shared::cta.b64 p, [%1], %3;\n"
                                 "setp.ne.and.u32 r, %5, 1, p;\nmov.u32 u, 1;\nmov.u32 v, 1;\n@r ld.shared.u32 u, [%4];\n@r ld.shared.u32 v, [%4 + 4096];\n"
                                 "and.pred p, p, q;\nmin.u32 u, u, v;\nsetp.eq.or.u32 p, u, 0, !p;\nvote.sync.any.pred p, p, 0xffffffff;\nselp.u32 %0, 1, 0, p;\n}"
                                 : "=r"(bad) : "r"(ofull + s8), "r"(bars + 8 * B_WOFULL + s8), "r"(ph), "r"(chk + s8 * (BOX / 8)), "r"(i) : "memory");
                    if (__builtin_expect(bad, 0)) {
                        mbar_wait(ofull + s8, ph, budget);
                        mbar_wait(bars + 8 * B_WOFULL + s8, ph, budget);
                        if (__any_sync(0xffffffffu, min(lds1(chk + s8 * (BOX / 8)), lds1(chk + s8 * (BOX / 8) + 4096)) == 0)) {
                            const uint32_t at = wi * 256 + (lane >> 4) * 1024 + (lane & 15) * 16;
                            const uint8_t* src = scr->o + ((size_t)((mt * 2 + rh) * 2 + 1 - w) * 16 + ((2 * p + (i < 2 ? i ^ hp : i)) & 15)) * BOX + at;
#pragma unroll 1
                            for (int n = 0; n < 8192; n += 2048) {
                                uint4 v; int tries = 4096;
#pragma unroll 1
                                do { v = ld_rlx4(src + n); } while (v.x == 0 && --tries > 0);
                                sts4(ring + s8 * (BOX / 8) + at + n, v.x, v.y, v.z, v.w);
                            }
                            NRETRY();
                            fence_async_smem();
                            __syncwarp();
                        }
                    }
                    TSC(TIMING % 10 == 1 && tid == 0, 48 + i);
                    TSC(TIMING % 10 == 2 && elect, 32 + w * 16 + i);
                } while (++i > last && i < 16);
                if (i > last) break;
                wg_wait<1>();
            }
            if (w) {
                bar_sync(9, 256);
#pragma unroll 1
                for (int i = HOLD - 10; i < 6; i++) {
                    wg_fence();
#pragma unroll
                    for (int kk = 0; kk < 4; kk++) wgmma_n128<0, 1>(acc, mkdesc(da0 + i * 512 + kk * 128, ahi), mkdesc(db0 + i * 1024 + kk * 128, bhi), 1);
                    wg_commit();
                }
            } else bar_arrive(9, 256);
            mbar_wait(bars + 8 * B_ZERO, 0, budget);
            const bool add = (__shfl_sync(0xffffffffu, lds1(sb + OFF_SEL), 0) >> (wi * 2 + 1 - w)) & 1;
            wg_wait<0>();
            TSC(elect, 7 + 9 * w);
            const uint32_t os0 = ring + wi * 4096;
#pragma unroll
            for (int hf = 0; hf < OUT_PARTS; hf++) {
#pragma unroll
                for (int j = hf * (8 / OUT_PARTS); j < (hf + 1) * (8 / OUT_PARTS); j++)
                    stsm4(((os0 + mad) ^ ((j & 3) * 32)) + (j >> 2) * 2048, pack_here(acc[8 * j], acc[8 * j + 1]), pack_here(acc[8 * j + 2], acc[8 * j + 3]),
                          pack_here(acc[8 * j + 4], acc[8 * j + 5]), pack_here(acc[8 * j + 6], acc[8 * j + 7]));
                fence_async_smem();
                __syncwarp();
                if (elect_one())
                    asm volatile("{\n.reg .pred p;\nsetp.ne.b32 p, %6, 0;\n@!p cp.async.bulk.tensor.5d.global.shared::cta.bulk_group [%0, {%2, %2, %3, %4, %5}], [%1];\n"
                                 "@p cp.reduce.async.bulk.tensor.5d.global.shared::cta.add.bulk_group [%0, {%2, %2, %3, %4, %5}], [%1];\n}"
                                 ::"l"(&mout), "r"(os0 + hf * 2048), "r"(0), "r"(((j0 + rh * 128) >> 5) + wi), "r"(1 - w), "r"(par * 16 + cb * 2 + hf), "r"((int)add) : "memory");
            }
            asm volatile("cp.async.bulk.commit_group;\ncp.async.bulk.wait_group.read 0;" ::: "memory");
            if (b == 0 && tid == 0) st_rlx(&scr->epoch[0], lds1(sb + OFF_EP));
            TSC(elect, 8 - 2 * w);
            TS_END();
        }
    }
}

typedef CUresult (*EncodeFn)(CUtensorMap*, CUtensorMapDataType, cuuint32_t, void*, const cuuint64_t*, const cuuint64_t*, const cuuint32_t*,
                             const cuuint32_t*, CUtensorMapInterleave, CUtensorMapSwizzle, CUtensorMapL2promotion, CUtensorMapFloatOOBfill);

CUtensorMap make_map(EncodeFn fn, const void* base, int rank, const cuuint64_t* dims, const cuuint64_t* strides, const cuuint32_t* box,
                     CUtensorMapSwizzle swz = CU_TENSOR_MAP_SWIZZLE_128B, CUtensorMapL2promotion pro = CU_TENSOR_MAP_L2_PROMOTION_L2_256B) {
    CUtensorMap m;
    cuuint32_t es[5] = {1, 1, 1, 1, 1};
    fn(&m, CU_TENSOR_MAP_DATA_TYPE_BFLOAT16, rank, (void*)base, dims, strides, box, es, CU_TENSOR_MAP_INTERLEAVE_NONE,
       swz, pro, CU_TENSOR_MAP_FLOAT_OOB_FILL_NONE);
    return m;
}

}

extern "C" void kernel_launch(void* const* d_in, const int* in_sizes, int n_in, void* d_out, int out_size) {
    (void)in_sizes; (void)n_in; (void)out_size;
    const __nv_bfloat16* x = (const __nv_bfloat16*)d_in[0];
    const __nv_bfloat16* wqkv = (const __nv_bfloat16*)d_in[1];
    const __nv_bfloat16* wo = (const __nv_bfloat16*)d_in[2];
    const __nv_bfloat16* wr = (const __nv_bfloat16*)d_in[4];
    const __nv_bfloat16* wg = (const __nv_bfloat16*)d_in[5];
    const __nv_bfloat16* wu = (const __nv_bfloat16*)d_in[6];
    const __nv_bfloat16* wd = (const __nv_bfloat16*)d_in[7];
    static EncodeFn fn = nullptr;
    static Scratch* scr = nullptr;
    if (!fn) {
        void* p = nullptr; cudaDriverEntryPointQueryResult q;
        cudaGetDriverEntryPoint("cuTensorMapEncodeTiled", &p, cudaEnableDefault, &q);
        fn = (EncodeFn)p;
        cudaFuncSetAttribute(fused_kernel, cudaFuncAttributeMaxDynamicSharedMemorySize, SMEM_LAUNCH);
        cudaGetSymbolAddress((void**)&scr, g_scr);
    }
    const cuuint64_t xd[4] = {2048, 16, 32, 2}, xs[4] = {4096, 131072, 65536, 128}, od[5] = {64, 16, 32, 2, 32};
    const cuuint32_t xb[4] = {64, 16, 4, 1}, ob[5] = {64, 16, 1, 1, 2 / OUT_PARTS};
    const cuuint64_t wdm[3] = {1024, 1024, 3}, wst[2] = {6144, 2048};
    const cuuint32_t wb[3] = {64, 64, 3};
    const cuuint64_t wod[3] = {64, 1024, 16}, wdd[3] = {64, 3584, 16}, wos[2] = {2048, 128};
    const cuuint32_t wob[3] = {64, 64, 2}, wdb[3] = {64, 64, 1};
    CUtensorMap mx = make_map(fn, x, 4, xd, xs, xb), mw = make_map(fn, wqkv, 3, wdm, wst, wb);
    CUtensorMap mwo = make_map(fn, wo, 3, wod, wos, wob), mout = make_map(fn, d_out, 5, od, xs, ob);
    const int swap_gu = wu < wg;
    const cuuint64_t gd[3] = {3584, 1024, 2}, gst[2] = {7168, (cuuint64_t)(swap_gu ? (const char*)wg - (const char*)wu : (const char*)wu - (const char*)wg)};
    const cuuint32_t gb[3] = {32, 64, 2};
    CUtensorMap mgu = make_map(fn, swap_gu ? wu : wg, 3, gd, gst, gb, CU_TENSOR_MAP_SWIZZLE_64B, CU_TENSOR_MAP_L2_PROMOTION_L2_128B);
    CUtensorMap mwd = make_map(fn, wd, 3, wdd, wos, wdb, CU_TENSOR_MAP_SWIZZLE_128B, CU_TENSOR_MAP_L2_PROMOTION_L2_128B);
    const cuuint64_t md[2] = {64, 32768}, ms[1] = {128};
    const cuuint32_t mb[2] = {64, 64};
    CUtensorMap mo = make_map(fn, scr, 2, md, ms, mb, CU_TENSOR_MAP_SWIZZLE_NONE, CU_TENSOR_MAP_L2_PROMOTION_NONE);
    const cuuint64_t rd[2] = {1024, 2048};
    const cuuint32_t rb[2] = {256, 16};
    CUtensorMap mr = make_map(fn, x, 2, rd, wos, rb, CU_TENSOR_MAP_SWIZZLE_NONE);
    cudaLaunchConfig_t cfg = {};
    cfg.gridDim = dim3(132); cfg.blockDim = dim3(512); cfg.dynamicSmemBytes = SMEM_LAUNCH; cfg.stream = cudaStreamPerThread;
    cudaLaunchAttribute at[1];
    at[0].id = cudaLaunchAttributeClusterDimension; at[0].val.clusterDim.x = 2; at[0].val.clusterDim.y = 1; at[0].val.clusterDim.z = 1;
    cfg.attrs = at; cfg.numAttrs = 1;
    cudaLaunchKernelEx(&cfg, fused_kernel, mx, mw, mwo, mout, mgu, mwd, mo, mr, x, wr, scr, swap_gu, Weights{(const char*)wqkv, (const char*)wo, (const char*)wg, (const char*)wu, (const char*)wd, (char*)d_out});
}
```

```cpp
#include <cuda_runtime.h>
#include <cuda.h>
#include <cuda_bf16.h>
#include <stdint.h>

namespace {

constexpr int BOX = 8192, W_BYTES = 3 * BOX;
constexpr int OFF_X1 = 6 * BOX, OFF_FR = 12 * BOX, OFF_E = 16 * BOX, OFF_W = 19 * BOX;
constexpr int OFF_WO = OFF_E;
constexpr int OFF_HIN = OFF_FR + 2048, OFF_GU = OFF_HIN + 2048, OFF_FS = OFF_GU + 1024;
constexpr int F_BYTES = 9216;
constexpr int CS_BYTES = 3136;
constexpr int OFF_CS = OFF_FS + 5 * F_BYTES;
constexpr int OFF_STAT = 28 * BOX;
constexpr int OFF_SEL = OFF_STAT + 2112, OFF_EP = OFF_SEL + 4;
constexpr int OFF_BAR = OFF_SEL + 16;
constexpr int B_WFULL = 0, B_XFULL = 3, B_AUX = 15, B_XT = 16, B_ZERO = 17, B_WOFULL = 18, B_OFULL = 24, B_FFULL = 36, B_ROW = 41;
constexpr int B_WEMPTY = 48, B_F1DONE = 51, B_XEMPTY = 52, B_WOEMPTY = 58, B_OEMPTY = 64;
constexpr int B_G1DONE = 72, B_FEMPTY = 73, B_STAGED = 78, B_RDONE = 80, B_FREED = 81, NBAR = 84;
constexpr int SMEM_BYTES = OFF_BAR + NBAR * 8;
static_assert(OFF_FS + 3 * F_BYTES == OFF_E && OFF_CS + CS_BYTES <= OFF_W && SMEM_BYTES + 256 <= 232448 && OFF_BAR % 8 == 0, "smem");
#define POLL_NS 30
#define PF_RATE 10
#define PF_START 7
#define ZF_NS 100
#define FFN2_GATE (B_STAGED + 1)
#define PF_NW 6
#define EARLY_PK 17
#define ZF_GATE (B_ROW + 3)
#define HOLD 12
#define F2_DEPTH 0
#define OUT_PARTS 2
#define PF_D 8
#define NM 4
#define N7 8
#define NR 4
#define PF_DN 8
#define PF_DB 4096
#define PF_REV 0
#define ROWS_AT 0x280
constexpr int NH = 56 - 7 * NM - N7;
static_assert(NH >= NR + 6 && NH <= 32 && NR < 6, "FFN2 split");
constexpr int BUDGET = 1 << 18;

struct Scratch {
    uint8_t o[2048 * 1024 * 2];
    uint4 ypart[8][16][128];
    uint32_t halo[128][512];
    uint32_t act[2][14336 + 4096];
    uint2 row[2048];
    uint4 cs[16][3][24];
    uint32_t oflag[16][32];
    uint32_t cnt[10][32];
    uint32_t sel[32], zflag[32], epoch[32];
};
__device__ __align__(1024) Scratch g_scr;
struct Weights { const char *wqkv, *wo, *wg, *wu, *wd; char* out; };

#define TS(i) do {} while (0)
#define TS_END() do {} while (0)
#define TSC(c, i) do {} while (0)
#define NRETRY() do {} while (0)
constexpr int SMEM_LAUNCH = SMEM_BYTES;
__device__ __forceinline__ uint32_t smem_u32(const void* p) { return (uint32_t)__cvta_generic_to_shared(p); }
__device__ __forceinline__ void mbar_init(uint32_t bar, uint32_t cnt) { asm volatile("mbarrier.init.shared::cta.b64 [%0], %1;" ::"r"(bar), "r"(cnt) : "memory"); }
__device__ __forceinline__ void mbar_expect_tx(uint32_t bar, uint32_t bytes) { asm volatile("mbarrier.arrive.expect_tx.shared::cta.b64 _, [%0], %1;" ::"r"(bar), "r"(bytes) : "memory"); }
__device__ __forceinline__ void mbar_arrive(uint32_t bar) { asm volatile("mbarrier.arrive.shared::cta.b64 _, [%0];" ::"r"(bar) : "memory"); }
__device__ __forceinline__ uint32_t mapa(uint32_t a, uint32_t cta) { uint32_t r; asm("mapa.shared::cluster.u32 %0, %1, %2;" : "=r"(r) : "r"(a), "r"(cta)); return r; }
__device__ __forceinline__ void mbar_arrive_at(uint32_t cbar) { asm volatile("mbarrier.arrive.shared::cluster.b64 _, [%0];" ::"r"(cbar) : "memory"); }
__device__ __forceinline__ void mbar_wait(uint32_t bar, uint32_t parity, int& budget) {
    asm volatile("{\n.reg .pred p;\nLAB_WAIT:\nmbarrier.try_wait.parity.shared::cta.b64 p, [%1], %2;\n"
                 "add.s32 %0, %0, -1;\nsetp.gt.and.s32 p, %0, 0, !p;\n@p bra LAB_WAIT;\n}" : "+r"(budget) : "r"(bar), "r"(parity) : "memory");
}
__device__ __forceinline__ void mbar_wait_hot(uint32_t bar, uint32_t parity, int& budget) {
    asm volatile("{\n.reg .pred p;\nmbarrier.try_wait.parity.shared::cta.b64 p, [%1], %2;\n@p bra LAB_DONE;\nLAB_WAIT:\nmbarrier.try_wait.parity.shared::cta.b64 p, [%1], %2;\n"
                 "add.s32 %0, %0, -1;\nsetp.gt.and.s32 p, %0, 0, !p;\n@p bra LAB_WAIT;\nLAB_DONE:\n}" : "+r"(budget) : "r"(bar), "r"(parity) : "memory");
}
__device__ __forceinline__ void tma_2d(uint32_t dst, const CUtensorMap* m, uint32_t bar, int c0, int c1) {
    asm volatile("cp.async.bulk.tensor.2d.shared::cluster.global.mbarrier::complete_tx::bytes [%0], [%1, {%3, %4}], [%2];" ::"r"(dst), "l"(m), "r"(bar), "r"(c0), "r"(c1) : "memory");
}
__device__ __forceinline__ void tma_2d_mc(uint32_t dst, const CUtensorMap* m, uint32_t bar, int c0, int c1) {
    asm volatile("cp.async.bulk.tensor.2d.shared::cluster.global.mbarrier::complete_tx::bytes.multicast::cluster [%0], [%1, {%3, %4}], [%2], %5;" ::"r"(dst), "l"(m), "r"(bar), "r"(c0), "r"(c1), "h"((uint16_t)3) : "memory");
}
__device__ __forceinline__ void tma_3d(uint32_t dst, const CUtensorMap* m, uint32_t bar, int c0, int c1, int c2) {
    asm volatile("cp.async.bulk.tensor.3d.shared::cluster.global.mbarrier::complete_tx::bytes [%0], [%1, {%3, %4, %5}], [%2];" ::"r"(dst), "l"(m), "r"(bar), "r"(c0), "r"(c1), "r"(c2) : "memory");
}
__device__ __forceinline__ void tma_4d(uint32_t dst, const CUtensorMap* m, uint32_t bar, int c0, int c1, int c2, int c3) {
    asm volatile("cp.async.bulk.tensor.4d.shared::cluster.global.mbarrier::complete_tx::bytes [%0], [%1, {%3, %4, %5, %6}], [%2];" ::"r"(dst), "l"(m), "r"(bar), "r"(c0), "r"(c1), "r"(c2), "r"(c3) : "memory");
}
__device__ __forceinline__ void tma_4d_mc(uint32_t dst, const CUtensorMap* m, uint32_t bar, int c0, int c1, int c2, int c3) {
    asm volatile("cp.async.bulk.tensor.4d.shared::cluster.global.mbarrier::complete_tx::bytes.multicast::cluster [%0], [%1, {%3, %4, %5, %6}], [%2], %7;" ::"r"(dst), "l"(m), "r"(bar), "r"(c0), "r"(c1), "r"(c2), "r"(c3), "h"((uint16_t)3) : "memory");
}
__device__ __forceinline__ void bulk_pf(const void* p, uint32_t bytes) { asm volatile("cp.async.bulk.prefetch.L2.global [%0], %1;" ::"l"(p), "r"(bytes) : "memory"); }
__device__ __forceinline__ void bulk_g2s(uint32_t dst, const void* src, uint32_t bytes, uint32_t bar) {
    asm volatile("cp.async.bulk.shared::cluster.global.mbarrier::complete_tx::bytes [%0], [%1], %2, [%3];" ::"r"(dst), "l"(src), "r"(bytes), "r"(bar) : "memory");
}
__device__ __forceinline__ void bulk_s2c(uint32_t cdst, uint32_t src, uint32_t bytes, uint32_t cbar) {
    asm volatile("cp.async.bulk.shared::cluster.shared::cta.mbarrier::complete_tx::bytes [%0], [%1], %2, [%3];" ::"r"(cdst), "r"(src), "r"(bytes), "r"(cbar) : "memory");
}
__device__ __forceinline__ void cluster_wait() { asm volatile("barrier.cluster.wait.aligned;" ::: "memory"); }
__device__ __forceinline__ void fence_gpu() { asm volatile("fence.acq_rel.gpu;" ::: "memory"); }
__device__ __forceinline__ void fence_async_smem() { asm volatile("fence.proxy.async.shared::cta;" ::: "memory"); }
__device__ __forceinline__ void wg_fence() { asm volatile("wgmma.fence.sync.aligned;" ::: "memory"); }
__device__ __forceinline__ void wg_commit() { asm volatile("wgmma.commit_group.sync.aligned;" ::: "memory"); }
template <int N> __device__ __forceinline__ void wg_wait() { asm volatile("wgmma.wait_group.sync.aligned %0;" ::"n"(N) : "memory"); }
__device__ __forceinline__ uint64_t mkdesc(uint32_t lo, uint32_t hi) { return ((uint64_t)hi << 32) | lo; }
__host__ __device__ constexpr uint32_t dhi(uint32_t sbo, uint32_t mode) { return (sbo >> 4) | (mode << 30); }
__host__ __device__ constexpr uint32_t dlo(uint32_t off, uint32_t lbo) { return (off >> 4) + ((lbo >> 4) << 16); }
__device__ __forceinline__ bool elect_one() {
    uint32_t e;
    asm volatile("{\n.reg .pred p;\nelect.sync _|p, 0xffffffff;\nselp.u32 %0, 1, 0, p;\n}" : "=r"(e));
    return e;
}
template <int R> __device__ __forceinline__ void reg_inc() { asm volatile("setmaxnreg.inc.sync.aligned.u32 %0;" ::"n"(R)); }
template <int R> __device__ __forceinline__ void reg_dec() { asm volatile("setmaxnreg.dec.sync.aligned.u32 %0;" ::"n"(R)); }
__device__ __forceinline__ void bar_sync(int id, int n) { asm volatile("bar.sync %0, %1;" ::"r"(id), "r"(n) : "memory"); }
__device__ __forceinline__ void bar_arrive(int id, int n) { asm volatile("bar.arrive %0, %1;" ::"r"(id), "r"(n) : "memory"); }
__device__ __forceinline__ uint32_t pack_bf16(float lo, float hi) { uint32_t r; asm("cvt.rn.bf16x2.f32 %0, %1, %2;" : "=r"(r) : "f"(hi), "f"(lo)); return r; }
__device__ __forceinline__ uint32_t pack_here(float lo, float hi) { uint32_t r; asm volatile("cvt.rn.bf16x2.f32 %0, %1, %2;" : "=r"(r) : "f"(hi), "f"(lo)); return r; }
__device__ __forceinline__ float bf_lo(uint32_t u) { return __uint_as_float(u << 16); }
__device__ __forceinline__ float bf_hi(uint32_t u) { return __uint_as_float(u & 0xffff0000u); }
__device__ __forceinline__ float bf16r(float v) { return bf_lo(pack_bf16(v, 0.f)); }
__device__ __forceinline__ float rcp(float x) { float r; asm("rcp.approx.ftz.f32 %0, %1;" : "=f"(r) : "f"(x)); return r; }
__device__ __forceinline__ float ex2(float x) { float r; asm("ex2.approx.ftz.f32 %0, %1;" : "=f"(r) : "f"(x)); return r; }
__device__ __forceinline__ float sigmoidf(float v) { return rcp(1.f + ex2(v * -1.4426950408889634f)); }
__device__ __forceinline__ uint32_t movm(uint32_t a) { uint32_t d; asm volatile("movmatrix.sync.aligned.m8n8.trans.b16 %0, %1;" : "=r"(d) : "r"(a)); return d; }
__device__ __forceinline__ void mma16816(float (&c)[4], uint32_t a0, uint32_t a1, uint32_t a2, uint32_t a3, uint32_t b0, uint32_t b1) {
    asm volatile("mma.sync.aligned.m16n8k16.row.col.f32.bf16.bf16.f32 {%0,%1,%2,%3}, {%4,%5,%6,%7}, {%8,%9}, {%0,%1,%2,%3};"
                 : "+f"(c[0]), "+f"(c[1]), "+f"(c[2]), "+f"(c[3]) : "r"(a0), "r"(a1), "r"(a2), "r"(a3), "r"(b0), "r"(b1));
}
__device__ __forceinline__ void mma1688(float (&c)[4], uint32_t a0, uint32_t a1, uint32_t b0) {
    asm volatile("mma.sync.aligned.m16n8k8.row.col.f32.bf16.bf16.f32 {%0,%1,%2,%3}, {%4,%5}, {%6}, {%0,%1,%2,%3};"
                 : "+f"(c[0]), "+f"(c[1]), "+f"(c[2]), "+f"(c[3]) : "r"(a0), "r"(a1), "r"(b0));
}
__device__ __forceinline__ void stsm4(uint32_t a, uint32_t r0, uint32_t r1, uint32_t r2, uint32_t r3) {
    asm volatile("stmatrix.sync.aligned.m8n8.x4.shared.b16 [%0], {%1,%2,%3,%4};" ::"r"(a), "r"(r0), "r"(r1), "r"(r2), "r"(r3) : "memory");
}
__device__ __forceinline__ void ldsm4(uint32_t* r, uint32_t a) {
    asm volatile("ldmatrix.sync.aligned.m8n8.x4.shared.b16 {%0,%1,%2,%3}, [%4];" : "=r"(r[0]), "=r"(r[1]), "=r"(r[2]), "=r"(r[3]) : "r"(a) : "memory");
}
__device__ __forceinline__ void ldsm4t(uint32_t* r, uint32_t a) {
    asm volatile("ldmatrix.sync.aligned.m8n8.x4.trans.shared.b16 {%0,%1,%2,%3}, [%4];" : "=r"(r[0]), "=r"(r[1]), "=r"(r[2]), "=r"(r[3]) : "r"(a) : "memory");
}
__device__ __forceinline__ uint32_t ld_rlx(const void* p) { uint32_t v; asm volatile("ld.relaxed.gpu.global.u32 %0, [%1];" : "=r"(v) : "l"(p) : "memory"); return v; }
__device__ __forceinline__ uint32_t ld_acq(const void* p) { uint32_t v; asm volatile("ld.acquire.gpu.global.u32 %0, [%1];" : "=r"(v) : "l"(p) : "memory"); return v; }
__device__ __forceinline__ uint2 ld_rlx2(const void* p) { uint2 v; asm volatile("ld.relaxed.gpu.global.v2.u32 {%0,%1}, [%2];" : "=r"(v.x), "=r"(v.y) : "l"(p) : "memory"); return v; }
__device__ __forceinline__ uint4 ld_rlx4(const void* p) { uint4 v; asm volatile("ld.relaxed.gpu.global.v4.u32 {%0,%1,%2,%3}, [%4];" : "=r"(v.x), "=r"(v.y), "=r"(v.z), "=r"(v.w) : "l"(p) : "memory"); return v; }
__device__ __forceinline__ void st_rlx(void* p, uint32_t v) { asm volatile("st.relaxed.gpu.global.u32 [%0], %1;" ::"l"(p), "r"(v) : "memory"); }
__device__ __forceinline__ void st_rlx2(void* p, uint32_t a, uint32_t b) { asm volatile("st.relaxed.gpu.global.v2.u32 [%0], {%1,%2};" ::"l"(p), "r"(a), "r"(b) : "memory"); }
__device__ __forceinline__ void st_rlx4(void* p, uint32_t a, uint32_t b, uint32_t c, uint32_t d) { asm volatile("st.relaxed.gpu.global.v4.u32 [%0], {%1,%2,%3,%4};" ::"l"(p), "r"(a), "r"(b), "r"(c), "r"(d) : "memory"); }
__device__ __forceinline__ void red_add(uint32_t* p) { asm volatile("red.relaxed.gpu.global.add.u32 [%0], 1;" ::"l"(p) : "memory"); }
__device__ __forceinline__ uint4 ldg_nc(const void* p) { uint4 v; asm volatile("ld.global.nc.v4.u32 {%0,%1,%2,%3}, [%4];" : "=r"(v.x), "=r"(v.y), "=r"(v.z), "=r"(v.w) : "l"(p)); return v; }
__device__ __forceinline__ void sts4(uint32_t a, uint32_t x, uint32_t y, uint32_t z, uint32_t w) { asm volatile("st.shared.v4.u32 [%0], {%1,%2,%3,%4};" ::"r"(a), "r"(x), "r"(y), "r"(z), "r"(w) : "memory"); }
__device__ __forceinline__ void sts2(uint32_t a, uint32_t x, uint32_t y) { asm volatile("st.shared.v2.u32 [%0], {%1,%2};" ::"r"(a), "r"(x), "r"(y) : "memory"); }
__device__ __forceinline__ void sts1(uint32_t a, uint32_t v) { asm volatile("st.shared.u32 [%0], %1;" ::"r"(a), "r"(v) : "memory"); }
__device__ __forceinline__ uint4 lds4(uint32_t a) { uint4 v; asm volatile("ld.shared.v4.u32 {%0,%1,%2,%3}, [%4];" : "=r"(v.x), "=r"(v.y), "=r"(v.z), "=r"(v.w) : "r"(a) : "memory"); return v; }
__device__ __forceinline__ float4 lds4f(uint32_t a) { float4 v; asm volatile("ld.shared.v4.f32 {%0,%1,%2,%3}, [%4];" : "=f"(v.x), "=f"(v.y), "=f"(v.z), "=f"(v.w) : "r"(a) : "memory"); return v; }
__device__ __forceinline__ float2 lds2f(uint32_t a) { float2 v; asm volatile("ld.shared.v2.f32 {%0,%1}, [%2];" : "=f"(v.x), "=f"(v.y) : "r"(a) : "memory"); return v; }
__device__ __forceinline__ float lds1f(uint32_t a) { float v; asm volatile("ld.shared.f32 %0, [%1];" : "=f"(v) : "r"(a) : "memory"); return v; }
__device__ __forceinline__ uint32_t lds1(uint32_t a) { uint32_t v; asm volatile("ld.shared.u32 %0, [%1];" : "=r"(v) : "r"(a) : "memory"); return v; }
__device__ __forceinline__ uint32_t redux_max(uint32_t v) { uint32_t r; asm volatile("redux.sync.max.u32 %0, %1, 0xffffffff;" : "=r"(r) : "r"(v)); return r; }
__device__ __forceinline__ uint32_t poll_all(const uint32_t* p, uint32_t mask, uint32_t want, int& budget) {
    uint32_t v;
#pragma unroll 1
    while (v = ld_acq(p), !__all_sync(0xffffffffu, (v & mask) == want) && --budget > 0) __nanosleep(POLL_NS);
    return v;
}

template <int TA, int TB>
__device__ __forceinline__ void wgmma_n192(float (&d)[96], uint64_t da, uint64_t db, int keep) {
    asm volatile("{\n.reg .pred p;\nsetp.ne.b32 p, %98, 0;\n"
        "wgmma.mma_async.sync.aligned.m64n192k16.f32.bf16.bf16 "
        "{%0, %1, %2, %3, %4, %5, %6, %7, %8, %9, %10, %11, %12, %13, %14, %15, "
        "%16, %17, %18, %19, %20, %21, %22, %23, %24, %25, %26, %27, %28, %29, %30, %31, "
        "%32, %33, %34, %35, %36, %37, %38, %39, %40, %41, %42, %43, %44, %45, %46, %47, "
        "%48, %49, %50, %51, %52, %53, %54, %55, %56, %57, %58, %59, %60, %61, %62, %63, "
        "%64, %65, %66, %67, %68, %69, %70, %71, %72, %73, %74, %75, %76, %77, %78, %79, "
        "%80, %81, %82, %83, %84, %85, %86, %87, %88, %89, %90, %91, %92, %93, %94, %95}, "
        "%96, %97, p, 1, 1, %99, %100;\n}\n"
        : "+f"(d[0]), "+f"(d[1]), "+f"(d[2]), "+f"(d[3]), "+f"(d[4]), "+f"(d[5]), "+f"(d[6]), "+f"(d[7]),
          "+f"(d[8]), "+f"(d[9]), "+f"(d[10]), "+f"(d[11]), "+f"(d[12]), "+f"(d[13]), "+f"(d[14]), "+f"(d[15]),
          "+f"(d[16]), "+f"(d[17]), "+f"(d[18]), "+f"(d[19]), "+f"(d[20]), "+f"(d[21]), "+f"(d[22]), "+f"(d[23]),
          "+f"(d[24]), "+f"(d[25]), "+f"(d[26]), "+f"(d[27]), "+f"(d[28]), "+f"(d[29]), "+f"(d[30]), "+f"(d[31]),
          "+f"(d[32]), "+f"(d[33]), "+f"(d[34]), "+f"(d[35]), "+f"(d[36]), "+f"(d[37]), "+f"(d[38]), "+f"(d[39]),
          "+f"(d[40]), "+f"(d[41]), "+f"(d[42]), "+f"(d[43]), "+f"(d[44]), "+f"(d[45]), "+f"(d[46]), "+f"(d[47]),
          "+f"(d[48]), "+f"(d[49]), "+f"(d[50]), "+f"(d[51]), "+f"(d[52]), "+f"(d[53]), "+f"(d[54]), "+f"(d[55]),
          "+f"(d[56]), "+f"(d[57]), "+f"(d[58]), "+f"(d[59]), "+f"(d[60]), "+f"(d[61]), "+f"(d[62]), "+f"(d[63]),
          "+f"(d[64]), "+f"(d[65]), "+f"(d[66]), "+f"(d[67]), "+f"(d[68]), "+f"(d[69]), "+f"(d[70]), "+f"(d[71]),
          "+f"(d[72]), "+f"(d[73]), "+f"(d[74]), "+f"(d[75]), "+f"(d[76]), "+f"(d[77]), "+f"(d[78]), "+f"(d[79]),
          "+f"(d[80]), "+f"(d[81]), "+f"(d[82]), "+f"(d[83]), "+f"(d[84]), "+f"(d[85]), "+f"(d[86]), "+f"(d[87]),
          "+f"(d[88]), "+f"(d[89]), "+f"(d[90]), "+f"(d[91]), "+f"(d[92]), "+f"(d[93]), "+f"(d[94]), "+f"(d[95])
        : "l"(da), "l"(db), "r"(keep), "n"(TA), "n"(TB));
}
template <int TA, int TB>
__device__ __forceinline__ void wgmma_n128(float (&d)[64], uint64_t da, uint64_t db, int keep) {
    asm volatile("{\n.reg .pred p;\nsetp.ne.b32 p, %66, 0;\n"
        "wgmma.mma_async.sync.aligned.m64n128k16.f32.bf16.bf16 "
        "{%0, %1, %2, %3, %4, %5, %6, %7, %8, %9, %10, %11, %12, %13, %14, %15, "
        "%16, %17, %18, %19, %20, %21, %22, %23, %24, %25, %26, %27, %28, %29, %30, %31, "
        "%32, %33, %34, %35, %36, %37, %38, %39, %40, %41, %42, %43, %44, %45, %46, %47, "
        "%48, %49, %50, %51, %52, %53, %54, %55, %56, %57, %58, %59, %60, %61, %62, %63}, "
        "%64, %65, p, 1, 1, %67, %68;\n}\n"
        : "+f"(d[0]), "+f"(d[1]), "+f"(d[2]), "+f"(d[3]), "+f"(d[4]), "+f"(d[5]), "+f"(d[6]), "+f"(d[7]),
          "+f"(d[8]), "+f"(d[9]), "+f"(d[10]), "+f"(d[11]), "+f"(d[12]), "+f"(d[13]), "+f"(d[14]), "+f"(d[15]),
          "+f"(d[16]), "+f"(d[17]), "+f"(d[18]), "+f"(d[19]), "+f"(d[20]), "+f"(d[21]), "+f"(d[22]), "+f"(d[23]),
          "+f"(d[24]), "+f"(d[25]), "+f"(d[26]), "+f"(d[27]), "+f"(d[28]), "+f"(d[29]), "+f"(d[30]), "+f"(d[31]),
          "+f"(d[32]), "+f"(d[33]), "+f"(d[34]), "+f"(d[35]), "+f"(d[36]), "+f"(d[37]), "+f"(d[38]), "+f"(d[39]),
          "+f"(d[40]), "+f"(d[41]), "+f"(d[42]), "+f"(d[43]), "+f"(d[44]), "+f"(d[45]), "+f"(d[46]), "+f"(d[47]),
          "+f"(d[48]), "+f"(d[49]), "+f"(d[50]), "+f"(d[51]), "+f"(d[52]), "+f"(d[53]), "+f"(d[54]), "+f"(d[55]),
          "+f"(d[56]), "+f"(d[57]), "+f"(d[58]), "+f"(d[59]), "+f"(d[60]), "+f"(d[61]), "+f"(d[62]), "+f"(d[63])
        : "l"(da), "l"(db), "r"(keep), "n"(TA), "n"(TB));
}
template <int TA, int TB>
__device__ __forceinline__ void wgmma_n8(float (&d)[4], uint64_t da, uint64_t db, int keep) {
    asm volatile("{\n.reg .pred p;\nsetp.ne.b32 p, %6, 0;\n"
        "wgmma.mma_async.sync.aligned.m64n8k16.f32.bf16.bf16 "
        "{%0, %1, %2, %3}, "
        "%4, %5, p, 1, 1, %7, %8;\n}\n"
        : "+f"(d[0]), "+f"(d[1]), "+f"(d[2]), "+f"(d[3])
        : "l"(da), "l"(db), "r"(keep), "n"(TA), "n"(TB));
}
__device__ __forceinline__ void wgmma_rs_n192(float (&d)[96], uint32_t a0, uint32_t a1, uint32_t a2, uint32_t a3, uint64_t db) {
    asm volatile("{\n.reg .pred p;\nsetp.ne.b32 p, 1, 0;\n"
        "wgmma.mma_async.sync.aligned.m64n192k16.f32.bf16.bf16 "
        "{%0, %1, %2, %3, %4, %5, %6, %7, %8, %9, %10, %11, %12, %13, %14, %15, "
        "%16, %17, %18, %19, %20, %21, %22, %23, %24, %25, %26, %27, %28, %29, %30, %31, "
        "%32, %33, %34, %35, %36, %37, %38, %39, %40, %41, %42, %43, %44, %45, %46, %47, "
        "%48, %49, %50, %51, %52, %53, %54, %55, %56, %57, %58, %59, %60, %61, %62, %63, "
        "%64, %65, %66, %67, %68, %69, %70, %71, %72, %73, %74, %75, %76, %77, %78, %79, "
        "%80, %81, %82, %83, %84, %85, %86, %87, %88, %89, %90, %91, %92, %93, %94, %95}, "
        "{%96, %97, %98, %99}, %100, p, 1, 1, 1;\n}\n"
        : "+f"(d[0]), "+f"(d[1]), "+f"(d[2]), "+f"(d[3]), "+f"(d[4]), "+f"(d[5]), "+f"(d[6]), "+f"(d[7]),
          "+f"(d[8]), "+f"(d[9]), "+f"(d[10]), "+f"(d[11]), "+f"(d[12]), "+f"(d[13]), "+f"(d[14]), "+f"(d[15]),
          "+f"(d[16]), "+f"(d[17]), "+f"(d[18]), "+f"(d[19]), "+f"(d[20]), "+f"(d[21]), "+f"(d[22]), "+f"(d[23]),
          "+f"(d[24]), "+f"(d[25]), "+f"(d[26]), "+f"(d[27]), "+f"(d[28]), "+f"(d[29]), "+f"(d[30]), "+f"(d[31]),
          "+f"(d[32]), "+f"(d[33]), "+f"(d[34]), "+f"(d[35]), "+f"(d[36]), "+f"(d[37]), "+f"(d[38]), "+f"(d[39]),
          "+f"(d[40]), "+f"(d[41]), "+f"(d[42]), "+f"(d[43]), "+f"(d[44]), "+f"(d[45]), "+f"(d[46]), "+f"(d[47]),
          "+f"(d[48]), "+f"(d[49]), "+f"(d[50]), "+f"(d[51]), "+f"(d[52]), "+f"(d[53]), "+f"(d[54]), "+f"(d[55]),
          "+f"(d[56]), "+f"(d[57]), "+f"(d[58]), "+f"(d[59]), "+f"(d[60]), "+f"(d[61]), "+f"(d[62]), "+f"(d[63]),
          "+f"(d[64]), "+f"(d[65]), "+f"(d[66]), "+f"(d[67]), "+f"(d[68]), "+f"(d[69]), "+f"(d[70]), "+f"(d[71]),
          "+f"(d[72]), "+f"(d[73]), "+f"(d[74]), "+f"(d[75]), "+f"(d[76]), "+f"(d[77]), "+f"(d[78]), "+f"(d[79]),
          "+f"(d[80]), "+f"(d[81]), "+f"(d[82]), "+f"(d[83]), "+f"(d[84]), "+f"(d[85]), "+f"(d[86]), "+f"(d[87]),
          "+f"(d[88]), "+f"(d[89]), "+f"(d[90]), "+f"(d[91]), "+f"(d[92]), "+f"(d[93]), "+f"(d[94]), "+f"(d[95])
        : "r"(a0), "r"(a1), "r"(a2), "r"(a3), "l"(db));
}
__device__ __forceinline__ void wgmma_rs_n8(float (&d)[4], uint32_t a0, uint32_t a1, uint32_t a2, uint32_t a3, uint64_t db) {
    asm volatile("{\n.reg .pred p;\nsetp.ne.b32 p, 1, 0;\n"
        "wgmma.mma_async.sync.aligned.m64n8k16.f32.bf16.bf16 "
        "{%0, %1, %2, %3}, "
        "{%4, %5, %6, %7}, %8, p, 1, 1, 0;\n}\n"
        : "+f"(d[0]), "+f"(d[1]), "+f"(d[2]), "+f"(d[3])
        : "r"(a0), "r"(a1), "r"(a2), "r"(a3), "l"(db));
}

template <int HS>
__device__ __forceinline__ void attn_pair(const uint32_t* q, const uint32_t* k, const uint32_t* v, const uint32_t* kh, const uint32_t* vh,
                                          const float* fu, const float* fn, const float* rk, float bias0, float bias1, uint32_t mU, uint32_t zero, const float* ci, uint32_t* o) {
    float s0[2][4] = {}, s1[2][4] = {}, s2[2][4] = {};
#pragma unroll
    for (int n = 0; n < 4; n++) {
        const int hd = n & 1, a = 8 * hd + 2 * (n & 2);
        mma16816(s1[hd], q[a], q[a + 1], q[a + 2], q[a + 3], k[a], k[a + 2]);
        mma16816(s2[hd], q[a], q[a + 1], q[a + 2], q[a + 3], k[a + 1], k[a + 3]);
    }
#pragma unroll
    for (int n = 0; n < 4; n++) {
        const int hd = n & 1, a = 8 * hd + 2 * (n & 2);
        mma16816(s0[hd], q[a], q[a + 1], q[a + 2], q[a + 3], kh[HS * (a / 2)], kh[HS * (a / 2 + 1)]);
    }
    float e[2][4], m[2][2];
#pragma unroll
    for (int hd = 0; hd < 2; hd++) {
        e[hd][2] = fmaf(s1[hd][2], fu[2], s2[hd][2] * fn[2]); e[hd][3] = fmaf(s1[hd][3], fu[3], s2[hd][3] * fn[3]);
        e[hd][0] = fmaf(s0[hd][0], fu[0], fmaf(s1[hd][0], fn[0], bias0)); e[hd][1] = fmaf(s0[hd][1], fu[1], fmaf(s1[hd][1], fn[1], bias1));
        m[hd][1] = fmaxf(e[hd][2], e[hd][3]); m[hd][0] = fmaxf(e[hd][0], e[hd][1]);
    }
#pragma unroll
    for (int x = 1; x < 3; x++)
#pragma unroll
        for (int n = 0; n < 4; n++) m[n & 1][1 - (n >> 1)] = fmaxf(m[n & 1][1 - (n >> 1)], __shfl_xor_sync(0xffffffffu, m[n & 1][1 - (n >> 1)], x));
#pragma unroll
    for (int hd = 0; hd < 2; hd++) {
#pragma unroll
        for (int n = 0; n < 4; n++) e[hd][n] = ex2(e[hd][n] - m[hd][n >> 1]);
        float sum[4] = {};
        mma1688(sum, pack_bf16(e[hd][0], e[hd][1]), pack_bf16(e[hd][2], e[hd][3]), 0x3f803f80u);
        const float i0 = rcp(sum[0]), i1 = rcp(sum[2]);
        const uint32_t plo = pack_bf16(e[hd][0] * rk[0] * i0, e[hd][1] * rk[1] * i0), phi = pack_bf16(e[hd][2] * rk[2] * i1, e[hd][3] * rk[3] * i1);
        const uint32_t z0 = plo & zero, z1 = phi & zero;
        const uint32_t a0 = plo & ~mU, a1 = phi & mU, a3 = phi & ~mU, b0 = plo & mU;
#pragma unroll
        for (int jj = 0; jj < 4; jj++) {
            float c[4];
            asm volatile("mma.sync.aligned.m16n8k16.row.col.f32.bf16.bf16.f32 {%0,%1,%2,%3}, {%4,%5,%6,%7}, {%8,%9}, {%10,%11,%12,%13};"
                         : "=f"(c[0]), "=f"(c[1]), "=f"(c[2]), "=f"(c[3])
                         : "r"(a0), "r"(a1), "r"(z0), "r"(a3), "r"(v[8 * hd + 2 * jj]), "r"(v[8 * hd + 2 * jj + 1]), "f"(ci[0]), "f"(ci[1]), "f"(ci[2]), "f"(ci[3]));
            mma1688(c, b0, z1, vh[HS * (4 * hd + jj)]);
            o[8 * hd + 2 * jj] = pack_bf16(c[0], c[1]); o[8 * hd + 2 * jj + 1] = pack_bf16(c[2], c[3]);
        }
    }
}

__device__ __forceinline__ uint32_t norm_pair(uint32_t u, float m, float rinv) {
    const uint32_t d = pack_bf16(bf_lo(u) - m, bf_hi(u) - m);
    return max(pack_bf16(bf_lo(d) * rinv, bf_hi(d) * rinv), 1u);
}

__global__ void __launch_bounds__(512, 1)
fused_kernel(const __grid_constant__ CUtensorMap mx, const __grid_constant__ CUtensorMap mw, const __grid_constant__ CUtensorMap mwo,
             const __grid_constant__ CUtensorMap mout, const __grid_constant__ CUtensorMap mgu, const __grid_constant__ CUtensorMap mwd,
             const __grid_constant__ CUtensorMap mo, const __grid_constant__ CUtensorMap mr,
             const __nv_bfloat16* __restrict__ x, const __nv_bfloat16* __restrict__ wr, Scratch* __restrict__ scr, int swap_gu, const Weights pf) {
    extern __shared__ __align__(1024) uint8_t smem[];
    const uint32_t sb = smem_u32(smem);
    const uint32_t bars = sb + OFF_BAR;
    const int tid = threadIdx.x, lane = tid & 31, warp = __shfl_sync(0xffffffffu, tid >> 5, 0);
    const uint32_t sd = (sb & 0x3FFFF) >> 4;
    const int hp = blockIdx.x & 1, cl = blockIdx.x >> 1;
    int pr = cl - 4 + (max(cl - 36, 0) * 37 >> 8);
    asm("{\n.reg .pred p;\nsetp.lt.s32 p, %1, 4;\nselp.s32 %0, %2, %0, p;\n}" : "+r"(pr) : "r"(cl), "r"(39 + 8 * cl));
    const int b = pr * 2 + hp, mt = pr >> 3, p = pr & 7, nt = 2 * p + hp, rh = p & 1, cb = (p & 6) + hp;
    const int par = mt >> 2, j0 = (mt & 3) * 256;
    int budget = BUDGET;

    TSC(tid == 0, 0);
    auto load_w = [&](int k, int s) {
        const uint32_t full = bars + 8 * (B_WFULL + s);
        mbar_expect_tx(full, W_BYTES);
        tma_3d(sb + OFF_W + s * W_BYTES, &mw, full, nt * 64, k * 64, 0);
    };
    auto load_x = [&](int n) {
        const int w = n & 1, j = n < 4 ? (n >> 1) + 4 : (n >> 1) - 2;
        const uint32_t full = bars + 8 * (B_XFULL + w * 6 + 5 - j);
        mbar_expect_tx(full, BOX);
        tma_4d(sb + w * OFF_X1 + j * BOX, &mx, full, par * 1024 + (n >> 2) * 64, 0, (j0 + w * 128) >> 5, (~n >> 1) & 1);
    };
    if (warp < NBAR / 6 && elect_one()) {
        const uint32_t cnt = warp < B_WEMPTY / 6 ? 1 : warp < B_G1DONE / 6 ? 2 : warp < B_STAGED / 6 ? 4 : 8;
#pragma unroll
        for (int i = 0; i < 6; i++) mbar_init(bars + 48 * warp + 8 * i, cnt);
        asm volatile("fence.mbarrier_init.release.cluster;" ::: "memory");
        if (warp == 0 && b < 128) { load_x(0); load_w(0, 2); }
    }
    __syncthreads();

    if (b >= 128) {
        const int hc = b - 128, g = lane >> 2, t = lane & 3;
        const uint32_t ep = ld_rlx(&scr->epoch[0]) + 1;
        if (warp < 12) {
            const int n = warp / 3, part = warp - 3 * n;
            auto load = [&](int k) {
                const uint32_t full = bars + 8 * (2 * n + (k & 1));
                mbar_expect_tx(full, W_BYTES);
                tma_3d(sb + (2 * n + (k & 1)) * W_BYTES, &mw, full, (4 * hc + n) * 64, k * 64, 0);
            };
            if (part == 0 && elect_one()) { load(0); load(1); }
            __syncwarp();
            float c0[4] = {0.f, 0.f, 0.f, 0.f}, c1[4] = {0.f, 0.f, 0.f, 0.f};
            const uint32_t sel = g == 0 ? 0x3f80u : g == 1 ? 0x3f800000u : 0u;
            const uint32_t a = sb + 2 * n * W_BYTES + part * BOX + t * 256 + ((g ^ (2 * t)) << 4);
#pragma unroll 1
            for (int k = 0; k < 16; k++) {
                mbar_wait(bars + 8 * (2 * n + (k & 1)), (k >> 1) & 1, budget);
                uint4 v[8], u[8];
#pragma unroll
                for (int i = 0; i < 8; i++) { v[i] = lds4(a + (k & 1) * W_BYTES + i * 1024); u[i] = lds4(((a + 128) ^ 16) + (k & 1) * W_BYTES + i * 1024); }
                bar_sync(1 + n, 96);
                if (part == k % 3 && k < 14 && elect_one()) load(k + 2);
                __syncwarp();
#pragma unroll
                for (int i = 0; i < 8; i++) { mma16816(c0, v[i].x, v[i].y, u[i].x, u[i].y, sel, sel); mma16816(c1, v[i].z, v[i].w, u[i].z, u[i].w, sel, sel); }
            }
            if (t == 0) {
#pragma unroll
                for (int r = 0; r < 3; r++) {
                    const uint32_t q0 = (pack_bf16(c0[0], c0[1]) & ~1u) | (ep & 1), q1 = pack_bf16(c0[2], c0[3]), q2 = pack_bf16(c1[0], c1[1]), q3 = pack_bf16(c1[2], c1[3]);
                    st_rlx4(&scr->cs[4 * hc + n][r][part * 8 + g], q0, q1, q2, q3);
                    c0[0] -= bf_lo(q0); c0[1] -= bf_hi(q0); c0[2] -= bf_lo(q1); c0[3] -= bf_hi(q1);
                    c1[0] -= bf_lo(q2); c1[1] -= bf_hi(q2); c1[2] -= bf_lo(q3); c1[3] -= bf_hi(q3);
                }
            }
            TSC(tid == 0, 19);
        }
        {
            const int wg = warp >> 2, c2 = 4 * hc + wg, tw = tid & 127;
            const uint32_t ring = sb + wg * 6 * BOX, full = bars + 8 * (8 + wg * 6), ha = sb + 24 * BOX;
            const uint32_t* hsrc = scr->act[ep & 1] + (56 - NH) * 256;
            auto load = [&](int q, int s) { mbar_expect_tx(full + 8 * s, BOX); tma_3d(ring + s * BOX, &mwd, full + 8 * s, 0, (56 - NH + q) * 64, c2); };
            const uint32_t key = poll_all(&scr->sel[lane & 7], 31u, ep & 31, budget);
            __syncthreads();
            TSC(tid == 0, 12);
            if ((warp & 3) == 0 && elect_one()) {
#pragma unroll 1
                for (int q = 0; q < 6; q++) load(q, q);
            }
            __syncwarp();
            const int zr = (2047 - ((__shfl_sync(0xffffffffu, key, warp >> 1) >> 5) & 2047)) & ~30;
#pragma unroll
            for (int i = 0; i < 8; i++) st_rlx4(pf.out + (size_t)(zr + (warp & 1) * 16 + 2 * i) * 2048 + hc * 512 + lane * 16, 0, 0, 0, 0);
            __syncthreads();
            uint32_t wa[NR * 16];
#pragma unroll
            for (int q = 0; q < NR; q++) {
                mbar_wait(full + 8 * q, 0, budget);
                TSC(tid == 0, 32 + q);
#pragma unroll
                for (int j = 0; j < 4; j++) ldsm4t(wa + 16 * q + 4 * j, ring + q * BOX + j * 2048 + (lane >> 4) * 1024 + (lane & 7) * 128 + ((((warp & 3) * 2 + ((lane >> 3) & 1)) ^ (lane & 7)) << 4));
                bar_sync(1 + wg, 128);
                if ((warp & 3) == 0 && elect_one()) load(q + 6, q);
                __syncwarp();
            }
            if (tid == 64) { fence_gpu(); st_rlx(&scr->zflag[hc], ep); }
            if (warp == 1 && elect_one()) {
                int tries = BUDGET;
#pragma unroll 1
                while (ld_rlx(&scr->cnt[8][0]) != ep * (4 * NH) && --tries > 0) {}
                mbar_expect_tx(bars + 8 * 32, NH * 1024);
                bulk_g2s(ha, hsrc, NH * 1024, bars + 8 * 32);
                TS(17);
            }
            __syncwarp();
            mbar_wait(bars + 8 * 32, 0, budget);
#pragma unroll 1
            for (int i = tid; i < NH * 64; i += 512) {
                int tries = BUDGET;
                if (lds1(ha + i * 16) == 0) {
                    uint4 v;
#pragma unroll 1
                    do { v = ld_rlx4(hsrc + i * 4); } while (v.x == 0 && --tries > 0);
                    sts4(ha + i * 16, v.x, v.y, v.z, v.w);
                }
            }
            fence_async_smem();
            __syncthreads();
            TSC(tid == 0, 5);
            float acc[4] = {0.f, 0.f, 0.f, 0.f};
            int s = NR; uint32_t ph = 0;
#pragma unroll 1
            for (int q = NR; q < NH; q++) {
                mbar_wait(full + 8 * s, ph, budget);
                TSC(tid == 0, 32 + q);
                wg_fence();
#pragma unroll
                for (int j = 0; j < 4; j++)
                    wgmma_n8<1, 0>(acc, mkdesc(sd + dlo((wg * 6 + s) * BOX, BOX) + j * 128, dhi(1024, 1)), mkdesc(sd + dlo(24 * BOX + q * 1024, 128) + j * 16, dhi(128, 0)), 1);
                wg_commit();
                wg_wait<1>();
                if ((warp & 3) == (q & 3) && q > NR && q + 5 < NH && elect_one()) load(q + 5, s ? s - 1 : 5);
                __syncwarp();
                if (++s == 6) { s = 0; ph ^= 1; }
                if (q == NR + 5) {
                    wg_fence();
#pragma unroll
                    for (int j = 0; j < 4 * NR; j++) wgmma_rs_n8(acc, wa[4 * j], wa[4 * j + 1], wa[4 * j + 2], wa[4 * j + 3], mkdesc(sd + dlo(24 * BOX, 128) + j * 16, dhi(128, 0)));
                    wg_commit();
                }
            }
            wg_wait<0>();
            TSC(tid == 0, 18);
            uint4 v[8]; uint32_t bad; int tries = BUDGET;
#pragma unroll 1
            do {
                bad = 0;
#pragma unroll
                for (int m = 0; m < 8; m++) v[m] = ld_rlx4(&scr->ypart[m][c2][tw]);
#pragma unroll
                for (int m = 0; m < 8; m++) bad |= v[m].x ^ ep;
            } while ((bad & 1) && --tries > 0);
            __syncwarp();
            const float sig = bf16r(sigmoidf(__uint_as_float(((int)key < 0 ? key & 0x7fffffffu : ~key) & 0xffff0000u)));
#pragma unroll
            for (int c = 0; c < 4; c++) {
#pragma unroll
                for (int m = 0; m < 8; m++) acc[c] += __uint_as_float((&v[m].x)[c]);
                acc[c] = bf16r(acc[c]) * __shfl_sync(0xffffffffu, sig, 2 * t + (c & 1));
            }
            char* dst = pf.out + (size_t)(2047 - ((__shfl_sync(0xffffffffu, key, g) >> 5) & 2047)) * 2048 + c2 * 128 + (warp & 3) * 32 + t * 4;
            asm volatile("red.relaxed.gpu.global.add.noftz.bf16x2 [%0], %1;" ::"l"(dst), "r"(movm(pack_bf16(acc[0], acc[1]))) : "memory");
            asm volatile("red.relaxed.gpu.global.add.noftz.bf16x2 [%0], %1;" ::"l"(dst + 16), "r"(movm(pack_bf16(acc[2], acc[3]))) : "memory");
            TSC(tid == 0, 20);
        }
        if (warp < 8) TS_END();
        return;
    }
    asm volatile("barrier.cluster.arrive.relaxed.aligned;" ::: "memory");

    const int c2 = b & 15, n2 = mt < 7 ? NM : N7;
    if (warp >= 12) {
        reg_dec<24>();
        if (warp == 12) {
            if (elect_one()) {
                int c = 0;
#pragma unroll 1
                for (int n = 1; n < 12; n++) {
                    load_x(n);
                    #pragma unroll 1
                    for (; c < (n == 11 ? 4 : __popc(ROWS_AT & ((2 << n) - 1))); c++) { mbar_expect_tx(bars + 8 * (B_ROW + c), BOX); tma_2d(sb + OFF_FR + c * BOX, &mr, bars + 8 * (B_ROW + c), c * 256, b * 16); }
                    if (n == 3 || n == 7) load_w((n + 1) >> 2, n >> 2);
                }
                int s = 2; uint32_t ph = 0;
#pragma unroll 1
                for (int k = 3; k < 16; k++) {
                    mbar_wait(bars + 8 * (B_WEMPTY + s), ph, budget);
                    load_w(k, s);
                    if (++s == 3) s = 0;
                    if (s == 2) ph ^= 1;
                }
                s = 2;
#pragma unroll 1
                for (int i = 0; i < 16; i++) {
                    mbar_wait(bars + 8 * (i < 2 ? B_WEMPTY + i : i < 4 ? B_G1DONE : i < 6 ? B_F1DONE : B_WOEMPTY + s), i >= 12, budget);
                    if (i == 0) {
                        mbar_expect_tx(bars + 8 * B_XT, 4 * BOX);
#pragma unroll 1
                        for (int n = 0; n < 4; n++)
                            tma_4d(sb + (n >> 1) * OFF_X1 + (n & 1) * BOX, &mx, bars + 8 * B_XT, par * 1024 + cb * 128 + (n & 1) * 64, 0, (j0 + rh * 128) >> 5, 1 - (n >> 1));
                    }
                    const uint32_t full = bars + 8 * (B_WOFULL + s);
                    mbar_expect_tx(full, 2 * BOX);
                    tma_3d(sb + OFF_WO + s * 2 * BOX, &mwo, full, 0, ((2 * p + (i < 2 ? i ^ hp : i)) & 15) * 64, cb * 2);
                    TSC(TIMING % 10 == 4, 48 + i);
                    if (++s == 6) s = 0;
                }
            }
        } else {
            bar_sync(8, 224);
            const uint32_t ep = __shfl_sync(0xffffffffu, lds1(sb + OFF_EP), 0);
            if (warp == 13) {
                cluster_wait();
                if (elect_one()) {
                    int j = 4, q = 0, left = BUDGET; uint32_t ph = 0;
#pragma unroll 1
                    for (int n = 6; n < 32; n++) {
                        mbar_wait(bars + 8 * (B_XEMPTY + j), ph, left);
                        tma_4d_mc(sb + hp * OFF_X1 + j * BOX, &mx, bars + 8 * (B_XFULL + hp * 6 + 5 - j), par * 1024 + (n >> 1) * 64, 0, (j0 + hp * 128) >> 5, ~n & 1);
                        if (++j == 6) j = 0;
                        if (j == 4) ph ^= 1;
#pragma unroll 1
                        for (; q < (PF_RATE * (n - PF_START) >> 3) && q < 18 + PF_NW; q++) {
                            const int u = q - PF_NW;
                            if (u < 0) bulk_pf(pf.wqkv + (size_t)(1024 + 128 * u + b) * 6144, 6144);
                            else if (u < 16) bulk_pf((b < 64 ? pf.wg : pf.wu) + (size_t)(u * 64 + (b & 63)) * 7168, 7168);
                            else bulk_pf(pf.wo + (size_t)((u - 16) * 128 + b) * 8192, 8192);
                        }
                    }
                }
                __syncwarp();
                uint32_t* hs = &scr->halo[b - 16][lane * 4];
                uint4 v[4] = {};
                if (j0) {
#pragma unroll 1
                    do {
#pragma unroll
                        for (int c = 0; c < 4; c++) v[c] = ld_rlx4(hs + c * 128);
                    } while (__any_sync(0xffffffffu, min(min(v[0].x, v[1].x), min(v[2].x, v[3].x)) == 0) && --budget > 0);
#pragma unroll
                    for (int c = 0; c < 4; c++) st_rlx(hs + c * 128, 0);
                }
#pragma unroll
                for (int c = 0; c < 4; c++) stsm4(sb + OFF_HIN + c * 512 + lane * 16, v[c].x, v[c].y, v[c].z, v[c].w);
                bar_arrive(11, 64);
                TSC(lane == 0, 31);
                const int src = ((mt * 2 + rh) * 2 + 1 - hp) * 1024;
                if (elect_one()) {
                    const uint32_t* fl = &scr->oflag[mt * 2 + 1 - hp][0];
                    const uint32_t inv = (ep & 1) - 1;
                    uint32_t ready = 0, ph = 0;
                    int s = 4;
#pragma unroll 1
                    for (int i = 2; i < 16; i++) {
                        const int kb = (2 * p + i) & 15;
#pragma unroll 1
                        while (!((ready >> kb) & 1) && --budget > 0) ready = ld_rlx(fl) ^ inv;
                        TSC(i == 2, 30);
                        mbar_wait(bars + 8 * (B_OEMPTY + s), ph, budget);
                        tma_2d_mc(sb + hp * OFF_X1 + s * BOX, &mo, bars + 8 * (B_OFULL + hp * 6 + s), 0, src + kb * 64);
                        TSC(TIMING % 10 == 4 && hp == 0, 32 + i);
                        if (++s == 6) s = 0;
                        if (s == 4) ph ^= 1;
                    }
                }
            } else if (warp == 14) {
                if (elect_one()) {
                    uint32_t s8 = 0, ph = 0;
                    int tries = BUDGET;
                    const uint32_t* act = scr->act[ep & 1];
                    auto counted = [&](int c, uint32_t n) {
#pragma unroll 1
                        while (ld_rlx(&scr->cnt[c][0]) != ep * n && --tries > 0) __nanosleep(POLL_NS);
                    };
                    auto weights = [&](const CUtensorMap* m, int c0, int c1, int c2_) {
                        mbar_wait(bars + 8 * B_FEMPTY + s8, ph, budget);
                        mbar_expect_tx(bars + 8 * B_FFULL + s8, F_BYTES);
                        tma_3d(sb + OFF_FS + s8 * (F_BYTES / 8), m, bars + 8 * B_FFULL + s8, c0, c1, c2_);
                    };
                    if (b < 112) {
                        counted(9, 32);
                        TS(26);
#pragma unroll 1
                        for (int q = 0; q < 16; q++) {
                            weights(&mgu, b * 32, q * 64, 0);
                            bulk_g2s(sb + OFF_FS + BOX + s8 * (F_BYTES / 8), act + 14336 + q * 256, 1024, bars + 8 * B_FFULL + s8);
                            TSC(TIMING % 10 == 5, 32 + q);
                            if (q >= PF_D && q < PF_D + PF_DN) bulk_pf(pf.wd + 7340032 - (size_t)((PF_REV ? q - PF_D + 1 : PF_DN + PF_D - q) * 112 - b) * PF_DB, PF_DB);
                            s8 += 8;
                            if (s8 == 40) { s8 = 0; ph ^= 1; }
                        }
                    }
#pragma unroll 1
                    for (int q = -3; q < n2; q++) {
                        if (q == 0) { counted(mt, 4 * n2); TS(29); }
                        if ((unsigned)q >= 3) weights(&mwd, 0, (mt * NM + (q < 0 ? q + 3 : q)) * 64, c2);
                        if (q >= 0) bulk_g2s(sb + OFF_FS + BOX + s8 * (F_BYTES / 8), act + (mt * NM + q) * 256, 1024, bars + 8 * B_FFULL + s8);
                        TSC(TIMING % 10 == 5, 51 + q);
                        s8 += 8;
                        if (s8 == 24) { s8 = 0; if ((unsigned)q >= 3) ph ^= 1; }
                    }
                }
            } else {
#pragma unroll 1
                for (int i = lane * 16; i < CS_BYTES; i += 512) sts4(sb + OFF_CS + i, 0, 0, 0, 0);
                mbar_wait(bars + 8 * ZF_GATE, 0, budget);
                uint8_t* oz = scr->o + ((size_t)mt * 64 + nt) * BOX + lane * 16;
#pragma unroll 1
                for (int i = 0; i < 16; i++, oz += 512) {
#pragma unroll
                    for (int n = 0; n < 4; n++) st_rlx4(oz + n * 16 * BOX, 0, 0, 0, 0);
                    __nanosleep(ZF_NS);
                }
                __syncwarp();
                TSC(lane == 0, 5);
                fence_gpu();
                TSC(lane == 0, 12);
                mbar_wait(bars + 8 * B_RDONE, 0, budget);
                int tries = BUDGET;
#pragma unroll 1
                for (int i = lane; i < 88; i += 32) {
                    const uint2* rp = &scr->row[2 * (j0 - 8 + i) + par];
                    uint2 v0, v1, v2;
#pragma unroll 1
                    do { v0 = ld_rlx2(rp + (j0 + i < 8 ? 16 : 0)); v1 = ld_rlx2(rp + 176); v2 = ld_rlx2(rp + 352); } while ((((v0.y ^ ep) | (v1.y ^ ep) | (v2.y ^ ep)) & 31) && --tries > 0);
                    sts2(sb + OFF_STAT + i * 8, (v0.x << 16) ^ 0x80000000u, __float_as_uint(rcp(bf_hi(v0.x))));
                    sts2(sb + OFF_STAT + i * 8 + 704, (v1.x << 16) ^ 0x80000000u, __float_as_uint(rcp(bf_hi(v1.x))));
                    sts2(sb + OFF_STAT + i * 8 + 1408, (v2.x << 16) ^ 0x80000000u, __float_as_uint(rcp(bf_hi(v2.x))));
                }
                __syncwarp();
                {
                    const int row = 2047 - ((poll_all(&scr->sel[lane & 7], 31u, ep & 31, budget) >> 5) & 2047), jj = (row >> 1) - j0 - rh * 128;
                    sts1(sb + OFF_SEL, __reduce_or_sync(0xffffffffu, (row & 1) == par && (unsigned)jj < 128 ? 1u << (jj >> 4) : 0u));
                }
                TSC(lane == 0, 14);
                if (lane < 24) {
                    uint4 v[3];
#pragma unroll 1
                    while (v[0] = ld_rlx4(&scr->cs[nt][0][lane]), v[1] = ld_rlx4(&scr->cs[nt][1][lane]), v[2] = ld_rlx4(&scr->cs[nt][2][lane]),
                           (((v[0].x ^ ep) | (v[1].x ^ ep) | (v[2].x ^ ep)) & 1) && --tries > 0) __nanosleep(100);
#pragma unroll
                    for (int r = 0; r < 3; r++) sts4(sb + OFF_CS + 64 + lane * 128 + r * 16, v[r].x, v[r].y, v[r].z, v[r].w);
                }
                fence_async_smem();
                __syncwarp();
                if (elect_one()) {
                    mbar_arrive(bars + 8 * B_AUX);
                    TS(21);
                    mbar_expect_tx(bars + 8 * (B_OFULL + 3), BOX); mbar_expect_tx(bars + 8 * (B_OFULL + 9), BOX);
#pragma unroll 1
                    for (int v = 0; v < 2; v++) {
                        const uint32_t ring = sb + v * OFF_X1 + 2 * BOX, fb = bars + 8 * (B_OFULL + v * 6 + 2);
                        mbar_wait(bars + 8 * (B_STAGED + v), 0, budget);
                        asm volatile("red.relaxed.gpu.global.xor.b32 [%0], %1;" ::"l"(&scr->oflag[mt * 2 + 1 - v][0]), "r"(1u << nt) : "memory");
                        TS(13 + 2 * v);
                        mbar_arrive(fb);
                        mbar_wait(bars + 8 * B_G1DONE, 0, budget);
                        bulk_s2c(mapa(ring + BOX, hp ^ 1), ring, BOX, mapa(fb + 8, hp ^ 1));
                        if (v == 0) mbar_wait(bars + 8 * B_FREED, 0, budget);
#pragma unroll
                        for (int n = 0; n < 4; n++) {
                            mbar_expect_tx(bars + 8 * (B_OFULL + (n >> 1) * 6 + 4 + (n & 1)) - v * 32, BOX);
                            mbar_arrive_at(mapa(bars + 8 * B_OEMPTY, n >> 1) + (4 + (n & 1)) * 8 - v * 32);
                        }
                    }
                    if (lds1(sb + OFF_SEL)) {
#pragma unroll 1
                        while (ld_acq(&scr->zflag[p >> 1]) != ep && --tries > 0) {}
                        asm volatile("fence.proxy.async.global;" ::: "memory");
                    }
                    mbar_arrive(bars + 8 * B_ZERO);
                }
            }
        }
    } else if (warp >= 8) {
        reg_dec<40>();
        const int wq = warp - 8, ta = tid - 256;
        const uint32_t rbuf = sb + OFF_FR + wq * 2048;
        const uint4 wv = ldg_nc(wr + ta * 8);
        if (ta == 0) sts1(sb + OFF_EP, ld_rlx(&scr->epoch[0]) + 1);
        sts4(sb + OFF_STAT + ta * 16, wv.x, wv.y, wv.z, wv.w);
        bar_sync(8, 224);
        const uint32_t ep = __shfl_sync(0xffffffffu, lds1(sb + OFF_EP), 0);
        {
            const int s = b * 16 + wq * 4 + (lane >> 3);
            if ((lane & 7) == 0) st_rlx2(&scr->row[s], 0, ep - 1);
            float sw = 0.f;
#pragma unroll 1
            for (int i = 0; i < 16; i++) { const uint32_t q = lds1(sb + OFF_STAT + i * 128 + lane * 4); sw += bf_lo(q) + bf_hi(q); }
#pragma unroll 1
            for (int o = 16; o > 0; o >>= 1) sw += __shfl_xor_sync(0xffffffffu, sw, o);
            float s1 = 0.f, s2 = 0.f, sr = 0.f;
            {
                float s1b = 0.f, s2b = 0.f, srb = 0.f;
                const uint32_t xb = rbuf + (lane >> 4) * 1024 + (lane & 15) * 16, wb = sb + OFF_STAT + (lane & 15) * 16;
#pragma unroll 1
                for (int i = 0; i < 8; i++) {
                    const uint4 w4 = lds4(wb + i * 256);
                    mbar_wait_hot(bars + 8 * (B_ROW + (i >> 1)), 0, budget);
                    TSC(ta == 0 && i == 0, 17);
                    const uint32_t o = (i >> 1) * BOX + (i & 1) * 256;
                    const uint4 u = lds4(xb + o), v = lds4(xb + o + 512);
#pragma unroll
                    for (int c = 0; c < 4; c++) {
                        const float w0 = bf_lo((&w4.x)[c]), w1 = bf_hi((&w4.x)[c]);
                        const float a0 = bf_lo((&u.x)[c]), a1 = bf_hi((&u.x)[c]), b0 = bf_lo((&v.x)[c]), b1 = bf_hi((&v.x)[c]);
                        s1 += a0; s2 = fmaf(a0, a0, s2); sr = fmaf(a0, w0, sr);
                        s1 += a1; s2 = fmaf(a1, a1, s2); sr = fmaf(a1, w1, sr);
                        s1b += b0; s2b = fmaf(b0, b0, s2b); srb = fmaf(b0, w0, srb);
                        s1b += b1; s2b = fmaf(b1, b1, s2b); srb = fmaf(b1, w1, srb);
                    }
                }
                const bool up = lane & 8;
                s1 = (up ? s1b : s1) + __shfl_xor_sync(0xffffffffu, up ? s1 : s1b, 8);
                s2 = (up ? s2b : s2) + __shfl_xor_sync(0xffffffffu, up ? s2 : s2b, 8);
                sr = (up ? srb : sr) + __shfl_xor_sync(0xffffffffu, up ? sr : srb, 8);
            }
#pragma unroll
            for (int o = 1; o < 8; o <<= 1) {
                s1 += __shfl_xor_sync(0xffffffffu, s1, o); s2 += __shfl_xor_sync(0xffffffffu, s2, o); sr += __shfl_xor_sync(0xffffffffu, sr, o);
            }
            const float mean = s1 * (1.f / 1024.f), mb = bf16r(mean);
            float var = fmaf(-mean, mean, s2 * (1.f / 1024.f));
            sr = fmaf(-mb, sw, sr);
            if (__builtin_expect(__any_sync(0xffffffffu, mean * mean > 256.f * var), 0)) {
                float a2 = 0.f, ar = 0.f;
#pragma unroll 1
                for (int i = 0; i < 64; i++) {
                    const uint32_t o = i * 32 + (lane & 7) * 4, q1 = lds1(rbuf + (lane >> 3) * 512 + (o >> 9) * BOX + (o & 511)), q2 = lds1(sb + OFF_STAT + o);
                    a2 = fmaf(bf_lo(q1) - mean, bf_lo(q1) - mean, fmaf(bf_hi(q1) - mean, bf_hi(q1) - mean, a2));
                    ar = fmaf(bf_lo(q1) - mb, bf_lo(q2), fmaf(bf_hi(q1) - mb, bf_hi(q2), ar));
                }
#pragma unroll 1
                for (int o = 1; o < 8; o <<= 1) { a2 += __shfl_xor_sync(0xffffffffu, a2, o); ar += __shfl_xor_sync(0xffffffffu, ar, o); }
                var = a2 * (1.f / 1024.f); sr = ar;
            }
            float den;
            asm("sqrt.approx.f32 %0, %1;" : "=f"(den) : "f"(bf16r(bf16r(var) + 1e-5f)));
            const uint32_t st = pack_bf16(mb, den);
            const uint32_t rb = pack_bf16(0.f, sr * rcp(bf_hi(st)) + 0.f);
            uint32_t ord = (int)rb < 0 ? ~rb & 0xffff0000u : rb | 0x80000000u;
            if ((rb & 0x7fffffffu) > 0x7f800000u) ord = 0;
            if ((lane & 7) == 0) st_rlx2(&scr->row[s], st, ord | ((2047 - s) << 5) | (ep & 31));
            __syncwarp();
            if (lane < 7) mbar_arrive(bars + 8 * (lane < 5 ? B_FEMPTY + lane : B_RDONE));
        }
        TSC(ta == 0, 18);
        if ((b >> 3) == 14) {
            const uint32_t gm = sb + OFF_E, cnt = gm + 64, res = gm + 80, list = gm + 128;
            uint32_t kv[16];
            int tries = BUDGET;
#pragma unroll 1
            do {
                uint32_t bad = 0;
#pragma unroll
                for (int n = 0; n < 16; n++) kv[n] = ld_rlx(&scr->row[n * 128 + ta].y);
#pragma unroll
                for (int n = 0; n < 16; n++) bad |= kv[n] ^ ep;
                if ((bad & 31) == 0) break;
            } while (--tries > 0);
            __syncwarp();
            TSC(ta == 0, 26);
            uint32_t m = 0;
#pragma unroll
            for (int n = 0; n < 16; n++) m = max(m, kv[n]);
            uint32_t gmax = m;
#pragma unroll
            for (int o = 1; o < 8; o <<= 1) gmax = max(gmax, __shfl_xor_sync(0xffffffffu, gmax, o));
            sts1(gm + (ta >> 3) * 4, gmax);
            sts1(cnt, 0);
            bar_sync(12, 128);
            const uint32_t c = lds1(gm + (lane & 15) * 4);
            int rank = 0;
#pragma unroll
            for (int i = 0; i < 2; i++) { const uint4 q = lds4(gm + (lane >> 4) * 32 + i * 16); rank += (q.x > c) + (q.y > c) + (q.z > c) + (q.w > c); }
            rank += __shfl_xor_sync(0xffffffffu, rank, 16);
            const uint32_t thr = redux_max(rank == 7 ? c : 0u);
#pragma unroll 1
            while (m >= thr) {
                uint32_t at, m2 = 0;
                asm volatile("atom.shared.add.u32 %0, [%1], 1;" : "=r"(at) : "r"(cnt) : "memory");
#pragma unroll
                for (int n = 0; n < 16; n++) m2 = max(m2, kv[n] < m ? kv[n] : 0u);
                sts1(list + at * 4, m);
                if (m2 == 0) break;
                m = m2;
            }
            bar_sync(12, 128);
            const int nc = lds1(cnt);
#pragma unroll 1
            for (int i = ta >> 3; i < ((nc + 3) & ~3); i += 16) {
                const uint32_t ki = lds1(list + i * 4);
                int r = 0;
#pragma unroll 1
                for (int n = lane & 7; n < nc; n += 8) r += lds1(list + n * 4) > ki;
                __syncwarp();
#pragma unroll
                for (int o = 1; o < 8; o <<= 1) r += __shfl_xor_sync(0xffffffffu, r, o);
                if (r == (b & 7) && i < nc) sts1(res, ki);
            }
            bar_sync(12, 128);
            const uint32_t k0 = lds1(res);
            const int r0 = 2047 - ((k0 >> 5) & 2047);
            TSC(ta == 0, 22);
            if (ta == 0) st_rlx(&scr->sel[b & 7], k0);
            const uint4 v0 = ldg_nc(x + (size_t)r0 * 1024 + ta * 8);
            const uint32_t s0 = ld_rlx(&scr->row[r0]);
            const float m0 = bf_lo(s0), i0 = rcp(bf_hi(s0));
            const int ao = 14336 + (ta >> 3) * 256 + (b & 7) * 32 + ((ta ^ b) & 7) * 4;
            st_rlx4(scr->act[ep & 1] + ao, norm_pair(v0.x, m0, i0), norm_pair(v0.y, m0, i0), norm_pair(v0.z, m0, i0), norm_pair(v0.w, m0, i0));
            __syncwarp();
            if (lane == 0) red_add(&scr->cnt[9][tries >> 30]);
            st_rlx4(scr->act[~ep & 1] + ao, 0, 0, 0, 0);
        }
        uint32_t s8 = 0, fph = 0;
        const uint32_t chk = __shfl_sync(0xffffffffu, sb + OFF_FS + BOX + lane * 32 + (lane & 28), lane);
        int left = BUDGET;
        if (b >= 112 && ta < 2) mbar_arrive(bars + 8 * B_F1DONE);
#pragma unroll 1
        for (int ph = b >= 112; ph < 2; ph++) {
            {
                float acc[4] = {0.f, 0.f, 0.f, 0.f};
                const uint32_t alo = sd + (ph ? dlo(OFF_FS, 8192) : dlo(OFF_FS, 4096)), ahi = ph ? dhi(1024, 1) : dhi(512, 2), astep = ph ? 128 : 64;
                const uint32_t bhi = ph ? dhi(128, 0) : dhi(1024, 1), bstep = ph ? 16 : 2, wrap = ph ? 24 : 40;
                uint32_t prev = 0;
                if (ph) mbar_wait(bars + 8 * FFN2_GATE, 0, left);
#pragma unroll 1
                for (int q = ph ? n2 : 16; q > 0; q--) {
                    const uint32_t da = alo + s8 * (F_BYTES >> 7), db = sd + dlo(OFF_FS + BOX, 128) + s8 * (F_BYTES >> 7);
                    mbar_wait_hot(bars + 8 * B_FFULL + s8, fph, left);
                    if (__builtin_expect(__any_sync(0xffffffffu, lds1(chk + s8 * (F_BYTES / 8)) == 0), 0)) {
                        int tries = BUDGET;
#pragma unroll 1
                        for (int n = lane * 4 + (left >> 30); n < 256; n += 128) {
                            uint4 v;
#pragma unroll 1
                            do { v = ld_rlx4(scr->act[ep & 1] + ((ph ? mt * NM + n2 : 72) - q) * 256 + n); } while (v.x == 0 && --tries > 0);
                            __syncwarp();
                            sts4(sb + OFF_FS + BOX + s8 * (F_BYTES / 8) + n * 4, v.x, v.y, v.z, v.w);
                        }
                        NRETRY();
                        fence_async_smem();
                        __syncwarp();
                    }
                    TSC(TIMING % 10 == 3 && ta == 0, 32 + (ph ? 16 + n2 : 16) - q);
                    wg_fence();
#pragma unroll
                    for (int j = 0; j < 4; j++) wgmma_n8<1, 0>(acc, mkdesc(da + j * astep, ahi), mkdesc(db + j * bstep, bhi), 1);
                    wg_commit();
                    wg_wait<1>();
                    if (ph) { wg_wait<0>(); if (lane == 0) prev = bars + 8 * B_FEMPTY + s8; }
                    if (prev) mbar_arrive(prev);
                    if (lane == 0) prev = bars + 8 * B_FEMPTY + s8;
                    s8 += 8;
                    if (s8 == wrap) { s8 = 0; fph ^= 1; }
                }
                wg_wait<0>();
                const int ln = lane + (left >> 30);
                if (ph == 0) {
                    if (prev) mbar_arrive(prev);
                    const bool second = (wq >= 2) != (swap_gu != 0);
                    const uint32_t xa = sb + OFF_GU + ((wq & 1) * 32 + ln) * 16;
                    if (second) sts4(xa, __float_as_uint(acc[0]), __float_as_uint(acc[1]), __float_as_uint(acc[2]), __float_as_uint(acc[3]));
                    bar_sync(12, 128);
                    if (second) { if (ln == 0) mbar_arrive(bars + 8 * B_F1DONE); }
                    else {
                        const float4 up = lds4f(xa);
                        float hv[4];
#pragma unroll
                        for (int c = 0; c < 4; c++) { const float ga = bf16r(acc[c]); hv[c] = bf16r(ga * sigmoidf(ga)) * bf16r((&up.x)[c]); }
                        const int ao = (b * 4 + (wq & 1) * 2) * 32 + ln;
                        st_rlx(scr->act[ep & 1] + ao, max(movm(pack_bf16(hv[0], hv[1])), 1u)); st_rlx(scr->act[ep & 1] + 32 + ao, max(movm(pack_bf16(hv[2], hv[3])), 1u));
                        __syncwarp();
                        if (ln == 0) red_add(&scr->cnt[b < 14 * NM ? b / (2 * NM) : b < 14 * NM + 2 * N7 ? 7 : 8][0]);
                        st_rlx(scr->act[~ep & 1] + ao, 0); st_rlx(scr->act[~ep & 1] + 32 + ao, 0);
                    }
                } else {
                    st_rlx4(&scr->ypart[mt][c2][wq * 32 + ln], (__float_as_uint(acc[0]) & ~1u) | (ep & 1), __float_as_uint(acc[1]), __float_as_uint(acc[2]), __float_as_uint(acc[3]));
                }
                TSC(ta == 0, 22 + ph);
            }
        }
        TSC(ta == 0, 24);
    } else {
        reg_inc<224>();
        const int w = warp >> 2, wi = warp & 3, g = lane >> 2, t = lane & 3;
        const bool elect = (tid & 127) == 0;
        const uint32_t mad = (lane & 15) * 128 + (((lane >> 4) ^ (lane & 7)) << 4);
        float acc[64];
        const uint32_t ring = sb + w * OFF_X1, ofull = bars + 8 * (B_OFULL + w * 6), oempty = mapa(bars + 8 * B_OEMPTY, w);
        const int r0 = rh * 128 + wi * 32 + (1 - w) * 16 + g;
        {
            float acc0[96], acc1[96];
            const uint32_t sta = sb + OFF_STAT + (8 + w * 128 + wi * 32) * 8;
            {
                const uint32_t xfull = bars + 8 * (B_XFULL + w * 6 + 5), xempty = mapa(bars + 8 * B_XEMPTY, w), dx0 = sd + dlo(w * OFF_X1, 16);
                uint32_t s8 = 16, ps8 = 0, ph = 0;
                cluster_wait();
#pragma unroll 1
                for (int k = 0; k < 16; k++) {
                    const uint32_t dx = dx0 + s8 * (2 * BOX >> 7), dw = sd + dlo(OFF_W, BOX) + s8 * (W_BYTES >> 7);
                    mbar_wait(bars + 8 * B_WFULL + s8, ph, budget);
                    mbar_wait(xfull - 2 * s8, ph, budget);
                    TSC(elect && k == 0, 1 + 8 * w);
                    TSC(TIMING % 10 == 1 && tid == 0, 32 + k);
                    wg_wait<0>();
                    wg_fence();
#pragma unroll
                    for (int kk = 0; kk < 4; kk++) wgmma_n192<0, 1>(acc1, mkdesc(dx + kk * 2, dhi(1024, 1)), mkdesc(dw + kk * 128, dhi(1024, 1)), kk ? 1 : k);
                    wg_commit();
                    TSC(TIMING % 10 == 6 && elect, 32 + 16 * w + k);
                    if (elect && k > 0) {
                        mbar_arrive(bars + 8 * B_WEMPTY + ps8);
                        if (k <= 13) { mbar_expect_tx(xfull - 2 * ps8 - 8, BOX); mbar_arrive_at(xempty + 2 * ps8 + 8); }
                    }
                    if (k == 15) {
                        mbar_wait(bars + 8 * B_AUX, 0, budget);
                        const uint32_t zero = budget >> 30, pm = t & 1 ? 0x4432 : 0x3232, ra = sta + ((t >> 1) * 16 + g) * 8;
                        const uint32_t a0 = __byte_perm(lds1(ra), 0, pm), a1 = __byte_perm(lds1(ra + 64), 0, pm), a2 = a0 & zero, a3 = a1 & zero;
                        wg_fence();
                        wgmma_rs_n192(acc1, a0, a1, a2, a3, mkdesc(sd + dlo(OFF_CS, 0), dhi(128, 0)));
                        wgmma_rs_n192(acc0, a0, a1, a2, a3, mkdesc(sd + dlo(OFF_CS + 64, 0), dhi(128, 0)));
                        wg_commit();
                    }
                    mbar_wait(xfull - 2 * s8 - 8, ph, budget);
                    wg_wait<0>();
                    wg_fence();
#pragma unroll
                    for (int kk = 0; kk < 4; kk++) wgmma_n192<0, 1>(acc0, mkdesc(dx + 512 + kk * 2, dhi(1024, 1)), mkdesc(dw + kk * 128, dhi(1024, 1)), kk ? 1 : k);
                    wg_commit();
                    if (elect && k <= 12) { mbar_expect_tx(xfull - 2 * s8, BOX); mbar_arrive_at(xempty + 2 * s8); }
                    ps8 = s8;
                    s8 = s8 == 16 ? 0 : s8 + 8;
                    if (s8 == 16) ph ^= 1;
                }
            }
            const uint32_t zero = budget >> 30;
            const bool u0 = 2 * t > g, u1 = 2 * t + 1 > g;
            uint32_t mU = (u0 ? 0xffffu : 0u) | (u1 ? 0xffff0000u : 0u);
            uint32_t ka0 = sta + (2 * t - (u0 ? 8 : 0)) * 8 + 4, ka1 = sta + (2 * t + 1 - (u1 ? 8 : 0)) * 8 + 4;
            float rk[2][4], fu[2][4], fn[2][4];
            auto factors = [&](int h) {
#pragma unroll
                for (int n = 0; n < 4; n += 2) {
                    const float rq = lds1f(sta + (16 * h + 4 * n + g) * 8 + 4) * (0.17677669529663687f * 1.4426950408889634f);
                    rk[h][n] = lds1f(ka0 + h * 128 + n * 32); rk[h][n + 1] = lds1f(ka1 + h * 128 + n * 32);
                    const float f0 = rq * rk[h][n], f1 = rq * rk[h][n + 1];
                    fu[h][n] = u0 ? f0 : 0.f; fn[h][n] = f0 - fu[h][n]; fu[h][n + 1] = u1 ? f1 : 0.f; fn[h][n + 1] = f1 - fu[h][n + 1];
                }
#pragma unroll
                for (int n = 0; n < 4; n++) asm volatile("" : "+f"(fu[h][n]), "+f"(fn[h][n]));
            };
            uint8_t* og = scr->o + ((size_t)(mt * 4 + w * 2) * 16 + nt) * BOX + wi * 256 + lane * 4;
            TSC(elect, 19 + w);
            uint32_t pk0[48], pk1[48], o[16] = {};
#pragma unroll
            for (int j = 0; j < 48; j++) if (j < 16 || (j & 1)) pk1[j] = pack_here(acc1[2 * j], acc1[2 * j + 1]);
            if (warp < 7) {
#pragma unroll
                for (int c = 0; c < 4; c++) stsm4(ring + 4 * BOX + wi * 2048 + c * 512 + lane * 16, pk1[17 + 8 * c], pk1[19 + 8 * c], pk1[21 + 8 * c], pk1[23 + 8 * c]);
                bar_arrive(1 + warp, 64);
            } else if (j0 != 768) {
#pragma unroll
                for (int c = 0; c < 4; c++) {
                    pk1[17 + 8 * c] = max(pk1[17 + 8 * c], 1u);
                    st_rlx4(&scr->halo[b][c * 128 + lane * 4], pk1[17 + 8 * c], pk1[19 + 8 * c], pk1[21 + 8 * c], pk1[23 + 8 * c]);
                }
            }
            TSC(tid == 224, 28);
#pragma unroll
            for (int j = 16; j < 48; j += 2) pk1[j] = pack_here(acc1[2 * j], acc1[2 * j + 1]);
            factors(1);
            uint32_t od = sb + 2 * BOX + wi * 256 + (lane >> 4) * 1024 + (lane & 15) * 16, g1peer = mapa(bars + 8 * B_G1DONE, hp ^ 1);
            uint32_t ha = sb + (warp == 0 ? OFF_HIN : warp <= 4 ? 4 * BOX - 2048 : OFF_X1 + 4 * BOX - 5 * 2048) + warp * 2048 + lane * 16;
            const bool first = warp == 0 && j0 == 0;
            float bias0 = first && u0 ? -INFINITY : 0.f, bias1 = first && u1 ? -INFINITY : 0.f;
            asm volatile("" : "+l"(og), "+r"(mU), "+r"(od), "+r"(ha), "+f"(bias0), "+f"(bias1));
            mbar_wait(bars + 8 * B_XT, 0, budget);
            mbar_wait(bars + 8 * (B_WEMPTY + 1), 0, budget);
            wg_wait<0>();
            if (elect) { mbar_arrive(bars + 8 * B_G1DONE); mbar_arrive_at(g1peer); }
            TSC(elect, 2 + 8 * w);
            float ci[4];
#pragma unroll
            for (int n = 0; n < 4; n++) ci[n] = __uint_as_float((0x03800000u + n) | (budget >> 30));
            auto hand_over = [&](int v) {
                asm volatile("{\n.reg .pred p;\nsetp.ne.b32 p, %17, 0;\n"
                             "@p stmatrix.sync.aligned.m8n8.x4.shared.b16 [%16], {%0,%1,%2,%3};\n@p stmatrix.sync.aligned.m8n8.x4.shared.b16 [%16 + 2048], {%4,%5,%6,%7};\n"
                             "@p stmatrix.sync.aligned.m8n8.x4.shared.b16 [%16 + 4096], {%8,%9,%10,%11};\n@p stmatrix.sync.aligned.m8n8.x4.shared.b16 [%16 + 6144], {%12,%13,%14,%15};\n"
                             "fence.proxy.async.shared::cta;\n}"
                             ::"r"(o[0]), "r"(o[1]), "r"(o[2]), "r"(o[3]), "r"(o[4]), "r"(o[5]), "r"(o[6]), "r"(o[7]), "r"(o[8]), "r"(o[9]), "r"(o[10]), "r"(o[11]),
                               "r"(o[12]), "r"(o[13]), "r"(o[14]), "r"(o[15]), "r"(od + v * OFF_X1), "r"((int)(w == rh)) : "memory");
#pragma unroll
                for (int i = 0; i < 16; i++) asm volatile("st.global.u32 [%0], %1;" ::"l"(og + (1 - v) * 16 * BOX + (i >> 1) * 1024 + (i & 1) * 128), "r"(o[i]) : "memory");
                __syncwarp();
                if (lane == 0) mbar_arrive(bars + 8 * (B_STAGED + v));
            };
#pragma unroll
            for (int j = 32; j < 48; j++) pk1[j] = movm(pk1[j]);
#pragma unroll
            for (int j = EARLY_PK; j < 48; j++) if (j >= 32 || (j & 1) || EARLY_PK < 17) pk0[j] = pack_here(acc0[2 * j], acc0[2 * j + 1]);
#pragma unroll
            for (int j = 32; j < 48; j++) pk0[j] = movm(pk0[j]);
            attn_pair<2>(pk1, pk1 + 16, pk1 + 32, pk0 + 17, pk0 + 33, fu[1], fn[1], rk[1], 0.f, 0.f, mU, zero, ci, o);
            hand_over(0);
            TSC(elect, 3 + 8 * w);
#pragma unroll
            for (int j = 0; j < 32; j++) if (j < EARLY_PK || (!(j & 1) && EARLY_PK == 17)) pk0[j] = pack_here(acc0[2 * j], acc0[2 * j + 1]);
            factors(0);
            bar_sync(warp ? warp : 11, 64);
            uint32_t hl[16];
            ldsm4(hl, ha); ldsm4(hl + 4, ha + 512); ldsm4t(hl + 8, ha + 1024); ldsm4t(hl + 12, ha + 1536);
            __syncwarp();
            if (lane == 0) mbar_arrive(bars + 8 * B_FREED);
            attn_pair<1>(pk0, pk0 + 16, pk0 + 32, hl, hl + 8, fu[0], fn[0], rk[0], bias0, bias1, mU, zero, ci, o);
            const float2 s0 = lds2f(sb + OFF_STAT + (8 + r0) * 8), s1 = lds2f(sb + OFF_STAT + (16 + r0) * 8);
            const float m0 = s0.x * s0.y, f0 = 1.f + s0.y, m1 = s1.x * s1.y, f1 = 1.f + s1.y;
            uint32_t xt[32];
#pragma unroll
            for (int j = 0; j < 8; j++) ldsm4(xt + 4 * j, ((ring + wi * 2048 + mad) ^ ((j & 3) * 32)) + (j >> 2) * BOX);
            hand_over(1);
#pragma unroll
            for (int j = 0; j < 32; j++) {
                acc[2 * j] = fmaf(bf_lo(xt[j]), j & 1 ? f1 : f0, j & 1 ? m1 : m0); acc[2 * j + 1] = fmaf(bf_hi(xt[j]), j & 1 ? f1 : f0, j & 1 ? m1 : m0);
            }
        }
        TSC(tid == 0, 4);
        {
            const uint32_t da0 = sd + dlo(w * OFF_X1, 1024), db0 = sd + dlo(OFF_WO, BOX);
            const uint32_t chk = ring + wi * 256 + (lane >> 3) * 1032 + (lane & 7) * 32 + (lane & 4);
            uint32_t s8 = 16, ps8 = 0, ph = 0;
            mbar_wait(ofull + s8, 0, budget);
            mbar_wait(bars + 8 * B_WOFULL + s8, 0, budget);
            TSC(TIMING % 10 == 2 && elect, 32 + w * 16);
            const uint32_t ahi = dhi(128, 0) | (budget >> 30), bhi = dhi(1024, 1) | (budget >> 30);
            const int last = w ? HOLD : 16;
            uint32_t rel = elect ? 0x7fe : 0;
#pragma unroll 1
            for (int i = 1;;) {
                const uint32_t da = da0 + s8 * (BOX >> 7), db = db0 + s8 * (BOX >> 6);
                wg_fence();
#pragma unroll
                for (int kk = 0; kk < 4; kk++) {
                    wgmma_n128<0, 1>(acc, mkdesc(da + kk * 128, ahi), mkdesc(db + kk * 128, bhi), 1);
                    if (kk & 1) wg_commit();
                }
                wg_wait<2>();
                if (rel & 1) { mbar_expect_tx(ofull + ps8, BOX); mbar_arrive_at(oempty + ps8); mbar_arrive(bars + 8 * B_WOEMPTY + ps8); }
                if (i == 16) break;
                rel >>= 1;
                ps8 = s8;
#pragma unroll 1
                do {
                    s8 = s8 == 40 ? 0 : s8 + 8;
                    if (s8 == 16) ph ^= 1;
                    uint32_t bad;
                    asm volatile("{\n.reg .pred p, q, r;\n.reg .u32 u, v;\nmbarrier.try_wait.parity.shared::cta.b64 q, [%2], %3;\nmbarrier.try_wait.parity.shared::cta.b64 p, [%1], %3;\n"
                                 "setp.ne.and.u32 r, %5, 1, p;\nmov.u32 u, 1;\nmov.u32 v, 1;\n@r ld.shared.u32 u, [%4];\n@r ld.shared.u32 v, [%4 + 4096];\n"
                                 "and.pred p, p, q;\nmin.u32 u, u, v;\nsetp.eq.or.u32 p, u, 0, !p;\nvote.sync.any.pred p, p, 0xffffffff;\nselp.u32 %0, 1, 0, p;\n}"
                                 : "=r"(bad) : "r"(ofull + s8), "r"(bars + 8 * B_WOFULL + s8), "r"(ph), "r"(chk + s8 * (BOX / 8)), "r"(i) : "memory");
                    if (__builtin_expect(bad, 0)) {
                        mbar_wait(ofull + s8, ph, budget);
                        mbar_wait(bars + 8 * B_WOFULL + s8, ph, budget);
                        if (__any_sync(0xffffffffu, min(lds1(chk + s8 * (BOX / 8)), lds1(chk + s8 * (BOX / 8) + 4096)) == 0)) {
                            const uint32_t at = wi * 256 + (lane >> 4) * 1024 + (lane & 15) * 16;
                            const uint8_t* src = scr->o + ((size_t)((mt * 2 + rh) * 2 + 1 - w) * 16 + ((2 * p + (i < 2 ? i ^ hp : i)) & 15)) * BOX + at;
#pragma unroll 1
                            for (int n = 0; n < 8192; n += 2048) {
                                uint4 v; int tries = 4096;
#pragma unroll 1
                                do { v = ld_rlx4(src + n); } while (v.x == 0 && --tries > 0);
                                sts4(ring + s8 * (BOX / 8) + at + n, v.x, v.y, v.z, v.w);
                            }
                            NRETRY();
                            fence_async_smem();
                            __syncwarp();
                        }
                    }
                    TSC(TIMING % 10 == 1 && tid == 0, 48 + i);
                    TSC(TIMING % 10 == 2 && elect, 32 + w * 16 + i);
                } while (++i > last && i < 16);
                if (i > last) break;
                wg_wait<1>();
            }
            if (w) {
                bar_sync(9, 256);
#pragma unroll 1
                for (int i = HOLD - 10; i < 6; i++) {
                    wg_fence();
#pragma unroll
                    for (int kk = 0; kk < 4; kk++) wgmma_n128<0, 1>(acc, mkdesc(da0 + i * 512 + kk * 128, ahi), mkdesc(db0 + i * 1024 + kk * 128, bhi), 1);
                    wg_commit();
                }
            } else bar_arrive(9, 256);
            mbar_wait(bars + 8 * B_ZERO, 0, budget);
            const bool add = (__shfl_sync(0xffffffffu, lds1(sb + OFF_SEL), 0) >> (wi * 2 + 1 - w)) & 1;
            wg_wait<0>();
            TSC(elect, 7 + 9 * w);
            const uint32_t os0 = ring + wi * 4096;
#pragma unroll
            for (int hf = 0; hf < OUT_PARTS; hf++) {
#pragma unroll
                for (int j = hf * (8 / OUT_PARTS); j < (hf + 1) * (8 / OUT_PARTS); j++)
                    stsm4(((os0 + mad) ^ ((j & 3) * 32)) + (j >> 2) * 2048, pack_here(acc[8 * j], acc[8 * j + 1]), pack_here(acc[8 * j + 2], acc[8 * j + 3]),
                          pack_here(acc[8 * j + 4], acc[8 * j + 5]), pack_here(acc[8 * j + 6], acc[8 * j + 7]));
                fence_async_smem();
                __syncwarp();
                if (elect_one())
                    asm volatile("{\n.reg .pred p;\nsetp.ne.b32 p, %6, 0;\n@!p cp.async.bulk.tensor.5d.global.shared::cta.bulk_group [%0, {%2, %2, %3, %4, %5}], [%1];\n"
                                 "@p cp.reduce.async.bulk.tensor.5d.global.shared::cta.add.bulk_group [%0, {%2, %2, %3, %4, %5}], [%1];\n}"
                                 ::"l"(&mout), "r"(os0 + hf * 2048), "r"(0), "r"(((j0 + rh * 128) >> 5) + wi), "r"(1 - w), "r"(par * 16 + cb * 2 + hf), "r"((int)add) : "memory");
            }
            asm volatile("cp.async.bulk.commit_group;\ncp.async.bulk.wait_group.read 0;" ::: "memory");
            if (b == 0 && tid == 0) st_rlx(&scr->epoch[0], lds1(sb + OFF_EP));
            TSC(elect, 8 - 2 * w);
            TS_END();
        }
    }
}

typedef CUresult (*EncodeFn)(CUtensorMap*, CUtensorMapDataType, cuuint32_t, void*, const cuuint64_t*, const cuuint64_t*, const cuuint32_t*,
                             const cuuint32_t*, CUtensorMapInterleave, CUtensorMapSwizzle, CUtensorMapL2promotion, CUtensorMapFloatOOBfill);

CUtensorMap make_map(EncodeFn fn, const void* base, int rank, const cuuint64_t* dims, const cuuint64_t* strides, const cuuint32_t* box,
                     CUtensorMapSwizzle swz = CU_TENSOR_MAP_SWIZZLE_128B, CUtensorMapL2promotion pro = CU_TENSOR_MAP_L2_PROMOTION_L2_256B) {
    CUtensorMap m;
    cuuint32_t es[5] = {1, 1, 1, 1, 1};
    fn(&m, CU_TENSOR_MAP_DATA_TYPE_BFLOAT16, rank, (void*)base, dims, strides, box, es, CU_TENSOR_MAP_INTERLEAVE_NONE,
       swz, pro, CU_TENSOR_MAP_FLOAT_OOB_FILL_NONE);
    return m;
}

}

extern "C" void kernel_launch(void* const* d_in, const int* in_sizes, int n_in, void* d_out, int out_size) {
    (void)in_sizes; (void)n_in; (void)out_size;
    const __nv_bfloat16* x = (const __nv_bfloat16*)d_in[0];
    const __nv_bfloat16* wqkv = (const __nv_bfloat16*)d_in[1];
    const __nv_bfloat16* wo = (const __nv_bfloat16*)d_in[2];
    const __nv_bfloat16* wr = (const __nv_bfloat16*)d_in[4];
    const __nv_bfloat16* wg = (const __nv_bfloat16*)d_in[5];
    const __nv_bfloat16* wu = (const __nv_bfloat16*)d_in[6];
    const __nv_bfloat16* wd = (const __nv_bfloat16*)d_in[7];
    static EncodeFn fn = nullptr;
    static Scratch* scr = nullptr;
    if (!fn) {
        void* p = nullptr; cudaDriverEntryPointQueryResult q;
        cudaGetDriverEntryPoint("cuTensorMapEncodeTiled", &p, cudaEnableDefault, &q);
        fn = (EncodeFn)p;
        cudaFuncSetAttribute(fused_kernel, cudaFuncAttributeMaxDynamicSharedMemorySize, SMEM_LAUNCH);
        cudaGetSymbolAddress((void**)&scr, g_scr);
    }
    const cuuint64_t xd[4] = {2048, 16, 32, 2}, xs[4] = {4096, 131072, 65536, 128}, od[5] = {64, 16, 32, 2, 32};
    const cuuint32_t xb[4] = {64, 16, 4, 1}, ob[5] = {64, 16, 1, 1, 2 / OUT_PARTS};
    const cuuint64_t wdm[3] = {1024, 1024, 3}, wst[2] = {6144, 2048};
    const cuuint32_t wb[3] = {64, 64, 3};
    const cuuint64_t wod[3] = {64, 1024, 16}, wdd[3] = {64, 3584, 16}, wos[2] = {2048, 128};
    const cuuint32_t wob[3] = {64, 64, 2}, wdb[3] = {64, 64, 1};
    CUtensorMap mx = make_map(fn, x, 4, xd, xs, xb), mw = make_map(fn, wqkv, 3, wdm, wst, wb);
    CUtensorMap mwo = make_map(fn, wo, 3, wod, wos, wob), mout = make_map(fn, d_out, 5, od, xs, ob);
    const int swap_gu = wu < wg;
    const cuuint64_t gd[3] = {3584, 1024, 2}, gst[2] = {7168, (cuuint64_t)(swap_gu ? (const char*)wg - (const char*)wu : (const char*)wu - (const char*)wg)};
    const cuuint32_t gb[3] = {32, 64, 2};
    CUtensorMap mgu = make_map(fn, swap_gu ? wu : wg, 3, gd, gst, gb, CU_TENSOR_MAP_SWIZZLE_64B, CU_TENSOR_MAP_L2_PROMOTION_L2_128B);
    CUtensorMap mwd = make_map(fn, wd, 3, wdd, wos, wdb, CU_TENSOR_MAP_SWIZZLE_128B, CU_TENSOR_MAP_L2_PROMOTION_L2_128B);
    const cuuint64_t md[2] = {64, 32768}, ms[1] = {128};
    const cuuint32_t mb[2] = {64, 64};
    CUtensorMap mo = make_map(fn, scr, 2, md, ms, mb, CU_TENSOR_MAP_SWIZZLE_NONE, CU_TENSOR_MAP_L2_PROMOTION_NONE);
    const cuuint64_t rd[2] = {1024, 2048};
    const cuuint32_t rb[2] = {256, 16};
    CUtensorMap mr = make_map(fn, x, 2, rd, wos, rb, CU_TENSOR_MAP_SWIZZLE_NONE);
    cudaLaunchConfig_t cfg = {};
    cfg.gridDim = dim3(132); cfg.blockDim = dim3(512); cfg.dynamicSmemBytes = SMEM_LAUNCH; cfg.stream = cudaStreamPerThread;
    cudaLaunchAttribute at[1];
    at[0].id = cudaLaunchAttributeClusterDimension; at[0].val.clusterDim.x = 2; at[0].val.clusterDim.y = 1; at[0].val.clusterDim.z = 1;
    cfg.attrs = at; cfg.numAttrs = 1;
    cudaLaunchKernelEx(&cfg, fused_kernel, mx, mw, mwo, mout, mgu, mwd, mo, mr, x, wr, scr, swap_gu, Weights{(const char*)wqkv, (const char*)wo, (const char*)wg, (const char*)wu, (const char*)wd, (char*)d_out});
}
```

```cpp
#include <cuda_runtime.h>
#include <cuda.h>
#include <cuda_bf16.h>
#include <stdint.h>

namespace {

constexpr int BOX = 8192, W_BYTES = 3 * BOX;
constexpr int OFF_X1 = 6 * BOX, OFF_FR = 12 * BOX, OFF_E = 16 * BOX, OFF_W = 19 * BOX;
constexpr int OFF_WO = OFF_E;
constexpr int OFF_HIN = OFF_FR + 2048, OFF_GU = OFF_HIN + 2048, OFF_FS = OFF_GU + 1024;
constexpr int F_BYTES = 9216;
constexpr int CS_BYTES = 3136;
constexpr int OFF_CS = OFF_FS + 5 * F_BYTES;
constexpr int OFF_STAT = 28 * BOX;
constexpr int OFF_SEL = OFF_STAT + 2112, OFF_EP = OFF_SEL + 4;
constexpr int OFF_BAR = OFF_SEL + 16;
constexpr int B_WFULL = 0, B_XFULL = 3, B_AUX = 15, B_XT = 16, B_ZERO = 17, B_WOFULL = 18, B_OFULL = 24, B_FFULL = 36, B_ROW = 41;
constexpr int B_WEMPTY = 48, B_F1DONE = 51, B_XEMPTY = 52, B_WOEMPTY = 58, B_OEMPTY = 64;
constexpr int B_G1DONE = 72, B_FEMPTY = 73, B_STAGED = 78, B_RDONE = 80, B_FREED = 81, NBAR = 84;
constexpr int SMEM_BYTES = OFF_BAR + NBAR * 8;
static_assert(OFF_FS + 3 * F_BYTES == OFF_E && OFF_CS + CS_BYTES <= OFF_W && SMEM_BYTES + 256 <= 232448 && OFF_BAR % 8 == 0, "smem");
#define POLL_NS 30
#define PF_RATE 10
#define PF_START 7
#define ZF_NS 100
#define FFN2_GATE (B_STAGED + 1)
#define PF_NW 6
#define EARLY_PK 17
#define ZF_GATE (B_ROW + 3)
#define HOLD 12
#define F2_DEPTH 0
#define OUT_PARTS 2
#define PF_D 8
#define NM 3
#define N7 9
#define NR 5
#define PF_DN 8
#define PF_DB 4096
#define PF_REV 0
#define RS_AT 5
#define Y_AT 4
#define ROWS_AT 0x280
constexpr int NH = 56 - 7 * NM - N7;
static_assert(NH >= NR + 12 && NH <= 32 && NR < 6, "FFN2 split");
constexpr int BUDGET = 1 << 18;

struct Scratch {
    uint8_t o[2048 * 1024 * 2];
    uint4 ypart[8][16][128];
    uint32_t halo[128][512];
    uint32_t act[2][14336 + 4096];
    uint2 row[2048];
    uint4 cs[16][3][24];
    uint32_t oflag[16][32];
    uint32_t cnt[10][32];
    uint32_t sel[32], zflag[32], epoch[32];
};
__device__ __align__(1024) Scratch g_scr;
struct Weights { const char *wqkv, *wo, *wg, *wu, *wd; char* out; };

#define TS(i) do {} while (0)
#define TS_END() do {} while (0)
#define TSC(c, i) do {} while (0)
#define NRETRY() do {} while (0)
constexpr int SMEM_LAUNCH = SMEM_BYTES;
__device__ __forceinline__ uint32_t smem_u32(const void* p) { return (uint32_t)__cvta_generic_to_shared(p); }
__device__ __forceinline__ void mbar_init(uint32_t bar, uint32_t cnt) { asm volatile("mbarrier.init.shared::cta.b64 [%0], %1;" ::"r"(bar), "r"(cnt) : "memory"); }
__device__ __forceinline__ void mbar_expect_tx(uint32_t bar, uint32_t bytes) { asm volatile("mbarrier.arrive.expect_tx.shared::cta.b64 _, [%0], %1;" ::"r"(bar), "r"(bytes) : "memory"); }
__device__ __forceinline__ void mbar_arrive(uint32_t bar) { asm volatile("mbarrier.arrive.shared::cta.b64 _, [%0];" ::"r"(bar) : "memory"); }
__device__ __forceinline__ uint32_t mapa(uint32_t a, uint32_t cta) { uint32_t r; asm("mapa.shared::cluster.u32 %0, %1, %2;" : "=r"(r) : "r"(a), "r"(cta)); return r; }
__device__ __forceinline__ void mbar_arrive_at(uint32_t cbar) { asm volatile("mbarrier.arrive.shared::cluster.b64 _, [%0];" ::"r"(cbar) : "memory"); }
__device__ __forceinline__ void mbar_wait(uint32_t bar, uint32_t parity, int& budget) {
    asm volatile("{\n.reg .pred p;\nLAB_WAIT:\nmbarrier.try_wait.parity.shared::cta.b64 p, [%1], %2;\n"
                 "add.s32 %0, %0, -1;\nsetp.gt.and.s32 p, %0, 0, !p;\n@p bra LAB_WAIT;\n}" : "+r"(budget) : "r"(bar), "r"(parity) : "memory");
}
__device__ __forceinline__ void mbar_wait_hot(uint32_t bar, uint32_t parity, int& budget) {
    asm volatile("{\n.reg .pred p;\nmbarrier.try_wait.parity.shared::cta.b64 p, [%1], %2;\n@p bra LAB_DONE;\nLAB_WAIT:\nmbarrier.try_wait.parity.shared::cta.b64 p, [%1], %2;\n"
                 "add.s32 %0, %0, -1;\nsetp.gt.and.s32 p, %0, 0, !p;\n@p bra LAB_WAIT;\nLAB_DONE:\n}" : "+r"(budget) : "r"(bar), "r"(parity) : "memory");
}
__device__ __forceinline__ void tma_2d(uint32_t dst, const CUtensorMap* m, uint32_t bar, int c0, int c1) {
    asm volatile("cp.async.bulk.tensor.2d.shared::cluster.global.mbarrier::complete_tx::bytes [%0], [%1, {%3, %4}], [%2];" ::"r"(dst), "l"(m), "r"(bar), "r"(c0), "r"(c1) : "memory");
}
__device__ __forceinline__ void tma_2d_mc(uint32_t dst, const CUtensorMap* m, uint32_t bar, int c0, int c1) {
    asm volatile("cp.async.bulk.tensor.2d.shared::cluster.global.mbarrier::complete_tx::bytes.multicast::cluster [%0], [%1, {%3, %4}], [%2], %5;" ::"r"(dst), "l"(m), "r"(bar), "r"(c0), "r"(c1), "h"((uint16_t)3) : "memory");
}
__device__ __forceinline__ void tma_3d(uint32_t dst, const CUtensorMap* m, uint32_t bar, int c0, int c1, int c2) {
    asm volatile("cp.async.bulk.tensor.3d.shared::cluster.global.mbarrier::complete_tx::bytes [%0], [%1, {%3, %4, %5}], [%2];" ::"r"(dst), "l"(m), "r"(bar), "r"(c0), "r"(c1), "r"(c2) : "memory");
}
__device__ __forceinline__ void tma_4d(uint32_t dst, const CUtensorMap* m, uint32_t bar, int c0, int c1, int c2, int c3) {
    asm volatile("cp.async.bulk.tensor.4d.shared::cluster.global.mbarrier::complete_tx::bytes [%0], [%1, {%3, %4, %5, %6}], [%2];" ::"r"(dst), "l"(m), "r"(bar), "r"(c0), "r"(c1), "r"(c2), "r"(c3) : "memory");
}
__device__ __forceinline__ void tma_4d_mc(uint32_t dst, const CUtensorMap* m, uint32_t bar, int c0, int c1, int c2, int c3) {
    asm volatile("cp.async.bulk.tensor.4d.shared::cluster.global.mbarrier::complete_tx::bytes.multicast::cluster [%0], [%1, {%3, %4, %5, %6}], [%2], %7;" ::"r"(dst), "l"(m), "r"(bar), "r"(c0), "r"(c1), "r"(c2), "r"(c3), "h"((uint16_t)3) : "memory");
}
__device__ __forceinline__ void bulk_pf(const void* p, uint32_t bytes) { asm volatile("cp.async.bulk.prefetch.L2.global [%0], %1;" ::"l"(p), "r"(bytes) : "memory"); }
__device__ __forceinline__ void bulk_g2s(uint32_t dst, const void* src, uint32_t bytes, uint32_t bar) {
    asm volatile("cp.async.bulk.shared::cluster.global.mbarrier::complete_tx::bytes [%0], [%1], %2, [%3];" ::"r"(dst), "l"(src), "r"(bytes), "r"(bar) : "memory");
}
__device__ __forceinline__ void bulk_s2c(uint32_t cdst, uint32_t src, uint32_t bytes, uint32_t cbar) {
    asm volatile("cp.async.bulk.shared::cluster.shared::cta.mbarrier::complete_tx::bytes [%0], [%1], %2, [%3];" ::"r"(cdst), "r"(src), "r"(bytes), "r"(cbar) : "memory");
}
__device__ __forceinline__ void cluster_wait() { asm volatile("barrier.cluster.wait.aligned;" ::: "memory"); }
__device__ __forceinline__ void fence_gpu() { asm volatile("fence.acq_rel.gpu;" ::: "memory"); }
__device__ __forceinline__ void fence_async_smem() { asm volatile("fence.proxy.async.shared::cta;" ::: "memory"); }
__device__ __forceinline__ void wg_fence() { asm volatile("wgmma.fence.sync.aligned;" ::: "memory"); }
__device__ __forceinline__ void wg_commit() { asm volatile("wgmma.commit_group.sync.aligned;" ::: "memory"); }
template <int N> __device__ __forceinline__ void wg_wait() { asm volatile("wgmma.wait_group.sync.aligned %0;" ::"n"(N) : "memory"); }
__device__ __forceinline__ uint64_t mkdesc(uint32_t lo, uint32_t hi) { return ((uint64_t)hi << 32) | lo; }
__host__ __device__ constexpr uint32_t dhi(uint32_t sbo, uint32_t mode) { return (sbo >> 4) | (mode << 30); }
__host__ __device__ constexpr uint32_t dlo(uint32_t off, uint32_t lbo) { return (off >> 4) + ((lbo >> 4) << 16); }
__device__ __forceinline__ bool elect_one() {
    uint32_t e;
    asm volatile("{\n.reg .pred p;\nelect.sync _|p, 0xffffffff;\nselp.u32 %0, 1, 0, p;\n}" : "=r"(e));
    return e;
}
template <int R> __device__ __forceinline__ void reg_inc() { asm volatile("setmaxnreg.inc.sync.aligned.u32 %0;" ::"n"(R)); }
template <int R> __device__ __forceinline__ void reg_dec() { asm volatile("setmaxnreg.dec.sync.aligned.u32 %0;" ::"n"(R)); }
__device__ __forceinline__ void bar_sync(int id, int n) { asm volatile("bar.sync %0, %1;" ::"r"(id), "r"(n) : "memory"); }
__device__ __forceinline__ void bar_arrive(int id, int n) { asm volatile("bar.arrive %0, %1;" ::"r"(id), "r"(n) : "memory"); }
__device__ __forceinline__ uint32_t pack_bf16(float lo, float hi) { uint32_t r; asm("cvt.rn.bf16x2.f32 %0, %1, %2;" : "=r"(r) : "f"(hi), "f"(lo)); return r; }
__device__ __forceinline__ uint32_t pack_here(float lo, float hi) { uint32_t r; asm volatile("cvt.rn.bf16x2.f32 %0, %1, %2;" : "=r"(r) : "f"(hi), "f"(lo)); return r; }
__device__ __forceinline__ float bf_lo(uint32_t u) { return __uint_as_float(u << 16); }
__device__ __forceinline__ float bf_hi(uint32_t u) { return __uint_as_float(u & 0xffff0000u); }
__device__ __forceinline__ float bf16r(float v) { return bf_lo(pack_bf16(v, 0.f)); }
__device__ __forceinline__ float rcp(float x) { float r; asm("rcp.approx.ftz.f32 %0, %1;" : "=f"(r) : "f"(x)); return r; }
__device__ __forceinline__ float ex2(float x) { float r; asm("ex2.approx.ftz.f32 %0, %1;" : "=f"(r) : "f"(x)); return r; }
__device__ __forceinline__ float sigmoidf(float v) { return rcp(1.f + ex2(v * -1.4426950408889634f)); }
__device__ __forceinline__ uint32_t movm(uint32_t a) { uint32_t d; asm volatile("movmatrix.sync.aligned.m8n8.trans.b16 %0, %1;" : "=r"(d) : "r"(a)); return d; }
__device__ __forceinline__ void mma16816(float (&c)[4], uint32_t a0, uint32_t a1, uint32_t a2, uint32_t a3, uint32_t b0, uint32_t b1) {
    asm volatile("mma.sync.aligned.m16n8k16.row.col.f32.bf16.bf16.f32 {%0,%1,%2,%3}, {%4,%5,%6,%7}, {%8,%9}, {%0,%1,%2,%3};"
                 : "+f"(c[0]), "+f"(c[1]), "+f"(c[2]), "+f"(c[3]) : "r"(a0), "r"(a1), "r"(a2), "r"(a3), "r"(b0), "r"(b1));
}
__device__ __forceinline__ void mma1688(float (&c)[4], uint32_t a0, uint32_t a1, uint32_t b0) {
    asm volatile("mma.sync.aligned.m16n8k8.row.col.f32.bf16.bf16.f32 {%0,%1,%2,%3}, {%4,%5}, {%6}, {%0,%1,%2,%3};"
                 : "+f"(c[0]), "+f"(c[1]), "+f"(c[2]), "+f"(c[3]) : "r"(a0), "r"(a1), "r"(b0));
}
__device__ __forceinline__ void stsm4(uint32_t a, uint32_t r0, uint32_t r1, uint32_t r2, uint32_t r3) {
    asm volatile("stmatrix.sync.aligned.m8n8.x4.shared.b16 [%0], {%1,%2,%3,%4};" ::"r"(a), "r"(r0), "r"(r1), "r"(r2), "r"(r3) : "memory");
}
__device__ __forceinline__ void ldsm4(uint32_t* r, uint32_t a) {
    asm volatile("ldmatrix.sync.aligned.m8n8.x4.shared.b16 {%0,%1,%2,%3}, [%4];" : "=r"(r[0]), "=r"(r[1]), "=r"(r[2]), "=r"(r[3]) : "r"(a) : "memory");
}
__device__ __forceinline__ void ldsm4t(uint32_t* r, uint32_t a) {
    asm volatile("ldmatrix.sync.aligned.m8n8.x4.trans.shared.b16 {%0,%1,%2,%3}, [%4];" : "=r"(r[0]), "=r"(r[1]), "=r"(r[2]), "=r"(r[3]) : "r"(a) : "memory");
}
__device__ __forceinline__ uint32_t ld_rlx(const void* p) { uint32_t v; asm volatile("ld.relaxed.gpu.global.u32 %0, [%1];" : "=r"(v) : "l"(p) : "memory"); return v; }
__device__ __forceinline__ uint32_t ld_acq(const void* p) { uint32_t v; asm volatile("ld.acquire.gpu.global.u32 %0, [%1];" : "=r"(v) : "l"(p) : "memory"); return v; }
__device__ __forceinline__ uint2 ld_rlx2(const void* p) { uint2 v; asm volatile("ld.relaxed.gpu.global.v2.u32 {%0,%1}, [%2];" : "=r"(v.x), "=r"(v.y) : "l"(p) : "memory"); return v; }
__device__ __forceinline__ uint4 ld_rlx4(const void* p) { uint4 v; asm volatile("ld.relaxed.gpu.global.v4.u32 {%0,%1,%2,%3}, [%4];" : "=r"(v.x), "=r"(v.y), "=r"(v.z), "=r"(v.w) : "l"(p) : "memory"); return v; }
__device__ __forceinline__ void st_rlx(void* p, uint32_t v) { asm volatile("st.relaxed.gpu.global.u32 [%0], %1;" ::"l"(p), "r"(v) : "memory"); }
__device__ __forceinline__ void st_rlx2(void* p, uint32_t a, uint32_t b) { asm volatile("st.relaxed.gpu.global.v2.u32 [%0], {%1,%2};" ::"l"(p), "r"(a), "r"(b) : "memory"); }
__device__ __forceinline__ void st_rlx4(void* p, uint32_t a, uint32_t b, uint32_t c, uint32_t d) { asm volatile("st.relaxed.gpu.global.v4.u32 [%0], {%1,%2,%3,%4};" ::"l"(p), "r"(a), "r"(b), "r"(c), "r"(d) : "memory"); }
__device__ __forceinline__ void red_add(uint32_t* p) { asm volatile("red.relaxed.gpu.global.add.u32 [%0], 1;" ::"l"(p) : "memory"); }
__device__ __forceinline__ uint4 ldg_nc(const void* p) { uint4 v; asm volatile("ld.global.nc.v4.u32 {%0,%1,%2,%3}, [%4];" : "=r"(v.x), "=r"(v.y), "=r"(v.z), "=r"(v.w) : "l"(p)); return v; }
__device__ __forceinline__ void sts4(uint32_t a, uint32_t x, uint32_t y, uint32_t z, uint32_t w) { asm volatile("st.shared.v4.u32 [%0], {%1,%2,%3,%4};" ::"r"(a), "r"(x), "r"(y), "r"(z), "r"(w) : "memory"); }
__device__ __forceinline__ void sts2(uint32_t a, uint32_t x, uint32_t y) { asm volatile("st.shared.v2.u32 [%0], {%1,%2};" ::"r"(a), "r"(x), "r"(y) : "memory"); }
__device__ __forceinline__ void sts1(uint32_t a, uint32_t v) { asm volatile("st.shared.u32 [%0], %1;" ::"r"(a), "r"(v) : "memory"); }
__device__ __forceinline__ uint4 lds4(uint32_t a) { uint4 v; asm volatile("ld.shared.v4.u32 {%0,%1,%2,%3}, [%4];" : "=r"(v.x), "=r"(v.y), "=r"(v.z), "=r"(v.w) : "r"(a) : "memory"); return v; }
__device__ __forceinline__ float4 lds4f(uint32_t a) { float4 v; asm volatile("ld.shared.v4.f32 {%0,%1,%2,%3}, [%4];" : "=f"(v.x), "=f"(v.y), "=f"(v.z), "=f"(v.w) : "r"(a) : "memory"); return v; }
__device__ __forceinline__ float2 lds2f(uint32_t a) { float2 v; asm volatile("ld.shared.v2.f32 {%0,%1}, [%2];" : "=f"(v.x), "=f"(v.y) : "r"(a) : "memory"); return v; }
__device__ __forceinline__ float lds1f(uint32_t a) { float v; asm volatile("ld.shared.f32 %0, [%1];" : "=f"(v) : "r"(a) : "memory"); return v; }
__device__ __forceinline__ uint32_t lds1(uint32_t a) { uint32_t v; asm volatile("ld.shared.u32 %0, [%1];" : "=r"(v) : "r"(a) : "memory"); return v; }
__device__ __forceinline__ uint32_t redux_max(uint32_t v) { uint32_t r; asm volatile("redux.sync.max.u32 %0, %1, 0xffffffff;" : "=r"(r) : "r"(v)); return r; }
__device__ __forceinline__ uint32_t poll_all(const uint32_t* p, uint32_t mask, uint32_t want, int& budget) {
    uint32_t v;
#pragma unroll 1
    while (v = ld_acq(p), !__all_sync(0xffffffffu, (v & mask) == want) && --budget > 0) __nanosleep(POLL_NS);
    return v;
}

template <int TA, int TB>
__device__ __forceinline__ void wgmma_n192(float (&d)[96], uint64_t da, uint64_t db, int keep) {
    asm volatile("{\n.reg .pred p;\nsetp.ne.b32 p, %98, 0;\n"
        "wgmma.mma_async.sync.aligned.m64n192k16.f32.bf16.bf16 "
        "{%0, %1, %2, %3, %4, %5, %6, %7, %8, %9, %10, %11, %12, %13, %14, %15, "
        "%16, %17, %18, %19, %20, %21, %22, %23, %24, %25, %26, %27, %28, %29, %30, %31, "
        "%32, %33, %34, %35, %36, %37, %38, %39, %40, %41, %42, %43, %44, %45, %46, %47, "
        "%48, %49, %50, %51, %52, %53, %54, %55, %56, %57, %58, %59, %60, %61, %62, %63, "
        "%64, %65, %66, %67, %68, %69, %70, %71, %72, %73, %74, %75, %76, %77, %78, %79, "
        "%80, %81, %82, %83, %84, %85, %86, %87, %88, %89, %90, %91, %92, %93, %94, %95}, "
        "%96, %97, p, 1, 1, %99, %100;\n}\n"
        : "+f"(d[0]), "+f"(d[1]), "+f"(d[2]), "+f"(d[3]), "+f"(d[4]), "+f"(d[5]), "+f"(d[6]), "+f"(d[7]),
          "+f"(d[8]), "+f"(d[9]), "+f"(d[10]), "+f"(d[11]), "+f"(d[12]), "+f"(d[13]), "+f"(d[14]), "+f"(d[15]),
          "+f"(d[16]), "+f"(d[17]), "+f"(d[18]), "+f"(d[19]), "+f"(d[20]), "+f"(d[21]), "+f"(d[22]), "+f"(d[23]),
          "+f"(d[24]), "+f"(d[25]), "+f"(d[26]), "+f"(d[27]), "+f"(d[28]), "+f"(d[29]), "+f"(d[30]), "+f"(d[31]),
          "+f"(d[32]), "+f"(d[33]), "+f"(d[34]), "+f"(d[35]), "+f"(d[36]), "+f"(d[37]), "+f"(d[38]), "+f"(d[39]),
          "+f"(d[40]), "+f"(d[41]), "+f"(d[42]), "+f"(d[43]), "+f"(d[44]), "+f"(d[45]), "+f"(d[46]), "+f"(d[47]),
          "+f"(d[48]), "+f"(d[49]), "+f"(d[50]), "+f"(d[51]), "+f"(d[52]), "+f"(d[53]), "+f"(d[54]), "+f"(d[55]),
          "+f"(d[56]), "+f"(d[57]), "+f"(d[58]), "+f"(d[59]), "+f"(d[60]), "+f"(d[61]), "+f"(d[62]), "+f"(d[63]),
          "+f"(d[64]), "+f"(d[65]), "+f"(d[66]), "+f"(d[67]), "+f"(d[68]), "+f"(d[69]), "+f"(d[70]), "+f"(d[71]),
          "+f"(d[72]), "+f"(d[73]), "+f"(d[74]), "+f"(d[75]), "+f"(d[76]), "+f"(d[77]), "+f"(d[78]), "+f"(d[79]),
          "+f"(d[80]), "+f"(d[81]), "+f"(d[82]), "+f"(d[83]), "+f"(d[84]), "+f"(d[85]), "+f"(d[86]), "+f"(d[87]),
          "+f"(d[88]), "+f"(d[89]), "+f"(d[90]), "+f"(d[91]), "+f"(d[92]), "+f"(d[93]), "+f"(d[94]), "+f"(d[95])
        : "l"(da), "l"(db), "r"(keep), "n"(TA), "n"(TB));
}
template <int TA, int TB>
__device__ __forceinline__ void wgmma_n128(float (&d)[64], uint64_t da, uint64_t db, int keep) {
    asm volatile("{\n.reg .pred p;\nsetp.ne.b32 p, %66, 0;\n"
        "wgmma.mma_async.sync.aligned.m64n128k16.f32.bf16.bf16 "
        "{%0, %1, %2, %3, %4, %5, %6, %7, %8, %9, %10, %11, %12, %13, %14, %15, "
        "%16, %17, %18, %19, %20, %21, %22, %23, %24, %25, %26, %27, %28, %29, %30, %31, "
        "%32, %33, %34, %35, %36, %37, %38, %39, %40, %41, %42, %43, %44, %45, %46, %47, "
        "%48, %49, %50, %51, %52, %53, %54, %55, %56, %57, %58, %59, %60, %61, %62, %63}, "
        "%64, %65, p, 1, 1, %67, %68;\n}\n"
        : "+f"(d[0]), "+f"(d[1]), "+f"(d[2]), "+f"(d[3]), "+f"(d[4]), "+f"(d[5]), "+f"(d[6]), "+f"(d[7]),
          "+f"(d[8]), "+f"(d[9]), "+f"(d[10]), "+f"(d[11]), "+f"(d[12]), "+f"(d[13]), "+f"(d[14]), "+f"(d[15]),
          "+f"(d[16]), "+f"(d[17]), "+f"(d[18]), "+f"(d[19]), "+f"(d[20]), "+f"(d[21]), "+f"(d[22]), "+f"(d[23]),
          "+f"(d[24]), "+f"(d[25]), "+f"(d[26]), "+f"(d[27]), "+f"(d[28]), "+f"(d[29]), "+f"(d[30]), "+f"(d[31]),
          "+f"(d[32]), "+f"(d[33]), "+f"(d[34]), "+f"(d[35]), "+f"(d[36]), "+f"(d[37]), "+f"(d[38]), "+f"(d[39]),
          "+f"(d[40]), "+f"(d[41]), "+f"(d[42]), "+f"(d[43]), "+f"(d[44]), "+f"(d[45]), "+f"(d[46]), "+f"(d[47]),
          "+f"(d[48]), "+f"(d[49]), "+f"(d[50]), "+f"(d[51]), "+f"(d[52]), "+f"(d[53]), "+f"(d[54]), "+f"(d[55]),
          "+f"(d[56]), "+f"(d[57]), "+f"(d[58]), "+f"(d[59]), "+f"(d[60]), "+f"(d[61]), "+f"(d[62]), "+f"(d[63])
        : "l"(da), "l"(db), "r"(keep), "n"(TA), "n"(TB));
}
template <int TA, int TB>
__device__ __forceinline__ void wgmma_n8(float (&d)[4], uint64_t da, uint64_t db, int keep) {
    asm volatile("{\n.reg .pred p;\nsetp.ne.b32 p, %6, 0;\n"
        "wgmma.mma_async.sync.aligned.m64n8k16.f32.bf16.bf16 "
        "{%0, %1, %2, %3}, "
        "%4, %5, p, 1, 1, %7, %8;\n}\n"
        : "+f"(d[0]), "+f"(d[1]), "+f"(d[2]), "+f"(d[3])
        : "l"(da), "l"(db), "r"(keep), "n"(TA), "n"(TB));
}
__device__ __forceinline__ void wgmma_rs_n192(float (&d)[96], uint32_t a0, uint32_t a1, uint32_t a2, uint32_t a3, uint64_t db) {
    asm volatile("{\n.reg .pred p;\nsetp.ne.b32 p, 1, 0;\n"
        "wgmma.mma_async.sync.aligned.m64n192k16.f32.bf16.bf16 "
        "{%0, %1, %2, %3, %4, %5, %6, %7, %8, %9, %10, %11, %12, %13, %14, %15, "
        "%16, %17, %18, %19, %20, %21, %22, %23, %24, %25, %26, %27, %28, %29, %30, %31, "
        "%32, %33, %34, %35, %36, %37, %38, %39, %40, %41, %42, %43, %44, %45, %46, %47, "
        "%48, %49, %50, %51, %52, %53, %54, %55, %56, %57, %58, %59, %60, %61, %62, %63, "
        "%64, %65, %66, %67, %68, %69, %70, %71, %72, %73, %74, %75, %76, %77, %78, %79, "
        "%80, %81, %82, %83, %84, %85, %86, %87, %88, %89, %90, %91, %92, %93, %94, %95}, "
        "{%96, %97, %98, %99}, %100, p, 1, 1, 1;\n}\n"
        : "+f"(d[0]), "+f"(d[1]), "+f"(d[2]), "+f"(d[3]), "+f"(d[4]), "+f"(d[5]), "+f"(d[6]), "+f"(d[7]),
          "+f"(d[8]), "+f"(d[9]), "+f"(d[10]), "+f"(d[11]), "+f"(d[12]), "+f"(d[13]), "+f"(d[14]), "+f"(d[15]),
          "+f"(d[16]), "+f"(d[17]), "+f"(d[18]), "+f"(d[19]), "+f"(d[20]), "+f"(d[21]), "+f"(d[22]), "+f"(d[23]),
          "+f"(d[24]), "+f"(d[25]), "+f"(d[26]), "+f"(d[27]), "+f"(d[28]), "+f"(d[29]), "+f"(d[30]), "+f"(d[31]),
          "+f"(d[32]), "+f"(d[33]), "+f"(d[34]), "+f"(d[35]), "+f"(d[36]), "+f"(d[37]), "+f"(d[38]), "+f"(d[39]),
          "+f"(d[40]), "+f"(d[41]), "+f"(d[42]), "+f"(d[43]), "+f"(d[44]), "+f"(d[45]), "+f"(d[46]), "+f"(d[47]),
          "+f"(d[48]), "+f"(d[49]), "+f"(d[50]), "+f"(d[51]), "+f"(d[52]), "+f"(d[53]), "+f"(d[54]), "+f"(d[55]),
          "+f"(d[56]), "+f"(d[57]), "+f"(d[58]), "+f"(d[59]), "+f"(d[60]), "+f"(d[61]), "+f"(d[62]), "+f"(d[63]),
          "+f"(d[64]), "+f"(d[65]), "+f"(d[66]), "+f"(d[67]), "+f"(d[68]), "+f"(d[69]), "+f"(d[70]), "+f"(d[71]),
          "+f"(d[72]), "+f"(d[73]), "+f"(d[74]), "+f"(d[75]), "+f"(d[76]), "+f"(d[77]), "+f"(d[78]), "+f"(d[79]),
          "+f"(d[80]), "+f"(d[81]), "+f"(d[82]), "+f"(d[83]), "+f"(d[84]), "+f"(d[85]), "+f"(d[86]), "+f"(d[87]),
          "+f"(d[88]), "+f"(d[89]), "+f"(d[90]), "+f"(d[91]), "+f"(d[92]), "+f"(d[93]), "+f"(d[94]), "+f"(d[95])
        : "r"(a0), "r"(a1), "r"(a2), "r"(a3), "l"(db));
}
__device__ __forceinline__ void wgmma_rs_n8(float (&d)[4], uint32_t a0, uint32_t a1, uint32_t a2, uint32_t a3, uint64_t db) {
    asm volatile("{\n.reg .pred p;\nsetp.ne.b32 p, 1, 0;\n"
        "wgmma.mma_async.sync.aligned.m64n8k16.f32.bf16.bf16 "
        "{%0, %1, %2, %3}, "
        "{%4, %5, %6, %7}, %8, p, 1, 1, 0;\n}\n"
        : "+f"(d[0]), "+f"(d[1]), "+f"(d[2]), "+f"(d[3])
        : "r"(a0), "r"(a1), "r"(a2), "r"(a3), "l"(db));
}

template <int HS>
__device__ __forceinline__ void attn_pair(const uint32_t* q, const uint32_t* k, const uint32_t* v, const uint32_t* kh, const uint32_t* vh,
                                          const float* fu, const float* fn, const float* rk, float bias0, float bias1, uint32_t mU, uint32_t zero, const float* ci, uint32_t* o) {
    float s0[2][4] = {}, s1[2][4] = {}, s2[2][4] = {};
#pragma unroll
    for (int n = 0; n < 4; n++) {
        const int hd = n & 1, a = 8 * hd + 2 * (n & 2);
        mma16816(s1[hd], q[a], q[a + 1], q[a + 2], q[a + 3], k[a], k[a + 2]);
        mma16816(s2[hd], q[a], q[a + 1], q[a + 2], q[a + 3], k[a + 1], k[a + 3]);
    }
#pragma unroll
    for (int n = 0; n < 4; n++) {
        const int hd = n & 1, a = 8 * hd + 2 * (n & 2);
        mma16816(s0[hd], q[a], q[a + 1], q[a + 2], q[a + 3], kh[HS * (a / 2)], kh[HS * (a / 2 + 1)]);
    }
    float e[2][4], m[2][2];
#pragma unroll
    for (int hd = 0; hd < 2; hd++) {
        e[hd][2] = fmaf(s1[hd][2], fu[2], s2[hd][2] * fn[2]); e[hd][3] = fmaf(s1[hd][3], fu[3], s2[hd][3] * fn[3]);
        e[hd][0] = fmaf(s0[hd][0], fu[0], fmaf(s1[hd][0], fn[0], bias0)); e[hd][1] = fmaf(s0[hd][1], fu[1], fmaf(s1[hd][1], fn[1], bias1));
        m[hd][1] = fmaxf(e[hd][2], e[hd][3]); m[hd][0] = fmaxf(e[hd][0], e[hd][1]);
    }
#pragma unroll
    for (int x = 1; x < 3; x++)
#pragma unroll
        for (int n = 0; n < 4; n++) m[n & 1][1 - (n >> 1)] = fmaxf(m[n & 1][1 - (n >> 1)], __shfl_xor_sync(0xffffffffu, m[n & 1][1 - (n >> 1)], x));
#pragma unroll
    for (int hd = 0; hd < 2; hd++) {
#pragma unroll
        for (int n = 0; n < 4; n++) e[hd][n] = ex2(e[hd][n] - m[hd][n >> 1]);
        float sum[4] = {};
        mma1688(sum, pack_bf16(e[hd][0], e[hd][1]), pack_bf16(e[hd][2], e[hd][3]), 0x3f803f80u);
        const float i0 = rcp(sum[0]), i1 = rcp(sum[2]);
        const uint32_t plo = pack_bf16(e[hd][0] * rk[0] * i0, e[hd][1] * rk[1] * i0), phi = pack_bf16(e[hd][2] * rk[2] * i1, e[hd][3] * rk[3] * i1);
        const uint32_t z0 = plo & zero, z1 = phi & zero;
        const uint32_t a0 = plo & ~mU, a1 = phi & mU, a3 = phi & ~mU, b0 = plo & mU;
#pragma unroll
        for (int jj = 0; jj < 4; jj++) {
            float c[4];
            asm volatile("mma.sync.aligned.m16n8k16.row.col.f32.bf16.bf16.f32 {%0,%1,%2,%3}, {%4,%5,%6,%7}, {%8,%9}, {%10,%11,%12,%13};"
                         : "=f"(c[0]), "=f"(c[1]), "=f"(c[2]), "=f"(c[3])
                         : "r"(a0), "r"(a1), "r"(z0), "r"(a3), "r"(v[8 * hd + 2 * jj]), "r"(v[8 * hd + 2 * jj + 1]), "f"(ci[0]), "f"(ci[1]), "f"(ci[2]), "f"(ci[3]));
            mma1688(c, b0, z1, vh[HS * (4 * hd + jj)]);
            o[8 * hd + 2 * jj] = pack_bf16(c[0], c[1]); o[8 * hd + 2 * jj + 1] = pack_bf16(c[2], c[3]);
        }
    }
}

__device__ __forceinline__ uint32_t norm_pair(uint32_t u, float m, float rinv) {
    const uint32_t d = pack_bf16(bf_lo(u) - m, bf_hi(u) - m);
    return max(pack_bf16(bf_lo(d) * rinv, bf_hi(d) * rinv), 1u);
}

__global__ void __launch_bounds__(512, 1)
fused_kernel(const __grid_constant__ CUtensorMap mx, const __grid_constant__ CUtensorMap mw, const __grid_constant__ CUtensorMap mwo,
             const __grid_constant__ CUtensorMap mout, const __grid_constant__ CUtensorMap mgu, const __grid_constant__ CUtensorMap mwd,
             const __grid_constant__ CUtensorMap mo, const __grid_constant__ CUtensorMap mr,
             const __nv_bfloat16* __restrict__ x, const __nv_bfloat16* __restrict__ wr, Scratch* __restrict__ scr, int swap_gu, const Weights pf) {
    extern __shared__ __align__(1024) uint8_t smem[];
    const uint32_t sb = smem_u32(smem);
    const uint32_t bars = sb + OFF_BAR;
    const int tid = threadIdx.x, lane = tid & 31, warp = __shfl_sync(0xffffffffu, tid >> 5, 0);
    const uint32_t sd = (sb & 0x3FFFF) >> 4;
    const int hp = blockIdx.x & 1, cl = blockIdx.x >> 1;
    int pr = cl - 4 + (max(cl - 36, 0) * 37 >> 8);
    asm("{\n.reg .pred p;\nsetp.lt.s32 p, %1, 4;\nselp.s32 %0, %2, %0, p;\n}" : "+r"(pr) : "r"(cl), "r"(39 + 8 * cl));
    const int b = pr * 2 + hp, mt = pr >> 3, p = pr & 7, nt = 2 * p + hp, rh = p & 1, cb = (p & 6) + hp;
    const int par = mt >> 2, j0 = (mt & 3) * 256;
    int budget = BUDGET;

    TSC(tid == 0, 0);
    auto load_w = [&](int k, int s) {
        const uint32_t full = bars + 8 * (B_WFULL + s);
        mbar_expect_tx(full, W_BYTES);
        tma_3d(sb + OFF_W + s * W_BYTES, &mw, full, nt * 64, k * 64, 0);
    };
    auto load_x = [&](int n) {
        const int w = n & 1, j = n < 4 ? (n >> 1) + 4 : (n >> 1) - 2;
        const uint32_t full = bars + 8 * (B_XFULL + w * 6 + 5 - j);
        mbar_expect_tx(full, BOX);
        tma_4d(sb + w * OFF_X1 + j * BOX, &mx, full, par * 1024 + (n >> 2) * 64, 0, (j0 + w * 128) >> 5, (~n >> 1) & 1);
    };
    if (warp < NBAR / 6 && elect_one()) {
        const uint32_t cnt = warp < B_WEMPTY / 6 ? 1 : warp < B_G1DONE / 6 ? 2 : warp < B_STAGED / 6 ? 4 : 8;
#pragma unroll
        for (int i = 0; i < 6; i++) mbar_init(bars + 48 * warp + 8 * i, cnt);
        asm volatile("fence.mbarrier_init.release.cluster;" ::: "memory");
        if (warp == 0 && b < 128) { load_x(0); load_w(0, 2); }
    }
    __syncthreads();

    if (b >= 128) {
        const int hc = b - 128, g = lane >> 2, t = lane & 3;
        const uint32_t ep = ld_rlx(&scr->epoch[0]) + 1;
        if (warp < 12) {
            const int n = warp / 3, part = warp - 3 * n;
            auto load = [&](int k) {
                const uint32_t full = bars + 8 * (2 * n + (k & 1));
                mbar_expect_tx(full, W_BYTES);
                tma_3d(sb + (2 * n + (k & 1)) * W_BYTES, &mw, full, (4 * hc + n) * 64, k * 64, 0);
            };
            if (part == 0 && elect_one()) { load(0); load(1); }
            __syncwarp();
            float c0[4] = {0.f, 0.f, 0.f, 0.f}, c1[4] = {0.f, 0.f, 0.f, 0.f};
            const uint32_t sel = g == 0 ? 0x3f80u : g == 1 ? 0x3f800000u : 0u;
            const uint32_t a = sb + 2 * n * W_BYTES + part * BOX + t * 256 + ((g ^ (2 * t)) << 4);
#pragma unroll 1
            for (int k = 0; k < 16; k++) {
                mbar_wait(bars + 8 * (2 * n + (k & 1)), (k >> 1) & 1, budget);
                uint4 v[8], u[8];
#pragma unroll
                for (int i = 0; i < 8; i++) { v[i] = lds4(a + (k & 1) * W_BYTES + i * 1024); u[i] = lds4(((a + 128) ^ 16) + (k & 1) * W_BYTES + i * 1024); }
                bar_sync(1 + n, 96);
                if (part == k % 3 && k < 14 && elect_one()) load(k + 2);
                __syncwarp();
#pragma unroll
                for (int i = 0; i < 8; i++) { mma16816(c0, v[i].x, v[i].y, u[i].x, u[i].y, sel, sel); mma16816(c1, v[i].z, v[i].w, u[i].z, u[i].w, sel, sel); }
            }
            if (t == 0) {
#pragma unroll
                for (int r = 0; r < 3; r++) {
                    const uint32_t q0 = (pack_bf16(c0[0], c0[1]) & ~1u) | (ep & 1), q1 = pack_bf16(c0[2], c0[3]), q2 = pack_bf16(c1[0], c1[1]), q3 = pack_bf16(c1[2], c1[3]);
                    st_rlx4(&scr->cs[4 * hc + n][r][part * 8 + g], q0, q1, q2, q3);
                    c0[0] -= bf_lo(q0); c0[1] -= bf_hi(q0); c0[2] -= bf_lo(q1); c0[3] -= bf_hi(q1);
                    c1[0] -= bf_lo(q2); c1[1] -= bf_hi(q2); c1[2] -= bf_lo(q3); c1[3] -= bf_hi(q3);
                }
            }
            TSC(tid == 0, 19);
        }
        {
            const int wg = warp >> 2, c2 = 4 * hc + wg, tw = tid & 127;
            const uint32_t ring = sb + wg * 6 * BOX, full = bars + 8 * (8 + wg * 6), ha = sb + 24 * BOX;
            const uint32_t* hsrc = scr->act[ep & 1] + (56 - NH) * 256;
            auto load = [&](int q, int s) { mbar_expect_tx(full + 8 * s, BOX); tma_3d(ring + s * BOX, &mwd, full + 8 * s, 0, (56 - NH + q) * 64, c2); };
            const uint32_t key = poll_all(&scr->sel[lane & 7], 31u, ep & 31, budget);
            __syncthreads();
            TSC(tid == 0, 12);
            if ((warp & 3) == 0 && elect_one()) {
#pragma unroll 1
                for (int q = 0; q < 6; q++) load(q, q);
            }
            __syncwarp();
            const int zr = (2047 - ((__shfl_sync(0xffffffffu, key, warp >> 1) >> 5) & 2047)) & ~30;
#pragma unroll
            for (int i = 0; i < 8; i++) st_rlx4(pf.out + (size_t)(zr + (warp & 1) * 16 + 2 * i) * 2048 + hc * 512 + lane * 16, 0, 0, 0, 0);
            __syncthreads();
            uint32_t wa[NR * 16];
#pragma unroll
            for (int q = 0; q < NR; q++) {
                mbar_wait(full + 8 * q, 0, budget);
#pragma unroll
                for (int j = 0; j < 4; j++) ldsm4t(wa + 16 * q + 4 * j, ring + q * BOX + j * 2048 + (lane >> 4) * 1024 + (lane & 7) * 128 + ((((warp & 3) * 2 + ((lane >> 3) & 1)) ^ (lane & 7)) << 4));
                bar_sync(1 + wg, 128);
                if ((warp & 3) == 0 && elect_one()) load(q + 6, q);
                __syncwarp();
            }
            if (tid == 64) { fence_gpu(); st_rlx(&scr->zflag[hc], ep); }
            if (warp == 1 && elect_one()) {
                int tries = BUDGET;
#pragma unroll 1
                while (ld_rlx(&scr->cnt[8][0]) != ep * (4 * NH) && --tries > 0) {}
                mbar_expect_tx(bars + 8 * 32, NH * 1024);
                bulk_g2s(ha, hsrc, NH * 1024, bars + 8 * 32);
                TS(17);
            }
            __syncwarp();
            mbar_wait(bars + 8 * 32, 0, budget);
#pragma unroll 1
            for (int i = tid; i < NH * 64; i += 512) {
                int tries = BUDGET;
                if (lds1(ha + i * 16) == 0) {
                    uint4 v;
#pragma unroll 1
                    do { v = ld_rlx4(hsrc + i * 4); } while (v.x == 0 && --tries > 0);
                    sts4(ha + i * 16, v.x, v.y, v.z, v.w);
                }
            }
            fence_async_smem();
            __syncthreads();
            TSC(tid == 0, 5);
            float acc[4] = {0.f, 0.f, 0.f, 0.f};
            int left = BUDGET;
            mbar_wait(full + 8 * NR, 0, left);
            const uint32_t da = sd + dlo(wg * 6 * BOX, BOX), db = sd + dlo(24 * BOX, 128), ahi = dhi(1024, 1) | (left >> 30), bhi = dhi(128, 0) | (left >> 30);
            uint4 v[8];
#pragma unroll
            for (int q = NR; q < NH; q++) {
                if (q > NR) mbar_wait(full + 8 * (q % 6), (q / 6) & 1, left);
                TSC(TIMING % 10 == 7 && tid == 0, 32 + q);
                wg_fence();
#pragma unroll
                for (int j = 0; j < 4; j++) wgmma_n8<1, 0>(acc, mkdesc(da + q % 6 * 512 + j * 128, ahi), mkdesc(db + q * 64 + j * 16, bhi), 1);
                wg_commit();
                if (q > NR && q + 5 < NH) {
                    wg_wait<1>();
                    if ((warp & 3) == (q & 3) && elect_one()) load(q + 5, (q - 1) % 6);
                    __syncwarp();
                }
                if (q == NR + RS_AT) {
                    wg_fence();
#pragma unroll
                    for (int j = 0; j < 4 * NR; j++) wgmma_rs_n8(acc, wa[4 * j], wa[4 * j + 1], wa[4 * j + 2], wa[4 * j + 3], mkdesc(db + j * 16, bhi));
                    wg_commit();
                }
                if (q == NH - Y_AT) {
#pragma unroll
                    for (int m = 0; m < 8; m++) v[m] = ld_rlx4(&scr->ypart[m][c2][tw]);
                }
            }
            wg_wait<0>();
            TSC(tid == 0, 18);
#pragma unroll 1
            for (int tries = BUDGET; tries > 0; tries--) {
                uint32_t bad = 0;
#pragma unroll
                for (int m = 0; m < 8; m++) bad |= v[m].x ^ ep;
                if (!(bad & 1)) break;
#pragma unroll
                for (int m = 0; m < 8; m++) if ((v[m].x ^ ep) & 1) v[m] = ld_rlx4(&scr->ypart[m][c2][tw]);
            }
            __syncwarp();
            const float sig = bf16r(sigmoidf(__uint_as_float(((int)key < 0 ? key & 0x7fffffffu : ~key) & 0xffff0000u)));
#pragma unroll
            for (int c = 0; c < 4; c++) {
#pragma unroll
                for (int m = 0; m < 8; m++) acc[c] += __uint_as_float((&v[m].x)[c]);
                acc[c] = bf16r(acc[c]) * __shfl_sync(0xffffffffu, sig, 2 * t + (c & 1));
            }
            char* dst = pf.out + (size_t)(2047 - ((__shfl_sync(0xffffffffu, key, g) >> 5) & 2047)) * 2048 + c2 * 128 + (warp & 3) * 32 + t * 4;
            asm volatile("red.relaxed.gpu.global.add.noftz.bf16x2 [%0], %1;" ::"l"(dst), "r"(movm(pack_bf16(acc[0], acc[1]))) : "memory");
            asm volatile("red.relaxed.gpu.global.add.noftz.bf16x2 [%0], %1;" ::"l"(dst + 16), "r"(movm(pack_bf16(acc[2], acc[3]))) : "memory");
            TSC(tid == 0, 20);
        }
        if (warp < 8) TS_END();
        return;
    }
    asm volatile("barrier.cluster.arrive.relaxed.aligned;" ::: "memory");

    const int c2 = b & 15, n2 = mt < 7 ? NM : N7;
    if (warp >= 12) {
        reg_dec<24>();
        if (warp == 12) {
            if (elect_one()) {
                int c = 0;
#pragma unroll 1
                for (int n = 1; n < 12; n++) {
                    load_x(n);
                    #pragma unroll 1
                    for (; c < (n == 11 ? 4 : __popc(ROWS_AT & ((2 << n) - 1))); c++) { mbar_expect_tx(bars + 8 * (B_ROW + c), BOX); tma_2d(sb + OFF_FR + c * BOX, &mr, bars + 8 * (B_ROW + c), c * 256, b * 16); }
                    if (n == 3 || n == 7) load_w((n + 1) >> 2, n >> 2);
                }
                int s = 2; uint32_t ph = 0;
#pragma unroll 1
                for (int k = 3; k < 16; k++) {
                    mbar_wait(bars + 8 * (B_WEMPTY + s), ph, budget);
                    load_w(k, s);
                    if (++s == 3) s = 0;
                    if (s == 2) ph ^= 1;
                }
                s = 2;
#pragma unroll 1
                for (int i = 0; i < 16; i++) {
                    mbar_wait(bars + 8 * (i < 2 ? B_WEMPTY + i : i < 4 ? B_G1DONE : i < 6 ? B_F1DONE : B_WOEMPTY + s), i >= 12, budget);
                    if (i == 0) {
                        mbar_expect_tx(bars + 8 * B_XT, 4 * BOX);
#pragma unroll 1
                        for (int n = 0; n < 4; n++)
                            tma_4d(sb + (n >> 1) * OFF_X1 + (n & 1) * BOX, &mx, bars + 8 * B_XT, par * 1024 + cb * 128 + (n & 1) * 64, 0, (j0 + rh * 128) >> 5, 1 - (n >> 1));
                    }
                    const uint32_t full = bars + 8 * (B_WOFULL + s);
                    mbar_expect_tx(full, 2 * BOX);
                    tma_3d(sb + OFF_WO + s * 2 * BOX, &mwo, full, 0, ((2 * p + (i < 2 ? i ^ hp : i)) & 15) * 64, cb * 2);
                    TSC(TIMING % 10 == 4, 48 + i);
                    if (++s == 6) s = 0;
                }
            }
        } else {
            bar_sync(8, 224);
            const uint32_t ep = __shfl_sync(0xffffffffu, lds1(sb + OFF_EP), 0);
            if (warp == 13) {
                cluster_wait();
                if (elect_one()) {
                    int j = 4, q = 0, left = BUDGET; uint32_t ph = 0;
#pragma unroll 1
                    for (int n = 6; n < 32; n++) {
                        mbar_wait(bars + 8 * (B_XEMPTY + j), ph, left);
                        tma_4d_mc(sb + hp * OFF_X1 + j * BOX, &mx, bars + 8 * (B_XFULL + hp * 6 + 5 - j), par * 1024 + (n >> 1) * 64, 0, (j0 + hp * 128) >> 5, ~n & 1);
                        if (++j == 6) j = 0;
                        if (j == 4) ph ^= 1;
#pragma unroll 1
                        for (; q < (PF_RATE * (n - PF_START) >> 3) && q < 18 + PF_NW; q++) {
                            const int u = q - PF_NW;
                            if (u < 0) bulk_pf(pf.wqkv + (size_t)(1024 + 128 * u + b) * 6144, 6144);
                            else if (u < 16) bulk_pf((b < 64 ? pf.wg : pf.wu) + (size_t)(u * 64 + (b & 63)) * 7168, 7168);
                            else bulk_pf(pf.wo + (size_t)((u - 16) * 128 + b) * 8192, 8192);
                        }
                    }
                }
                __syncwarp();
                uint32_t* hs = &scr->halo[b - 16][lane * 4];
                uint4 v[4] = {};
                if (j0) {
#pragma unroll 1
                    do {
#pragma unroll
                        for (int c = 0; c < 4; c++) v[c] = ld_rlx4(hs + c * 128);
                    } while (__any_sync(0xffffffffu, min(min(v[0].x, v[1].x), min(v[2].x, v[3].x)) == 0) && --budget > 0);
#pragma unroll
                    for (int c = 0; c < 4; c++) st_rlx(hs + c * 128, 0);
                }
#pragma unroll
                for (int c = 0; c < 4; c++) stsm4(sb + OFF_HIN + c * 512 + lane * 16, v[c].x, v[c].y, v[c].z, v[c].w);
                bar_arrive(11, 64);
                TSC(lane == 0, 31);
                const int src = ((mt * 2 + rh) * 2 + 1 - hp) * 1024;
                if (elect_one()) {
                    const uint32_t* fl = &scr->oflag[mt * 2 + 1 - hp][0];
                    const uint32_t inv = (ep & 1) - 1;
                    uint32_t ready = 0, ph = 0;
                    int s = 4;
#pragma unroll 1
                    for (int i = 2; i < 16; i++) {
                        const int kb = (2 * p + i) & 15;
#pragma unroll 1
                        while (!((ready >> kb) & 1) && --budget > 0) ready = ld_rlx(fl) ^ inv;
                        TSC(i == 2, 30);
                        mbar_wait(bars + 8 * (B_OEMPTY + s), ph, budget);
                        tma_2d_mc(sb + hp * OFF_X1 + s * BOX, &mo, bars + 8 * (B_OFULL + hp * 6 + s), 0, src + kb * 64);
                        TSC(TIMING % 10 == 4 && hp == 0, 32 + i);
                        if (++s == 6) s = 0;
                        if (s == 4) ph ^= 1;
                    }
                }
            } else if (warp == 14) {
                if (elect_one()) {
                    uint32_t s8 = 0, ph = 0;
                    int tries = BUDGET;
                    const uint32_t* act = scr->act[ep & 1];
                    auto counted = [&](int c, uint32_t n) {
#pragma unroll 1
                        while (ld_rlx(&scr->cnt[c][0]) != ep * n && --tries > 0) __nanosleep(POLL_NS);
                    };
                    auto weights = [&](const CUtensorMap* m, int c0, int c1, int c2_) {
                        mbar_wait(bars + 8 * B_FEMPTY + s8, ph, budget);
                        mbar_expect_tx(bars + 8 * B_FFULL + s8, F_BYTES);
                        tma_3d(sb + OFF_FS + s8 * (F_BYTES / 8), m, bars + 8 * B_FFULL + s8, c0, c1, c2_);
                    };
                    if (b < 112) {
                        counted(9, 32);
                        TS(26);
#pragma unroll 1
                        for (int q = 0; q < 16; q++) {
                            weights(&mgu, b * 32, q * 64, 0);
                            bulk_g2s(sb + OFF_FS + BOX + s8 * (F_BYTES / 8), act + 14336 + q * 256, 1024, bars + 8 * B_FFULL + s8);
                            TSC(TIMING % 10 == 5, 32 + q);
                            if (q >= PF_D && q < PF_D + PF_DN) bulk_pf(pf.wd + 7340032 - (size_t)((PF_REV ? q - PF_D + 1 : PF_DN + PF_D - q) * 112 - b) * PF_DB, PF_DB);
                            s8 += 8;
                            if (s8 == 40) { s8 = 0; ph ^= 1; }
                        }
                    }
#pragma unroll 1
                    for (int q = -3; q < n2; q++) {
                        if (q == 0) { counted(mt, 4 * n2); TS(29); }
                        if ((unsigned)q >= 3) weights(&mwd, 0, (mt * NM + (q < 0 ? q + 3 : q)) * 64, c2);
                        if (q >= 0) bulk_g2s(sb + OFF_FS + BOX + s8 * (F_BYTES / 8), act + (mt * NM + q) * 256, 1024, bars + 8 * B_FFULL + s8);
                        TSC(TIMING % 10 == 5, 51 + q);
                        s8 += 8;
                        if (s8 == 24) { s8 = 0; if ((unsigned)q >= 3) ph ^= 1; }
                    }
                }
            } else {
#pragma unroll 1
                for (int i = lane * 16; i < CS_BYTES; i += 512) sts4(sb + OFF_CS + i, 0, 0, 0, 0);
                mbar_wait(bars + 8 * ZF_GATE, 0, budget);
                uint8_t* oz = scr->o + ((size_t)mt * 64 + nt) * BOX + lane * 16;
#pragma unroll 1
                for (int i = 0; i < 16; i++, oz += 512) {
#pragma unroll
                    for (int n = 0; n < 4; n++) st_rlx4(oz + n * 16 * BOX, 0, 0, 0, 0);
                    __nanosleep(ZF_NS);
                }
                __syncwarp();
                TSC(lane == 0, 5);
                fence_gpu();
                TSC(lane == 0, 12);
                mbar_wait(bars + 8 * B_RDONE, 0, budget);
                int tries = BUDGET;
#pragma unroll 1
                for (int i = lane; i < 88; i += 32) {
                    const uint2* rp = &scr->row[2 * (j0 - 8 + i) + par];
                    uint2 v0, v1, v2;
#pragma unroll 1
                    do { v0 = ld_rlx2(rp + (j0 + i < 8 ? 16 : 0)); v1 = ld_rlx2(rp + 176); v2 = ld_rlx2(rp + 352); } while ((((v0.y ^ ep) | (v1.y ^ ep) | (v2.y ^ ep)) & 31) && --tries > 0);
                    sts2(sb + OFF_STAT + i * 8, (v0.x << 16) ^ 0x80000000u, __float_as_uint(rcp(bf_hi(v0.x))));
                    sts2(sb + OFF_STAT + i * 8 + 704, (v1.x << 16) ^ 0x80000000u, __float_as_uint(rcp(bf_hi(v1.x))));
                    sts2(sb + OFF_STAT + i * 8 + 1408, (v2.x << 16) ^ 0x80000000u, __float_as_uint(rcp(bf_hi(v2.x))));
                }
                __syncwarp();
                {
                    const int row = 2047 - ((poll_all(&scr->sel[lane & 7], 31u, ep & 31, budget) >> 5) & 2047), jj = (row >> 1) - j0 - rh * 128;
                    sts1(sb + OFF_SEL, __reduce_or_sync(0xffffffffu, (row & 1) == par && (unsigned)jj < 128 ? 1u << (jj >> 4) : 0u));
                }
                TSC(lane == 0, 14);
                if (lane < 24) {
                    uint4 v[3];
#pragma unroll 1
                    while (v[0] = ld_rlx4(&scr->cs[nt][0][lane]), v[1] = ld_rlx4(&scr->cs[nt][1][lane]), v[2] = ld_rlx4(&scr->cs[nt][2][lane]),
                           (((v[0].x ^ ep) | (v[1].x ^ ep) | (v[2].x ^ ep)) & 1) && --tries > 0) __nanosleep(100);
#pragma unroll
                    for (int r = 0; r < 3; r++) sts4(sb + OFF_CS + 64 + lane * 128 + r * 16, v[r].x, v[r].y, v[r].z, v[r].w);
                }
                fence_async_smem();
                __syncwarp();
                if (elect_one()) {
                    mbar_arrive(bars + 8 * B_AUX);
                    TS(21);
                    mbar_expect_tx(bars + 8 * (B_OFULL + 3), BOX); mbar_expect_tx(bars + 8 * (B_OFULL + 9), BOX);
#pragma unroll 1
                    for (int v = 0; v < 2; v++) {
                        const uint32_t ring = sb + v * OFF_X1 + 2 * BOX, fb = bars + 8 * (B_OFULL + v * 6 + 2);
                        mbar_wait(bars + 8 * (B_STAGED + v), 0, budget);
                        asm volatile("red.relaxed.gpu.global.xor.b32 [%0], %1;" ::"l"(&scr->oflag[mt * 2 + 1 - v][0]), "r"(1u << nt) : "memory");
                        TS(13 + 2 * v);
                        mbar_arrive(fb);
                        mbar_wait(bars + 8 * B_G1DONE, 0, budget);
                        bulk_s2c(mapa(ring + BOX, hp ^ 1), ring, BOX, mapa(fb + 8, hp ^ 1));
                        if (v == 0) mbar_wait(bars + 8 * B_FREED, 0, budget);
#pragma unroll
                        for (int n = 0; n < 4; n++) {
                            mbar_expect_tx(bars + 8 * (B_OFULL + (n >> 1) * 6 + 4 + (n & 1)) - v * 32, BOX);
                            mbar_arrive_at(mapa(bars + 8 * B_OEMPTY, n >> 1) + (4 + (n & 1)) * 8 - v * 32);
                        }
                    }
                    if (lds1(sb + OFF_SEL)) {
#pragma unroll 1
                        while (ld_acq(&scr->zflag[p >> 1]) != ep && --tries > 0) {}
                        asm volatile("fence.proxy.async.global;" ::: "memory");
                    }
                    mbar_arrive(bars + 8 * B_ZERO);
                }
            }
        }
    } else if (warp >= 8) {
        reg_dec<40>();
        const int wq = warp - 8, ta = tid - 256;
        const uint32_t rbuf = sb + OFF_FR + wq * 2048;
        const uint4 wv = ldg_nc(wr + ta * 8);
        if (ta == 0) sts1(sb + OFF_EP, ld_rlx(&scr->epoch[0]) + 1);
        sts4(sb + OFF_STAT + ta * 16, wv.x, wv.y, wv.z, wv.w);
        bar_sync(8, 224);
        const uint32_t ep = __shfl_sync(0xffffffffu, lds1(sb + OFF_EP), 0);
        {
            const int s = b * 16 + wq * 4 + (lane >> 3);
            if ((lane & 7) == 0) st_rlx2(&scr->row[s], 0, ep - 1);
            float sw = 0.f;
#pragma unroll 1
            for (int i = 0; i < 16; i++) { const uint32_t q = lds1(sb + OFF_STAT + i * 128 + lane * 4); sw += bf_lo(q) + bf_hi(q); }
#pragma unroll 1
            for (int o = 16; o > 0; o >>= 1) sw += __shfl_xor_sync(0xffffffffu, sw, o);
            float s1 = 0.f, s2 = 0.f, sr = 0.f;
            {
                float s1b = 0.f, s2b = 0.f, srb = 0.f;
                const uint32_t xb = rbuf + (lane >> 4) * 1024 + (lane & 15) * 16, wb = sb + OFF_STAT + (lane & 15) * 16;
#pragma unroll 1
                for (int i = 0; i < 8; i++) {
                    const uint4 w4 = lds4(wb + i * 256);
                    mbar_wait_hot(bars + 8 * (B_ROW + (i >> 1)), 0, budget);
                    TSC(ta == 0 && i == 0, 17);
                    const uint32_t o = (i >> 1) * BOX + (i & 1) * 256;
                    const uint4 u = lds4(xb + o), v = lds4(xb + o + 512);
#pragma unroll
                    for (int c = 0; c < 4; c++) {
                        const float w0 = bf_lo((&w4.x)[c]), w1 = bf_hi((&w4.x)[c]);
                        const float a0 = bf_lo((&u.x)[c]), a1 = bf_hi((&u.x)[c]), b0 = bf_lo((&v.x)[c]), b1 = bf_hi((&v.x)[c]);
                        s1 += a0; s2 = fmaf(a0, a0, s2); sr = fmaf(a0, w0, sr);
                        s1 += a1; s2 = fmaf(a1, a1, s2); sr = fmaf(a1, w1, sr);
                        s1b += b0; s2b = fmaf(b0, b0, s2b); srb = fmaf(b0, w0, srb);
                        s1b += b1; s2b = fmaf(b1, b1, s2b); srb = fmaf(b1, w1, srb);
                    }
                }
                const bool up = lane & 8;
                s1 = (up ? s1b : s1) + __shfl_xor_sync(0xffffffffu, up ? s1 : s1b, 8);
                s2 = (up ? s2b : s2) + __shfl_xor_sync(0xffffffffu, up ? s2 : s2b, 8);
                sr = (up ? srb : sr) + __shfl_xor_sync(0xffffffffu, up ? sr : srb, 8);
            }
#pragma unroll
            for (int o = 1; o < 8; o <<= 1) {
                s1 += __shfl_xor_sync(0xffffffffu, s1, o); s2 += __shfl_xor_sync(0xffffffffu, s2, o); sr += __shfl_xor_sync(0xffffffffu, sr, o);
            }
            const float mean = s1 * (1.f / 1024.f), mb = bf16r(mean);
            float var = fmaf(-mean, mean, s2 * (1.f / 1024.f));
            sr = fmaf(-mb, sw, sr);
            if (__builtin_expect(__any_sync(0xffffffffu, mean * mean > 256.f * var), 0)) {
                float a2 = 0.f, ar = 0.f;
#pragma unroll 1
                for (int i = 0; i < 64; i++) {
                    const uint32_t o = i * 32 + (lane & 7) * 4, q1 = lds1(rbuf + (lane >> 3) * 512 + (o >> 9) * BOX + (o & 511)), q2 = lds1(sb + OFF_STAT + o);
                    a2 = fmaf(bf_lo(q1) - mean, bf_lo(q1) - mean, fmaf(bf_hi(q1) - mean, bf_hi(q1) - mean, a2));
                    ar = fmaf(bf_lo(q1) - mb, bf_lo(q2), fmaf(bf_hi(q1) - mb, bf_hi(q2), ar));
                }
#pragma unroll 1
                for (int o = 1; o < 8; o <<= 1) { a2 += __shfl_xor_sync(0xffffffffu, a2, o); ar += __shfl_xor_sync(0xffffffffu, ar, o); }
                var = a2 * (1.f / 1024.f); sr = ar;
            }
            float den;
            asm("sqrt.approx.f32 %0, %1;" : "=f"(den) : "f"(bf16r(bf16r(var) + 1e-5f)));
            const uint32_t st = pack_bf16(mb, den);
            const uint32_t rb = pack_bf16(0.f, sr * rcp(bf_hi(st)) + 0.f);
            uint32_t ord = (int)rb < 0 ? ~rb & 0xffff0000u : rb | 0x80000000u;
            if ((rb & 0x7fffffffu) > 0x7f800000u) ord = 0;
            if ((lane & 7) == 0) st_rlx2(&scr->row[s], st, ord | ((2047 - s) << 5) | (ep & 31));
            __syncwarp();
            if (lane < 7) mbar_arrive(bars + 8 * (lane < 5 ? B_FEMPTY + lane : B_RDONE));
        }
        TSC(ta == 0, 18);
        if ((b >> 3) == 14) {
            const uint32_t gm = sb + OFF_E, cnt = gm + 64, res = gm + 80, list = gm + 128;
            uint32_t kv[16];
            int tries = BUDGET;
#pragma unroll 1
            do {
                uint32_t bad = 0;
#pragma unroll
                for (int n = 0; n < 16; n++) kv[n] = ld_rlx(&scr->row[n * 128 + ta].y);
#pragma unroll
                for (int n = 0; n < 16; n++) bad |= kv[n] ^ ep;
                if ((bad & 31) == 0) break;
            } while (--tries > 0);
            __syncwarp();
            TSC(ta == 0, 26);
            uint32_t m = 0;
#pragma unroll
            for (int n = 0; n < 16; n++) m = max(m, kv[n]);
            uint32_t gmax = m;
#pragma unroll
            for (int o = 1; o < 8; o <<= 1) gmax = max(gmax, __shfl_xor_sync(0xffffffffu, gmax, o));
            sts1(gm + (ta >> 3) * 4, gmax);
            sts1(cnt, 0);
            bar_sync(12, 128);
            const uint32_t c = lds1(gm + (lane & 15) * 4);
            int rank = 0;
#pragma unroll
            for (int i = 0; i < 2; i++) { const uint4 q = lds4(gm + (lane >> 4) * 32 + i * 16); rank += (q.x > c) + (q.y > c) + (q.z > c) + (q.w > c); }
            rank += __shfl_xor_sync(0xffffffffu, rank, 16);
            const uint32_t thr = redux_max(rank == 7 ? c : 0u);
#pragma unroll 1
            while (m >= thr) {
                uint32_t at, m2 = 0;
                asm volatile("atom.shared.add.u32 %0, [%1], 1;" : "=r"(at) : "r"(cnt) : "memory");
#pragma unroll
                for (int n = 0; n < 16; n++) m2 = max(m2, kv[n] < m ? kv[n] : 0u);
                sts1(list + at * 4, m);
                if (m2 == 0) break;
                m = m2;
            }
            bar_sync(12, 128);
            const int nc = lds1(cnt);
#pragma unroll 1
            for (int i = ta >> 3; i < ((nc + 3) & ~3); i += 16) {
                const uint32_t ki = lds1(list + i * 4);
                int r = 0;
#pragma unroll 1
                for (int n = lane & 7; n < nc; n += 8) r += lds1(list + n * 4) > ki;
                __syncwarp();
#pragma unroll
                for (int o = 1; o < 8; o <<= 1) r += __shfl_xor_sync(0xffffffffu, r, o);
                if (r == (b & 7) && i < nc) sts1(res, ki);
            }
            bar_sync(12, 128);
            const uint32_t k0 = lds1(res);
            const int r0 = 2047 - ((k0 >> 5) & 2047);
            TSC(ta == 0, 22);
            if (ta == 0) st_rlx(&scr->sel[b & 7], k0);
            const uint4 v0 = ldg_nc(x + (size_t)r0 * 1024 + ta * 8);
            const uint32_t s0 = ld_rlx(&scr->row[r0]);
            const float m0 = bf_lo(s0), i0 = rcp(bf_hi(s0));
            const int ao = 14336 + (ta >> 3) * 256 + (b & 7) * 32 + ((ta ^ b) & 7) * 4;
            st_rlx4(scr->act[ep & 1] + ao, norm_pair(v0.x, m0, i0), norm_pair(v0.y, m0, i0), norm_pair(v0.z, m0, i0), norm_pair(v0.w, m0, i0));
            __syncwarp();
            if (lane == 0) red_add(&scr->cnt[9][tries >> 30]);
            st_rlx4(scr->act[~ep & 1] + ao, 0, 0, 0, 0);
        }
        uint32_t s8 = 0, fph = 0;
        const uint32_t chk = __shfl_sync(0xffffffffu, sb + OFF_FS + BOX + lane * 32 + (lane & 28), lane);
        int left = BUDGET;
        if (b >= 112 && ta < 2) mbar_arrive(bars + 8 * B_F1DONE);
#pragma unroll 1
        for (int ph = b >= 112; ph < 2; ph++) {
            {
                float acc[4] = {0.f, 0.f, 0.f, 0.f};
                const uint32_t alo = sd + (ph ? dlo(OFF_FS, 8192) : dlo(OFF_FS, 4096)), ahi = ph ? dhi(1024, 1) : dhi(512, 2), astep = ph ? 128 : 64;
                const uint32_t bhi = ph ? dhi(128, 0) : dhi(1024, 1), bstep = ph ? 16 : 2, wrap = ph ? 24 : 40;
                uint32_t prev = 0;
                if (ph) mbar_wait(bars + 8 * FFN2_GATE, 0, left);
#pragma unroll 1
                for (int q = ph ? n2 : 16; q > 0; q--) {
                    const uint32_t da = alo + s8 * (F_BYTES >> 7), db = sd + dlo(OFF_FS + BOX, 128) + s8 * (F_BYTES >> 7);
                    mbar_wait_hot(bars + 8 * B_FFULL + s8, fph, left);
                    if (__builtin_expect(__any_sync(0xffffffffu, lds1(chk + s8 * (F_BYTES / 8)) == 0), 0)) {
                        int tries = BUDGET;
#pragma unroll 1
                        for (int n = lane * 4 + (left >> 30); n < 256; n += 128) {
                            uint4 v;
#pragma unroll 1
                            do { v = ld_rlx4(scr->act[ep & 1] + ((ph ? mt * NM + n2 : 72) - q) * 256 + n); } while (v.x == 0 && --tries > 0);
                            __syncwarp();
                            sts4(sb + OFF_FS + BOX + s8 * (F_BYTES / 8) + n * 4, v.x, v.y, v.z, v.w);
                        }
                        NRETRY();
                        fence_async_smem();
                        __syncwarp();
                    }
                    TSC(TIMING % 10 == 3 && ta == 0, 32 + (ph ? 16 + n2 : 16) - q);
                    wg_fence();
#pragma unroll
                    for (int j = 0; j < 4; j++) wgmma_n8<1, 0>(acc, mkdesc(da + j * astep, ahi), mkdesc(db + j * bstep, bhi), 1);
                    wg_commit();
                    wg_wait<1>();
                    if (ph) { wg_wait<0>(); if (lane == 0) prev = bars + 8 * B_FEMPTY + s8; }
                    if (prev) mbar_arrive(prev);
                    if (lane == 0) prev = bars + 8 * B_FEMPTY + s8;
                    s8 += 8;
                    if (s8 == wrap) { s8 = 0; fph ^= 1; }
                }
                wg_wait<0>();
                const int ln = lane + (left >> 30);
                if (ph == 0) {
                    if (prev) mbar_arrive(prev);
                    const bool second = (wq >= 2) != (swap_gu != 0);
                    const uint32_t xa = sb + OFF_GU + ((wq & 1) * 32 + ln) * 16;
                    if (second) sts4(xa, __float_as_uint(acc[0]), __float_as_uint(acc[1]), __float_as_uint(acc[2]), __float_as_uint(acc[3]));
                    bar_sync(12, 128);
                    if (second) { if (ln == 0) mbar_arrive(bars + 8 * B_F1DONE); }
                    else {
                        const float4 up = lds4f(xa);
                        float hv[4];
#pragma unroll
                        for (int c = 0; c < 4; c++) { const float ga = bf16r(acc[c]); hv[c] = bf16r(ga * sigmoidf(ga)) * bf16r((&up.x)[c]); }
                        const int ao = (b * 4 + (wq & 1) * 2) * 32 + ln;
                        st_rlx(scr->act[ep & 1] + ao, max(movm(pack_bf16(hv[0], hv[1])), 1u)); st_rlx(scr->act[ep & 1] + 32 + ao, max(movm(pack_bf16(hv[2], hv[3])), 1u));
                        __syncwarp();
                        if (ln == 0) red_add(&scr->cnt[b < 14 * NM ? b / (2 * NM) : b < 14 * NM + 2 * N7 ? 7 : 8][0]);
                        st_rlx(scr->act[~ep & 1] + ao, 0); st_rlx(scr->act[~ep & 1] + 32 + ao, 0);
                    }
                } else {
                    st_rlx4(&scr->ypart[mt][c2][wq * 32 + ln], (__float_as_uint(acc[0]) & ~1u) | (ep & 1), __float_as_uint(acc[1]), __float_as_uint(acc[2]), __float_as_uint(acc[3]));
                }
                TSC(ta == 0, 22 + ph);
            }
        }
        TSC(ta == 0, 24);
    } else {
        reg_inc<224>();
        const int w = warp >> 2, wi = warp & 3, g = lane >> 2, t = lane & 3;
        const bool elect = (tid & 127) == 0;
        const uint32_t mad = (lane & 15) * 128 + (((lane >> 4) ^ (lane & 7)) << 4);
        float acc[64];
        const uint32_t ring = sb + w * OFF_X1, ofull = bars + 8 * (B_OFULL + w * 6), oempty = mapa(bars + 8 * B_OEMPTY, w);
        const int r0 = rh * 128 + wi * 32 + (1 - w) * 16 + g;
        {
            float acc0[96], acc1[96];
            const uint32_t sta = sb + OFF_STAT + (8 + w * 128 + wi * 32) * 8;
            {
                const uint32_t xfull = bars + 8 * (B_XFULL + w * 6 + 5), xempty = mapa(bars + 8 * B_XEMPTY, w), dx0 = sd + dlo(w * OFF_X1, 16);
                uint32_t s8 = 16, ps8 = 0, ph = 0;
                cluster_wait();
#pragma unroll 1
                for (int k = 0; k < 16; k++) {
                    const uint32_t dx = dx0 + s8 * (2 * BOX >> 7), dw = sd + dlo(OFF_W, BOX) + s8 * (W_BYTES >> 7);
                    mbar_wait(bars + 8 * B_WFULL + s8, ph, budget);
                    mbar_wait(xfull - 2 * s8, ph, budget);
                    TSC(elect && k == 0, 1 + 8 * w);
                    TSC(TIMING % 10 == 1 && tid == 0, 32 + k);
                    wg_wait<0>();
                    wg_fence();
#pragma unroll
                    for (int kk = 0; kk < 4; kk++) wgmma_n192<0, 1>(acc1, mkdesc(dx + kk * 2, dhi(1024, 1)), mkdesc(dw + kk * 128, dhi(1024, 1)), kk ? 1 : k);
                    wg_commit();
                    TSC(TIMING % 10 == 6 && elect, 32 + 16 * w + k);
                    if (elect && k > 0) {
                        mbar_arrive(bars + 8 * B_WEMPTY + ps8);
                        if (k <= 13) { mbar_expect_tx(xfull - 2 * ps8 - 8, BOX); mbar_arrive_at(xempty + 2 * ps8 + 8); }
                    }
                    if (k == 15) {
                        mbar_wait(bars + 8 * B_AUX, 0, budget);
                        const uint32_t zero = budget >> 30, pm = t & 1 ? 0x4432 : 0x3232, ra = sta + ((t >> 1) * 16 + g) * 8;
                        const uint32_t a0 = __byte_perm(lds1(ra), 0, pm), a1 = __byte_perm(lds1(ra + 64), 0, pm), a2 = a0 & zero, a3 = a1 & zero;
                        wg_fence();
                        wgmma_rs_n192(acc1, a0, a1, a2, a3, mkdesc(sd + dlo(OFF_CS, 0), dhi(128, 0)));
                        wgmma_rs_n192(acc0, a0, a1, a2, a3, mkdesc(sd + dlo(OFF_CS + 64, 0), dhi(128, 0)));
                        wg_commit();
                    }
                    mbar_wait(xfull - 2 * s8 - 8, ph, budget);
                    wg_wait<0>();
                    wg_fence();
#pragma unroll
                    for (int kk = 0; kk < 4; kk++) wgmma_n192<0, 1>(acc0, mkdesc(dx + 512 + kk * 2, dhi(1024, 1)), mkdesc(dw + kk * 128, dhi(1024, 1)), kk ? 1 : k);
                    wg_commit();
                    if (elect && k <= 12) { mbar_expect_tx(xfull - 2 * s8, BOX); mbar_arrive_at(xempty + 2 * s8); }
                    ps8 = s8;
                    s8 = s8 == 16 ? 0 : s8 + 8;
                    if (s8 == 16) ph ^= 1;
                }
            }
            const uint32_t zero = budget >> 30;
            const bool u0 = 2 * t > g, u1 = 2 * t + 1 > g;
            uint32_t mU = (u0 ? 0xffffu : 0u) | (u1 ? 0xffff0000u : 0u);
            uint32_t ka0 = sta + (2 * t - (u0 ? 8 : 0)) * 8 + 4, ka1 = sta + (2 * t + 1 - (u1 ? 8 : 0)) * 8 + 4;
            float rk[2][4], fu[2][4], fn[2][4];
            auto factors = [&](int h) {
#pragma unroll
                for (int n = 0; n < 4; n += 2) {
                    const float rq = lds1f(sta + (16 * h + 4 * n + g) * 8 + 4) * (0.17677669529663687f * 1.4426950408889634f);
                    rk[h][n] = lds1f(ka0 + h * 128 + n * 32); rk[h][n + 1] = lds1f(ka1 + h * 128 + n * 32);
                    const float f0 = rq * rk[h][n], f1 = rq * rk[h][n + 1];
                    fu[h][n] = u0 ? f0 : 0.f; fn[h][n] = f0 - fu[h][n]; fu[h][n + 1] = u1 ? f1 : 0.f; fn[h][n + 1] = f1 - fu[h][n + 1];
                }
#pragma unroll
                for (int n = 0; n < 4; n++) asm volatile("" : "+f"(fu[h][n]), "+f"(fn[h][n]));
            };
            uint8_t* og = scr->o + ((size_t)(mt * 4 + w * 2) * 16 + nt) * BOX + wi * 256 + lane * 4;
            TSC(elect, 19 + w);
            uint32_t pk0[48], pk1[48], o[16] = {};
#pragma unroll
            for (int j = 0; j < 48; j++) if (j < 16 || (j & 1)) pk1[j] = pack_here(acc1[2 * j], acc1[2 * j + 1]);
            if (warp < 7) {
#pragma unroll
                for (int c = 0; c < 4; c++) stsm4(ring + 4 * BOX + wi * 2048 + c * 512 + lane * 16, pk1[17 + 8 * c], pk1[19 + 8 * c], pk1[21 + 8 * c], pk1[23 + 8 * c]);
                bar_arrive(1 + warp, 64);
            } else if (j0 != 768) {
#pragma unroll
                for (int c = 0; c < 4; c++) {
                    pk1[17 + 8 * c] = max(pk1[17 + 8 * c], 1u);
                    st_rlx4(&scr->halo[b][c * 128 + lane * 4], pk1[17 + 8 * c], pk1[19 + 8 * c], pk1[21 + 8 * c], pk1[23 + 8 * c]);
                }
            }
            TSC(tid == 224, 28);
#pragma unroll
            for (int j = 16; j < 48; j += 2) pk1[j] = pack_here(acc1[2 * j], acc1[2 * j + 1]);
            factors(1);
            uint32_t od = sb + 2 * BOX + wi * 256 + (lane >> 4) * 1024 + (lane & 15) * 16, g1peer = mapa(bars + 8 * B_G1DONE, hp ^ 1);
            uint32_t ha = sb + (warp == 0 ? OFF_HIN : warp <= 4 ? 4 * BOX - 2048 : OFF_X1 + 4 * BOX - 5 * 2048) + warp * 2048 + lane * 16;
            const bool first = warp == 0 && j0 == 0;
            float bias0 = first && u0 ? -INFINITY : 0.f, bias1 = first && u1 ? -INFINITY : 0.f;
            asm volatile("" : "+l"(og), "+r"(mU), "+r"(od), "+r"(ha), "+f"(bias0), "+f"(bias1));
            mbar_wait(bars + 8 * B_XT, 0, budget);
            mbar_wait(bars + 8 * (B_WEMPTY + 1), 0, budget);
            wg_wait<0>();
            if (elect) { mbar_arrive(bars + 8 * B_G1DONE); mbar_arrive_at(g1peer); }
            TSC(elect, 2 + 8 * w);
            float ci[4];
#pragma unroll
            for (int n = 0; n < 4; n++) ci[n] = __uint_as_float((0x03800000u + n) | (budget >> 30));
            auto hand_over = [&](int v) {
                asm volatile("{\n.reg .pred p;\nsetp.ne.b32 p, %17, 0;\n"
                             "@p stmatrix.sync.aligned.m8n8.x4.shared.b16 [%16], {%0,%1,%2,%3};\n@p stmatrix.sync.aligned.m8n8.x4.shared.b16 [%16 + 2048], {%4,%5,%6,%7};\n"
                             "@p stmatrix.sync.aligned.m8n8.x4.shared.b16 [%16 + 4096], {%8,%9,%10,%11};\n@p stmatrix.sync.aligned.m8n8.x4.shared.b16 [%16 + 6144], {%12,%13,%14,%15};\n"
                             "fence.proxy.async.shared::cta;\n}"
                             ::"r"(o[0]), "r"(o[1]), "r"(o[2]), "r"(o[3]), "r"(o[4]), "r"(o[5]), "r"(o[6]), "r"(o[7]), "r"(o[8]), "r"(o[9]), "r"(o[10]), "r"(o[11]),
                               "r"(o[12]), "r"(o[13]), "r"(o[14]), "r"(o[15]), "r"(od + v * OFF_X1), "r"((int)(w == rh)) : "memory");
#pragma unroll
                for (int i = 0; i < 16; i++) asm volatile("st.global.u32 [%0], %1;" ::"l"(og + (1 - v) * 16 * BOX + (i >> 1) * 1024 + (i & 1) * 128), "r"(o[i]) : "memory");
                __syncwarp();
                if (lane == 0) mbar_arrive(bars + 8 * (B_STAGED + v));
            };
#pragma unroll
            for (int j = 32; j < 48; j++) pk1[j] = movm(pk1[j]);
#pragma unroll
            for (int j = EARLY_PK; j < 48; j++) if (j >= 32 || (j & 1) || EARLY_PK < 17) pk0[j] = pack_here(acc0[2 * j], acc0[2 * j + 1]);
#pragma unroll
            for (int j = 32; j < 48; j++) pk0[j] = movm(pk0[j]);
            attn_pair<2>(pk1, pk1 + 16, pk1 + 32, pk0 + 17, pk0 + 33, fu[1], fn[1], rk[1], 0.f, 0.f, mU, zero, ci, o);
            hand_over(0);
            TSC(elect, 3 + 8 * w);
#pragma unroll
            for (int j = 0; j < 32; j++) if (j < EARLY_PK || (!(j & 1) && EARLY_PK == 17)) pk0[j] = pack_here(acc0[2 * j], acc0[2 * j + 1]);
            factors(0);
            bar_sync(warp ? warp : 11, 64);
            uint32_t hl[16];
            ldsm4(hl, ha); ldsm4(hl + 4, ha + 512); ldsm4t(hl + 8, ha + 1024); ldsm4t(hl + 12, ha + 1536);
            __syncwarp();
            if (lane == 0) mbar_arrive(bars + 8 * B_FREED);
            attn_pair<1>(pk0, pk0 + 16, pk0 + 32, hl, hl + 8, fu[0], fn[0], rk[0], bias0, bias1, mU, zero, ci, o);
            const float2 s0 = lds2f(sb + OFF_STAT + (8 + r0) * 8), s1 = lds2f(sb + OFF_STAT + (16 + r0) * 8);
            const float m0 = s0.x * s0.y, f0 = 1.f + s0.y, m1 = s1.x * s1.y, f1 = 1.f + s1.y;
            uint32_t xt[32];
#pragma unroll
            for (int j = 0; j < 8; j++) ldsm4(xt + 4 * j, ((ring + wi * 2048 + mad) ^ ((j & 3) * 32)) + (j >> 2) * BOX);
            hand_over(1);
#pragma unroll
            for (int j = 0; j < 32; j++) {
                acc[2 * j] = fmaf(bf_lo(xt[j]), j & 1 ? f1 : f0, j & 1 ? m1 : m0); acc[2 * j + 1] = fmaf(bf_hi(xt[j]), j & 1 ? f1 : f0, j & 1 ? m1 : m0);
            }
        }
        TSC(tid == 0, 4);
        {
            const uint32_t da0 = sd + dlo(w * OFF_X1, 1024), db0 = sd + dlo(OFF_WO, BOX);
            const uint32_t chk = ring + wi * 256 + (lane >> 3) * 1032 + (lane & 7) * 32 + (lane & 4);
            uint32_t s8 = 16, ps8 = 0, ph = 0;
            mbar_wait(ofull + s8, 0, budget);
            mbar_wait(bars + 8 * B_WOFULL + s8, 0, budget);
            TSC(TIMING % 10 == 2 && elect, 32 + w * 16);
            const uint32_t ahi = dhi(128, 0) | (budget >> 30), bhi = dhi(1024, 1) | (budget >> 30);
            const int last = w ? HOLD : 16;
            uint32_t rel = elect ? 0x7fe : 0;
#pragma unroll 1
            for (int i = 1;;) {
                const uint32_t da = da0 + s8 * (BOX >> 7), db = db0 + s8 * (BOX >> 6);
                wg_fence();
#pragma unroll
                for (int kk = 0; kk < 4; kk++) {
                    wgmma_n128<0, 1>(acc, mkdesc(da + kk * 128, ahi), mkdesc(db + kk * 128, bhi), 1);
                    if (kk & 1) wg_commit();
                }
                wg_wait<2>();
                if (rel & 1) { mbar_expect_tx(ofull + ps8, BOX); mbar_arrive_at(oempty + ps8); mbar_arrive(bars + 8 * B_WOEMPTY + ps8); }
                if (i == 16) break;
                rel >>= 1;
                ps8 = s8;
#pragma unroll 1
                do {
                    s8 = s8 == 40 ? 0 : s8 + 8;
                    if (s8 == 16) ph ^= 1;
                    uint32_t bad;
                    asm volatile("{\n.reg .pred p, q, r;\n.reg .u32 u, v;\nmbarrier.try_wait.parity.shared::cta.b64 q, [%2], %3;\nmbarrier.try_wait.parity.shared::cta.b64 p, [%1], %3;\n"
                                 "setp.ne.and.u32 r, %5, 1, p;\nmov.u32 u, 1;\nmov.u32 v, 1;\n@r ld.shared.u32 u, [%4];\n@r ld.shared.u32 v, [%4 + 4096];\n"
                                 "and.pred p, p, q;\nmin.u32 u, u, v;\nsetp.eq.or.u32 p, u, 0, !p;\nvote.sync.any.pred p, p, 0xffffffff;\nselp.u32 %0, 1, 0, p;\n}"
                                 : "=r"(bad) : "r"(ofull + s8), "r"(bars + 8 * B_WOFULL + s8), "r"(ph), "r"(chk + s8 * (BOX / 8)), "r"(i) : "memory");
                    if (__builtin_expect(bad, 0)) {
                        mbar_wait(ofull + s8, ph, budget);
                        mbar_wait(bars + 8 * B_WOFULL + s8, ph, budget);
                        if (__any_sync(0xffffffffu, min(lds1(chk + s8 * (BOX / 8)), lds1(chk + s8 * (BOX / 8) + 4096)) == 0)) {
                            const uint32_t at = wi * 256 + (lane >> 4) * 1024 + (lane & 15) * 16;
                            const uint8_t* src = scr->o + ((size_t)((mt * 2 + rh) * 2 + 1 - w) * 16 + ((2 * p + (i < 2 ? i ^ hp : i)) & 15)) * BOX + at;
#pragma unroll 1
                            for (int n = 0; n < 8192; n += 2048) {
                                uint4 v; int tries = 4096;
#pragma unroll 1
                                do { v = ld_rlx4(src + n); } while (v.x == 0 && --tries > 0);
                                sts4(ring + s8 * (BOX / 8) + at + n, v.x, v.y, v.z, v.w);
                            }
                            NRETRY();
                            fence_async_smem();
                            __syncwarp();
                        }
                    }
                    TSC(TIMING % 10 == 1 && tid == 0, 48 + i);
                    TSC(TIMING % 10 == 2 && elect, 32 + w * 16 + i);
                } while (++i > last && i < 16);
                if (i > last) break;
                wg_wait<1>();
            }
            if (w) {
                bar_sync(9, 256);
#pragma unroll 1
                for (int i = HOLD - 10; i < 6; i++) {
                    wg_fence();
#pragma unroll
                    for (int kk = 0; kk < 4; kk++) wgmma_n128<0, 1>(acc, mkdesc(da0 + i * 512 + kk * 128, ahi), mkdesc(db0 + i * 1024 + kk * 128, bhi), 1);
                    wg_commit();
                }
            } else bar_arrive(9, 256);
            mbar_wait(bars + 8 * B_ZERO, 0, budget);
            const bool add = (__shfl_sync(0xffffffffu, lds1(sb + OFF_SEL), 0) >> (wi * 2 + 1 - w)) & 1;
            wg_wait<0>();
            TSC(elect, 7 + 9 * w);
            const uint32_t os0 = ring + wi * 4096;
#pragma unroll
            for (int hf = 0; hf < OUT_PARTS; hf++) {
#pragma unroll
                for (int j = hf * (8 / OUT_PARTS); j < (hf + 1) * (8 / OUT_PARTS); j++)
                    stsm4(((os0 + mad) ^ ((j & 3) * 32)) + (j >> 2) * 2048, pack_here(acc[8 * j], acc[8 * j + 1]), pack_here(acc[8 * j + 2], acc[8 * j + 3]),
                          pack_here(acc[8 * j + 4], acc[8 * j + 5]), pack_here(acc[8 * j + 6], acc[8 * j + 7]));
                fence_async_smem();
                __syncwarp();
                if (elect_one())
                    asm volatile("{\n.reg .pred p;\nsetp.ne.b32 p, %6, 0;\n@!p cp.async.bulk.tensor.5d.global.shared::cta.bulk_group [%0, {%2, %2, %3, %4, %5}], [%1];\n"
                                 "@p cp.reduce.async.bulk.tensor.5d.global.shared::cta.add.bulk_group [%0, {%2, %2, %3, %4, %5}], [%1];\n}"
                                 ::"l"(&mout), "r"(os0 + hf * 2048), "r"(0), "r"(((j0 + rh * 128) >> 5) + wi), "r"(1 - w), "r"(par * 16 + cb * 2 + hf), "r"((int)add) : "memory");
            }
            asm volatile("cp.async.bulk.commit_group;\ncp.async.bulk.wait_group.read 0;" ::: "memory");
            if (b == 0 && tid == 0) st_rlx(&scr->epoch[0], lds1(sb + OFF_EP));
            TSC(elect, 8 - 2 * w);
            TS_END();
        }
    }
}

typedef CUresult (*EncodeFn)(CUtensorMap*, CUtensorMapDataType, cuuint32_t, void*, const cuuint64_t*, const cuuint64_t*, const cuuint32_t*,
                             const cuuint32_t*, CUtensorMapInterleave, CUtensorMapSwizzle, CUtensorMapL2promotion, CUtensorMapFloatOOBfill);

CUtensorMap make_map(EncodeFn fn, const void* base, int rank, const cuuint64_t* dims, const cuuint64_t* strides, const cuuint32_t* box,
                     CUtensorMapSwizzle swz = CU_TENSOR_MAP_SWIZZLE_128B, CUtensorMapL2promotion pro = CU_TENSOR_MAP_L2_PROMOTION_L2_256B) {
    CUtensorMap m;
    cuuint32_t es[5] = {1, 1, 1, 1, 1};
    fn(&m, CU_TENSOR_MAP_DATA_TYPE_BFLOAT16, rank, (void*)base, dims, strides, box, es, CU_TENSOR_MAP_INTERLEAVE_NONE,
       swz, pro, CU_TENSOR_MAP_FLOAT_OOB_FILL_NONE);
    return m;
}

}

extern "C" void kernel_launch(void* const* d_in, const int* in_sizes, int n_in, void* d_out, int out_size) {
    (void)in_sizes; (void)n_in; (void)out_size;
    const __nv_bfloat16* x = (const __nv_bfloat16*)d_in[0];
    const __nv_bfloat16* wqkv = (const __nv_bfloat16*)d_in[1];
    const __nv_bfloat16* wo = (const __nv_bfloat16*)d_in[2];
    const __nv_bfloat16* wr = (const __nv_bfloat16*)d_in[4];
    const __nv_bfloat16* wg = (const __nv_bfloat16*)d_in[5];
    const __nv_bfloat16* wu = (const __nv_bfloat16*)d_in[6];
    const __nv_bfloat16* wd = (const __nv_bfloat16*)d_in[7];
    static EncodeFn fn = nullptr;
    static Scratch* scr = nullptr;
    if (!fn) {
        void* p = nullptr; cudaDriverEntryPointQueryResult q;
        cudaGetDriverEntryPoint("cuTensorMapEncodeTiled", &p, cudaEnableDefault, &q);
        fn = (EncodeFn)p;
        cudaFuncSetAttribute(fused_kernel, cudaFuncAttributeMaxDynamicSharedMemorySize, SMEM_LAUNCH);
        cudaGetSymbolAddress((void**)&scr, g_scr);
    }
    const cuuint64_t xd[4] = {2048, 16, 32, 2}, xs[4] = {4096, 131072, 65536, 128}, od[5] = {64, 16, 32, 2, 32};
    const cuuint32_t xb[4] = {64, 16, 4, 1}, ob[5] = {64, 16, 1, 1, 2 / OUT_PARTS};
    const cuuint64_t wdm[3] = {1024, 1024, 3}, wst[2] = {6144, 2048};
    const cuuint32_t wb[3] = {64, 64, 3};
    const cuuint64_t wod[3] = {64, 1024, 16}, wdd[3] = {64, 3584, 16}, wos[2] = {2048, 128};
    const cuuint32_t wob[3] = {64, 64, 2}, wdb[3] = {64, 64, 1};
    CUtensorMap mx = make_map(fn, x, 4, xd, xs, xb), mw = make_map(fn, wqkv, 3, wdm, wst, wb);
    CUtensorMap mwo = make_map(fn, wo, 3, wod, wos, wob), mout = make_map(fn, d_out, 5, od, xs, ob);
    const int swap_gu = wu < wg;
    const cuuint64_t gd[3] = {3584, 1024, 2}, gst[2] = {7168, (cuuint64_t)(swap_gu ? (const char*)wg - (const char*)wu : (const char*)wu - (const char*)wg)};
    const cuuint32_t gb[3] = {32, 64, 2};
    CUtensorMap mgu = make_map(fn, swap_gu ? wu : wg, 3, gd, gst, gb, CU_TENSOR_MAP_SWIZZLE_64B, CU_TENSOR_MAP_L2_PROMOTION_L2_128B);
    CUtensorMap mwd = make_map(fn, wd, 3, wdd, wos, wdb, CU_TENSOR_MAP_SWIZZLE_128B, CU_TENSOR_MAP_L2_PROMOTION_L2_128B);
    const cuuint64_t md[2] = {64, 32768}, ms[1] = {128};
    const cuuint32_t mb[2] = {64, 64};
    CUtensorMap mo = make_map(fn, scr, 2, md, ms, mb, CU_TENSOR_MAP_SWIZZLE_NONE, CU_TENSOR_MAP_L2_PROMOTION_NONE);
    const cuuint64_t rd[2] = {1024, 2048};
    const cuuint32_t rb[2] = {256, 16};
    CUtensorMap mr = make_map(fn, x, 2, rd, wos, rb, CU_TENSOR_MAP_SWIZZLE_NONE);
    cudaLaunchConfig_t cfg = {};
    cfg.gridDim = dim3(132); cfg.blockDim = dim3(512); cfg.dynamicSmemBytes = SMEM_LAUNCH; cfg.stream = cudaStreamPerThread;
    cudaLaunchAttribute at[1];
    at[0].id = cudaLaunchAttributeClusterDimension; at[0].val.clusterDim.x = 2; at[0].val.clusterDim.y = 1; at[0].val.clusterDim.z = 1;
    cfg.attrs = at; cfg.numAttrs = 1;
    cudaLaunchKernelEx(&cfg, fused_kernel, mx, mw, mwo, mout, mgu, mwd, mo, mr, x, wr, scr, swap_gu, Weights{(const char*)wqkv, (const char*)wo, (const char*)wg, (const char*)wu, (const char*)wd, (char*)d_out});
}
```

```cpp
#include <cuda_runtime.h>
#include <cuda.h>
#include <cuda_bf16.h>
#include <stdint.h>

namespace {

constexpr int BOX = 8192, W_BYTES = 3 * BOX;
constexpr int OFF_X1 = 6 * BOX, OFF_FR = 12 * BOX, OFF_E = 16 * BOX, OFF_W = 19 * BOX;
constexpr int OFF_WO = OFF_E;
constexpr int OFF_HIN = OFF_FR + 2048, OFF_GU = OFF_HIN + 2048, OFF_FS = OFF_GU + 1024;
constexpr int F_BYTES = 9216;
constexpr int CS_BYTES = 3136;
constexpr int OFF_CS = OFF_FS + 5 * F_BYTES;
constexpr int OFF_STAT = 28 * BOX;
constexpr int OFF_SEL = OFF_STAT + 2112, OFF_EP = OFF_SEL + 4;
constexpr int OFF_BAR = OFF_SEL + 16;
constexpr int B_WFULL = 0, B_XFULL = 3, B_AUX = 15, B_XT = 16, B_ZERO = 17, B_WOFULL = 18, B_OFULL = 24, B_FFULL = 36, B_ROW = 41;
constexpr int B_WEMPTY = 48, B_F1DONE = 51, B_XEMPTY = 52, B_WOEMPTY = 58, B_OEMPTY = 64;
constexpr int B_G1DONE = 72, B_FEMPTY = 73, B_STAGED = 78, B_RDONE = 80, B_FREED = 81, NBAR = 84;
constexpr int SMEM_BYTES = OFF_BAR + NBAR * 8;
static_assert(OFF_FS + 3 * F_BYTES == OFF_E && OFF_CS + CS_BYTES <= OFF_W && SMEM_BYTES + 256 <= 232448 && OFF_BAR % 8 == 0, "smem");
#define POLL_NS 30
#define PF_RATE 10
#define PF_START 7
#define ZF_NS 100
#define FFN2_GATE (B_STAGED + 1)
#define PF_NW 6
#define EARLY_PK 17
#define ZF_GATE (B_ROW + 3)
#define HOLD 12
#define F2_DEPTH 0
#define OUT_PARTS 2
#define PF_D 8
#define NM 3
#define N7 9
#define NR 5
#define PF_DN 8
#define PF_DB 4096
#define PF_REV 0
#define RS_AT 5
#define Y_AT 2
#define P_X 0
#define P_W 0
#define P_WO 0
#define P_OUT 0
#define P_GU 2
#define P_WD 2
#define P_O 0
#define P_R 0
#define ROWS_AT 0x280
constexpr int NH = 56 - 7 * NM - N7;
static_assert(NH >= NR + 12 && NH <= 32 && NR < 6, "FFN2 split");
constexpr int BUDGET = 1 << 18;

struct Scratch {
    uint8_t o[2048 * 1024 * 2];
    uint4 ypart[8][16][128];
    uint32_t halo[128][512];
    uint32_t act[2][14336 + 4096];
    uint2 row[2048];
    uint4 cs[16][3][24];
    uint32_t oflag[16][32];
    uint32_t cnt[10][32];
    uint32_t sel[32], zflag[32], epoch[32];
};
__device__ __align__(1024) Scratch g_scr;
struct Weights { const char *wqkv, *wo, *wg, *wu, *wd; char* out; };

#define TS(i) do {} while (0)
#define TS_END() do {} while (0)
#define TSC(c, i) do {} while (0)
#define NRETRY() do {} while (0)
constexpr int SMEM_LAUNCH = SMEM_BYTES;
__device__ __forceinline__ uint32_t smem_u32(const void* p) { return (uint32_t)__cvta_generic_to_shared(p); }
__device__ __forceinline__ void mbar_init(uint32_t bar, uint32_t cnt) { asm volatile("mbarrier.init.shared::cta.b64 [%0], %1;" ::"r"(bar), "r"(cnt) : "memory"); }
__device__ __forceinline__ void mbar_expect_tx(uint32_t bar, uint32_t bytes) { asm volatile("mbarrier.arrive.expect_tx.shared::cta.b64 _, [%0], %1;" ::"r"(bar), "r"(bytes) : "memory"); }
__device__ __forceinline__ void mbar_arrive(uint32_t bar) { asm volatile("mbarrier.arrive.shared::cta.b64 _, [%0];" ::"r"(bar) : "memory"); }
__device__ __forceinline__ uint32_t mapa(uint32_t a, uint32_t cta) { uint32_t r; asm("mapa.shared::cluster.u32 %0, %1, %2;" : "=r"(r) : "r"(a), "r"(cta)); return r; }
__device__ __forceinline__ void mbar_arrive_at(uint32_t cbar) { asm volatile("mbarrier.arrive.shared::cluster.b64 _, [%0];" ::"r"(cbar) : "memory"); }
__device__ __forceinline__ void mbar_wait(uint32_t bar, uint32_t parity, int& budget) {
    asm volatile("{\n.reg .pred p;\nLAB_WAIT:\nmbarrier.try_wait.parity.shared::cta.b64 p, [%1], %2;\n"
                 "add.s32 %0, %0, -1;\nsetp.gt.and.s32 p, %0, 0, !p;\n@p bra LAB_WAIT;\n}" : "+r"(budget) : "r"(bar), "r"(parity) : "memory");
}
__device__ __forceinline__ void mbar_wait_hot(uint32_t bar, uint32_t parity, int& budget) {
    asm volatile("{\n.reg .pred p;\nmbarrier.try_wait.parity.shared::cta.b64 p, [%1], %2;\n@p bra LAB_DONE;\nLAB_WAIT:\nmbarrier.try_wait.parity.shared::cta.b64 p, [%1], %2;\n"
                 "add.s32 %0, %0, -1;\nsetp.gt.and.s32 p, %0, 0, !p;\n@p bra LAB_WAIT;\nLAB_DONE:\n}" : "+r"(budget) : "r"(bar), "r"(parity) : "memory");
}
__device__ __forceinline__ void tma_2d(uint32_t dst, const CUtensorMap* m, uint32_t bar, int c0, int c1) {
    asm volatile("cp.async.bulk.tensor.2d.shared::cluster.global.mbarrier::complete_tx::bytes [%0], [%1, {%3, %4}], [%2];" ::"r"(dst), "l"(m), "r"(bar), "r"(c0), "r"(c1) : "memory");
}
__device__ __forceinline__ void tma_2d_mc(uint32_t dst, const CUtensorMap* m, uint32_t bar, int c0, int c1) {
    asm volatile("cp.async.bulk.tensor.2d.shared::cluster.global.mbarrier::complete_tx::bytes.multicast::cluster [%0], [%1, {%3, %4}], [%2], %5;" ::"r"(dst), "l"(m), "r"(bar), "r"(c0), "r"(c1), "h"((uint16_t)3) : "memory");
}
__device__ __forceinline__ void tma_3d(uint32_t dst, const CUtensorMap* m, uint32_t bar, int c0, int c1, int c2) {
    asm volatile("cp.async.bulk.tensor.3d.shared::cluster.global.mbarrier::complete_tx::bytes [%0], [%1, {%3, %4, %5}], [%2];" ::"r"(dst), "l"(m), "r"(bar), "r"(c0), "r"(c1), "r"(c2) : "memory");
}
__device__ __forceinline__ void tma_4d(uint32_t dst, const CUtensorMap* m, uint32_t bar, int c0, int c1, int c2, int c3) {
    asm volatile("cp.async.bulk.tensor.4d.shared::cluster.global.mbarrier::complete_tx::bytes [%0], [%1, {%3, %4, %5, %6}], [%2];" ::"r"(dst), "l"(m), "r"(bar), "r"(c0), "r"(c1), "r"(c2), "r"(c3) : "memory");
}
__device__ __forceinline__ void tma_4d_mc(uint32_t dst, const CUtensorMap* m, uint32_t bar, int c0, int c1, int c2, int c3) {
    asm volatile("cp.async.bulk.tensor.4d.shared::cluster.global.mbarrier::complete_tx::bytes.multicast::cluster [%0], [%1, {%3, %4, %5, %6}], [%2], %7;" ::"r"(dst), "l"(m), "r"(bar), "r"(c0), "r"(c1), "r"(c2), "r"(c3), "h"((uint16_t)3) : "memory");
}
__device__ __forceinline__ void bulk_pf(const void* p, uint32_t bytes) { asm volatile("cp.async.bulk.prefetch.L2.global [%0], %1;" ::"l"(p), "r"(bytes) : "memory"); }
__device__ __forceinline__ void bulk_g2s(uint32_t dst, const void* src, uint32_t bytes, uint32_t bar) {
    asm volatile("cp.async.bulk.shared::cluster.global.mbarrier::complete_tx::bytes [%0], [%1], %2, [%3];" ::"r"(dst), "l"(src), "r"(bytes), "r"(bar) : "memory");
}
__device__ __forceinline__ void bulk_s2c(uint32_t cdst, uint32_t src, uint32_t bytes, uint32_t cbar) {
    asm volatile("cp.async.bulk.shared::cluster.shared::cta.mbarrier::complete_tx::bytes [%0], [%1], %2, [%3];" ::"r"(cdst), "r"(src), "r"(bytes), "r"(cbar) : "memory");
}
__device__ __forceinline__ void cluster_wait() { asm volatile("barrier.cluster.wait.aligned;" ::: "memory"); }
__device__ __forceinline__ void fence_gpu() { asm volatile("fence.acq_rel.gpu;" ::: "memory"); }
__device__ __forceinline__ void fence_async_smem() { asm volatile("fence.proxy.async.shared::cta;" ::: "memory"); }
__device__ __forceinline__ void wg_fence() { asm volatile("wgmma.fence.sync.aligned;" ::: "memory"); }
__device__ __forceinline__ void wg_commit() { asm volatile("wgmma.commit_group.sync.aligned;" ::: "memory"); }
template <int N> __device__ __forceinline__ void wg_wait() { asm volatile("wgmma.wait_group.sync.aligned %0;" ::"n"(N) : "memory"); }
__device__ __forceinline__ uint64_t mkdesc(uint32_t lo, uint32_t hi) { return ((uint64_t)hi << 32) | lo; }
__host__ __device__ constexpr uint32_t dhi(uint32_t sbo, uint32_t mode) { return (sbo >> 4) | (mode << 30); }
__host__ __device__ constexpr uint32_t dlo(uint32_t off, uint32_t lbo) { return (off >> 4) + ((lbo >> 4) << 16); }
__device__ __forceinline__ bool elect_one() {
    uint32_t e;
    asm volatile("{\n.reg .pred p;\nelect.sync _|p, 0xffffffff;\nselp.u32 %0, 1, 0, p;\n}" : "=r"(e));
    return e;
}
template <int R> __device__ __forceinline__ void reg_inc() { asm volatile("setmaxnreg.inc.sync.aligned.u32 %0;" ::"n"(R)); }
template <int R> __device__ __forceinline__ void reg_dec() { asm volatile("setmaxnreg.dec.sync.aligned.u32 %0;" ::"n"(R)); }
__device__ __forceinline__ void bar_sync(int id, int n) { asm volatile("bar.sync %0, %1;" ::"r"(id), "r"(n) : "memory"); }
__device__ __forceinline__ void bar_arrive(int id, int n) { asm volatile("bar.arrive %0, %1;" ::"r"(id), "r"(n) : "memory"); }
__device__ __forceinline__ uint32_t pack_bf16(float lo, float hi) { uint32_t r; asm("cvt.rn.bf16x2.f32 %0, %1, %2;" : "=r"(r) : "f"(hi), "f"(lo)); return r; }
__device__ __forceinline__ uint32_t pack_here(float lo, float hi) { uint32_t r; asm volatile("cvt.rn.bf16x2.f32 %0, %1, %2;" : "=r"(r) : "f"(hi), "f"(lo)); return r; }
__device__ __forceinline__ float bf_lo(uint32_t u) { return __uint_as_float(u << 16); }
__device__ __forceinline__ float bf_hi(uint32_t u) { return __uint_as_float(u & 0xffff0000u); }
__device__ __forceinline__ float bf16r(float v) { return bf_lo(pack_bf16(v, 0.f)); }
__device__ __forceinline__ float rcp(float x) { float r; asm("rcp.approx.ftz.f32 %0, %1;" : "=f"(r) : "f"(x)); return r; }
__device__ __forceinline__ float ex2(float x) { float r; asm("ex2.approx.ftz.f32 %0, %1;" : "=f"(r) : "f"(x)); return r; }
__device__ __forceinline__ float sigmoidf(float v) { return rcp(1.f + ex2(v * -1.4426950408889634f)); }
__device__ __forceinline__ uint32_t movm(uint32_t a) { uint32_t d; asm volatile("movmatrix.sync.aligned.m8n8.trans.b16 %0, %1;" : "=r"(d) : "r"(a)); return d; }
__device__ __forceinline__ void mma16816(float (&c)[4], uint32_t a0, uint32_t a1, uint32_t a2, uint32_t a3, uint32_t b0, uint32_t b1) {
    asm volatile("mma.sync.aligned.m16n8k16.row.col.f32.bf16.bf16.f32 {%0,%1,%2,%3}, {%4,%5,%6,%7}, {%8,%9}, {%0,%1,%2,%3};"
                 : "+f"(c[0]), "+f"(c[1]), "+f"(c[2]), "+f"(c[3]) : "r"(a0), "r"(a1), "r"(a2), "r"(a3), "r"(b0), "r"(b1));
}
__device__ __forceinline__ void mma1688(float (&c)[4], uint32_t a0, uint32_t a1, uint32_t b0) {
    asm volatile("mma.sync.aligned.m16n8k8.row.col.f32.bf16.bf16.f32 {%0,%1,%2,%3}, {%4,%5}, {%6}, {%0,%1,%2,%3};"
                 : "+f"(c[0]), "+f"(c[1]), "+f"(c[2]), "+f"(c[3]) : "r"(a0), "r"(a1), "r"(b0));
}
__device__ __forceinline__ void stsm4(uint32_t a, uint32_t r0, uint32_t r1, uint32_t r2, uint32_t r3) {
    asm volatile("stmatrix.sync.aligned.m8n8.x4.shared.b16 [%0], {%1,%2,%3,%4};" ::"r"(a), "r"(r0), "r"(r1), "r"(r2), "r"(r3) : "memory");
}
__device__ __forceinline__ void ldsm4(uint32_t* r, uint32_t a) {
    asm volatile("ldmatrix.sync.aligned.m8n8.x4.shared.b16 {%0,%1,%2,%3}, [%4];" : "=r"(r[0]), "=r"(r[1]), "=r"(r[2]), "=r"(r[3]) : "r"(a) : "memory");
}
__device__ __forceinline__ void ldsm4t(uint32_t* r, uint32_t a) {
    asm volatile("ldmatrix.sync.aligned.m8n8.x4.trans.shared.b16 {%0,%1,%2,%3}, [%4];" : "=r"(r[0]), "=r"(r[1]), "=r"(r[2]), "=r"(r[3]) : "r"(a) : "memory");
}
__device__ __forceinline__ uint32_t ld_rlx(const void* p) { uint32_t v; asm volatile("ld.relaxed.gpu.global.u32 %0, [%1];" : "=r"(v) : "l"(p) : "memory"); return v; }
__device__ __forceinline__ uint32_t ld_acq(const void* p) { uint32_t v; asm volatile("ld.acquire.gpu.global.u32 %0, [%1];" : "=r"(v) : "l"(p) : "memory"); return v; }
__device__ __forceinline__ uint2 ld_rlx2(const void* p) { uint2 v; asm volatile("ld.relaxed.gpu.global.v2.u32 {%0,%1}, [%2];" : "=r"(v.x), "=r"(v.y) : "l"(p) : "memory"); return v; }
__device__ __forceinline__ uint4 ld_rlx4(const void* p) { uint4 v; asm volatile("ld.relaxed.gpu.global.v4.u32 {%0,%1,%2,%3}, [%4];" : "=r"(v.x), "=r"(v.y), "=r"(v.z), "=r"(v.w) : "l"(p) : "memory"); return v; }
__device__ __forceinline__ void st_rlx(void* p, uint32_t v) { asm volatile("st.relaxed.gpu.global.u32 [%0], %1;" ::"l"(p), "r"(v) : "memory"); }
__device__ __forceinline__ void st_rlx2(void* p, uint32_t a, uint32_t b) { asm volatile("st.relaxed.gpu.global.v2.u32 [%0], {%1,%2};" ::"l"(p), "r"(a), "r"(b) : "memory"); }
__device__ __forceinline__ void st_rlx4(void* p, uint32_t a, uint32_t b, uint32_t c, uint32_t d) { asm volatile("st.relaxed.gpu.global.v4.u32 [%0], {%1,%2,%3,%4};" ::"l"(p), "r"(a), "r"(b), "r"(c), "r"(d) : "memory"); }
__device__ __forceinline__ void red_add(uint32_t* p) { asm volatile("red.relaxed.gpu.global.add.u32 [%0], 1;" ::"l"(p) : "memory"); }
__device__ __forceinline__ uint4 ldg_nc(const void* p) { uint4 v; asm volatile("ld.global.nc.v4.u32 {%0,%1,%2,%3}, [%4];" : "=r"(v.x), "=r"(v.y), "=r"(v.z), "=r"(v.w) : "l"(p)); return v; }
__device__ __forceinline__ void sts4(uint32_t a, uint32_t x, uint32_t y, uint32_t z, uint32_t w) { asm volatile("st.shared.v4.u32 [%0], {%1,%2,%3,%4};" ::"r"(a), "r"(x), "r"(y), "r"(z), "r"(w) : "memory"); }
__device__ __forceinline__ void sts2(uint32_t a, uint32_t x, uint32_t y) { asm volatile("st.shared.v2.u32 [%0], {%1,%2};" ::"r"(a), "r"(x), "r"(y) : "memory"); }
__device__ __forceinline__ void sts1(uint32_t a, uint32_t v) { asm volatile("st.shared.u32 [%0], %1;" ::"r"(a), "r"(v) : "memory"); }
__device__ __forceinline__ uint4 lds4(uint32_t a) { uint4 v; asm volatile("ld.shared.v4.u32 {%0,%1,%2,%3}, [%4];" : "=r"(v.x), "=r"(v.y), "=r"(v.z), "=r"(v.w) : "r"(a) : "memory"); return v; }
__device__ __forceinline__ float4 lds4f(uint32_t a) { float4 v; asm volatile("ld.shared.v4.f32 {%0,%1,%2,%3}, [%4];" : "=f"(v.x), "=f"(v.y), "=f"(v.z), "=f"(v.w) : "r"(a) : "memory"); return v; }
__device__ __forceinline__ float2 lds2f(uint32_t a) { float2 v; asm volatile("ld.shared.v2.f32 {%0,%1}, [%2];" : "=f"(v.x), "=f"(v.y) : "r"(a) : "memory"); return v; }
__device__ __forceinline__ float lds1f(uint32_t a) { float v; asm volatile("ld.shared.f32 %0, [%1];" : "=f"(v) : "r"(a) : "memory"); return v; }
__device__ __forceinline__ uint32_t lds1(uint32_t a) { uint32_t v; asm volatile("ld.shared.u32 %0, [%1];" : "=r"(v) : "r"(a) : "memory"); return v; }
__device__ __forceinline__ uint32_t redux_max(uint32_t v) { uint32_t r; asm volatile("redux.sync.max.u32 %0, %1, 0xffffffff;" : "=r"(r) : "r"(v)); return r; }
__device__ __forceinline__ uint32_t poll_all(const uint32_t* p, uint32_t mask, uint32_t want, int& budget) {
    uint32_t v;
#pragma unroll 1
    while (v = ld_acq(p), !__all_sync(0xffffffffu, (v & mask) == want) && --budget > 0) __nanosleep(POLL_NS);
    return v;
}

template <int TA, int TB>
__device__ __forceinline__ void wgmma_n192(float (&d)[96], uint64_t da, uint64_t db, int keep) {
    asm volatile("{\n.reg .pred p;\nsetp.ne.b32 p, %98, 0;\n"
        "wgmma.mma_async.sync.aligned.m64n192k16.f32.bf16.bf16 "
        "{%0, %1, %2, %3, %4, %5, %6, %7, %8, %9, %10, %11, %12, %13, %14, %15, "
        "%16, %17, %18, %19, %20, %21, %22, %23, %24, %25, %26, %27, %28, %29, %30, %31, "
        "%32, %33, %34, %35, %36, %37, %38, %39, %40, %41, %42, %43, %44, %45, %46, %47, "
        "%48, %49, %50, %51, %52, %53, %54, %55, %56, %57, %58, %59, %60, %61, %62, %63, "
        "%64, %65, %66, %67, %68, %69, %70, %71, %72, %73, %74, %75, %76, %77, %78, %79, "
        "%80, %81, %82, %83, %84, %85, %86, %87, %88, %89, %90, %91, %92, %93, %94, %95}, "
        "%96, %97, p, 1, 1, %99, %100;\n}\n"
        : "+f"(d[0]), "+f"(d[1]), "+f"(d[2]), "+f"(d[3]), "+f"(d[4]), "+f"(d[5]), "+f"(d[6]), "+f"(d[7]),
          "+f"(d[8]), "+f"(d[9]), "+f"(d[10]), "+f"(d[11]), "+f"(d[12]), "+f"(d[13]), "+f"(d[14]), "+f"(d[15]),
          "+f"(d[16]), "+f"(d[17]), "+f"(d[18]), "+f"(d[19]), "+f"(d[20]), "+f"(d[21]), "+f"(d[22]), "+f"(d[23]),
          "+f"(d[24]), "+f"(d[25]), "+f"(d[26]), "+f"(d[27]), "+f"(d[28]), "+f"(d[29]), "+f"(d[30]), "+f"(d[31]),
          "+f"(d[32]), "+f"(d[33]), "+f"(d[34]), "+f"(d[35]), "+f"(d[36]), "+f"(d[37]), "+f"(d[38]), "+f"(d[39]),
          "+f"(d[40]), "+f"(d[41]), "+f"(d[42]), "+f"(d[43]), "+f"(d[44]), "+f"(d[45]), "+f"(d[46]), "+f"(d[47]),
          "+f"(d[48]), "+f"(d[49]), "+f"(d[50]), "+f"(d[51]), "+f"(d[52]), "+f"(d[53]), "+f"(d[54]), "+f"(d[55]),
          "+f"(d[56]), "+f"(d[57]), "+f"(d[58]), "+f"(d[59]), "+f"(d[60]), "+f"(d[61]), "+f"(d[62]), "+f"(d[63]),
          "+f"(d[64]), "+f"(d[65]), "+f"(d[66]), "+f"(d[67]), "+f"(d[68]), "+f"(d[69]), "+f"(d[70]), "+f"(d[71]),
          "+f"(d[72]), "+f"(d[73]), "+f"(d[74]), "+f"(d[75]), "+f"(d[76]), "+f"(d[77]), "+f"(d[78]), "+f"(d[79]),
          "+f"(d[80]), "+f"(d[81]), "+f"(d[82]), "+f"(d[83]), "+f"(d[84]), "+f"(d[85]), "+f"(d[86]), "+f"(d[87]),
          "+f"(d[88]), "+f"(d[89]), "+f"(d[90]), "+f"(d[91]), "+f"(d[92]), "+f"(d[93]), "+f"(d[94]), "+f"(d[95])
        : "l"(da), "l"(db), "r"(keep), "n"(TA), "n"(TB));
}
template <int TA, int TB>
__device__ __forceinline__ void wgmma_n128(float (&d)[64], uint64_t da, uint64_t db, int keep) {
    asm volatile("{\n.reg .pred p;\nsetp.ne.b32 p, %66, 0;\n"
        "wgmma.mma_async.sync.aligned.m64n128k16.f32.bf16.bf16 "
        "{%0, %1, %2, %3, %4, %5, %6, %7, %8, %9, %10, %11, %12, %13, %14, %15, "
        "%16, %17, %18, %19, %20, %21, %22, %23, %24, %25, %26, %27, %28, %29, %30, %31, "
        "%32, %33, %34, %35, %36, %37, %38, %39, %40, %41, %42, %43, %44, %45, %46, %47, "
        "%48, %49, %50, %51, %52, %53, %54, %55, %56, %57, %58, %59, %60, %61, %62, %63}, "
        "%64, %65, p, 1, 1, %67, %68;\n}\n"
        : "+f"(d[0]), "+f"(d[1]), "+f"(d[2]), "+f"(d[3]), "+f"(d[4]), "+f"(d[5]), "+f"(d[6]), "+f"(d[7]),
          "+f"(d[8]), "+f"(d[9]), "+f"(d[10]), "+f"(d[11]), "+f"(d[12]), "+f"(d[13]), "+f"(d[14]), "+f"(d[15]),
          "+f"(d[16]), "+f"(d[17]), "+f"(d[18]), "+f"(d[19]), "+f"(d[20]), "+f"(d[21]), "+f"(d[22]), "+f"(d[23]),
          "+f"(d[24]), "+f"(d[25]), "+f"(d[26]), "+f"(d[27]), "+f"(d[28]), "+f"(d[29]), "+f"(d[30]), "+f"(d[31]),
          "+f"(d[32]), "+f"(d[33]), "+f"(d[34]), "+f"(d[35]), "+f"(d[36]), "+f"(d[37]), "+f"(d[38]), "+f"(d[39]),
          "+f"(d[40]), "+f"(d[41]), "+f"(d[42]), "+f"(d[43]), "+f"(d[44]), "+f"(d[45]), "+f"(d[46]), "+f"(d[47]),
          "+f"(d[48]), "+f"(d[49]), "+f"(d[50]), "+f"(d[51]), "+f"(d[52]), "+f"(d[53]), "+f"(d[54]), "+f"(d[55]),
          "+f"(d[56]), "+f"(d[57]), "+f"(d[58]), "+f"(d[59]), "+f"(d[60]), "+f"(d[61]), "+f"(d[62]), "+f"(d[63])
        : "l"(da), "l"(db), "r"(keep), "n"(TA), "n"(TB));
}
template <int TA, int TB>
__device__ __forceinline__ void wgmma_n8(float (&d)[4], uint64_t da, uint64_t db, int keep) {
    asm volatile("{\n.reg .pred p;\nsetp.ne.b32 p, %6, 0;\n"
        "wgmma.mma_async.sync.aligned.m64n8k16.f32.bf16.bf16 "
        "{%0, %1, %2, %3}, "
        "%4, %5, p, 1, 1, %7, %8;\n}\n"
        : "+f"(d[0]), "+f"(d[1]), "+f"(d[2]), "+f"(d[3])
        : "l"(da), "l"(db), "r"(keep), "n"(TA), "n"(TB));
}
__device__ __forceinline__ void wgmma_rs_n192(float (&d)[96], uint32_t a0, uint32_t a1, uint32_t a2, uint32_t a3, uint64_t db) {
    asm volatile("{\n.reg .pred p;\nsetp.ne.b32 p, 1, 0;\n"
        "wgmma.mma_async.sync.aligned.m64n192k16.f32.bf16.bf16 "
        "{%0, %1, %2, %3, %4, %5, %6, %7, %8, %9, %10, %11, %12, %13, %14, %15, "
        "%16, %17, %18, %19, %20, %21, %22, %23, %24, %25, %26, %27, %28, %29, %30, %31, "
        "%32, %33, %34, %35, %36, %37, %38, %39, %40, %41, %42, %43, %44, %45, %46, %47, "
        "%48, %49, %50, %51, %52, %53, %54, %55, %56, %57, %58, %59, %60, %61, %62, %63, "
        "%64, %65, %66, %67, %68, %69, %70, %71, %72, %73, %74, %75, %76, %77, %78, %79, "
        "%80, %81, %82, %83, %84, %85, %86, %87, %88, %89, %90, %91, %92, %93, %94, %95}, "
        "{%96, %97, %98, %99}, %100, p, 1, 1, 1;\n}\n"
        : "+f"(d[0]), "+f"(d[1]), "+f"(d[2]), "+f"(d[3]), "+f"(d[4]), "+f"(d[5]), "+f"(d[6]), "+f"(d[7]),
          "+f"(d[8]), "+f"(d[9]), "+f"(d[10]), "+f"(d[11]), "+f"(d[12]), "+f"(d[13]), "+f"(d[14]), "+f"(d[15]),
          "+f"(d[16]), "+f"(d[17]), "+f"(d[18]), "+f"(d[19]), "+f"(d[20]), "+f"(d[21]), "+f"(d[22]), "+f"(d[23]),
          "+f"(d[24]), "+f"(d[25]), "+f"(d[26]), "+f"(d[27]), "+f"(d[28]), "+f"(d[29]), "+f"(d[30]), "+f"(d[31]),
          "+f"(d[32]), "+f"(d[33]), "+f"(d[34]), "+f"(d[35]), "+f"(d[36]), "+f"(d[37]), "+f"(d[38]), "+f"(d[39]),
          "+f"(d[40]), "+f"(d[41]), "+f"(d[42]), "+f"(d[43]), "+f"(d[44]), "+f"(d[45]), "+f"(d[46]), "+f"(d[47]),
          "+f"(d[48]), "+f"(d[49]), "+f"(d[50]), "+f"(d[51]), "+f"(d[52]), "+f"(d[53]), "+f"(d[54]), "+f"(d[55]),
          "+f"(d[56]), "+f"(d[57]), "+f"(d[58]), "+f"(d[59]), "+f"(d[60]), "+f"(d[61]), "+f"(d[62]), "+f"(d[63]),
          "+f"(d[64]), "+f"(d[65]), "+f"(d[66]), "+f"(d[67]), "+f"(d[68]), "+f"(d[69]), "+f"(d[70]), "+f"(d[71]),
          "+f"(d[72]), "+f"(d[73]), "+f"(d[74]), "+f"(d[75]), "+f"(d[76]), "+f"(d[77]), "+f"(d[78]), "+f"(d[79]),
          "+f"(d[80]), "+f"(d[81]), "+f"(d[82]), "+f"(d[83]), "+f"(d[84]), "+f"(d[85]), "+f"(d[86]), "+f"(d[87]),
          "+f"(d[88]), "+f"(d[89]), "+f"(d[90]), "+f"(d[91]), "+f"(d[92]), "+f"(d[93]), "+f"(d[94]), "+f"(d[95])
        : "r"(a0), "r"(a1), "r"(a2), "r"(a3), "l"(db));
}
__device__ __forceinline__ void wgmma_rs_n8(float (&d)[4], uint32_t a0, uint32_t a1, uint32_t a2, uint32_t a3, uint64_t db) {
    asm volatile("{\n.reg .pred p;\nsetp.ne.b32 p, 1, 0;\n"
        "wgmma.mma_async.sync.aligned.m64n8k16.f32.bf16.bf16 "
        "{%0, %1, %2, %3}, "
        "{%4, %5, %6, %7}, %8, p, 1, 1, 0;\n}\n"
        : "+f"(d[0]), "+f"(d[1]), "+f"(d[2]), "+f"(d[3])
        : "r"(a0), "r"(a1), "r"(a2), "r"(a3), "l"(db));
}

template <int HS>
__device__ __forceinline__ void attn_pair(const uint32_t* q, const uint32_t* k, const uint32_t* v, const uint32_t* kh, const uint32_t* vh,
                                          const float* fu, const float* fn, const float* rk, float bias0, float bias1, uint32_t mU, uint32_t zero, const float* ci, uint32_t* o) {
    float s0[2][4] = {}, s1[2][4] = {}, s2[2][4] = {};
#pragma unroll
    for (int n = 0; n < 4; n++) {
        const int hd = n & 1, a = 8 * hd + 2 * (n & 2);
        mma16816(s1[hd], q[a], q[a + 1], q[a + 2], q[a + 3], k[a], k[a + 2]);
        mma16816(s2[hd], q[a], q[a + 1], q[a + 2], q[a + 3], k[a + 1], k[a + 3]);
    }
#pragma unroll
    for (int n = 0; n < 4; n++) {
        const int hd = n & 1, a = 8 * hd + 2 * (n & 2);
        mma16816(s0[hd], q[a], q[a + 1], q[a + 2], q[a + 3], kh[HS * (a / 2)], kh[HS * (a / 2 + 1)]);
    }
    float e[2][4], m[2][2];
#pragma unroll
    for (int hd = 0; hd < 2; hd++) {
        e[hd][2] = fmaf(s1[hd][2], fu[2], s2[hd][2] * fn[2]); e[hd][3] = fmaf(s1[hd][3], fu[3], s2[hd][3] * fn[3]);
        e[hd][0] = fmaf(s0[hd][0], fu[0], fmaf(s1[hd][0], fn[0], bias0)); e[hd][1] = fmaf(s0[hd][1], fu[1], fmaf(s1[hd][1], fn[1], bias1));
        m[hd][1] = fmaxf(e[hd][2], e[hd][3]); m[hd][0] = fmaxf(e[hd][0], e[hd][1]);
    }
#pragma unroll
    for (int x = 1; x < 3; x++)
#pragma unroll
        for (int n = 0; n < 4; n++) m[n & 1][1 - (n >> 1)] = fmaxf(m[n & 1][1 - (n >> 1)], __shfl_xor_sync(0xffffffffu, m[n & 1][1 - (n >> 1)], x));
#pragma unroll
    for (int hd = 0; hd < 2; hd++) {
#pragma unroll
        for (int n = 0; n < 4; n++) e[hd][n] = ex2(e[hd][n] - m[hd][n >> 1]);
        float sum[4] = {};
        mma1688(sum, pack_bf16(e[hd][0], e[hd][1]), pack_bf16(e[hd][2], e[hd][3]), 0x3f803f80u);
        const float i0 = rcp(sum[0]), i1 = rcp(sum[2]);
        const uint32_t plo = pack_bf16(e[hd][0] * rk[0] * i0, e[hd][1] * rk[1] * i0), phi = pack_bf16(e[hd][2] * rk[2] * i1, e[hd][3] * rk[3] * i1);
        const uint32_t z0 = plo & zero, z1 = phi & zero;
        const uint32_t a0 = plo & ~mU, a1 = phi & mU, a3 = phi & ~mU, b0 = plo & mU;
#pragma unroll
        for (int jj = 0; jj < 4; jj++) {
            float c[4];
            asm volatile("mma.sync.aligned.m16n8k16.row.col.f32.bf16.bf16.f32 {%0,%1,%2,%3}, {%4,%5,%6,%7}, {%8,%9}, {%10,%11,%12,%13};"
                         : "=f"(c[0]), "=f"(c[1]), "=f"(c[2]), "=f"(c[3])
                         : "r"(a0), "r"(a1), "r"(z0), "r"(a3), "r"(v[8 * hd + 2 * jj]), "r"(v[8 * hd + 2 * jj + 1]), "f"(ci[0]), "f"(ci[1]), "f"(ci[2]), "f"(ci[3]));
            mma1688(c, b0, z1, vh[HS * (4 * hd + jj)]);
            o[8 * hd + 2 * jj] = pack_bf16(c[0], c[1]); o[8 * hd + 2 * jj + 1] = pack_bf16(c[2], c[3]);
        }
    }
}

__device__ __forceinline__ uint32_t norm_pair(uint32_t u, float m, float rinv) {
    const uint32_t d = pack_bf16(bf_lo(u) - m, bf_hi(u) - m);
    return max(pack_bf16(bf_lo(d) * rinv, bf_hi(d) * rinv), 1u);
}

__global__ void __launch_bounds__(512, 1)
fused_kernel(const __grid_constant__ CUtensorMap mx, const __grid_constant__ CUtensorMap mw, const __grid_constant__ CUtensorMap mwo,
             const __grid_constant__ CUtensorMap mout, const __grid_constant__ CUtensorMap mgu, const __grid_constant__ CUtensorMap mwd,
             const __grid_constant__ CUtensorMap mo, const __grid_constant__ CUtensorMap mr,
             const __nv_bfloat16* __restrict__ x, const __nv_bfloat16* __restrict__ wr, Scratch* __restrict__ scr, int swap_gu, const Weights pf) {
    extern __shared__ __align__(1024) uint8_t smem[];
    const uint32_t sb = smem_u32(smem);
    const uint32_t bars = sb + OFF_BAR;
    const int tid = threadIdx.x, lane = tid & 31, warp = __shfl_sync(0xffffffffu, tid >> 5, 0);
    const uint32_t sd = (sb & 0x3FFFF) >> 4;
    const int hp = blockIdx.x & 1, cl = blockIdx.x >> 1;
    int pr = cl - 4 + (max(cl - 36, 0) * 37 >> 8);
    asm("{\n.reg .pred p;\nsetp.lt.s32 p, %1, 4;\nselp.s32 %0, %2, %0, p;\n}" : "+r"(pr) : "r"(cl), "r"(39 + 8 * cl));
    const int b = pr * 2 + hp, mt = pr >> 3, p = pr & 7, nt = 2 * p + hp, rh = p & 1, cb = (p & 6) + hp;
    const int par = mt >> 2, j0 = (mt & 3) * 256;
    int budget = BUDGET;

    TSC(tid == 0, 0);
    auto load_w = [&](int k, int s) {
        const uint32_t full = bars + 8 * (B_WFULL + s);
        mbar_expect_tx(full, W_BYTES);
        tma_3d(sb + OFF_W + s * W_BYTES, &mw, full, nt * 64, k * 64, 0);
    };
    auto load_x = [&](int n) {
        const int w = n & 1, j = n < 4 ? (n >> 1) + 4 : (n >> 1) - 2;
        const uint32_t full = bars + 8 * (B_XFULL + w * 6 + 5 - j);
        mbar_expect_tx(full, BOX);
        tma_4d(sb + w * OFF_X1 + j * BOX, &mx, full, par * 1024 + (n >> 2) * 64, 0, (j0 + w * 128) >> 5, (~n >> 1) & 1);
    };
    if (warp < NBAR / 6 && elect_one()) {
        const uint32_t cnt = warp < B_WEMPTY / 6 ? 1 : warp < B_G1DONE / 6 ? 2 : warp < B_STAGED / 6 ? 4 : 8;
#pragma unroll
        for (int i = 0; i < 6; i++) mbar_init(bars + 48 * warp + 8 * i, cnt);
        asm volatile("fence.mbarrier_init.release.cluster;" ::: "memory");
        if (warp == 0 && b < 128) { load_x(0); load_w(0, 2); }
    }
    __syncthreads();

    if (b >= 128) {
        const int hc = b - 128, g = lane >> 2, t = lane & 3;
        const uint32_t ep = ld_rlx(&scr->epoch[0]) + 1;
        if (warp < 12) {
            const int n = warp / 3, part = warp - 3 * n;
            auto load = [&](int k) {
                const uint32_t full = bars + 8 * (2 * n + (k & 1));
                mbar_expect_tx(full, W_BYTES);
                tma_3d(sb + (2 * n + (k & 1)) * W_BYTES, &mw, full, (4 * hc + n) * 64, k * 64, 0);
            };
            if (part == 0 && elect_one()) { load(0); load(1); }
            __syncwarp();
            float c0[4] = {0.f, 0.f, 0.f, 0.f}, c1[4] = {0.f, 0.f, 0.f, 0.f};
            const uint32_t sel = g == 0 ? 0x3f80u : g == 1 ? 0x3f800000u : 0u;
            const uint32_t a = sb + 2 * n * W_BYTES + part * BOX + t * 256 + ((g ^ (2 * t)) << 4);
#pragma unroll 1
            for (int k = 0; k < 16; k++) {
                mbar_wait(bars + 8 * (2 * n + (k & 1)), (k >> 1) & 1, budget);
                uint4 v[8], u[8];
#pragma unroll
                for (int i = 0; i < 8; i++) { v[i] = lds4(a + (k & 1) * W_BYTES + i * 1024); u[i] = lds4(((a + 128) ^ 16) + (k & 1) * W_BYTES + i * 1024); }
                bar_sync(1 + n, 96);
                if (part == k % 3 && k < 14 && elect_one()) load(k + 2);
                __syncwarp();
#pragma unroll
                for (int i = 0; i < 8; i++) { mma16816(c0, v[i].x, v[i].y, u[i].x, u[i].y, sel, sel); mma16816(c1, v[i].z, v[i].w, u[i].z, u[i].w, sel, sel); }
            }
            if (t == 0) {
#pragma unroll
                for (int r = 0; r < 3; r++) {
                    const uint32_t q0 = (pack_bf16(c0[0], c0[1]) & ~1u) | (ep & 1), q1 = pack_bf16(c0[2], c0[3]), q2 = pack_bf16(c1[0], c1[1]), q3 = pack_bf16(c1[2], c1[3]);
                    st_rlx4(&scr->cs[4 * hc + n][r][part * 8 + g], q0, q1, q2, q3);
                    c0[0] -= bf_lo(q0); c0[1] -= bf_hi(q0); c0[2] -= bf_lo(q1); c0[3] -= bf_hi(q1);
                    c1[0] -= bf_lo(q2); c1[1] -= bf_hi(q2); c1[2] -= bf_lo(q3); c1[3] -= bf_hi(q3);
                }
            }
            TSC(tid == 0, 19);
        }
        {
            const int wg = warp >> 2, c2 = 4 * hc + wg, tw = tid & 127;
            const uint32_t ring = sb + wg * 6 * BOX, full = bars + 8 * (8 + wg * 6), ha = sb + 24 * BOX;
            const uint32_t* hsrc = scr->act[ep & 1] + (56 - NH) * 256;
            auto load = [&](int q, int s) { mbar_expect_tx(full + 8 * s, BOX); tma_3d(ring + s * BOX, &mwd, full + 8 * s, 0, (56 - NH + q) * 64, c2); };
            const uint32_t key = poll_all(&scr->sel[lane & 7], 31u, ep & 31, budget);
            __syncthreads();
            TSC(tid == 0, 12);
            if ((warp & 3) == 0 && elect_one()) {
#pragma unroll 1
                for (int q = 0; q < 6; q++) load(q, q);
            }
            __syncwarp();
            const int zr = (2047 - ((__shfl_sync(0xffffffffu, key, warp >> 1) >> 5) & 2047)) & ~30;
#pragma unroll
            for (int i = 0; i < 8; i++) st_rlx4(pf.out + (size_t)(zr + (warp & 1) * 16 + 2 * i) * 2048 + hc * 512 + lane * 16, 0, 0, 0, 0);
            __syncthreads();
            uint32_t wa[NR * 16];
#pragma unroll
            for (int q = 0; q < NR; q++) {
                mbar_wait(full + 8 * q, 0, budget);
#pragma unroll
                for (int j = 0; j < 4; j++) ldsm4t(wa + 16 * q + 4 * j, ring + q * BOX + j * 2048 + (lane >> 4) * 1024 + (lane & 7) * 128 + ((((warp & 3) * 2 + ((lane >> 3) & 1)) ^ (lane & 7)) << 4));
                bar_sync(1 + wg, 128);
                if ((warp & 3) == 0 && elect_one()) load(q + 6, q);
                __syncwarp();
            }
            if (tid == 64) { fence_gpu(); st_rlx(&scr->zflag[hc], ep); }
            if (warp == 1 && elect_one()) {
                int tries = BUDGET;
#pragma unroll 1
                while (ld_rlx(&scr->cnt[8][0]) != ep * (4 * NH) && --tries > 0) {}
                mbar_expect_tx(bars + 8 * 32, NH * 1024);
                bulk_g2s(ha, hsrc, NH * 1024, bars + 8 * 32);
                TS(17);
            }
            __syncwarp();
            mbar_wait(bars + 8 * 32, 0, budget);
#pragma unroll 1
            for (int i = tid; i < NH * 64; i += 512) {
                int tries = BUDGET;
                if (lds1(ha + i * 16) == 0) {
                    uint4 v;
#pragma unroll 1
                    do { v = ld_rlx4(hsrc + i * 4); } while (v.x == 0 && --tries > 0);
                    sts4(ha + i * 16, v.x, v.y, v.z, v.w);
                }
            }
            fence_async_smem();
            __syncthreads();
            TSC(tid == 0, 5);
            float acc[4] = {0.f, 0.f, 0.f, 0.f};
            int left = BUDGET;
            mbar_wait(full + 8 * NR, 0, left);
            const uint32_t da = sd + dlo(wg * 6 * BOX, BOX), db = sd + dlo(24 * BOX, 128), ahi = dhi(1024, 1) | (left >> 30), bhi = dhi(128, 0) | (left >> 30);
            uint4 v[8];
#pragma unroll
            for (int q = NR; q < NH; q++) {
                if (q > NR) mbar_wait(full + 8 * (q % 6), (q / 6) & 1, left);
                TSC(TIMING % 10 == 7 && tid == 0, 32 + q);
                wg_fence();
#pragma unroll
                for (int j = 0; j < 4; j++) wgmma_n8<1, 0>(acc, mkdesc(da + q % 6 * 512 + j * 128, ahi), mkdesc(db + q * 64 + j * 16, bhi), 1);
                wg_commit();
                if (q > NR && q + 5 < NH) {
                    wg_wait<1>();
                    if ((warp & 3) == (q & 3) && elect_one()) load(q + 5, (q - 1) % 6);
                    __syncwarp();
                }
                if (q == NR + RS_AT) {
                    wg_fence();
#pragma unroll
                    for (int j = 0; j < 4 * NR; j++) wgmma_rs_n8(acc, wa[4 * j], wa[4 * j + 1], wa[4 * j + 2], wa[4 * j + 3], mkdesc(db + j * 16, bhi));
                    wg_commit();
                }
                if (q == NH - Y_AT) {
#pragma unroll
                    for (int m = 0; m < 8; m++) v[m] = ld_rlx4(&scr->ypart[m][c2][tw]);
                }
            }
            wg_wait<0>();
            TSC(tid == 0, 18);
#pragma unroll 1
            for (int tries = BUDGET; tries > 0; tries--) {
                uint32_t bad = 0;
#pragma unroll
                for (int m = 0; m < 8; m++) bad |= v[m].x ^ ep;
                if (!(bad & 1)) break;
#pragma unroll
                for (int m = 0; m < 8; m++) if ((v[m].x ^ ep) & 1) v[m] = ld_rlx4(&scr->ypart[m][c2][tw]);
            }
            __syncwarp();
            const float sig = bf16r(sigmoidf(__uint_as_float(((int)key < 0 ? key & 0x7fffffffu : ~key) & 0xffff0000u)));
#pragma unroll
            for (int c = 0; c < 4; c++) {
#pragma unroll
                for (int m = 0; m < 8; m++) acc[c] += __uint_as_float((&v[m].x)[c]);
                acc[c] = bf16r(acc[c]) * __shfl_sync(0xffffffffu, sig, 2 * t + (c & 1));
            }
            char* dst = pf.out + (size_t)(2047 - ((__shfl_sync(0xffffffffu, key, g) >> 5) & 2047)) * 2048 + c2 * 128 + (warp & 3) * 32 + t * 4;
            asm volatile("red.relaxed.gpu.global.add.noftz.bf16x2 [%0], %1;" ::"l"(dst), "r"(movm(pack_bf16(acc[0], acc[1]))) : "memory");
            asm volatile("red.relaxed.gpu.global.add.noftz.bf16x2 [%0], %1;" ::"l"(dst + 16), "r"(movm(pack_bf16(acc[2], acc[3]))) : "memory");
            TSC(tid == 0, 20);
        }
        if (warp < 8) TS_END();
        return;
    }
    asm volatile("barrier.cluster.arrive.relaxed.aligned;" ::: "memory");

    const int c2 = b & 15, n2 = mt < 7 ? NM : N7;
    if (warp >= 12) {
        reg_dec<24>();
        if (warp == 12) {
            if (elect_one()) {
                int c = 0;
#pragma unroll 1
                for (int n = 1; n < 12; n++) {
                    load_x(n);
                    #pragma unroll 1
                    for (; c < (n == 11 ? 4 : __popc(ROWS_AT & ((2 << n) - 1))); c++) { mbar_expect_tx(bars + 8 * (B_ROW + c), BOX); tma_2d(sb + OFF_FR + c * BOX, &mr, bars + 8 * (B_ROW + c), c * 256, b * 16); }
                    if (n == 3 || n == 7) load_w((n + 1) >> 2, n >> 2);
                }
                int s = 2; uint32_t ph = 0;
#pragma unroll 1
                for (int k = 3; k < 16; k++) {
                    mbar_wait(bars + 8 * (B_WEMPTY + s), ph, budget);
                    load_w(k, s);
                    if (++s == 3) s = 0;
                    if (s == 2) ph ^= 1;
                }
                s = 2;
#pragma unroll 1
                for (int i = 0; i < 16; i++) {
                    mbar_wait(bars + 8 * (i < 2 ? B_WEMPTY + i : i < 4 ? B_G1DONE : i < 6 ? B_F1DONE : B_WOEMPTY + s), i >= 12, budget);
                    if (i == 0) {
                        mbar_expect_tx(bars + 8 * B_XT, 4 * BOX);
#pragma unroll 1
                        for (int n = 0; n < 4; n++)
                            tma_4d(sb + (n >> 1) * OFF_X1 + (n & 1) * BOX, &mx, bars + 8 * B_XT, par * 1024 + cb * 128 + (n & 1) * 64, 0, (j0 + rh * 128) >> 5, 1 - (n >> 1));
                    }
                    const uint32_t full = bars + 8 * (B_WOFULL + s);
                    mbar_expect_tx(full, 2 * BOX);
                    tma_3d(sb + OFF_WO + s * 2 * BOX, &mwo, full, 0, ((2 * p + (i < 2 ? i ^ hp : i)) & 15) * 64, cb * 2);
                    TSC(TIMING % 10 == 4, 48 + i);
                    if (++s == 6) s = 0;
                }
            }
        } else {
            bar_sync(8, 224);
            const uint32_t ep = __shfl_sync(0xffffffffu, lds1(sb + OFF_EP), 0);
            if (warp == 13) {
                cluster_wait();
                if (elect_one()) {
                    int j = 4, q = 0, left = BUDGET; uint32_t ph = 0;
#pragma unroll 1
                    for (int n = 6; n < 32; n++) {
                        mbar_wait(bars + 8 * (B_XEMPTY + j), ph, left);
                        tma_4d_mc(sb + hp * OFF_X1 + j * BOX, &mx, bars + 8 * (B_XFULL + hp * 6 + 5 - j), par * 1024 + (n >> 1) * 64, 0, (j0 + hp * 128) >> 5, ~n & 1);
                        if (++j == 6) j = 0;
                        if (j == 4) ph ^= 1;
#pragma unroll 1
                        for (; q < (PF_RATE * (n - PF_START) >> 3) && q < 18 + PF_NW; q++) {
                            const int u = q - PF_NW;
                            if (u < 0) bulk_pf(pf.wqkv + (size_t)(1024 + 128 * u + b) * 6144, 6144);
                            else if (u < 16) bulk_pf((b < 64 ? pf.wg : pf.wu) + (size_t)(u * 64 + (b & 63)) * 7168, 7168);
                            else bulk_pf(pf.wo + (size_t)((u - 16) * 128 + b) * 8192, 8192);
                        }
                    }
                }
                __syncwarp();
                uint32_t* hs = &scr->halo[b - 16][lane * 4];
                uint4 v[4] = {};
                if (j0) {
#pragma unroll 1
                    do {
#pragma unroll
                        for (int c = 0; c < 4; c++) v[c] = ld_rlx4(hs + c * 128);
                    } while (__any_sync(0xffffffffu, min(min(v[0].x, v[1].x), min(v[2].x, v[3].x)) == 0) && --budget > 0);
#pragma unroll
                    for (int c = 0; c < 4; c++) st_rlx(hs + c * 128, 0);
                }
#pragma unroll
                for (int c = 0; c < 4; c++) stsm4(sb + OFF_HIN + c * 512 + lane * 16, v[c].x, v[c].y, v[c].z, v[c].w);
                bar_arrive(11, 64);
                TSC(lane == 0, 31);
                const int src = ((mt * 2 + rh) * 2 + 1 - hp) * 1024;
                if (elect_one()) {
                    const uint32_t* fl = &scr->oflag[mt * 2 + 1 - hp][0];
                    const uint32_t inv = (ep & 1) - 1;
                    uint32_t ready = 0, ph = 0;
                    int s = 4;
#pragma unroll 1
                    for (int i = 2; i < 16; i++) {
                        const int kb = (2 * p + i) & 15;
#pragma unroll 1
                        while (!((ready >> kb) & 1) && --budget > 0) ready = ld_rlx(fl) ^ inv;
                        TSC(i == 2, 30);
                        mbar_wait(bars + 8 * (B_OEMPTY + s), ph, budget);
                        tma_2d_mc(sb + hp * OFF_X1 + s * BOX, &mo, bars + 8 * (B_OFULL + hp * 6 + s), 0, src + kb * 64);
                        TSC(TIMING % 10 == 4 && hp == 0, 32 + i);
                        if (++s == 6) s = 0;
                        if (s == 4) ph ^= 1;
                    }
                }
            } else if (warp == 14) {
                if (elect_one()) {
                    uint32_t s8 = 0, ph = 0;
                    int tries = BUDGET;
                    const uint32_t* act = scr->act[ep & 1];
                    auto counted = [&](int c, uint32_t n) {
#pragma unroll 1
                        while (ld_rlx(&scr->cnt[c][0]) != ep * n && --tries > 0) __nanosleep(POLL_NS);
                    };
                    auto weights = [&](const CUtensorMap* m, int c0, int c1, int c2_) {
                        mbar_wait(bars + 8 * B_FEMPTY + s8, ph, budget);
                        mbar_expect_tx(bars + 8 * B_FFULL + s8, F_BYTES);
                        tma_3d(sb + OFF_FS + s8 * (F_BYTES / 8), m, bars + 8 * B_FFULL + s8, c0, c1, c2_);
                    };
                    if (b < 112) {
                        counted(9, 32);
                        TS(26);
#pragma unroll 1
                        for (int q = 0; q < 16; q++) {
                            weights(&mgu, b * 32, q * 64, 0);
                            bulk_g2s(sb + OFF_FS + BOX + s8 * (F_BYTES / 8), act + 14336 + q * 256, 1024, bars + 8 * B_FFULL + s8);
                            TSC(TIMING % 10 == 5, 32 + q);
                            if (q >= PF_D && q < PF_D + PF_DN) bulk_pf(pf.wd + 7340032 - (size_t)((PF_REV ? q - PF_D + 1 : PF_DN + PF_D - q) * 112 - b) * PF_DB, PF_DB);
                            s8 += 8;
                            if (s8 == 40) { s8 = 0; ph ^= 1; }
                        }
                    }
#pragma unroll 1
                    for (int q = -3; q < n2; q++) {
                        if (q == 0) { counted(mt, 4 * n2); TS(29); }
                        if ((unsigned)q >= 3) weights(&mwd, 0, (mt * NM + (q < 0 ? q + 3 : q)) * 64, c2);
                        if (q >= 0) bulk_g2s(sb + OFF_FS + BOX + s8 * (F_BYTES / 8), act + (mt * NM + q) * 256, 1024, bars + 8 * B_FFULL + s8);
                        TSC(TIMING % 10 == 5, 51 + q);
                        s8 += 8;
                        if (s8 == 24) { s8 = 0; if ((unsigned)q >= 3) ph ^= 1; }
                    }
                }
            } else {
#pragma unroll 1
                for (int i = lane * 16; i < CS_BYTES; i += 512) sts4(sb + OFF_CS + i, 0, 0, 0, 0);
                mbar_wait(bars + 8 * ZF_GATE, 0, budget);
                uint8_t* oz = scr->o + ((size_t)mt * 64 + nt) * BOX + lane * 16;
#pragma unroll 1
                for (int i = 0; i < 16; i++, oz += 512) {
#pragma unroll
                    for (int n = 0; n < 4; n++) st_rlx4(oz + n * 16 * BOX, 0, 0, 0, 0);
                    __nanosleep(ZF_NS);
                }
                __syncwarp();
                TSC(lane == 0, 5);
                fence_gpu();
                TSC(lane == 0, 12);
                mbar_wait(bars + 8 * B_RDONE, 0, budget);
                int tries = BUDGET;
#pragma unroll 1
                for (int i = lane; i < 88; i += 32) {
                    const uint2* rp = &scr->row[2 * (j0 - 8 + i) + par];
                    uint2 v0, v1, v2;
#pragma unroll 1
                    do { v0 = ld_rlx2(rp + (j0 + i < 8 ? 16 : 0)); v1 = ld_rlx2(rp + 176); v2 = ld_rlx2(rp + 352); } while ((((v0.y ^ ep) | (v1.y ^ ep) | (v2.y ^ ep)) & 31) && --tries > 0);
                    sts2(sb + OFF_STAT + i * 8, (v0.x << 16) ^ 0x80000000u, __float_as_uint(rcp(bf_hi(v0.x))));
                    sts2(sb + OFF_STAT + i * 8 + 704, (v1.x << 16) ^ 0x80000000u, __float_as_uint(rcp(bf_hi(v1.x))));
                    sts2(sb + OFF_STAT + i * 8 + 1408, (v2.x << 16) ^ 0x80000000u, __float_as_uint(rcp(bf_hi(v2.x))));
                }
                __syncwarp();
                {
                    const int row = 2047 - ((poll_all(&scr->sel[lane & 7], 31u, ep & 31, budget) >> 5) & 2047), jj = (row >> 1) - j0 - rh * 128;
                    sts1(sb + OFF_SEL, __reduce_or_sync(0xffffffffu, (row & 1) == par && (unsigned)jj < 128 ? 1u << (jj >> 4) : 0u));
                }
                TSC(lane == 0, 14);
                if (lane < 24) {
                    uint4 v[3];
#pragma unroll 1
                    while (v[0] = ld_rlx4(&scr->cs[nt][0][lane]), v[1] = ld_rlx4(&scr->cs[nt][1][lane]), v[2] = ld_rlx4(&scr->cs[nt][2][lane]),
                           (((v[0].x ^ ep) | (v[1].x ^ ep) | (v[2].x ^ ep)) & 1) && --tries > 0) __nanosleep(100);
#pragma unroll
                    for (int r = 0; r < 3; r++) sts4(sb + OFF_CS + 64 + lane * 128 + r * 16, v[r].x, v[r].y, v[r].z, v[r].w);
                }
                fence_async_smem();
                __syncwarp();
                if (elect_one()) {
                    mbar_arrive(bars + 8 * B_AUX);
                    TS(21);
                    mbar_expect_tx(bars + 8 * (B_OFULL + 3), BOX); mbar_expect_tx(bars + 8 * (B_OFULL + 9), BOX);
#pragma unroll 1
                    for (int v = 0; v < 2; v++) {
                        const uint32_t ring = sb + v * OFF_X1 + 2 * BOX, fb = bars + 8 * (B_OFULL + v * 6 + 2);
                        mbar_wait(bars + 8 * (B_STAGED + v), 0, budget);
                        asm volatile("red.relaxed.gpu.global.xor.b32 [%0], %1;" ::"l"(&scr->oflag[mt * 2 + 1 - v][0]), "r"(1u << nt) : "memory");
                        TS(13 + 2 * v);
                        mbar_arrive(fb);
                        mbar_wait(bars + 8 * B_G1DONE, 0, budget);
                        bulk_s2c(mapa(ring + BOX, hp ^ 1), ring, BOX, mapa(fb + 8, hp ^ 1));
                        if (v == 0) mbar_wait(bars + 8 * B_FREED, 0, budget);
#pragma unroll
                        for (int n = 0; n < 4; n++) {
                            mbar_expect_tx(bars + 8 * (B_OFULL + (n >> 1) * 6 + 4 + (n & 1)) - v * 32, BOX);
                            mbar_arrive_at(mapa(bars + 8 * B_OEMPTY, n >> 1) + (4 + (n & 1)) * 8 - v * 32);
                        }
                    }
                    if (lds1(sb + OFF_SEL)) {
#pragma unroll 1
                        while (ld_acq(&scr->zflag[p >> 1]) != ep && --tries > 0) {}
                        asm volatile("fence.proxy.async.global;" ::: "memory");
                    }
                    mbar_arrive(bars + 8 * B_ZERO);
                }
            }
        }
    } else if (warp >= 8) {
        reg_dec<40>();
        const int wq = warp - 8, ta = tid - 256;
        const uint32_t rbuf = sb + OFF_FR + wq * 2048;
        const uint4 wv = ldg_nc(wr + ta * 8);
        if (ta == 0) sts1(sb + OFF_EP, ld_rlx(&scr->epoch[0]) + 1);
        sts4(sb + OFF_STAT + ta * 16, wv.x, wv.y, wv.z, wv.w);
        bar_sync(8, 224);
        const uint32_t ep = __shfl_sync(0xffffffffu, lds1(sb + OFF_EP), 0);
        {
            const int s = b * 16 + wq * 4 + (lane >> 3);
            if ((lane & 7) == 0) st_rlx2(&scr->row[s], 0, ep - 1);
            float sw = 0.f;
#pragma unroll 1
            for (int i = 0; i < 16; i++) { const uint32_t q = lds1(sb + OFF_STAT + i * 128 + lane * 4); sw += bf_lo(q) + bf_hi(q); }
#pragma unroll 1
            for (int o = 16; o > 0; o >>= 1) sw += __shfl_xor_sync(0xffffffffu, sw, o);
            float s1 = 0.f, s2 = 0.f, sr = 0.f;
            {
                float s1b = 0.f, s2b = 0.f, srb = 0.f;
                const uint32_t xb = rbuf + (lane >> 4) * 1024 + (lane & 15) * 16, wb = sb + OFF_STAT + (lane & 15) * 16;
#pragma unroll 1
                for (int i = 0; i < 8; i++) {
                    const uint4 w4 = lds4(wb + i * 256);
                    mbar_wait_hot(bars + 8 * (B_ROW + (i >> 1)), 0, budget);
                    TSC(ta == 0 && i == 0, 17);
                    const uint32_t o = (i >> 1) * BOX + (i & 1) * 256;
                    const uint4 u = lds4(xb + o), v = lds4(xb + o + 512);
#pragma unroll
                    for (int c = 0; c < 4; c++) {
                        const float w0 = bf_lo((&w4.x)[c]), w1 = bf_hi((&w4.x)[c]);
                        const float a0 = bf_lo((&u.x)[c]), a1 = bf_hi((&u.x)[c]), b0 = bf_lo((&v.x)[c]), b1 = bf_hi((&v.x)[c]);
                        s1 += a0; s2 = fmaf(a0, a0, s2); sr = fmaf(a0, w0, sr);
                        s1 += a1; s2 = fmaf(a1, a1, s2); sr = fmaf(a1, w1, sr);
                        s1b += b0; s2b = fmaf(b0, b0, s2b); srb = fmaf(b0, w0, srb);
                        s1b += b1; s2b = fmaf(b1, b1, s2b); srb = fmaf(b1, w1, srb);
                    }
                }
                const bool up = lane & 8;
                s1 = (up ? s1b : s1) + __shfl_xor_sync(0xffffffffu, up ? s1 : s1b, 8);
                s2 = (up ? s2b : s2) + __shfl_xor_sync(0xffffffffu, up ? s2 : s2b, 8);
                sr = (up ? srb : sr) + __shfl_xor_sync(0xffffffffu, up ? sr : srb, 8);
            }
#pragma unroll
            for (int o = 1; o < 8; o <<= 1) {
                s1 += __shfl_xor_sync(0xffffffffu, s1, o); s2 += __shfl_xor_sync(0xffffffffu, s2, o); sr += __shfl_xor_sync(0xffffffffu, sr, o);
            }
            const float mean = s1 * (1.f / 1024.f), mb = bf16r(mean);
            float var = fmaf(-mean, mean, s2 * (1.f / 1024.f));
            sr = fmaf(-mb, sw, sr);
            if (__builtin_expect(__any_sync(0xffffffffu, mean * mean > 256.f * var), 0)) {
                float a2 = 0.f, ar = 0.f;
#pragma unroll 1
                for (int i = 0; i < 64; i++) {
                    const uint32_t o = i * 32 + (lane & 7) * 4, q1 = lds1(rbuf + (lane >> 3) * 512 + (o >> 9) * BOX + (o & 511)), q2 = lds1(sb + OFF_STAT + o);
                    a2 = fmaf(bf_lo(q1) - mean, bf_lo(q1) - mean, fmaf(bf_hi(q1) - mean, bf_hi(q1) - mean, a2));
                    ar = fmaf(bf_lo(q1) - mb, bf_lo(q2), fmaf(bf_hi(q1) - mb, bf_hi(q2), ar));
                }
#pragma unroll 1
                for (int o = 1; o < 8; o <<= 1) { a2 += __shfl_xor_sync(0xffffffffu, a2, o); ar += __shfl_xor_sync(0xffffffffu, ar, o); }
                var = a2 * (1.f / 1024.f); sr = ar;
            }
            float den;
            asm("sqrt.approx.f32 %0, %1;" : "=f"(den) : "f"(bf16r(bf16r(var) + 1e-5f)));
            const uint32_t st = pack_bf16(mb, den);
            const uint32_t rb = pack_bf16(0.f, sr * rcp(bf_hi(st)) + 0.f);
            uint32_t ord = (int)rb < 0 ? ~rb & 0xffff0000u : rb | 0x80000000u;
            if ((rb & 0x7fffffffu) > 0x7f800000u) ord = 0;
            if ((lane & 7) == 0) st_rlx2(&scr->row[s], st, ord | ((2047 - s) << 5) | (ep & 31));
            __syncwarp();
            if (lane < 7) mbar_arrive(bars + 8 * (lane < 5 ? B_FEMPTY + lane : B_RDONE));
        }
        TSC(ta == 0, 18);
        if ((b >> 3) == 14) {
            const uint32_t gm = sb + OFF_E, cnt = gm + 64, res = gm + 80, list = gm + 128;
            uint32_t kv[16];
            int tries = BUDGET;
#pragma unroll 1
            do {
                uint32_t bad = 0;
#pragma unroll
                for (int n = 0; n < 16; n++) kv[n] = ld_rlx(&scr->row[n * 128 + ta].y);
#pragma unroll
                for (int n = 0; n < 16; n++) bad |= kv[n] ^ ep;
                if ((bad & 31) == 0) break;
            } while (--tries > 0);
            __syncwarp();
            TSC(ta == 0, 26);
            uint32_t m = 0;
#pragma unroll
            for (int n = 0; n < 16; n++) m = max(m, kv[n]);
            uint32_t gmax = m;
#pragma unroll
            for (int o = 1; o < 8; o <<= 1) gmax = max(gmax, __shfl_xor_sync(0xffffffffu, gmax, o));
            sts1(gm + (ta >> 3) * 4, gmax);
            sts1(cnt, 0);
            bar_sync(12, 128);
            const uint32_t c = lds1(gm + (lane & 15) * 4);
            int rank = 0;
#pragma unroll
            for (int i = 0; i < 2; i++) { const uint4 q = lds4(gm + (lane >> 4) * 32 + i * 16); rank += (q.x > c) + (q.y > c) + (q.z > c) + (q.w > c); }
            rank += __shfl_xor_sync(0xffffffffu, rank, 16);
            const uint32_t thr = redux_max(rank == 7 ? c : 0u);
#pragma unroll 1
            while (m >= thr) {
                uint32_t at, m2 = 0;
                asm volatile("atom.shared.add.u32 %0, [%1], 1;" : "=r"(at) : "r"(cnt) : "memory");
#pragma unroll
                for (int n = 0; n < 16; n++) m2 = max(m2, kv[n] < m ? kv[n] : 0u);
                sts1(list + at * 4, m);
                if (m2 == 0) break;
                m = m2;
            }
            bar_sync(12, 128);
            const int nc = lds1(cnt);
#pragma unroll 1
            for (int i = ta >> 3; i < ((nc + 3) & ~3); i += 16) {
                const uint32_t ki = lds1(list + i * 4);
                int r = 0;
#pragma unroll 1
                for (int n = lane & 7; n < nc; n += 8) r += lds1(list + n * 4) > ki;
                __syncwarp();
#pragma unroll
                for (int o = 1; o < 8; o <<= 1) r += __shfl_xor_sync(0xffffffffu, r, o);
                if (r == (b & 7) && i < nc) sts1(res, ki);
            }
            bar_sync(12, 128);
            const uint32_t k0 = lds1(res);
            const int r0 = 2047 - ((k0 >> 5) & 2047);
            TSC(ta == 0, 22);
            if (ta == 0) st_rlx(&scr->sel[b & 7], k0);
            const uint4 v0 = ldg_nc(x + (size_t)r0 * 1024 + ta * 8);
            const uint32_t s0 = ld_rlx(&scr->row[r0]);
            const float m0 = bf_lo(s0), i0 = rcp(bf_hi(s0));
            const int ao = 14336 + (ta >> 3) * 256 + (b & 7) * 32 + ((ta ^ b) & 7) * 4;
            st_rlx4(scr->act[ep & 1] + ao, norm_pair(v0.x, m0, i0), norm_pair(v0.y, m0, i0), norm_pair(v0.z, m0, i0), norm_pair(v0.w, m0, i0));
            __syncwarp();
            if (lane == 0) red_add(&scr->cnt[9][tries >> 30]);
            st_rlx4(scr->act[~ep & 1] + ao, 0, 0, 0, 0);
        }
        uint32_t s8 = 0, fph = 0;
        const uint32_t chk = __shfl_sync(0xffffffffu, sb + OFF_FS + BOX + lane * 32 + (lane & 28), lane);
        int left = BUDGET;
        if (b >= 112 && ta < 2) mbar_arrive(bars + 8 * B_F1DONE);
#pragma unroll 1
        for (int ph = b >= 112; ph < 2; ph++) {
            {
                float acc[4] = {0.f, 0.f, 0.f, 0.f};
                const uint32_t alo = sd + (ph ? dlo(OFF_FS, 8192) : dlo(OFF_FS, 4096)), ahi = ph ? dhi(1024, 1) : dhi(512, 2), astep = ph ? 128 : 64;
                const uint32_t bhi = ph ? dhi(128, 0) : dhi(1024, 1), bstep = ph ? 16 : 2, wrap = ph ? 24 : 40;
                uint32_t prev = 0;
                if (ph) mbar_wait(bars + 8 * FFN2_GATE, 0, left);
#pragma unroll 1
                for (int q = ph ? n2 : 16; q > 0; q--) {
                    const uint32_t da = alo + s8 * (F_BYTES >> 7), db = sd + dlo(OFF_FS + BOX, 128) + s8 * (F_BYTES >> 7);
                    mbar_wait_hot(bars + 8 * B_FFULL + s8, fph, left);
                    if (__builtin_expect(__any_sync(0xffffffffu, lds1(chk + s8 * (F_BYTES / 8)) == 0), 0)) {
                        int tries = BUDGET;
#pragma unroll 1
                        for (int n = lane * 4 + (left >> 30); n < 256; n += 128) {
                            uint4 v;
#pragma unroll 1
                            do { v = ld_rlx4(scr->act[ep & 1] + ((ph ? mt * NM + n2 : 72) - q) * 256 + n); } while (v.x == 0 && --tries > 0);
                            __syncwarp();
                            sts4(sb + OFF_FS + BOX + s8 * (F_BYTES / 8) + n * 4, v.x, v.y, v.z, v.w);
                        }
                        NRETRY();
                        fence_async_smem();
                        __syncwarp();
                    }
                    TSC(TIMING % 10 == 3 && ta == 0, 32 + (ph ? 16 + n2 : 16) - q);
                    wg_fence();
#pragma unroll
                    for (int j = 0; j < 4; j++) wgmma_n8<1, 0>(acc, mkdesc(da + j * astep, ahi), mkdesc(db + j * bstep, bhi), 1);
                    wg_commit();
                    wg_wait<1>();
                    if (ph) { wg_wait<0>(); if (lane == 0) prev = bars + 8 * B_FEMPTY + s8; }
                    if (prev) mbar_arrive(prev);
                    if (lane == 0) prev = bars + 8 * B_FEMPTY + s8;
                    s8 += 8;
                    if (s8 == wrap) { s8 = 0; fph ^= 1; }
                }
                wg_wait<0>();
                const int ln = lane + (left >> 30);
                if (ph == 0) {
                    if (prev) mbar_arrive(prev);
                    const bool second = (wq >= 2) != (swap_gu != 0);
                    const uint32_t xa = sb + OFF_GU + ((wq & 1) * 32 + ln) * 16;
                    if (second) sts4(xa, __float_as_uint(acc[0]), __float_as_uint(acc[1]), __float_as_uint(acc[2]), __float_as_uint(acc[3]));
                    bar_sync(12, 128);
                    if (second) { if (ln == 0) mbar_arrive(bars + 8 * B_F1DONE); }
                    else {
                        const float4 up = lds4f(xa);
                        float hv[4];
#pragma unroll
                        for (int c = 0; c < 4; c++) { const float ga = bf16r(acc[c]); hv[c] = bf16r(ga * sigmoidf(ga)) * bf16r((&up.x)[c]); }
                        const int ao = (b * 4 + (wq & 1) * 2) * 32 + ln;
                        st_rlx(scr->act[ep & 1] + ao, max(movm(pack_bf16(hv[0], hv[1])), 1u)); st_rlx(scr->act[ep & 1] + 32 + ao, max(movm(pack_bf16(hv[2], hv[3])), 1u));
                        __syncwarp();
                        if (ln == 0) red_add(&scr->cnt[b < 14 * NM ? b / (2 * NM) : b < 14 * NM + 2 * N7 ? 7 : 8][0]);
                        st_rlx(scr->act[~ep & 1] + ao, 0); st_rlx(scr->act[~ep & 1] + 32 + ao, 0);
                    }
                } else {
                    st_rlx4(&scr->ypart[mt][c2][wq * 32 + ln], (__float_as_uint(acc[0]) & ~1u) | (ep & 1), __float_as_uint(acc[1]), __float_as_uint(acc[2]), __float_as_uint(acc[3]));
                }
                TSC(ta == 0, 22 + ph);
            }
        }
        TSC(ta == 0, 24);
    } else {
        reg_inc<224>();
        const int w = warp >> 2, wi = warp & 3, g = lane >> 2, t = lane & 3;
        const bool elect = (tid & 127) == 0;
        const uint32_t mad = (lane & 15) * 128 + (((lane >> 4) ^ (lane & 7)) << 4);
        float acc[64];
        const uint32_t ring = sb + w * OFF_X1, ofull = bars + 8 * (B_OFULL + w * 6), oempty = mapa(bars + 8 * B_OEMPTY, w);
        const int r0 = rh * 128 + wi * 32 + (1 - w) * 16 + g;
        {
            float acc0[96], acc1[96];
            const uint32_t sta = sb + OFF_STAT + (8 + w * 128 + wi * 32) * 8;
            {
                const uint32_t xfull = bars + 8 * (B_XFULL + w * 6 + 5), xempty = mapa(bars + 8 * B_XEMPTY, w), dx0 = sd + dlo(w * OFF_X1, 16);
                uint32_t s8 = 16, ps8 = 0, ph = 0;
                cluster_wait();
#pragma unroll 1
                for (int k = 0; k < 16; k++) {
                    const uint32_t dx = dx0 + s8 * (2 * BOX >> 7), dw = sd + dlo(OFF_W, BOX) + s8 * (W_BYTES >> 7);
                    mbar_wait(bars + 8 * B_WFULL + s8, ph, budget);
                    mbar_wait(xfull - 2 * s8, ph, budget);
                    TSC(elect && k == 0, 1 + 8 * w);
                    TSC(TIMING % 10 == 1 && tid == 0, 32 + k);
                    wg_wait<0>();
                    wg_fence();
#pragma unroll
                    for (int kk = 0; kk < 4; kk++) wgmma_n192<0, 1>(acc1, mkdesc(dx + kk * 2, dhi(1024, 1)), mkdesc(dw + kk * 128, dhi(1024, 1)), kk ? 1 : k);
                    wg_commit();
                    TSC(TIMING % 10 == 6 && elect, 32 + 16 * w + k);
                    if (elect && k > 0) {
                        mbar_arrive(bars + 8 * B_WEMPTY + ps8);
                        if (k <= 13) { mbar_expect_tx(xfull - 2 * ps8 - 8, BOX); mbar_arrive_at(xempty + 2 * ps8 + 8); }
                    }
                    if (k == 15) {
                        mbar_wait(bars + 8 * B_AUX, 0, budget);
                        const uint32_t zero = budget >> 30, pm = t & 1 ? 0x4432 : 0x3232, ra = sta + ((t >> 1) * 16 + g) * 8;
                        const uint32_t a0 = __byte_perm(lds1(ra), 0, pm), a1 = __byte_perm(lds1(ra + 64), 0, pm), a2 = a0 & zero, a3 = a1 & zero;
                        wg_fence();
                        wgmma_rs_n192(acc1, a0, a1, a2, a3, mkdesc(sd + dlo(OFF_CS, 0), dhi(128, 0)));
                        wgmma_rs_n192(acc0, a0, a1, a2, a3, mkdesc(sd + dlo(OFF_CS + 64, 0), dhi(128, 0)));
                        wg_commit();
                    }
                    mbar_wait(xfull - 2 * s8 - 8, ph, budget);
                    wg_wait<0>();
                    wg_fence();
#pragma unroll
                    for (int kk = 0; kk < 4; kk++) wgmma_n192<0, 1>(acc0, mkdesc(dx + 512 + kk * 2, dhi(1024, 1)), mkdesc(dw + kk * 128, dhi(1024, 1)), kk ? 1 : k);
                    wg_commit();
                    if (elect && k <= 12) { mbar_expect_tx(xfull - 2 * s8, BOX); mbar_arrive_at(xempty + 2 * s8); }
                    ps8 = s8;
                    s8 = s8 == 16 ? 0 : s8 + 8;
                    if (s8 == 16) ph ^= 1;
                }
            }
            const uint32_t zero = budget >> 30;
            const bool u0 = 2 * t > g, u1 = 2 * t + 1 > g;
            uint32_t mU = (u0 ? 0xffffu : 0u) | (u1 ? 0xffff0000u : 0u);
            uint32_t ka0 = sta + (2 * t - (u0 ? 8 : 0)) * 8 + 4, ka1 = sta + (2 * t + 1 - (u1 ? 8 : 0)) * 8 + 4;
            float rk[2][4], fu[2][4], fn[2][4];
            auto factors = [&](int h) {
#pragma unroll
                for (int n = 0; n < 4; n += 2) {
                    const float rq = lds1f(sta + (16 * h + 4 * n + g) * 8 + 4) * (0.17677669529663687f * 1.4426950408889634f);
                    rk[h][n] = lds1f(ka0 + h * 128 + n * 32); rk[h][n + 1] = lds1f(ka1 + h * 128 + n * 32);
                    const float f0 = rq * rk[h][n], f1 = rq * rk[h][n + 1];
                    fu[h][n] = u0 ? f0 : 0.f; fn[h][n] = f0 - fu[h][n]; fu[h][n + 1] = u1 ? f1 : 0.f; fn[h][n + 1] = f1 - fu[h][n + 1];
                }
#pragma unroll
                for (int n = 0; n < 4; n++) asm volatile("" : "+f"(fu[h][n]), "+f"(fn[h][n]));
            };
            uint8_t* og = scr->o + ((size_t)(mt * 4 + w * 2) * 16 + nt) * BOX + wi * 256 + lane * 4;
            TSC(elect, 19 + w);
            uint32_t pk0[48], pk1[48], o[16] = {};
#pragma unroll
            for (int j = 0; j < 48; j++) if (j < 16 || (j & 1)) pk1[j] = pack_here(acc1[2 * j], acc1[2 * j + 1]);
            if (warp < 7) {
#pragma unroll
                for (int c = 0; c < 4; c++) stsm4(ring + 4 * BOX + wi * 2048 + c * 512 + lane * 16, pk1[17 + 8 * c], pk1[19 + 8 * c], pk1[21 + 8 * c], pk1[23 + 8 * c]);
                bar_arrive(1 + warp, 64);
            } else if (j0 != 768) {
#pragma unroll
                for (int c = 0; c < 4; c++) {
                    pk1[17 + 8 * c] = max(pk1[17 + 8 * c], 1u);
                    st_rlx4(&scr->halo[b][c * 128 + lane * 4], pk1[17 + 8 * c], pk1[19 + 8 * c], pk1[21 + 8 * c], pk1[23 + 8 * c]);
                }
            }
            TSC(tid == 224, 28);
#pragma unroll
            for (int j = 16; j < 48; j += 2) pk1[j] = pack_here(acc1[2 * j], acc1[2 * j + 1]);
            factors(1);
            uint32_t od = sb + 2 * BOX + wi * 256 + (lane >> 4) * 1024 + (lane & 15) * 16, g1peer = mapa(bars + 8 * B_G1DONE, hp ^ 1);
            uint32_t ha = sb + (warp == 0 ? OFF_HIN : warp <= 4 ? 4 * BOX - 2048 : OFF_X1 + 4 * BOX - 5 * 2048) + warp * 2048 + lane * 16;
            const bool first = warp == 0 && j0 == 0;
            float bias0 = first && u0 ? -INFINITY : 0.f, bias1 = first && u1 ? -INFINITY : 0.f;
            asm volatile("" : "+l"(og), "+r"(mU), "+r"(od), "+r"(ha), "+f"(bias0), "+f"(bias1));
            mbar_wait(bars + 8 * B_XT, 0, budget);
            mbar_wait(bars + 8 * (B_WEMPTY + 1), 0, budget);
            wg_wait<0>();
            if (elect) { mbar_arrive(bars + 8 * B_G1DONE); mbar_arrive_at(g1peer); }
            TSC(elect, 2 + 8 * w);
            float ci[4];
#pragma unroll
            for (int n = 0; n < 4; n++) ci[n] = __uint_as_float((0x03800000u + n) | (budget >> 30));
            auto hand_over = [&](int v) {
                asm volatile("{\n.reg .pred p;\nsetp.ne.b32 p, %17, 0;\n"
                             "@p stmatrix.sync.aligned.m8n8.x4.shared.b16 [%16], {%0,%1,%2,%3};\n@p stmatrix.sync.aligned.m8n8.x4.shared.b16 [%16 + 2048], {%4,%5,%6,%7};\n"
                             "@p stmatrix.sync.aligned.m8n8.x4.shared.b16 [%16 + 4096], {%8,%9,%10,%11};\n@p stmatrix.sync.aligned.m8n8.x4.shared.b16 [%16 + 6144], {%12,%13,%14,%15};\n"
                             "fence.proxy.async.shared::cta;\n}"
                             ::"r"(o[0]), "r"(o[1]), "r"(o[2]), "r"(o[3]), "r"(o[4]), "r"(o[5]), "r"(o[6]), "r"(o[7]), "r"(o[8]), "r"(o[9]), "r"(o[10]), "r"(o[11]),
                               "r"(o[12]), "r"(o[13]), "r"(o[14]), "r"(o[15]), "r"(od + v * OFF_X1), "r"((int)(w == rh)) : "memory");
#pragma unroll
                for (int i = 0; i < 16; i++) asm volatile("st.global.u32 [%0], %1;" ::"l"(og + (1 - v) * 16 * BOX + (i >> 1) * 1024 + (i & 1) * 128), "r"(o[i]) : "memory");
                __syncwarp();
                if (lane == 0) mbar_arrive(bars + 8 * (B_STAGED + v));
            };
#pragma unroll
            for (int j = 32; j < 48; j++) pk1[j] = movm(pk1[j]);
#pragma unroll
            for (int j = EARLY_PK; j < 48; j++) if (j >= 32 || (j & 1) || EARLY_PK < 17) pk0[j] = pack_here(acc0[2 * j], acc0[2 * j + 1]);
#pragma unroll
            for (int j = 32; j < 48; j++) pk0[j] = movm(pk0[j]);
            attn_pair<2>(pk1, pk1 + 16, pk1 + 32, pk0 + 17, pk0 + 33, fu[1], fn[1], rk[1], 0.f, 0.f, mU, zero, ci, o);
            hand_over(0);
            TSC(elect, 3 + 8 * w);
#pragma unroll
            for (int j = 0; j < 32; j++) if (j < EARLY_PK || (!(j & 1) && EARLY_PK == 17)) pk0[j] = pack_here(acc0[2 * j], acc0[2 * j + 1]);
            factors(0);
            bar_sync(warp ? warp : 11, 64);
            uint32_t hl[16];
            ldsm4(hl, ha); ldsm4(hl + 4, ha + 512); ldsm4t(hl + 8, ha + 1024); ldsm4t(hl + 12, ha + 1536);
            __syncwarp();
            if (lane == 0) mbar_arrive(bars + 8 * B_FREED);
            attn_pair<1>(pk0, pk0 + 16, pk0 + 32, hl, hl + 8, fu[0], fn[0], rk[0], bias0, bias1, mU, zero, ci, o);
            const float2 s0 = lds2f(sb + OFF_STAT + (8 + r0) * 8), s1 = lds2f(sb + OFF_STAT + (16 + r0) * 8);
            const float m0 = s0.x * s0.y, f0 = 1.f + s0.y, m1 = s1.x * s1.y, f1 = 1.f + s1.y;
            uint32_t xt[32];
#pragma unroll
            for (int j = 0; j < 8; j++) ldsm4(xt + 4 * j, ((ring + wi * 2048 + mad) ^ ((j & 3) * 32)) + (j >> 2) * BOX);
            hand_over(1);
#pragma unroll
            for (int j = 0; j < 32; j++) {
                acc[2 * j] = fmaf(bf_lo(xt[j]), j & 1 ? f1 : f0, j & 1 ? m1 : m0); acc[2 * j + 1] = fmaf(bf_hi(xt[j]), j & 1 ? f1 : f0, j & 1 ? m1 : m0);
            }
        }
        TSC(tid == 0, 4);
        {
            const uint32_t da0 = sd + dlo(w * OFF_X1, 1024), db0 = sd + dlo(OFF_WO, BOX);
            const uint32_t chk = ring + wi * 256 + (lane >> 3) * 1032 + (lane & 7) * 32 + (lane & 4);
            uint32_t s8 = 16, ps8 = 0, ph = 0;
            mbar_wait(ofull + s8, 0, budget);
            mbar_wait(bars + 8 * B_WOFULL + s8, 0, budget);
            TSC(TIMING % 10 == 2 && elect, 32 + w * 16);
            const uint32_t ahi = dhi(128, 0) | (budget >> 30), bhi = dhi(1024, 1) | (budget >> 30);
            const int last = w ? HOLD : 16;
            uint32_t rel = elect ? 0x7fe : 0;
#pragma unroll 1
            for (int i = 1;;) {
                const uint32_t da = da0 + s8 * (BOX >> 7), db = db0 + s8 * (BOX >> 6);
                wg_fence();
#pragma unroll
                for (int kk = 0; kk < 4; kk++) {
                    wgmma_n128<0, 1>(acc, mkdesc(da + kk * 128, ahi), mkdesc(db + kk * 128, bhi), 1);
                    if (kk & 1) wg_commit();
                }
                wg_wait<2>();
                if (rel & 1) { mbar_expect_tx(ofull + ps8, BOX); mbar_arrive_at(oempty + ps8); mbar_arrive(bars + 8 * B_WOEMPTY + ps8); }
                if (i == 16) break;
                rel >>= 1;
                ps8 = s8;
#pragma unroll 1
                do {
                    s8 = s8 == 40 ? 0 : s8 + 8;
                    if (s8 == 16) ph ^= 1;
                    uint32_t bad;
                    asm volatile("{\n.reg .pred p, q, r;\n.reg .u32 u, v;\nmbarrier.try_wait.parity.shared::cta.b64 q, [%2], %3;\nmbarrier.try_wait.parity.shared::cta.b64 p, [%1], %3;\n"
                                 "setp.ne.and.u32 r, %5, 1, p;\nmov.u32 u, 1;\nmov.u32 v, 1;\n@r ld.shared.u32 u, [%4];\n@r ld.shared.u32 v, [%4 + 4096];\n"
                                 "and.pred p, p, q;\nmin.u32 u, u, v;\nsetp.eq.or.u32 p, u, 0, !p;\nvote.sync.any.pred p, p, 0xffffffff;\nselp.u32 %0, 1, 0, p;\n}"
                                 : "=r"(bad) : "r"(ofull + s8), "r"(bars + 8 * B_WOFULL + s8), "r"(ph), "r"(chk + s8 * (BOX / 8)), "r"(i) : "memory");
                    if (__builtin_expect(bad, 0)) {
                        mbar_wait(ofull + s8, ph, budget);
                        mbar_wait(bars + 8 * B_WOFULL + s8, ph, budget);
                        if (__any_sync(0xffffffffu, min(lds1(chk + s8 * (BOX / 8)), lds1(chk + s8 * (BOX / 8) + 4096)) == 0)) {
                            const uint32_t at = wi * 256 + (lane >> 4) * 1024 + (lane & 15) * 16;
                            const uint8_t* src = scr->o + ((size_t)((mt * 2 + rh) * 2 + 1 - w) * 16 + ((2 * p + (i < 2 ? i ^ hp : i)) & 15)) * BOX + at;
#pragma unroll 1
                            for (int n = 0; n < 8192; n += 2048) {
                                uint4 v; int tries = 4096;
#pragma unroll 1
                                do { v = ld_rlx4(src + n); } while (v.x == 0 && --tries > 0);
                                sts4(ring + s8 * (BOX / 8) + at + n, v.x, v.y, v.z, v.w);
                            }
                            NRETRY();
                            fence_async_smem();
                            __syncwarp();
                        }
                    }
                    TSC(TIMING % 10 == 1 && tid == 0, 48 + i);
                    TSC(TIMING % 10 == 2 && elect, 32 + w * 16 + i);
                } while (++i > last && i < 16);
                if (i > last) break;
                wg_wait<1>();
            }
            if (w) {
                bar_sync(9, 256);
#pragma unroll 1
                for (int i = HOLD - 10; i < 6; i++) {
                    wg_fence();
#pragma unroll
                    for (int kk = 0; kk < 4; kk++) wgmma_n128<0, 1>(acc, mkdesc(da0 + i * 512 + kk * 128, ahi), mkdesc(db0 + i * 1024 + kk * 128, bhi), 1);
                    wg_commit();
                }
            } else bar_arrive(9, 256);
            mbar_wait(bars + 8 * B_ZERO, 0, budget);
            const bool add = (__shfl_sync(0xffffffffu, lds1(sb + OFF_SEL), 0) >> (wi * 2 + 1 - w)) & 1;
            wg_wait<0>();
            TSC(elect, 7 + 9 * w);
            const uint32_t os0 = ring + wi * 4096;
#pragma unroll
            for (int hf = 0; hf < OUT_PARTS; hf++) {
#pragma unroll
                for (int j = hf * (8 / OUT_PARTS); j < (hf + 1) * (8 / OUT_PARTS); j++)
                    stsm4(((os0 + mad) ^ ((j & 3) * 32)) + (j >> 2) * 2048, pack_here(acc[8 * j], acc[8 * j + 1]), pack_here(acc[8 * j + 2], acc[8 * j + 3]),
                          pack_here(acc[8 * j + 4], acc[8 * j + 5]), pack_here(acc[8 * j + 6], acc[8 * j + 7]));
                fence_async_smem();
                __syncwarp();
                if (elect_one())
                    asm volatile("{\n.reg .pred p;\nsetp.ne.b32 p, %6, 0;\n@!p cp.async.bulk.tensor.5d.global.shared::cta.bulk_group [%0, {%2, %2, %3, %4, %5}], [%1];\n"
                                 "@p cp.reduce.async.bulk.tensor.5d.global.shared::cta.add.bulk_group [%0, {%2, %2, %3, %4, %5}], [%1];\n}"
                                 ::"l"(&mout), "r"(os0 + hf * 2048), "r"(0), "r"(((j0 + rh * 128) >> 5) + wi), "r"(1 - w), "r"(par * 16 + cb * 2 + hf), "r"((int)add) : "memory");
            }
            asm volatile("cp.async.bulk.commit_group;\ncp.async.bulk.wait_group.read 0;" ::: "memory");
            if (b == 0 && tid == 0) st_rlx(&scr->epoch[0], lds1(sb + OFF_EP));
            TSC(elect, 8 - 2 * w);
            TS_END();
        }
    }
}

typedef CUresult (*EncodeFn)(CUtensorMap*, CUtensorMapDataType, cuuint32_t, void*, const cuuint64_t*, const cuuint64_t*, const cuuint32_t*,
                             const cuuint32_t*, CUtensorMapInterleave, CUtensorMapSwizzle, CUtensorMapL2promotion, CUtensorMapFloatOOBfill);

CUtensorMap make_map(EncodeFn fn, const void* base, int rank, const cuuint64_t* dims, const cuuint64_t* strides, const cuuint32_t* box,
                     CUtensorMapSwizzle swz = CU_TENSOR_MAP_SWIZZLE_128B, CUtensorMapL2promotion pro = CU_TENSOR_MAP_L2_PROMOTION_L2_256B) {
    CUtensorMap m;
    cuuint32_t es[5] = {1, 1, 1, 1, 1};
    fn(&m, CU_TENSOR_MAP_DATA_TYPE_BFLOAT16, rank, (void*)base, dims, strides, box, es, CU_TENSOR_MAP_INTERLEAVE_NONE,
       swz, pro, CU_TENSOR_MAP_FLOAT_OOB_FILL_NONE);
    return m;
}

}

extern "C" void kernel_launch(void* const* d_in, const int* in_sizes, int n_in, void* d_out, int out_size) {
    (void)in_sizes; (void)n_in; (void)out_size;
    const __nv_bfloat16* x = (const __nv_bfloat16*)d_in[0];
    const __nv_bfloat16* wqkv = (const __nv_bfloat16*)d_in[1];
    const __nv_bfloat16* wo = (const __nv_bfloat16*)d_in[2];
    const __nv_bfloat16* wr = (const __nv_bfloat16*)d_in[4];
    const __nv_bfloat16* wg = (const __nv_bfloat16*)d_in[5];
    const __nv_bfloat16* wu = (const __nv_bfloat16*)d_in[6];
    const __nv_bfloat16* wd = (const __nv_bfloat16*)d_in[7];
    static EncodeFn fn = nullptr;
    static Scratch* scr = nullptr;
    if (!fn) {
        void* p = nullptr; cudaDriverEntryPointQueryResult q;
        cudaGetDriverEntryPoint("cuTensorMapEncodeTiled", &p, cudaEnableDefault, &q);
        fn = (EncodeFn)p;
        cudaFuncSetAttribute(fused_kernel, cudaFuncAttributeMaxDynamicSharedMemorySize, SMEM_LAUNCH);
        cudaGetSymbolAddress((void**)&scr, g_scr);
    }
    const cuuint64_t xd[4] = {2048, 16, 32, 2}, xs[4] = {4096, 131072, 65536, 128}, od[5] = {64, 16, 32, 2, 32};
    const cuuint32_t xb[4] = {64, 16, 4, 1}, ob[5] = {64, 16, 1, 1, 2 / OUT_PARTS};
    const cuuint64_t wdm[3] = {1024, 1024, 3}, wst[2] = {6144, 2048};
    const cuuint32_t wb[3] = {64, 64, 3};
    const cuuint64_t wod[3] = {64, 1024, 16}, wdd[3] = {64, 3584, 16}, wos[2] = {2048, 128};
    const cuuint32_t wob[3] = {64, 64, 2}, wdb[3] = {64, 64, 1};
    const CUtensorMapSwizzle s128 = CU_TENSOR_MAP_SWIZZLE_128B;
    CUtensorMap mx = make_map(fn, x, 4, xd, xs, xb, s128, (CUtensorMapL2promotion)P_X), mw = make_map(fn, wqkv, 3, wdm, wst, wb, s128, (CUtensorMapL2promotion)P_W);
    CUtensorMap mwo = make_map(fn, wo, 3, wod, wos, wob, s128, (CUtensorMapL2promotion)P_WO), mout = make_map(fn, d_out, 5, od, xs, ob, s128, (CUtensorMapL2promotion)P_OUT);
    const int swap_gu = wu < wg;
    const cuuint64_t gd[3] = {3584, 1024, 2}, gst[2] = {7168, (cuuint64_t)(swap_gu ? (const char*)wg - (const char*)wu : (const char*)wu - (const char*)wg)};
    const cuuint32_t gb[3] = {32, 64, 2};
    CUtensorMap mgu = make_map(fn, swap_gu ? wu : wg, 3, gd, gst, gb, CU_TENSOR_MAP_SWIZZLE_64B, (CUtensorMapL2promotion)P_GU);
    CUtensorMap mwd = make_map(fn, wd, 3, wdd, wos, wdb, s128, (CUtensorMapL2promotion)P_WD);
    const cuuint64_t md[2] = {64, 32768}, ms[1] = {128};
    const cuuint32_t mb[2] = {64, 64};
    CUtensorMap mo = make_map(fn, scr, 2, md, ms, mb, CU_TENSOR_MAP_SWIZZLE_NONE, (CUtensorMapL2promotion)P_O);
    const cuuint64_t rd[2] = {1024, 2048};
    const cuuint32_t rb[2] = {256, 16};
    CUtensorMap mr = make_map(fn, x, 2, rd, wos, rb, CU_TENSOR_MAP_SWIZZLE_NONE, (CUtensorMapL2promotion)P_R);
    cudaLaunchConfig_t cfg = {};
    cfg.gridDim = dim3(132); cfg.blockDim = dim3(512); cfg.dynamicSmemBytes = SMEM_LAUNCH; cfg.stream = cudaStreamPerThread;
    cudaLaunchAttribute at[1];
    at[0].id = cudaLaunchAttributeClusterDimension; at[0].val.clusterDim.x = 2; at[0].val.clusterDim.y = 1; at[0].val.clusterDim.z = 1;
    cfg.attrs = at; cfg.numAttrs = 1;
    cudaLaunchKernelEx(&cfg, fused_kernel, mx, mw, mwo, mout, mgu, mwd, mo, mr, x, wr, scr, swap_gu, Weights{(const char*)wqkv, (const char*)wo, (const char*)wg, (const char*)wu, (const char*)wd, (char*)d_out});
}
```

```cpp
#include <cuda_runtime.h>
#include <cuda.h>
#include <cuda_bf16.h>
#include <stdint.h>

namespace {

constexpr int BOX = 8192, W_BYTES = 3 * BOX;
constexpr int OFF_X1 = 6 * BOX, OFF_FR = 12 * BOX, OFF_E = 16 * BOX, OFF_W = 19 * BOX;
constexpr int OFF_WO = OFF_E;
constexpr int OFF_HIN = OFF_FR + 2048, OFF_GU = OFF_HIN + 2048, OFF_FS = OFF_GU + 1024;
constexpr int F_BYTES = 9216;
constexpr int CS_BYTES = 3136;
constexpr int OFF_CS = OFF_FS + 5 * F_BYTES;
constexpr int OFF_STAT = 28 * BOX;
constexpr int OFF_SEL = OFF_STAT + 2112, OFF_EP = OFF_SEL + 4;
constexpr int OFF_BAR = OFF_SEL + 16;
constexpr int B_WFULL = 0, B_XFULL = 3, B_AUX = 15, B_XT = 16, B_ZERO = 17, B_WOFULL = 18, B_OFULL = 24, B_FFULL = 36, B_ROW = 41;
constexpr int B_WEMPTY = 48, B_F1DONE = 51, B_XEMPTY = 52, B_WOEMPTY = 58, B_OEMPTY = 64;
constexpr int B_G1DONE = 72, B_FEMPTY = 73, B_STAGED = 78, B_RDONE = 80, B_FREED = 81, NBAR = 84;
constexpr int SMEM_BYTES = OFF_BAR + NBAR * 8;
static_assert(OFF_FS + 3 * F_BYTES == OFF_E && OFF_CS + CS_BYTES <= OFF_W && SMEM_BYTES + 256 <= 232448 && OFF_BAR % 8 == 0, "smem");
#define POLL_NS 30
#define PF_RATE 10
#define PF_START 7
#define ZF_NS 100
#define FFN2_GATE (B_STAGED + 1)
#define PF_NW 6
#define EARLY_PK 17
#define ZF_GATE (B_ROW + 3)
#define HOLD 12
#define F2_DEPTH 0
#define OUT_PARTS 2
#define PF_D 8
#define NM 3
#define N7 9
#define NR 5
#define PF_DN 8
#define PF_DB 4096
#define PF_REV 0
#define RS_AT 5
#define Y_AT 2
#define P_X 0
#define P_W 0
#define P_WO 0
#define P_OUT 0
#define P_GU 2
#define P_WD 2
#define P_O 0
#define P_R 0
#define START 0
#define ROWS_AT 0x280
constexpr int NH = 56 - 7 * NM - N7;
static_assert(NH >= NR + 12 && NH <= 32 && NR < 6, "FFN2 split");
constexpr int BUDGET = 1 << 18;

struct Scratch {
    uint8_t o[2048 * 1024 * 2];
    uint4 ypart[8][16][128];
    uint32_t halo[128][512];
    uint32_t act[2][14336 + 4096];
    uint2 row[2048];
    uint4 cs[16][3][24];
    uint32_t oflag[16][32];
    uint32_t cnt[10][32];
    uint32_t sel[32], zflag[32], epoch[32];
};
__device__ __align__(1024) Scratch g_scr;
struct Weights { const char *wqkv, *wo, *wg, *wu, *wd; char* out; };

#define TS(i) do {} while (0)
#define TS_END() do {} while (0)
#define TSC(c, i) do {} while (0)
#define NRETRY() do {} while (0)
constexpr int SMEM_LAUNCH = SMEM_BYTES;
__device__ __forceinline__ uint32_t smem_u32(const void* p) { return (uint32_t)__cvta_generic_to_shared(p); }
__device__ __forceinline__ void mbar_init(uint32_t bar, uint32_t cnt) { asm volatile("mbarrier.init.shared::cta.b64 [%0], %1;" ::"r"(bar), "r"(cnt) : "memory"); }
__device__ __forceinline__ void mbar_expect_tx(uint32_t bar, uint32_t bytes) { asm volatile("mbarrier.arrive.expect_tx.shared::cta.b64 _, [%0], %1;" ::"r"(bar), "r"(bytes) : "memory"); }
__device__ __forceinline__ void mbar_arrive(uint32_t bar) { asm volatile("mbarrier.arrive.shared::cta.b64 _, [%0];" ::"r"(bar) : "memory"); }
__device__ __forceinline__ uint32_t mapa(uint32_t a, uint32_t cta) { uint32_t r; asm("mapa.shared::cluster.u32 %0, %1, %2;" : "=r"(r) : "r"(a), "r"(cta)); return r; }
__device__ __forceinline__ void mbar_arrive_at(uint32_t cbar) { asm volatile("mbarrier.arrive.shared::cluster.b64 _, [%0];" ::"r"(cbar) : "memory"); }
__device__ __forceinline__ void mbar_wait(uint32_t bar, uint32_t parity, int& budget) {
    asm volatile("{\n.reg .pred p;\nLAB_WAIT:\nmbarrier.try_wait.parity.shared::cta.b64 p, [%1], %2;\n"
                 "add.s32 %0, %0, -1;\nsetp.gt.and.s32 p, %0, 0, !p;\n@p bra LAB_WAIT;\n}" : "+r"(budget) : "r"(bar), "r"(parity) : "memory");
}
__device__ __forceinline__ void mbar_wait_hot(uint32_t bar, uint32_t parity, int& budget) {
    asm volatile("{\n.reg .pred p;\nmbarrier.try_wait.parity.shared::cta.b64 p, [%1], %2;\n@p bra LAB_DONE;\nLAB_WAIT:\nmbarrier.try_wait.parity.shared::cta.b64 p, [%1], %2;\n"
                 "add.s32 %0, %0, -1;\nsetp.gt.and.s32 p, %0, 0, !p;\n@p bra LAB_WAIT;\nLAB_DONE:\n}" : "+r"(budget) : "r"(bar), "r"(parity) : "memory");
}
__device__ __forceinline__ void tma_2d(uint32_t dst, const CUtensorMap* m, uint32_t bar, int c0, int c1) {
    asm volatile("cp.async.bulk.tensor.2d.shared::cluster.global.mbarrier::complete_tx::bytes [%0], [%1, {%3, %4}], [%2];" ::"r"(dst), "l"(m), "r"(bar), "r"(c0), "r"(c1) : "memory");
}
__device__ __forceinline__ void tma_2d_mc(uint32_t dst, const CUtensorMap* m, uint32_t bar, int c0, int c1) {
    asm volatile("cp.async.bulk.tensor.2d.shared::cluster.global.mbarrier::complete_tx::bytes.multicast::cluster [%0], [%1, {%3, %4}], [%2], %5;" ::"r"(dst), "l"(m), "r"(bar), "r"(c0), "r"(c1), "h"((uint16_t)3) : "memory");
}
__device__ __forceinline__ void tma_3d(uint32_t dst, const CUtensorMap* m, uint32_t bar, int c0, int c1, int c2) {
    asm volatile("cp.async.bulk.tensor.3d.shared::cluster.global.mbarrier::complete_tx::bytes [%0], [%1, {%3, %4, %5}], [%2];" ::"r"(dst), "l"(m), "r"(bar), "r"(c0), "r"(c1), "r"(c2) : "memory");
}
__device__ __forceinline__ void tma_4d(uint32_t dst, const CUtensorMap* m, uint32_t bar, int c0, int c1, int c2, int c3) {
    asm volatile("cp.async.bulk.tensor.4d.shared::cluster.global.mbarrier::complete_tx::bytes [%0], [%1, {%3, %4, %5, %6}], [%2];" ::"r"(dst), "l"(m), "r"(bar), "r"(c0), "r"(c1), "r"(c2), "r"(c3) : "memory");
}
__device__ __forceinline__ void tma_4d_mc(uint32_t dst, const CUtensorMap* m, uint32_t bar, int c0, int c1, int c2, int c3) {
    asm volatile("cp.async.bulk.tensor.4d.shared::cluster.global.mbarrier::complete_tx::bytes.multicast::cluster [%0], [%1, {%3, %4, %5, %6}], [%2], %7;" ::"r"(dst), "l"(m), "r"(bar), "r"(c0), "r"(c1), "r"(c2), "r"(c3), "h"((uint16_t)3) : "memory");
}
__device__ __forceinline__ void bulk_pf(const void* p, uint32_t bytes) { asm volatile("cp.async.bulk.prefetch.L2.global [%0], %1;" ::"l"(p), "r"(bytes) : "memory"); }
__device__ __forceinline__ void bulk_g2s(uint32_t dst, const void* src, uint32_t bytes, uint32_t bar) {
    asm volatile("cp.async.bulk.shared::cluster.global.mbarrier::complete_tx::bytes [%0], [%1], %2, [%3];" ::"r"(dst), "l"(src), "r"(bytes), "r"(bar) : "memory");
}
__device__ __forceinline__ void bulk_s2c(uint32_t cdst, uint32_t src, uint32_t bytes, uint32_t cbar) {
    asm volatile("cp.async.bulk.shared::cluster.shared::cta.mbarrier::complete_tx::bytes [%0], [%1], %2, [%3];" ::"r"(cdst), "r"(src), "r"(bytes), "r"(cbar) : "memory");
}
__device__ __forceinline__ void cluster_wait() { asm volatile("barrier.cluster.wait.aligned;" ::: "memory"); }
__device__ __forceinline__ void fence_gpu() { asm volatile("fence.acq_rel.gpu;" ::: "memory"); }
__device__ __forceinline__ void fence_async_smem() { asm volatile("fence.proxy.async.shared::cta;" ::: "memory"); }
__device__ __forceinline__ void wg_fence() { asm volatile("wgmma.fence.sync.aligned;" ::: "memory"); }
__device__ __forceinline__ void wg_commit() { asm volatile("wgmma.commit_group.sync.aligned;" ::: "memory"); }
template <int N> __device__ __forceinline__ void wg_wait() { asm volatile("wgmma.wait_group.sync.aligned %0;" ::"n"(N) : "memory"); }
__device__ __forceinline__ uint64_t mkdesc(uint32_t lo, uint32_t hi) { return ((uint64_t)hi << 32) | lo; }
__host__ __device__ constexpr uint32_t dhi(uint32_t sbo, uint32_t mode) { return (sbo >> 4) | (mode << 30); }
__host__ __device__ constexpr uint32_t dlo(uint32_t off, uint32_t lbo) { return (off >> 4) + ((lbo >> 4) << 16); }
__device__ __forceinline__ bool elect_one() {
    uint32_t e;
    asm volatile("{\n.reg .pred p;\nelect.sync _|p, 0xffffffff;\nselp.u32 %0, 1, 0, p;\n}" : "=r"(e));
    return e;
}
template <int R> __device__ __forceinline__ void reg_inc() { asm volatile("setmaxnreg.inc.sync.aligned.u32 %0;" ::"n"(R)); }
template <int R> __device__ __forceinline__ void reg_dec() { asm volatile("setmaxnreg.dec.sync.aligned.u32 %0;" ::"n"(R)); }
__device__ __forceinline__ void bar_sync(int id, int n) { asm volatile("bar.sync %0, %1;" ::"r"(id), "r"(n) : "memory"); }
__device__ __forceinline__ void bar_arrive(int id, int n) { asm volatile("bar.arrive %0, %1;" ::"r"(id), "r"(n) : "memory"); }
__device__ __forceinline__ uint32_t pack_bf16(float lo, float hi) { uint32_t r; asm("cvt.rn.bf16x2.f32 %0, %1, %2;" : "=r"(r) : "f"(hi), "f"(lo)); return r; }
__device__ __forceinline__ uint32_t pack_here(float lo, float hi) { uint32_t r; asm volatile("cvt.rn.bf16x2.f32 %0, %1, %2;" : "=r"(r) : "f"(hi), "f"(lo)); return r; }
__device__ __forceinline__ float bf_lo(uint32_t u) { return __uint_as_float(u << 16); }
__device__ __forceinline__ float bf_hi(uint32_t u) { return __uint_as_float(u & 0xffff0000u); }
__device__ __forceinline__ float bf16r(float v) { return bf_lo(pack_bf16(v, 0.f)); }
__device__ __forceinline__ float rcp(float x) { float r; asm("rcp.approx.ftz.f32 %0, %1;" : "=f"(r) : "f"(x)); return r; }
__device__ __forceinline__ float ex2(float x) { float r; asm("ex2.approx.ftz.f32 %0, %1;" : "=f"(r) : "f"(x)); return r; }
__device__ __forceinline__ float sigmoidf(float v) { return rcp(1.f + ex2(v * -1.4426950408889634f)); }
__device__ __forceinline__ uint32_t movm(uint32_t a) { uint32_t d; asm volatile("movmatrix.sync.aligned.m8n8.trans.b16 %0, %1;" : "=r"(d) : "r"(a)); return d; }
__device__ __forceinline__ void mma16816(float (&c)[4], uint32_t a0, uint32_t a1, uint32_t a2, uint32_t a3, uint32_t b0, uint32_t b1) {
    asm volatile("mma.sync.aligned.m16n8k16.row.col.f32.bf16.bf16.f32 {%0,%1,%2,%3}, {%4,%5,%6,%7}, {%8,%9}, {%0,%1,%2,%3};"
                 : "+f"(c[0]), "+f"(c[1]), "+f"(c[2]), "+f"(c[3]) : "r"(a0), "r"(a1), "r"(a2), "r"(a3), "r"(b0), "r"(b1));
}
__device__ __forceinline__ void mma1688(float (&c)[4], uint32_t a0, uint32_t a1, uint32_t b0) {
    asm volatile("mma.sync.aligned.m16n8k8.row.col.f32.bf16.bf16.f32 {%0,%1,%2,%3}, {%4,%5}, {%6}, {%0,%1,%2,%3};"
                 : "+f"(c[0]), "+f"(c[1]), "+f"(c[2]), "+f"(c[3]) : "r"(a0), "r"(a1), "r"(b0));
}
__device__ __forceinline__ void stsm4(uint32_t a, uint32_t r0, uint32_t r1, uint32_t r2, uint32_t r3) {
    asm volatile("stmatrix.sync.aligned.m8n8.x4.shared.b16 [%0], {%1,%2,%3,%4};" ::"r"(a), "r"(r0), "r"(r1), "r"(r2), "r"(r3) : "memory");
}
__device__ __forceinline__ void ldsm4(uint32_t* r, uint32_t a) {
    asm volatile("ldmatrix.sync.aligned.m8n8.x4.shared.b16 {%0,%1,%2,%3}, [%4];" : "=r"(r[0]), "=r"(r[1]), "=r"(r[2]), "=r"(r[3]) : "r"(a) : "memory");
}
__device__ __forceinline__ void ldsm4t(uint32_t* r, uint32_t a) {
    asm volatile("ldmatrix.sync.aligned.m8n8.x4.trans.shared.b16 {%0,%1,%2,%3}, [%4];" : "=r"(r[0]), "=r"(r[1]), "=r"(r[2]), "=r"(r[3]) : "r"(a) : "memory");
}
__device__ __forceinline__ uint32_t ld_rlx(const void* p) { uint32_t v; asm volatile("ld.relaxed.gpu.global.u32 %0, [%1];" : "=r"(v) : "l"(p) : "memory"); return v; }
__device__ __forceinline__ uint32_t ld_acq(const void* p) { uint32_t v; asm volatile("ld.acquire.gpu.global.u32 %0, [%1];" : "=r"(v) : "l"(p) : "memory"); return v; }
__device__ __forceinline__ uint2 ld_rlx2(const void* p) { uint2 v; asm volatile("ld.relaxed.gpu.global.v2.u32 {%0,%1}, [%2];" : "=r"(v.x), "=r"(v.y) : "l"(p) : "memory"); return v; }
__device__ __forceinline__ uint4 ld_rlx4(const void* p) { uint4 v; asm volatile("ld.relaxed.gpu.global.v4.u32 {%0,%1,%2,%3}, [%4];" : "=r"(v.x), "=r"(v.y), "=r"(v.z), "=r"(v.w) : "l"(p) : "memory"); return v; }
__device__ __forceinline__ void st_rlx(void* p, uint32_t v) { asm volatile("st.relaxed.gpu.global.u32 [%0], %1;" ::"l"(p), "r"(v) : "memory"); }
__device__ __forceinline__ void st_rlx2(void* p, uint32_t a, uint32_t b) { asm volatile("st.relaxed.gpu.global.v2.u32 [%0], {%1,%2};" ::"l"(p), "r"(a), "r"(b) : "memory"); }
__device__ __forceinline__ void st_rlx4(void* p, uint32_t a, uint32_t b, uint32_t c, uint32_t d) { asm volatile("st.relaxed.gpu.global.v4.u32 [%0], {%1,%2,%3,%4};" ::"l"(p), "r"(a), "r"(b), "r"(c), "r"(d) : "memory"); }
__device__ __forceinline__ void red_add(uint32_t* p) { asm volatile("red.relaxed.gpu.global.add.u32 [%0], 1;" ::"l"(p) : "memory"); }
__device__ __forceinline__ uint4 ldg_nc(const void* p) { uint4 v; asm volatile("ld.global.nc.v4.u32 {%0,%1,%2,%3}, [%4];" : "=r"(v.x), "=r"(v.y), "=r"(v.z), "=r"(v.w) : "l"(p)); return v; }
__device__ __forceinline__ void sts4(uint32_t a, uint32_t x, uint32_t y, uint32_t z, uint32_t w) { asm volatile("st.shared.v4.u32 [%0], {%1,%2,%3,%4};" ::"r"(a), "r"(x), "r"(y), "r"(z), "r"(w) : "memory"); }
__device__ __forceinline__ void sts2(uint32_t a, uint32_t x, uint32_t y) { asm volatile("st.shared.v2.u32 [%0], {%1,%2};" ::"r"(a), "r"(x), "r"(y) : "memory"); }
__device__ __forceinline__ void sts1(uint32_t a, uint32_t v) { asm volatile("st.shared.u32 [%0], %1;" ::"r"(a), "r"(v) : "memory"); }
__device__ __forceinline__ uint4 lds4(uint32_t a) { uint4 v; asm volatile("ld.shared.v4.u32 {%0,%1,%2,%3}, [%4];" : "=r"(v.x), "=r"(v.y), "=r"(v.z), "=r"(v.w) : "r"(a) : "memory"); return v; }
__device__ __forceinline__ float4 lds4f(uint32_t a) { float4 v; asm volatile("ld.shared.v4.f32 {%0,%1,%2,%3}, [%4];" : "=f"(v.x), "=f"(v.y), "=f"(v.z), "=f"(v.w) : "r"(a) : "memory"); return v; }
__device__ __forceinline__ float2 lds2f(uint32_t a) { float2 v; asm volatile("ld.shared.v2.f32 {%0,%1}, [%2];" : "=f"(v.x), "=f"(v.y) : "r"(a) : "memory"); return v; }
__device__ __forceinline__ float lds1f(uint32_t a) { float v; asm volatile("ld.shared.f32 %0, [%1];" : "=f"(v) : "r"(a) : "memory"); return v; }
__device__ __forceinline__ uint32_t lds1(uint32_t a) { uint32_t v; asm volatile("ld.shared.u32 %0, [%1];" : "=r"(v) : "r"(a) : "memory"); return v; }
__device__ __forceinline__ uint32_t redux_max(uint32_t v) { uint32_t r; asm volatile("redux.sync.max.u32 %0, %1, 0xffffffff;" : "=r"(r) : "r"(v)); return r; }
__device__ __forceinline__ uint32_t poll_all(const uint32_t* p, uint32_t mask, uint32_t want, int& budget) {
    uint32_t v;
#pragma unroll 1
    while (v = ld_acq(p), !__all_sync(0xffffffffu, (v & mask) == want) && --budget > 0) __nanosleep(POLL_NS);
    return v;
}

template <int TA, int TB>
__device__ __forceinline__ void wgmma_n192(float (&d)[96], uint64_t da, uint64_t db, int keep) {
    asm volatile("{\n.reg .pred p;\nsetp.ne.b32 p, %98, 0;\n"
        "wgmma.mma_async.sync.aligned.m64n192k16.f32.bf16.bf16 "
        "{%0, %1, %2, %3, %4, %5, %6, %7, %8, %9, %10, %11, %12, %13, %14, %15, "
        "%16, %17, %18, %19, %20, %21, %22, %23, %24, %25, %26, %27, %28, %29, %30, %31, "
        "%32, %33, %34, %35, %36, %37, %38, %39, %40, %41, %42, %43, %44, %45, %46, %47, "
        "%48, %49, %50, %51, %52, %53, %54, %55, %56, %57, %58, %59, %60, %61, %62, %63, "
        "%64, %65, %66, %67, %68, %69, %70, %71, %72, %73, %74, %75, %76, %77, %78, %79, "
        "%80, %81, %82, %83, %84, %85, %86, %87, %88, %89, %90, %91, %92, %93, %94, %95}, "
        "%96, %97, p, 1, 1, %99, %100;\n}\n"
        : "+f"(d[0]), "+f"(d[1]), "+f"(d[2]), "+f"(d[3]), "+f"(d[4]), "+f"(d[5]), "+f"(d[6]), "+f"(d[7]),
          "+f"(d[8]), "+f"(d[9]), "+f"(d[10]), "+f"(d[11]), "+f"(d[12]), "+f"(d[13]), "+f"(d[14]), "+f"(d[15]),
          "+f"(d[16]), "+f"(d[17]), "+f"(d[18]), "+f"(d[19]), "+f"(d[20]), "+f"(d[21]), "+f"(d[22]), "+f"(d[23]),
          "+f"(d[24]), "+f"(d[25]), "+f"(d[26]), "+f"(d[27]), "+f"(d[28]), "+f"(d[29]), "+f"(d[30]), "+f"(d[31]),
          "+f"(d[32]), "+f"(d[33]), "+f"(d[34]), "+f"(d[35]), "+f"(d[36]), "+f"(d[37]), "+f"(d[38]), "+f"(d[39]),
          "+f"(d[40]), "+f"(d[41]), "+f"(d[42]), "+f"(d[43]), "+f"(d[44]), "+f"(d[45]), "+f"(d[46]), "+f"(d[47]),
          "+f"(d[48]), "+f"(d[49]), "+f"(d[50]), "+f"(d[51]), "+f"(d[52]), "+f"(d[53]), "+f"(d[54]), "+f"(d[55]),
          "+f"(d[56]), "+f"(d[57]), "+f"(d[58]), "+f"(d[59]), "+f"(d[60]), "+f"(d[61]), "+f"(d[62]), "+f"(d[63]),
          "+f"(d[64]), "+f"(d[65]), "+f"(d[66]), "+f"(d[67]), "+f"(d[68]), "+f"(d[69]), "+f"(d[70]), "+f"(d[71]),
          "+f"(d[72]), "+f"(d[73]), "+f"(d[74]), "+f"(d[75]), "+f"(d[76]), "+f"(d[77]), "+f"(d[78]), "+f"(d[79]),
          "+f"(d[80]), "+f"(d[81]), "+f"(d[82]), "+f"(d[83]), "+f"(d[84]), "+f"(d[85]), "+f"(d[86]), "+f"(d[87]),
          "+f"(d[88]), "+f"(d[89]), "+f"(d[90]), "+f"(d[91]), "+f"(d[92]), "+f"(d[93]), "+f"(d[94]), "+f"(d[95])
        : "l"(da), "l"(db), "r"(keep), "n"(TA), "n"(TB));
}
template <int TA, int TB>
__device__ __forceinline__ void wgmma_n128(float (&d)[64], uint64_t da, uint64_t db, int keep) {
    asm volatile("{\n.reg .pred p;\nsetp.ne.b32 p, %66, 0;\n"
        "wgmma.mma_async.sync.aligned.m64n128k16.f32.bf16.bf16 "
        "{%0, %1, %2, %3, %4, %5, %6, %7, %8, %9, %10, %11, %12, %13, %14, %15, "
        "%16, %17, %18, %19, %20, %21, %22, %23, %24, %25, %26, %27, %28, %29, %30, %31, "
        "%32, %33, %34, %35, %36, %37, %38, %39, %40, %41, %42, %43, %44, %45, %46, %47, "
        "%48, %49, %50, %51, %52, %53, %54, %55, %56, %57, %58, %59, %60, %61, %62, %63}, "
        "%64, %65, p, 1, 1, %67, %68;\n}\n"
        : "+f"(d[0]), "+f"(d[1]), "+f"(d[2]), "+f"(d[3]), "+f"(d[4]), "+f"(d[5]), "+f"(d[6]), "+f"(d[7]),
          "+f"(d[8]), "+f"(d[9]), "+f"(d[10]), "+f"(d[11]), "+f"(d[12]), "+f"(d[13]), "+f"(d[14]), "+f"(d[15]),
          "+f"(d[16]), "+f"(d[17]), "+f"(d[18]), "+f"(d[19]), "+f"(d[20]), "+f"(d[21]), "+f"(d[22]), "+f"(d[23]),
          "+f"(d[24]), "+f"(d[25]), "+f"(d[26]), "+f"(d[27]), "+f"(d[28]), "+f"(d[29]), "+f"(d[30]), "+f"(d[31]),
          "+f"(d[32]), "+f"(d[33]), "+f"(d[34]), "+f"(d[35]), "+f"(d[36]), "+f"(d[37]), "+f"(d[38]), "+f"(d[39]),
          "+f"(d[40]), "+f"(d[41]), "+f"(d[42]), "+f"(d[43]), "+f"(d[44]), "+f"(d[45]), "+f"(d[46]), "+f"(d[47]),
          "+f"(d[48]), "+f"(d[49]), "+f"(d[50]), "+f"(d[51]), "+f"(d[52]), "+f"(d[53]), "+f"(d[54]), "+f"(d[55]),
          "+f"(d[56]), "+f"(d[57]), "+f"(d[58]), "+f"(d[59]), "+f"(d[60]), "+f"(d[61]), "+f"(d[62]), "+f"(d[63])
        : "l"(da), "l"(db), "r"(keep), "n"(TA), "n"(TB));
}
template <int TA, int TB>
__device__ __forceinline__ void wgmma_n8(float (&d)[4], uint64_t da, uint64_t db, int keep) {
    asm volatile("{\n.reg .pred p;\nsetp.ne.b32 p, %6, 0;\n"
        "wgmma.mma_async.sync.aligned.m64n8k16.f32.bf16.bf16 "
        "{%0, %1, %2, %3}, "
        "%4, %5, p, 1, 1, %7, %8;\n}\n"
        : "+f"(d[0]), "+f"(d[1]), "+f"(d[2]), "+f"(d[3])
        : "l"(da), "l"(db), "r"(keep), "n"(TA), "n"(TB));
}
__device__ __forceinline__ void wgmma_rs_n192(float (&d)[96], uint32_t a0, uint32_t a1, uint32_t a2, uint32_t a3, uint64_t db) {
    asm volatile("{\n.reg .pred p;\nsetp.ne.b32 p, 1, 0;\n"
        "wgmma.mma_async.sync.aligned.m64n192k16.f32.bf16.bf16 "
        "{%0, %1, %2, %3, %4, %5, %6, %7, %8, %9, %10, %11, %12, %13, %14, %15, "
        "%16, %17, %18, %19, %20, %21, %22, %23, %24, %25, %26, %27, %28, %29, %30, %31, "
        "%32, %33, %34, %35, %36, %37, %38, %39, %40, %41, %42, %43, %44, %45, %46, %47, "
        "%48, %49, %50, %51, %52, %53, %54, %55, %56, %57, %58, %59, %60, %61, %62, %63, "
        "%64, %65, %66, %67, %68, %69, %70, %71, %72, %73, %74, %75, %76, %77, %78, %79, "
        "%80, %81, %82, %83, %84, %85, %86, %87, %88, %89, %90, %91, %92, %93, %94, %95}, "
        "{%96, %97, %98, %99}, %100, p, 1, 1, 1;\n}\n"
        : "+f"(d[0]), "+f"(d[1]), "+f"(d[2]), "+f"(d[3]), "+f"(d[4]), "+f"(d[5]), "+f"(d[6]), "+f"(d[7]),
          "+f"(d[8]), "+f"(d[9]), "+f"(d[10]), "+f"(d[11]), "+f"(d[12]), "+f"(d[13]), "+f"(d[14]), "+f"(d[15]),
          "+f"(d[16]), "+f"(d[17]), "+f"(d[18]), "+f"(d[19]), "+f"(d[20]), "+f"(d[21]), "+f"(d[22]), "+f"(d[23]),
          "+f"(d[24]), "+f"(d[25]), "+f"(d[26]), "+f"(d[27]), "+f"(d[28]), "+f"(d[29]), "+f"(d[30]), "+f"(d[31]),
          "+f"(d[32]), "+f"(d[33]), "+f"(d[34]), "+f"(d[35]), "+f"(d[36]), "+f"(d[37]), "+f"(d[38]), "+f"(d[39]),
          "+f"(d[40]), "+f"(d[41]), "+f"(d[42]), "+f"(d[43]), "+f"(d[44]), "+f"(d[45]), "+f"(d[46]), "+f"(d[47]),
          "+f"(d[48]), "+f"(d[49]), "+f"(d[50]), "+f"(d[51]), "+f"(d[52]), "+f"(d[53]), "+f"(d[54]), "+f"(d[55]),
          "+f"(d[56]), "+f"(d[57]), "+f"(d[58]), "+f"(d[59]), "+f"(d[60]), "+f"(d[61]), "+f"(d[62]), "+f"(d[63]),
          "+f"(d[64]), "+f"(d[65]), "+f"(d[66]), "+f"(d[67]), "+f"(d[68]), "+f"(d[69]), "+f"(d[70]), "+f"(d[71]),
          "+f"(d[72]), "+f"(d[73]), "+f"(d[74]), "+f"(d[75]), "+f"(d[76]), "+f"(d[77]), "+f"(d[78]), "+f"(d[79]),
          "+f"(d[80]), "+f"(d[81]), "+f"(d[82]), "+f"(d[83]), "+f"(d[84]), "+f"(d[85]), "+f"(d[86]), "+f"(d[87]),
          "+f"(d[88]), "+f"(d[89]), "+f"(d[90]), "+f"(d[91]), "+f"(d[92]), "+f"(d[93]), "+f"(d[94]), "+f"(d[95])
        : "r"(a0), "r"(a1), "r"(a2), "r"(a3), "l"(db));
}
__device__ __forceinline__ void wgmma_rs_n8(float (&d)[4], uint32_t a0, uint32_t a1, uint32_t a2, uint32_t a3, uint64_t db) {
    asm volatile("{\n.reg .pred p;\nsetp.ne.b32 p, 1, 0;\n"
        "wgmma.mma_async.sync.aligned.m64n8k16.f32.bf16.bf16 "
        "{%0, %1, %2, %3}, "
        "{%4, %5, %6, %7}, %8, p, 1, 1, 0;\n}\n"
        : "+f"(d[0]), "+f"(d[1]), "+f"(d[2]), "+f"(d[3])
        : "r"(a0), "r"(a1), "r"(a2), "r"(a3), "l"(db));
}

template <int HS>
__device__ __forceinline__ void attn_pair(const uint32_t* q, const uint32_t* k, const uint32_t* v, const uint32_t* kh, const uint32_t* vh,
                                          const float* fu, const float* fn, const float* rk, float bias0, float bias1, uint32_t mU, uint32_t zero, const float* ci, uint32_t* o) {
    float s0[2][4] = {}, s1[2][4] = {}, s2[2][4] = {};
#pragma unroll
    for (int n = 0; n < 4; n++) {
        const int hd = n & 1, a = 8 * hd + 2 * (n & 2);
        mma16816(s1[hd], q[a], q[a + 1], q[a + 2], q[a + 3], k[a], k[a + 2]);
        mma16816(s2[hd], q[a], q[a + 1], q[a + 2], q[a + 3], k[a + 1], k[a + 3]);
    }
#pragma unroll
    for (int n = 0; n < 4; n++) {
        const int hd = n & 1, a = 8 * hd + 2 * (n & 2);
        mma16816(s0[hd], q[a], q[a + 1], q[a + 2], q[a + 3], kh[HS * (a / 2)], kh[HS * (a / 2 + 1)]);
    }
    float e[2][4], m[2][2];
#pragma unroll
    for (int hd = 0; hd < 2; hd++) {
        e[hd][2] = fmaf(s1[hd][2], fu[2], s2[hd][2] * fn[2]); e[hd][3] = fmaf(s1[hd][3], fu[3], s2[hd][3] * fn[3]);
        e[hd][0] = fmaf(s0[hd][0], fu[0], fmaf(s1[hd][0], fn[0], bias0)); e[hd][1] = fmaf(s0[hd][1], fu[1], fmaf(s1[hd][1], fn[1], bias1));
        m[hd][1] = fmaxf(e[hd][2], e[hd][3]); m[hd][0] = fmaxf(e[hd][0], e[hd][1]);
    }
#pragma unroll
    for (int x = 1; x < 3; x++)
#pragma unroll
        for (int n = 0; n < 4; n++) m[n & 1][1 - (n >> 1)] = fmaxf(m[n & 1][1 - (n >> 1)], __shfl_xor_sync(0xffffffffu, m[n & 1][1 - (n >> 1)], x));
#pragma unroll
    for (int hd = 0; hd < 2; hd++) {
#pragma unroll
        for (int n = 0; n < 4; n++) e[hd][n] = ex2(e[hd][n] - m[hd][n >> 1]);
        float sum[4] = {};
        mma1688(sum, pack_bf16(e[hd][0], e[hd][1]), pack_bf16(e[hd][2], e[hd][3]), 0x3f803f80u);
        const float i0 = rcp(sum[0]), i1 = rcp(sum[2]);
        const uint32_t plo = pack_bf16(e[hd][0] * rk[0] * i0, e[hd][1] * rk[1] * i0), phi = pack_bf16(e[hd][2] * rk[2] * i1, e[hd][3] * rk[3] * i1);
        const uint32_t z0 = plo & zero, z1 = phi & zero;
        const uint32_t a0 = plo & ~mU, a1 = phi & mU, a3 = phi & ~mU, b0 = plo & mU;
#pragma unroll
        for (int jj = 0; jj < 4; jj++) {
            float c[4];
            asm volatile("mma.sync.aligned.m16n8k16.row.col.f32.bf16.bf16.f32 {%0,%1,%2,%3}, {%4,%5,%6,%7}, {%8,%9}, {%10,%11,%12,%13};"
                         : "=f"(c[0]), "=f"(c[1]), "=f"(c[2]), "=f"(c[3])
                         : "r"(a0), "r"(a1), "r"(z0), "r"(a3), "r"(v[8 * hd + 2 * jj]), "r"(v[8 * hd + 2 * jj + 1]), "f"(ci[0]), "f"(ci[1]), "f"(ci[2]), "f"(ci[3]));
            mma1688(c, b0, z1, vh[HS * (4 * hd + jj)]);
            o[8 * hd + 2 * jj] = pack_bf16(c[0], c[1]); o[8 * hd + 2 * jj + 1] = pack_bf16(c[2], c[3]);
        }
    }
}

__device__ __forceinline__ uint32_t norm_pair(uint32_t u, float m, float rinv) {
    const uint32_t d = pack_bf16(bf_lo(u) - m, bf_hi(u) - m);
    return max(pack_bf16(bf_lo(d) * rinv, bf_hi(d) * rinv), 1u);
}

__global__ void __launch_bounds__(512, 1)
fused_kernel(const __grid_constant__ CUtensorMap mx, const __grid_constant__ CUtensorMap mw, const __grid_constant__ CUtensorMap mwo,
             const __grid_constant__ CUtensorMap mout, const __grid_constant__ CUtensorMap mgu, const __grid_constant__ CUtensorMap mwd,
             const __grid_constant__ CUtensorMap mo, const __grid_constant__ CUtensorMap mr,
             const __nv_bfloat16* __restrict__ x, const __nv_bfloat16* __restrict__ wr, Scratch* __restrict__ scr, int swap_gu, const Weights pf) {
    extern __shared__ __align__(1024) uint8_t smem[];
    const uint32_t sb = smem_u32(smem);
    const uint32_t bars = sb + OFF_BAR;
    const int tid = threadIdx.x, lane = tid & 31, warp = __shfl_sync(0xffffffffu, tid >> 5, 0);
    const uint32_t sd = (sb & 0x3FFFF) >> 4;
    const int hp = blockIdx.x & 1, cl = blockIdx.x >> 1;
    int pr = cl - 4 + (max(cl - 36, 0) * 37 >> 8);
    asm("{\n.reg .pred p;\nsetp.lt.s32 p, %1, 4;\nselp.s32 %0, %2, %0, p;\n}" : "+r"(pr) : "r"(cl), "r"(39 + 8 * cl));
    const int b = pr * 2 + hp, mt = pr >> 3, p = pr & 7, nt = 2 * p + hp, rh = p & 1, cb = (p & 6) + hp;
    const int par = mt >> 2, j0 = (mt & 3) * 256;
    int budget = BUDGET;

    TSC(tid == 0, 0);
    auto load_w = [&](int k, int s) {
        const uint32_t full = bars + 8 * (B_WFULL + s);
        mbar_expect_tx(full, W_BYTES);
        tma_3d(sb + OFF_W + s * W_BYTES, &mw, full, nt * 64, k * 64, 0);
    };
    auto load_x = [&](int n) {
        const int w = n & 1, j = n < 4 ? (n >> 1) + 4 : (n >> 1) - 2;
        const uint32_t full = bars + 8 * (B_XFULL + w * 6 + 5 - j);
        mbar_expect_tx(full, BOX);
        tma_4d(sb + w * OFF_X1 + j * BOX, &mx, full, par * 1024 + (n >> 2) * 64, 0, (j0 + w * 128) >> 5, (~n >> 1) & 1);
    };
    if (warp < NBAR / 6 && elect_one()) {
        const uint32_t cnt = warp < B_WEMPTY / 6 ? 1 : warp < B_G1DONE / 6 ? 2 : warp < B_STAGED / 6 ? 4 : 8;
#pragma unroll
        for (int i = 0; i < 6; i++) mbar_init(bars + 48 * warp + 8 * i, cnt);
        asm volatile("fence.mbarrier_init.release.cluster;" ::: "memory");
        if (warp == 0 && b < 128) { load_x(0); load_w(0, 2); }
    }
    __syncthreads();

    if (b >= 128) {
        const int hc = b - 128, g = lane >> 2, t = lane & 3;
        const uint32_t ep = ld_rlx(&scr->epoch[0]) + 1;
        if (warp < 12) {
            const int n = warp / 3, part = warp - 3 * n;
            auto load = [&](int k) {
                const uint32_t full = bars + 8 * (2 * n + (k & 1));
                mbar_expect_tx(full, W_BYTES);
                tma_3d(sb + (2 * n + (k & 1)) * W_BYTES, &mw, full, (4 * hc + n) * 64, k * 64, 0);
            };
            if (part == 0 && elect_one()) { load(0); load(1); }
            __syncwarp();
            float c0[4] = {0.f, 0.f, 0.f, 0.f}, c1[4] = {0.f, 0.f, 0.f, 0.f};
            const uint32_t sel = g == 0 ? 0x3f80u : g == 1 ? 0x3f800000u : 0u;
            const uint32_t a = sb + 2 * n * W_BYTES + part * BOX + t * 256 + ((g ^ (2 * t)) << 4);
#pragma unroll 1
            for (int k = 0; k < 16; k++) {
                mbar_wait(bars + 8 * (2 * n + (k & 1)), (k >> 1) & 1, budget);
                uint4 v[8], u[8];
#pragma unroll
                for (int i = 0; i < 8; i++) { v[i] = lds4(a + (k & 1) * W_BYTES + i * 1024); u[i] = lds4(((a + 128) ^ 16) + (k & 1) * W_BYTES + i * 1024); }
                bar_sync(1 + n, 96);
                if (part == k % 3 && k < 14 && elect_one()) load(k + 2);
                __syncwarp();
#pragma unroll
                for (int i = 0; i < 8; i++) { mma16816(c0, v[i].x, v[i].y, u[i].x, u[i].y, sel, sel); mma16816(c1, v[i].z, v[i].w, u[i].z, u[i].w, sel, sel); }
            }
            if (t == 0) {
#pragma unroll
                for (int r = 0; r < 3; r++) {
                    const uint32_t q0 = (pack_bf16(c0[0], c0[1]) & ~1u) | (ep & 1), q1 = pack_bf16(c0[2], c0[3]), q2 = pack_bf16(c1[0], c1[1]), q3 = pack_bf16(c1[2], c1[3]);
                    st_rlx4(&scr->cs[4 * hc + n][r][part * 8 + g], q0, q1, q2, q3);
                    c0[0] -= bf_lo(q0); c0[1] -= bf_hi(q0); c0[2] -= bf_lo(q1); c0[3] -= bf_hi(q1);
                    c1[0] -= bf_lo(q2); c1[1] -= bf_hi(q2); c1[2] -= bf_lo(q3); c1[3] -= bf_hi(q3);
                }
            }
            TSC(tid == 0, 19);
        }
        {
            const int wg = warp >> 2, c2 = 4 * hc + wg, tw = tid & 127;
            const uint32_t ring = sb + wg * 6 * BOX, full = bars + 8 * (8 + wg * 6), ha = sb + 24 * BOX;
            const uint32_t* hsrc = scr->act[ep & 1] + (56 - NH) * 256;
            auto load = [&](int q, int s) { mbar_expect_tx(full + 8 * s, BOX); tma_3d(ring + s * BOX, &mwd, full + 8 * s, 0, (56 - NH + q) * 64, c2); };
            const uint32_t key = poll_all(&scr->sel[lane & 7], 31u, ep & 31, budget);
            __syncthreads();
            TSC(tid == 0, 12);
            if ((warp & 3) == 0 && elect_one()) {
#pragma unroll 1
                for (int q = 0; q < 6; q++) load(q, q);
            }
            __syncwarp();
            const int zr = (2047 - ((__shfl_sync(0xffffffffu, key, warp >> 1) >> 5) & 2047)) & ~30;
#pragma unroll
            for (int i = 0; i < 8; i++) st_rlx4(pf.out + (size_t)(zr + (warp & 1) * 16 + 2 * i) * 2048 + hc * 512 + lane * 16, 0, 0, 0, 0);
            __syncthreads();
            uint32_t wa[NR * 16];
#pragma unroll
            for (int q = 0; q < NR; q++) {
                mbar_wait(full + 8 * q, 0, budget);
#pragma unroll
                for (int j = 0; j < 4; j++) ldsm4t(wa + 16 * q + 4 * j, ring + q * BOX + j * 2048 + (lane >> 4) * 1024 + (lane & 7) * 128 + ((((warp & 3) * 2 + ((lane >> 3) & 1)) ^ (lane & 7)) << 4));
                bar_sync(1 + wg, 128);
                if ((warp & 3) == 0 && elect_one()) load(q + 6, q);
                __syncwarp();
            }
            if (tid == 64) { fence_gpu(); st_rlx(&scr->zflag[hc], ep); }
            if (warp == 1 && elect_one()) {
                int tries = BUDGET;
#pragma unroll 1
                while (ld_rlx(&scr->cnt[8][0]) != ep * (4 * NH) && --tries > 0) {}
                mbar_expect_tx(bars + 8 * 32, NH * 1024);
                bulk_g2s(ha, hsrc, NH * 1024, bars + 8 * 32);
                TS(17);
            }
            __syncwarp();
            mbar_wait(bars + 8 * 32, 0, budget);
#pragma unroll 1
            for (int i = tid; i < NH * 64; i += 512) {
                int tries = BUDGET;
                if (lds1(ha + i * 16) == 0) {
                    uint4 v;
#pragma unroll 1
                    do { v = ld_rlx4(hsrc + i * 4); } while (v.x == 0 && --tries > 0);
                    sts4(ha + i * 16, v.x, v.y, v.z, v.w);
                }
            }
            fence_async_smem();
            __syncthreads();
            TSC(tid == 0, 5);
            float acc[4] = {0.f, 0.f, 0.f, 0.f};
            int left = BUDGET;
            mbar_wait(full + 8 * NR, 0, left);
            const uint32_t da = sd + dlo(wg * 6 * BOX, BOX), db = sd + dlo(24 * BOX, 128), ahi = dhi(1024, 1) | (left >> 30), bhi = dhi(128, 0) | (left >> 30);
            uint4 v[8];
#pragma unroll
            for (int q = NR; q < NH; q++) {
                if (q > NR) mbar_wait(full + 8 * (q % 6), (q / 6) & 1, left);
                TSC(TIMING % 10 == 7 && tid == 0, 32 + q);
                wg_fence();
#pragma unroll
                for (int j = 0; j < 4; j++) wgmma_n8<1, 0>(acc, mkdesc(da + q % 6 * 512 + j * 128, ahi), mkdesc(db + q * 64 + j * 16, bhi), 1);
                wg_commit();
                if (q > NR && q + 5 < NH) {
                    wg_wait<1>();
                    if ((warp & 3) == (q & 3) && elect_one()) load(q + 5, (q - 1) % 6);
                    __syncwarp();
                }
                if (q == NR + RS_AT) {
                    wg_fence();
#pragma unroll
                    for (int j = 0; j < 4 * NR; j++) wgmma_rs_n8(acc, wa[4 * j], wa[4 * j + 1], wa[4 * j + 2], wa[4 * j + 3], mkdesc(db + j * 16, bhi));
                    wg_commit();
                }
                if (q == NH - Y_AT) {
#pragma unroll
                    for (int m = 0; m < 8; m++) v[m] = ld_rlx4(&scr->ypart[m][c2][tw]);
                }
            }
            wg_wait<0>();
            TSC(tid == 0, 18);
#pragma unroll 1
            for (int tries = BUDGET; tries > 0; tries--) {
                uint32_t bad = 0;
#pragma unroll
                for (int m = 0; m < 8; m++) bad |= v[m].x ^ ep;
                if (!(bad & 1)) break;
#pragma unroll
                for (int m = 0; m < 8; m++) if ((v[m].x ^ ep) & 1) v[m] = ld_rlx4(&scr->ypart[m][c2][tw]);
            }
            __syncwarp();
            const float sig = bf16r(sigmoidf(__uint_as_float(((int)key < 0 ? key & 0x7fffffffu : ~key) & 0xffff0000u)));
#pragma unroll
            for (int c = 0; c < 4; c++) {
#pragma unroll
                for (int m = 0; m < 8; m++) acc[c] += __uint_as_float((&v[m].x)[c]);
                acc[c] = bf16r(acc[c]) * __shfl_sync(0xffffffffu, sig, 2 * t + (c & 1));
            }
            char* dst = pf.out + (size_t)(2047 - ((__shfl_sync(0xffffffffu, key, g) >> 5) & 2047)) * 2048 + c2 * 128 + (warp & 3) * 32 + t * 4;
            asm volatile("red.relaxed.gpu.global.add.noftz.bf16x2 [%0], %1;" ::"l"(dst), "r"(movm(pack_bf16(acc[0], acc[1]))) : "memory");
            asm volatile("red.relaxed.gpu.global.add.noftz.bf16x2 [%0], %1;" ::"l"(dst + 16), "r"(movm(pack_bf16(acc[2], acc[3]))) : "memory");
            TSC(tid == 0, 20);
        }
        if (warp < 8) TS_END();
        return;
    }
    asm volatile("barrier.cluster.arrive.relaxed.aligned;" ::: "memory");

    const int c2 = b & 15, n2 = mt < 7 ? NM : N7;
    if (warp >= 12) {
        reg_dec<24>();
        if (warp == 12) {
            if (elect_one()) {
                int c = 0;
                if (START == 2 || START == 3) load_w(1, 0);
#pragma unroll 1
                for (int n = START == 0 ? 1 : START == 1 ? 2 : 4; n < 12; n++) {
                    load_x(n);
                    #pragma unroll 1
                    for (; c < (n == 11 ? 4 : __popc(ROWS_AT & ((2 << n) - 1))); c++) { mbar_expect_tx(bars + 8 * (B_ROW + c), BOX); tma_2d(sb + OFF_FR + c * BOX, &mr, bars + 8 * (B_ROW + c), c * 256, b * 16); }
                    if (n == 3 || n == 7) load_w((n + 1) >> 2, n >> 2);
                }
                int s = 2; uint32_t ph = 0;
#pragma unroll 1
                for (int k = 3; k < 16; k++) {
                    mbar_wait(bars + 8 * (B_WEMPTY + s), ph, budget);
                    load_w(k, s);
                    if (++s == 3) s = 0;
                    if (s == 2) ph ^= 1;
                }
                s = 2;
#pragma unroll 1
                for (int i = 0; i < 16; i++) {
                    mbar_wait(bars + 8 * (i < 2 ? B_WEMPTY + i : i < 4 ? B_G1DONE : i < 6 ? B_F1DONE : B_WOEMPTY + s), i >= 12, budget);
                    if (i == 0) {
                        mbar_expect_tx(bars + 8 * B_XT, 4 * BOX);
#pragma unroll 1
                        for (int n = 0; n < 4; n++)
                            tma_4d(sb + (n >> 1) * OFF_X1 + (n & 1) * BOX, &mx, bars + 8 * B_XT, par * 1024 + cb * 128 + (n & 1) * 64, 0, (j0 + rh * 128) >> 5, 1 - (n >> 1));
                    }
                    const uint32_t full = bars + 8 * (B_WOFULL + s);
                    mbar_expect_tx(full, 2 * BOX);
                    tma_3d(sb + OFF_WO + s * 2 * BOX, &mwo, full, 0, ((2 * p + (i < 2 ? i ^ hp : i)) & 15) * 64, cb * 2);
                    TSC(TIMING % 10 == 4, 48 + i);
                    if (++s == 6) s = 0;
                }
            }
        } else {
            bar_sync(8, 224);
            const uint32_t ep = __shfl_sync(0xffffffffu, lds1(sb + OFF_EP), 0);
            if (warp == 13) {
                cluster_wait();
                if (elect_one()) {
                    int j = 4, q = 0, left = BUDGET; uint32_t ph = 0;
#pragma unroll 1
                    for (int n = 6; n < 32; n++) {
                        mbar_wait(bars + 8 * (B_XEMPTY + j), ph, left);
                        tma_4d_mc(sb + hp * OFF_X1 + j * BOX, &mx, bars + 8 * (B_XFULL + hp * 6 + 5 - j), par * 1024 + (n >> 1) * 64, 0, (j0 + hp * 128) >> 5, ~n & 1);
                        if (++j == 6) j = 0;
                        if (j == 4) ph ^= 1;
#pragma unroll 1
                        for (; q < (PF_RATE * (n - PF_START) >> 3) && q < 18 + PF_NW; q++) {
                            const int u = q - PF_NW;
                            if (u < 0) bulk_pf(pf.wqkv + (size_t)(1024 + 128 * u + b) * 6144, 6144);
                            else if (u < 16) bulk_pf((b < 64 ? pf.wg : pf.wu) + (size_t)(u * 64 + (b & 63)) * 7168, 7168);
                            else bulk_pf(pf.wo + (size_t)((u - 16) * 128 + b) * 8192, 8192);
                        }
                    }
                }
                __syncwarp();
                uint32_t* hs = &scr->halo[b - 16][lane * 4];
                uint4 v[4] = {};
                if (j0) {
#pragma unroll 1
                    do {
#pragma unroll
                        for (int c = 0; c < 4; c++) v[c] = ld_rlx4(hs + c * 128);
                    } while (__any_sync(0xffffffffu, min(min(v[0].x, v[1].x), min(v[2].x, v[3].x)) == 0) && --budget > 0);
#pragma unroll
                    for (int c = 0; c < 4; c++) st_rlx(hs + c * 128, 0);
                }
#pragma unroll
                for (int c = 0; c < 4; c++) stsm4(sb + OFF_HIN + c * 512 + lane * 16, v[c].x, v[c].y, v[c].z, v[c].w);
                bar_arrive(11, 64);
                TSC(lane == 0, 31);
                const int src = ((mt * 2 + rh) * 2 + 1 - hp) * 1024;
                if (elect_one()) {
                    const uint32_t* fl = &scr->oflag[mt * 2 + 1 - hp][0];
                    const uint32_t inv = (ep & 1) - 1;
                    uint32_t ready = 0, ph = 0;
                    int s = 4;
#pragma unroll 1
                    for (int i = 2; i < 16; i++) {
                        const int kb = (2 * p + i) & 15;
#pragma unroll 1
                        while (!((ready >> kb) & 1) && --budget > 0) ready = ld_rlx(fl) ^ inv;
                        TSC(i == 2, 30);
                        mbar_wait(bars + 8 * (B_OEMPTY + s), ph, budget);
                        tma_2d_mc(sb + hp * OFF_X1 + s * BOX, &mo, bars + 8 * (B_OFULL + hp * 6 + s), 0, src + kb * 64);
                        TSC(TIMING % 10 == 4 && hp == 0, 32 + i);
                        if (++s == 6) s = 0;
                        if (s == 4) ph ^= 1;
                    }
                }
            } else if (warp == 14) {
                if (elect_one()) {
                    uint32_t s8 = 0, ph = 0;
                    int tries = BUDGET;
                    const uint32_t* act = scr->act[ep & 1];
                    auto counted = [&](int c, uint32_t n) {
#pragma unroll 1
                        while (ld_rlx(&scr->cnt[c][0]) != ep * n && --tries > 0) __nanosleep(POLL_NS);
                    };
                    auto weights = [&](const CUtensorMap* m, int c0, int c1, int c2_) {
                        mbar_wait(bars + 8 * B_FEMPTY + s8, ph, budget);
                        mbar_expect_tx(bars + 8 * B_FFULL + s8, F_BYTES);
                        tma_3d(sb + OFF_FS + s8 * (F_BYTES / 8), m, bars + 8 * B_FFULL + s8, c0, c1, c2_);
                    };
                    if (b < 112) {
                        counted(9, 32);
                        TS(26);
#pragma unroll 1
                        for (int q = 0; q < 16; q++) {
                            weights(&mgu, b * 32, q * 64, 0);
                            bulk_g2s(sb + OFF_FS + BOX + s8 * (F_BYTES / 8), act + 14336 + q * 256, 1024, bars + 8 * B_FFULL + s8);
                            TSC(TIMING % 10 == 5, 32 + q);
                            if (q >= PF_D && q < PF_D + PF_DN) bulk_pf(pf.wd + 7340032 - (size_t)((PF_REV ? q - PF_D + 1 : PF_DN + PF_D - q) * 112 - b) * PF_DB, PF_DB);
                            s8 += 8;
                            if (s8 == 40) { s8 = 0; ph ^= 1; }
                        }
                    }
#pragma unroll 1
                    for (int q = -3; q < n2; q++) {
                        if (q == 0) { counted(mt, 4 * n2); TS(29); }
                        if ((unsigned)q >= 3) weights(&mwd, 0, (mt * NM + (q < 0 ? q + 3 : q)) * 64, c2);
                        if (q >= 0) bulk_g2s(sb + OFF_FS + BOX + s8 * (F_BYTES / 8), act + (mt * NM + q) * 256, 1024, bars + 8 * B_FFULL + s8);
                        TSC(TIMING % 10 == 5, 51 + q);
                        s8 += 8;
                        if (s8 == 24) { s8 = 0; if ((unsigned)q >= 3) ph ^= 1; }
                    }
                }
            } else {
#pragma unroll 1
                for (int i = lane * 16; i < CS_BYTES; i += 512) sts4(sb + OFF_CS + i, 0, 0, 0, 0);
                mbar_wait(bars + 8 * ZF_GATE, 0, budget);
                uint8_t* oz = scr->o + ((size_t)mt * 64 + nt) * BOX + lane * 16;
#pragma unroll 1
                for (int i = 0; i < 16; i++, oz += 512) {
#pragma unroll
                    for (int n = 0; n < 4; n++) st_rlx4(oz + n * 16 * BOX, 0, 0, 0, 0);
                    __nanosleep(ZF_NS);
                }
                __syncwarp();
                TSC(lane == 0, 5);
                fence_gpu();
                TSC(lane == 0, 12);
                mbar_wait(bars + 8 * B_RDONE, 0, budget);
                int tries = BUDGET;
#pragma unroll 1
                for (int i = lane; i < 88; i += 32) {
                    const uint2* rp = &scr->row[2 * (j0 - 8 + i) + par];
                    uint2 v0, v1, v2;
#pragma unroll 1
                    do { v0 = ld_rlx2(rp + (j0 + i < 8 ? 16 : 0)); v1 = ld_rlx2(rp + 176); v2 = ld_rlx2(rp + 352); } while ((((v0.y ^ ep) | (v1.y ^ ep) | (v2.y ^ ep)) & 31) && --tries > 0);
                    sts2(sb + OFF_STAT + i * 8, (v0.x << 16) ^ 0x80000000u, __float_as_uint(rcp(bf_hi(v0.x))));
                    sts2(sb + OFF_STAT + i * 8 + 704, (v1.x << 16) ^ 0x80000000u, __float_as_uint(rcp(bf_hi(v1.x))));
                    sts2(sb + OFF_STAT + i * 8 + 1408, (v2.x << 16) ^ 0x80000000u, __float_as_uint(rcp(bf_hi(v2.x))));
                }
                __syncwarp();
                {
                    const int row = 2047 - ((poll_all(&scr->sel[lane & 7], 31u, ep & 31, budget) >> 5) & 2047), jj = (row >> 1) - j0 - rh * 128;
                    sts1(sb + OFF_SEL, __reduce_or_sync(0xffffffffu, (row & 1) == par && (unsigned)jj < 128 ? 1u << (jj >> 4) : 0u));
                }
                TSC(lane == 0, 14);
                if (lane < 24) {
                    uint4 v[3];
#pragma unroll 1
                    while (v[0] = ld_rlx4(&scr->cs[nt][0][lane]), v[1] = ld_rlx4(&scr->cs[nt][1][lane]), v[2] = ld_rlx4(&scr->cs[nt][2][lane]),
                           (((v[0].x ^ ep) | (v[1].x ^ ep) | (v[2].x ^ ep)) & 1) && --tries > 0) __nanosleep(100);
#pragma unroll
                    for (int r = 0; r < 3; r++) sts4(sb + OFF_CS + 64 + lane * 128 + r * 16, v[r].x, v[r].y, v[r].z, v[r].w);
                }
                fence_async_smem();
                __syncwarp();
                if (elect_one()) {
                    mbar_arrive(bars + 8 * B_AUX);
                    TS(21);
                    mbar_expect_tx(bars + 8 * (B_OFULL + 3), BOX); mbar_expect_tx(bars + 8 * (B_OFULL + 9), BOX);
#pragma unroll 1
                    for (int v = 0; v < 2; v++) {
                        const uint32_t ring = sb + v * OFF_X1 + 2 * BOX, fb = bars + 8 * (B_OFULL + v * 6 + 2);
                        mbar_wait(bars + 8 * (B_STAGED + v), 0, budget);
                        asm volatile("red.relaxed.gpu.global.xor.b32 [%0], %1;" ::"l"(&scr->oflag[mt * 2 + 1 - v][0]), "r"(1u << nt) : "memory");
                        TS(13 + 2 * v);
                        mbar_arrive(fb);
                        mbar_wait(bars + 8 * B_G1DONE, 0, budget);
                        bulk_s2c(mapa(ring + BOX, hp ^ 1), ring, BOX, mapa(fb + 8, hp ^ 1));
                        if (v == 0) mbar_wait(bars + 8 * B_FREED, 0, budget);
#pragma unroll
                        for (int n = 0; n < 4; n++) {
                            mbar_expect_tx(bars + 8 * (B_OFULL + (n >> 1) * 6 + 4 + (n & 1)) - v * 32, BOX);
                            mbar_arrive_at(mapa(bars + 8 * B_OEMPTY, n >> 1) + (4 + (n & 1)) * 8 - v * 32);
                        }
                    }
                    if (lds1(sb + OFF_SEL)) {
#pragma unroll 1
                        while (ld_acq(&scr->zflag[p >> 1]) != ep && --tries > 0) {}
                        asm volatile("fence.proxy.async.global;" ::: "memory");
                    }
                    mbar_arrive(bars + 8 * B_ZERO);
                }
            }
        }
    } else if (warp >= 8) {
        reg_dec<40>();
        const int wq = warp - 8, ta = tid - 256;
        const uint32_t rbuf = sb + OFF_FR + wq * 2048;
        const uint4 wv = ldg_nc(wr + ta * 8);
        if (ta == 0) sts1(sb + OFF_EP, ld_rlx(&scr->epoch[0]) + 1);
        sts4(sb + OFF_STAT + ta * 16, wv.x, wv.y, wv.z, wv.w);
        bar_sync(8, 224);
        const uint32_t ep = __shfl_sync(0xffffffffu, lds1(sb + OFF_EP), 0);
        {
            const int s = b * 16 + wq * 4 + (lane >> 3);
            if ((lane & 7) == 0) st_rlx2(&scr->row[s], 0, ep - 1);
            float sw = 0.f;
#pragma unroll 1
            for (int i = 0; i < 16; i++) { const uint32_t q = lds1(sb + OFF_STAT + i * 128 + lane * 4); sw += bf_lo(q) + bf_hi(q); }
#pragma unroll 1
            for (int o = 16; o > 0; o >>= 1) sw += __shfl_xor_sync(0xffffffffu, sw, o);
            float s1 = 0.f, s2 = 0.f, sr = 0.f;
            {
                float s1b = 0.f, s2b = 0.f, srb = 0.f;
                const uint32_t xb = rbuf + (lane >> 4) * 1024 + (lane & 15) * 16, wb = sb + OFF_STAT + (lane & 15) * 16;
#pragma unroll 1
                for (int i = 0; i < 8; i++) {
                    const uint4 w4 = lds4(wb + i * 256);
                    mbar_wait_hot(bars + 8 * (B_ROW + (i >> 1)), 0, budget);
                    TSC(ta == 0 && i == 0, 17);
                    const uint32_t o = (i >> 1) * BOX + (i & 1) * 256;
                    const uint4 u = lds4(xb + o), v = lds4(xb + o + 512);
#pragma unroll
                    for (int c = 0; c < 4; c++) {
                        const float w0 = bf_lo((&w4.x)[c]), w1 = bf_hi((&w4.x)[c]);
                        const float a0 = bf_lo((&u.x)[c]), a1 = bf_hi((&u.x)[c]), b0 = bf_lo((&v.x)[c]), b1 = bf_hi((&v.x)[c]);
                        s1 += a0; s2 = fmaf(a0, a0, s2); sr = fmaf(a0, w0, sr);
                        s1 += a1; s2 = fmaf(a1, a1, s2); sr = fmaf(a1, w1, sr);
                        s1b += b0; s2b = fmaf(b0, b0, s2b); srb = fmaf(b0, w0, srb);
                        s1b += b1; s2b = fmaf(b1, b1, s2b); srb = fmaf(b1, w1, srb);
                    }
                }
                const bool up = lane & 8;
                s1 = (up ? s1b : s1) + __shfl_xor_sync(0xffffffffu, up ? s1 : s1b, 8);
                s2 = (up ? s2b : s2) + __shfl_xor_sync(0xffffffffu, up ? s2 : s2b, 8);
                sr = (up ? srb : sr) + __shfl_xor_sync(0xffffffffu, up ? sr : srb, 8);
            }
#pragma unroll
            for (int o = 1; o < 8; o <<= 1) {
                s1 += __shfl_xor_sync(0xffffffffu, s1, o); s2 += __shfl_xor_sync(0xffffffffu, s2, o); sr += __shfl_xor_sync(0xffffffffu, sr, o);
            }
            const float mean = s1 * (1.f / 1024.f), mb = bf16r(mean);
            float var = fmaf(-mean, mean, s2 * (1.f / 1024.f));
            sr = fmaf(-mb, sw, sr);
            if (__builtin_expect(__any_sync(0xffffffffu, mean * mean > 256.f * var), 0)) {
                float a2 = 0.f, ar = 0.f;
#pragma unroll 1
                for (int i = 0; i < 64; i++) {
                    const uint32_t o = i * 32 + (lane & 7) * 4, q1 = lds1(rbuf + (lane >> 3) * 512 + (o >> 9) * BOX + (o & 511)), q2 = lds1(sb + OFF_STAT + o);
                    a2 = fmaf(bf_lo(q1) - mean, bf_lo(q1) - mean, fmaf(bf_hi(q1) - mean, bf_hi(q1) - mean, a2));
                    ar = fmaf(bf_lo(q1) - mb, bf_lo(q2), fmaf(bf_hi(q1) - mb, bf_hi(q2), ar));
                }
#pragma unroll 1
                for (int o = 1; o < 8; o <<= 1) { a2 += __shfl_xor_sync(0xffffffffu, a2, o); ar += __shfl_xor_sync(0xffffffffu, ar, o); }
                var = a2 * (1.f / 1024.f); sr = ar;
            }
            float den;
            asm("sqrt.approx.f32 %0, %1;" : "=f"(den) : "f"(bf16r(bf16r(var) + 1e-5f)));
            const uint32_t st = pack_bf16(mb, den);
            const uint32_t rb = pack_bf16(0.f, sr * rcp(bf_hi(st)) + 0.f);
            uint32_t ord = (int)rb < 0 ? ~rb & 0xffff0000u : rb | 0x80000000u;
            if ((rb & 0x7fffffffu) > 0x7f800000u) ord = 0;
            if ((lane & 7) == 0) st_rlx2(&scr->row[s], st, ord | ((2047 - s) << 5) | (ep & 31));
            __syncwarp();
            if (lane < 7) mbar_arrive(bars + 8 * (lane < 5 ? B_FEMPTY + lane : B_RDONE));
        }
        TSC(ta == 0, 18);
        if ((b >> 3) == 14) {
            const uint32_t gm = sb + OFF_E, cnt = gm + 64, res = gm + 80, list = gm + 128;
            uint32_t kv[16];
            int tries = BUDGET;
#pragma unroll 1
            do {
                uint32_t bad = 0;
#pragma unroll
                for (int n = 0; n < 16; n++) kv[n] = ld_rlx(&scr->row[n * 128 + ta].y);
#pragma unroll
                for (int n = 0; n < 16; n++) bad |= kv[n] ^ ep;
                if ((bad & 31) == 0) break;
            } while (--tries > 0);
            __syncwarp();
            TSC(ta == 0, 26);
            uint32_t m = 0;
#pragma unroll
            for (int n = 0; n < 16; n++) m = max(m, kv[n]);
            uint32_t gmax = m;
#pragma unroll
            for (int o = 1; o < 8; o <<= 1) gmax = max(gmax, __shfl_xor_sync(0xffffffffu, gmax, o));
            sts1(gm + (ta >> 3) * 4, gmax);
            sts1(cnt, 0);
            bar_sync(12, 128);
            const uint32_t c = lds1(gm + (lane & 15) * 4);
            int rank = 0;
#pragma unroll
            for (int i = 0; i < 2; i++) { const uint4 q = lds4(gm + (lane >> 4) * 32 + i * 16); rank += (q.x > c) + (q.y > c) + (q.z > c) + (q.w > c); }
            rank += __shfl_xor_sync(0xffffffffu, rank, 16);
            const uint32_t thr = redux_max(rank == 7 ? c : 0u);
#pragma unroll 1
            while (m >= thr) {
                uint32_t at, m2 = 0;
                asm volatile("atom.shared.add.u32 %0, [%1], 1;" : "=r"(at) : "r"(cnt) : "memory");
#pragma unroll
                for (int n = 0; n < 16; n++) m2 = max(m2, kv[n] < m ? kv[n] : 0u);
                sts1(list + at * 4, m);
                if (m2 == 0) break;
                m = m2;
            }
            bar_sync(12, 128);
            const int nc = lds1(cnt);
#pragma unroll 1
            for (int i = ta >> 3; i < ((nc + 3) & ~3); i += 16) {
                const uint32_t ki = lds1(list + i * 4);
                int r = 0;
#pragma unroll 1
                for (int n = lane & 7; n < nc; n += 8) r += lds1(list + n * 4) > ki;
                __syncwarp();
#pragma unroll
                for (int o = 1; o < 8; o <<= 1) r += __shfl_xor_sync(0xffffffffu, r, o);
                if (r == (b & 7) && i < nc) sts1(res, ki);
            }
            bar_sync(12, 128);
            const uint32_t k0 = lds1(res);
            const int r0 = 2047 - ((k0 >> 5) & 2047);
            TSC(ta == 0, 22);
            if (ta == 0) st_rlx(&scr->sel[b & 7], k0);
            const uint4 v0 = ldg_nc(x + (size_t)r0 * 1024 + ta * 8);
            const uint32_t s0 = ld_rlx(&scr->row[r0]);
            const float m0 = bf_lo(s0), i0 = rcp(bf_hi(s0));
            const int ao = 14336 + (ta >> 3) * 256 + (b & 7) * 32 + ((ta ^ b) & 7) * 4;
            st_rlx4(scr->act[ep & 1] + ao, norm_pair(v0.x, m0, i0), norm_pair(v0.y, m0, i0), norm_pair(v0.z, m0, i0), norm_pair(v0.w, m0, i0));
            __syncwarp();
            if (lane == 0) red_add(&scr->cnt[9][tries >> 30]);
            st_rlx4(scr->act[~ep & 1] + ao, 0, 0, 0, 0);
        }
        uint32_t s8 = 0, fph = 0;
        const uint32_t chk = __shfl_sync(0xffffffffu, sb + OFF_FS + BOX + lane * 32 + (lane & 28), lane);
        int left = BUDGET;
        if (b >= 112 && ta < 2) mbar_arrive(bars + 8 * B_F1DONE);
#pragma unroll 1
        for (int ph = b >= 112; ph < 2; ph++) {
            {
                float acc[4] = {0.f, 0.f, 0.f, 0.f};
                const uint32_t alo = sd + (ph ? dlo(OFF_FS, 8192) : dlo(OFF_FS, 4096)), ahi = ph ? dhi(1024, 1) : dhi(512, 2), astep = ph ? 128 : 64;
                const uint32_t bhi = ph ? dhi(128, 0) : dhi(1024, 1), bstep = ph ? 16 : 2, wrap = ph ? 24 : 40;
                uint32_t prev = 0;
                if (ph) mbar_wait(bars + 8 * FFN2_GATE, 0, left);
#pragma unroll 1
                for (int q = ph ? n2 : 16; q > 0; q--) {
                    const uint32_t da = alo + s8 * (F_BYTES >> 7), db = sd + dlo(OFF_FS + BOX, 128) + s8 * (F_BYTES >> 7);
                    mbar_wait_hot(bars + 8 * B_FFULL + s8, fph, left);
                    if (__builtin_expect(__any_sync(0xffffffffu, lds1(chk + s8 * (F_BYTES / 8)) == 0), 0)) {
                        int tries = BUDGET;
#pragma unroll 1
                        for (int n = lane * 4 + (left >> 30); n < 256; n += 128) {
                            uint4 v;
#pragma unroll 1
                            do { v = ld_rlx4(scr->act[ep & 1] + ((ph ? mt * NM + n2 : 72) - q) * 256 + n); } while (v.x == 0 && --tries > 0);
                            __syncwarp();
                            sts4(sb + OFF_FS + BOX + s8 * (F_BYTES / 8) + n * 4, v.x, v.y, v.z, v.w);
                        }
                        NRETRY();
                        fence_async_smem();
                        __syncwarp();
                    }
                    TSC(TIMING % 10 == 3 && ta == 0, 32 + (ph ? 16 + n2 : 16) - q);
                    wg_fence();
#pragma unroll
                    for (int j = 0; j < 4; j++) wgmma_n8<1, 0>(acc, mkdesc(da + j * astep, ahi), mkdesc(db + j * bstep, bhi), 1);
                    wg_commit();
                    wg_wait<1>();
                    if (ph) { wg_wait<0>(); if (lane == 0) prev = bars + 8 * B_FEMPTY + s8; }
                    if (prev) mbar_arrive(prev);
                    if (lane == 0) prev = bars + 8 * B_FEMPTY + s8;
                    s8 += 8;
                    if (s8 == wrap) { s8 = 0; fph ^= 1; }
                }
                wg_wait<0>();
                const int ln = lane + (left >> 30);
                if (ph == 0) {
                    if (prev) mbar_arrive(prev);
                    const bool second = (wq >= 2) != (swap_gu != 0);
                    const uint32_t xa = sb + OFF_GU + ((wq & 1) * 32 + ln) * 16;
                    if (second) sts4(xa, __float_as_uint(acc[0]), __float_as_uint(acc[1]), __float_as_uint(acc[2]), __float_as_uint(acc[3]));
                    bar_sync(12, 128);
                    if (second) { if (ln == 0) mbar_arrive(bars + 8 * B_F1DONE); }
                    else {
                        const float4 up = lds4f(xa);
                        float hv[4];
#pragma unroll
                        for (int c = 0; c < 4; c++) { const float ga = bf16r(acc[c]); hv[c] = bf16r(ga * sigmoidf(ga)) * bf16r((&up.x)[c]); }
                        const int ao = (b * 4 + (wq & 1) * 2) * 32 + ln;
                        st_rlx(scr->act[ep & 1] + ao, max(movm(pack_bf16(hv[0], hv[1])), 1u)); st_rlx(scr->act[ep & 1] + 32 + ao, max(movm(pack_bf16(hv[2], hv[3])), 1u));
                        __syncwarp();
                        if (ln == 0) red_add(&scr->cnt[b < 14 * NM ? b / (2 * NM) : b < 14 * NM + 2 * N7 ? 7 : 8][0]);
                        st_rlx(scr->act[~ep & 1] + ao, 0); st_rlx(scr->act[~ep & 1] + 32 + ao, 0);
                    }
                } else {
                    st_rlx4(&scr->ypart[mt][c2][wq * 32 + ln], (__float_as_uint(acc[0]) & ~1u) | (ep & 1), __float_as_uint(acc[1]), __float_as_uint(acc[2]), __float_as_uint(acc[3]));
                }
                TSC(ta == 0, 22 + ph);
            }
        }
        TSC(ta == 0, 24);
    } else {
        reg_inc<224>();
        const int w = warp >> 2, wi = warp & 3, g = lane >> 2, t = lane & 3;
        const bool elect = (tid & 127) == 0;
        const uint32_t mad = (lane & 15) * 128 + (((lane >> 4) ^ (lane & 7)) << 4);
        float acc[64];
        const uint32_t ring = sb + w * OFF_X1, ofull = bars + 8 * (B_OFULL + w * 6), oempty = mapa(bars + 8 * B_OEMPTY, w);
        const int r0 = rh * 128 + wi * 32 + (1 - w) * 16 + g;
        {
            float acc0[96], acc1[96];
            const uint32_t sta = sb + OFF_STAT + (8 + w * 128 + wi * 32) * 8;
            {
                const uint32_t xfull = bars + 8 * (B_XFULL + w * 6 + 5), xempty = mapa(bars + 8 * B_XEMPTY, w), dx0 = sd + dlo(w * OFF_X1, 16);
                uint32_t s8 = 16, ps8 = 0, ph = 0;
                cluster_wait();
#pragma unroll 1
                for (int k = 0; k < 16; k++) {
                    const uint32_t dx = dx0 + s8 * (2 * BOX >> 7), dw = sd + dlo(OFF_W, BOX) + s8 * (W_BYTES >> 7);
                    mbar_wait(bars + 8 * B_WFULL + s8, ph, budget);
                    mbar_wait(xfull - 2 * s8, ph, budget);
                    TSC(elect && k == 0, 1 + 8 * w);
                    TSC(TIMING % 10 == 1 && tid == 0, 32 + k);
                    wg_wait<0>();
                    wg_fence();
#pragma unroll
                    for (int kk = 0; kk < 4; kk++) wgmma_n192<0, 1>(acc1, mkdesc(dx + kk * 2, dhi(1024, 1)), mkdesc(dw + kk * 128, dhi(1024, 1)), kk ? 1 : k);
                    wg_commit();
                    TSC(TIMING % 10 == 6 && elect, 32 + 16 * w + k);
                    if (elect && k > 0) {
                        mbar_arrive(bars + 8 * B_WEMPTY + ps8);
                        if (k <= 13) { mbar_expect_tx(xfull - 2 * ps8 - 8, BOX); mbar_arrive_at(xempty + 2 * ps8 + 8); }
                    }
                    if (k == 15) {
                        mbar_wait(bars + 8 * B_AUX, 0, budget);
                        const uint32_t zero = budget >> 30, pm = t & 1 ? 0x4432 : 0x3232, ra = sta + ((t >> 1) * 16 + g) * 8;
                        const uint32_t a0 = __byte_perm(lds1(ra), 0, pm), a1 = __byte_perm(lds1(ra + 64), 0, pm), a2 = a0 & zero, a3 = a1 & zero;
                        wg_fence();
                        wgmma_rs_n192(acc1, a0, a1, a2, a3, mkdesc(sd + dlo(OFF_CS, 0), dhi(128, 0)));
                        wgmma_rs_n192(acc0, a0, a1, a2, a3, mkdesc(sd + dlo(OFF_CS + 64, 0), dhi(128, 0)));
                        wg_commit();
                    }
                    mbar_wait(xfull - 2 * s8 - 8, ph, budget);
                    wg_wait<0>();
                    wg_fence();
#pragma unroll
                    for (int kk = 0; kk < 4; kk++) wgmma_n192<0, 1>(acc0, mkdesc(dx + 512 + kk * 2, dhi(1024, 1)), mkdesc(dw + kk * 128, dhi(1024, 1)), kk ? 1 : k);
                    wg_commit();
                    if (elect && k <= 12) { mbar_expect_tx(xfull - 2 * s8, BOX); mbar_arrive_at(xempty + 2 * s8); }
                    ps8 = s8;
                    s8 = s8 == 16 ? 0 : s8 + 8;
                    if (s8 == 16) ph ^= 1;
                }
            }
            const uint32_t zero = budget >> 30;
            const bool u0 = 2 * t > g, u1 = 2 * t + 1 > g;
            uint32_t mU = (u0 ? 0xffffu : 0u) | (u1 ? 0xffff0000u : 0u);
            uint32_t ka0 = sta + (2 * t - (u0 ? 8 : 0)) * 8 + 4, ka1 = sta + (2 * t + 1 - (u1 ? 8 : 0)) * 8 + 4;
            float rk[2][4], fu[2][4], fn[2][4];
            auto factors = [&](int h) {
#pragma unroll
                for (int n = 0; n < 4; n += 2) {
                    const float rq = lds1f(sta + (16 * h + 4 * n + g) * 8 + 4) * (0.17677669529663687f * 1.4426950408889634f);
                    rk[h][n] = lds1f(ka0 + h * 128 + n * 32); rk[h][n + 1] = lds1f(ka1 + h * 128 + n * 32);
                    const float f0 = rq * rk[h][n], f1 = rq * rk[h][n + 1];
                    fu[h][n] = u0 ? f0 : 0.f; fn[h][n] = f0 - fu[h][n]; fu[h][n + 1] = u1 ? f1 : 0.f; fn[h][n + 1] = f1 - fu[h][n + 1];
                }
#pragma unroll
                for (int n = 0; n < 4; n++) asm volatile("" : "+f"(fu[h][n]), "+f"(fn[h][n]));
            };
            uint8_t* og = scr->o + ((size_t)(mt * 4 + w * 2) * 16 + nt) * BOX + wi * 256 + lane * 4;
            TSC(elect, 19 + w);
            uint32_t pk0[48], pk1[48], o[16] = {};
#pragma unroll
            for (int j = 0; j < 48; j++) if (j < 16 || (j & 1)) pk1[j] = pack_here(acc1[2 * j], acc1[2 * j + 1]);
            if (warp < 7) {
#pragma unroll
                for (int c = 0; c < 4; c++) stsm4(ring + 4 * BOX + wi * 2048 + c * 512 + lane * 16, pk1[17 + 8 * c], pk1[19 + 8 * c], pk1[21 + 8 * c], pk1[23 + 8 * c]);
                bar_arrive(1 + warp, 64);
            } else if (j0 != 768) {
#pragma unroll
                for (int c = 0; c < 4; c++) {
                    pk1[17 + 8 * c] = max(pk1[17 + 8 * c], 1u);
                    st_rlx4(&scr->halo[b][c * 128 + lane * 4], pk1[17 + 8 * c], pk1[19 + 8 * c], pk1[21 + 8 * c], pk1[23 + 8 * c]);
                }
            }
            TSC(tid == 224, 28);
#pragma unroll
            for (int j = 16; j < 48; j += 2) pk1[j] = pack_here(acc1[2 * j], acc1[2 * j + 1]);
            factors(1);
            uint32_t od = sb + 2 * BOX + wi * 256 + (lane >> 4) * 1024 + (lane & 15) * 16, g1peer = mapa(bars + 8 * B_G1DONE, hp ^ 1);
            uint32_t ha = sb + (warp == 0 ? OFF_HIN : warp <= 4 ? 4 * BOX - 2048 : OFF_X1 + 4 * BOX - 5 * 2048) + warp * 2048 + lane * 16;
            const bool first = warp == 0 && j0 == 0;
            float bias0 = first && u0 ? -INFINITY : 0.f, bias1 = first && u1 ? -INFINITY : 0.f;
            asm volatile("" : "+l"(og), "+r"(mU), "+r"(od), "+r"(ha), "+f"(bias0), "+f"(bias1));
            mbar_wait(bars + 8 * B_XT, 0, budget);
            mbar_wait(bars + 8 * (B_WEMPTY + 1), 0, budget);
            wg_wait<0>();
            if (elect) { mbar_arrive(bars + 8 * B_G1DONE); mbar_arrive_at(g1peer); }
            TSC(elect, 2 + 8 * w);
            float ci[4];
#pragma unroll
            for (int n = 0; n < 4; n++) ci[n] = __uint_as_float((0x03800000u + n) | (budget >> 30));
            auto hand_over = [&](int v) {
                asm volatile("{\n.reg .pred p;\nsetp.ne.b32 p, %17, 0;\n"
                             "@p stmatrix.sync.aligned.m8n8.x4.shared.b16 [%16], {%0,%1,%2,%3};\n@p stmatrix.sync.aligned.m8n8.x4.shared.b16 [%16 + 2048], {%4,%5,%6,%7};\n"
                             "@p stmatrix.sync.aligned.m8n8.x4.shared.b16 [%16 + 4096], {%8,%9,%10,%11};\n@p stmatrix.sync.aligned.m8n8.x4.shared.b16 [%16 + 6144], {%12,%13,%14,%15};\n"
                             "fence.proxy.async.shared::cta;\n}"
                             ::"r"(o[0]), "r"(o[1]), "r"(o[2]), "r"(o[3]), "r"(o[4]), "r"(o[5]), "r"(o[6]), "r"(o[7]), "r"(o[8]), "r"(o[9]), "r"(o[10]), "r"(o[11]),
                               "r"(o[12]), "r"(o[13]), "r"(o[14]), "r"(o[15]), "r"(od + v * OFF_X1), "r"((int)(w == rh)) : "memory");
#pragma unroll
                for (int i = 0; i < 16; i++) asm volatile("st.global.u32 [%0], %1;" ::"l"(og + (1 - v) * 16 * BOX + (i >> 1) * 1024 + (i & 1) * 128), "r"(o[i]) : "memory");
                __syncwarp();
                if (lane == 0) mbar_arrive(bars + 8 * (B_STAGED + v));
            };
#pragma unroll
            for (int j = 32; j < 48; j++) pk1[j] = movm(pk1[j]);
#pragma unroll
            for (int j = EARLY_PK; j < 48; j++) if (j >= 32 || (j & 1) || EARLY_PK < 17) pk0[j] = pack_here(acc0[2 * j], acc0[2 * j + 1]);
#pragma unroll
            for (int j = 32; j < 48; j++) pk0[j] = movm(pk0[j]);
            attn_pair<2>(pk1, pk1 + 16, pk1 + 32, pk0 + 17, pk0 + 33, fu[1], fn[1], rk[1], 0.f, 0.f, mU, zero, ci, o);
            hand_over(0);
            TSC(elect, 3 + 8 * w);
#pragma unroll
            for (int j = 0; j < 32; j++) if (j < EARLY_PK || (!(j & 1) && EARLY_PK == 17)) pk0[j] = pack_here(acc0[2 * j], acc0[2 * j + 1]);
            factors(0);
            bar_sync(warp ? warp : 11, 64);
            uint32_t hl[16];
            ldsm4(hl, ha); ldsm4(hl + 4, ha + 512); ldsm4t(hl + 8, ha + 1024); ldsm4t(hl + 12, ha + 1536);
            __syncwarp();
            if (lane == 0) mbar_arrive(bars + 8 * B_FREED);
            attn_pair<1>(pk0, pk0 + 16, pk0 + 32, hl, hl + 8, fu[0], fn[0], rk[0], bias0, bias1, mU, zero, ci, o);
            const float2 s0 = lds2f(sb + OFF_STAT + (8 + r0) * 8), s1 = lds2f(sb + OFF_STAT + (16 + r0) * 8);
            const float m0 = s0.x * s0.y, f0 = 1.f + s0.y, m1 = s1.x * s1.y, f1 = 1.f + s1.y;
            uint32_t xt[32];
#pragma unroll
            for (int j = 0; j < 8; j++) ldsm4(xt + 4 * j, ((ring + wi * 2048 + mad) ^ ((j & 3) * 32)) + (j >> 2) * BOX);
            hand_over(1);
#pragma unroll
            for (int j = 0; j < 32; j++) {
                acc[2 * j] = fmaf(bf_lo(xt[j]), j & 1 ? f1 : f0, j & 1 ? m1 : m0); acc[2 * j + 1] = fmaf(bf_hi(xt[j]), j & 1 ? f1 : f0, j & 1 ? m1 : m0);
            }
        }
        TSC(tid == 0, 4);
        {
            const uint32_t da0 = sd + dlo(w * OFF_X1, 1024), db0 = sd + dlo(OFF_WO, BOX);
            const uint32_t chk = ring + wi * 256 + (lane >> 3) * 1032 + (lane & 7) * 32 + (lane & 4);
            uint32_t s8 = 16, ps8 = 0, ph = 0;
            mbar_wait(ofull + s8, 0, budget);
            mbar_wait(bars + 8 * B_WOFULL + s8, 0, budget);
            TSC(TIMING % 10 == 2 && elect, 32 + w * 16);
            const uint32_t ahi = dhi(128, 0) | (budget >> 30), bhi = dhi(1024, 1) | (budget >> 30);
            const int last = w ? HOLD : 15;
            uint32_t rel = elect ? 0x7fe : 0;
            uint32_t da = da0 + s8 * (BOX >> 7), db = db0 + s8 * (BOX >> 6);
#pragma unroll 1
            for (int i = 1;; i++) {
                wg_fence();
#pragma unroll
                for (int kk = 0; kk < 4; kk++) {
                    wgmma_n128<0, 1>(acc, mkdesc(da + kk * 128, ahi), mkdesc(db + kk * 128, bhi), 1);
                    if (kk & 1) wg_commit();
                }
                wg_wait<2>();
                if (rel & 1) { mbar_expect_tx(ofull + ps8, BOX); mbar_arrive_at(oempty + ps8); mbar_arrive(bars + 8 * B_WOEMPTY + ps8); }
                rel >>= 1;
                ps8 = s8;
                s8 = s8 == 40 ? 0 : s8 + 8;
                if (s8 == 16) ph ^= 1;
                da = da0 + s8 * (BOX >> 7); db = db0 + s8 * (BOX >> 6);
                uint32_t slow;
                asm volatile("{\n.reg .pred p, q, r;\n.reg .u32 u, v;\nmbarrier.try_wait.parity.shared::cta.b64 p, [%1], %3;\nmbarrier.try_wait.parity.shared::cta.b64 q, [%2], %3;\n"
                             "setp.ne.and.u32 r, %5, 1, p;\nmov.u32 u, 1;\nmov.u32 v, 1;\n@r ld.shared.u32 u, [%4];\n@r ld.shared.u32 v, [%4 + 4096];\n"
                             "and.pred p, p, q;\nmin.u32 u, u, v;\nsetp.eq.or.u32 p, u, 0, !p;\nvote.sync.any.pred p, p, 0xffffffff;\nselp.u32 %0, 1, 0, p;\n}"
                             : "=r"(slow) : "r"(ofull + s8), "r"(bars + 8 * B_WOFULL + s8), "r"(ph), "r"(chk + s8 * (BOX / 8)), "r"(i) : "memory");
                if (__builtin_expect(slow || i == last, 0)) {
                    uint32_t c8 = slow ? s8 : s8 + 8;
#pragma unroll 1
                    for (int n = slow ? i : i + 1; n < (i == last ? 16 : i + 1); n++, c8 += 8) {
                        const uint32_t cph = ph ^ (HOLD < 12 && c8 >= 16 && s8 < 16);
                        mbar_wait(ofull + c8, cph, budget);
                        mbar_wait(bars + 8 * B_WOFULL + c8, cph, budget);
                        if (__any_sync(0xffffffffu, min(lds1(chk + c8 * (BOX / 8)), lds1(chk + c8 * (BOX / 8) + 4096)) == 0)) {
                            const uint32_t at = wi * 256 + (lane >> 4) * 1024 + (lane & 15) * 16;
                            const uint8_t* src = scr->o + ((size_t)((mt * 2 + rh) * 2 + 1 - w) * 16 + ((2 * p + (n < 2 ? n ^ hp : n)) & 15)) * BOX + at;
#pragma unroll 1
                            for (int m = 0; m < 8192; m += 2048) {
                                uint4 v; int tries = 4096;
#pragma unroll 1
                                do { v = ld_rlx4(src + m); } while (v.x == 0 && --tries > 0);
                                sts4(ring + c8 * (BOX / 8) + at + m, v.x, v.y, v.z, v.w);
                            }
                            NRETRY();
                            fence_async_smem();
                            __syncwarp();
                        }
                    }
                    if (i == last) break;
                }
                TSC(TIMING % 10 == 2 && elect, 32 + w * 16 + i);
                wg_wait<1>();
            }
            if (w) bar_sync(9, 256);
#pragma unroll 1
            for (int i = last; i < 16; i++, da += 512, db += 1024) {
                wg_fence();
#pragma unroll
                for (int kk = 0; kk < 4; kk++) wgmma_n128<0, 1>(acc, mkdesc(da + kk * 128, ahi), mkdesc(db + kk * 128, bhi), 1);
                wg_commit();
            }
            if (!w) bar_arrive(9, 256);
            mbar_wait(bars + 8 * B_ZERO, 0, budget);
            const bool add = (__shfl_sync(0xffffffffu, lds1(sb + OFF_SEL), 0) >> (wi * 2 + 1 - w)) & 1;
            wg_wait<0>();
            TSC(elect, 7 + 9 * w);
            const uint32_t os0 = ring + wi * 4096;
#pragma unroll
            for (int hf = 0; hf < OUT_PARTS; hf++) {
#pragma unroll
                for (int j = hf * (8 / OUT_PARTS); j < (hf + 1) * (8 / OUT_PARTS); j++)
                    stsm4(((os0 + mad) ^ ((j & 3) * 32)) + (j >> 2) * 2048, pack_here(acc[8 * j], acc[8 * j + 1]), pack_here(acc[8 * j + 2], acc[8 * j + 3]),
                          pack_here(acc[8 * j + 4], acc[8 * j + 5]), pack_here(acc[8 * j + 6], acc[8 * j + 7]));
                fence_async_smem();
                __syncwarp();
                if (elect_one())
                    asm volatile("{\n.reg .pred p;\nsetp.ne.b32 p, %6, 0;\n@!p cp.async.bulk.tensor.5d.global.shared::cta.bulk_group [%0, {%2, %2, %3, %4, %5}], [%1];\n"
                                 "@p cp.reduce.async.bulk.tensor.5d.global.shared::cta.add.bulk_group [%0, {%2, %2, %3, %4, %5}], [%1];\n}"
                                 ::"l"(&mout), "r"(os0 + hf * 2048), "r"(0), "r"(((j0 + rh * 128) >> 5) + wi), "r"(1 - w), "r"(par * 16 + cb * 2 + hf), "r"((int)add) : "memory");
            }
            asm volatile("cp.async.bulk.commit_group;\ncp.async.bulk.wait_group.read 0;" ::: "memory");
            if (b == 0 && tid == 0) st_rlx(&scr->epoch[0], lds1(sb + OFF_EP));
            TSC(elect, 8 - 2 * w);
            TS_END();
        }
    }
}

typedef CUresult (*EncodeFn)(CUtensorMap*, CUtensorMapDataType, cuuint32_t, void*, const cuuint64_t*, const cuuint64_t*, const cuuint32_t*,
                             const cuuint32_t*, CUtensorMapInterleave, CUtensorMapSwizzle, CUtensorMapL2promotion, CUtensorMapFloatOOBfill);

CUtensorMap make_map(EncodeFn fn, const void* base, int rank, const cuuint64_t* dims, const cuuint64_t* strides, const cuuint32_t* box,
                     CUtensorMapSwizzle swz = CU_TENSOR_MAP_SWIZZLE_128B, CUtensorMapL2promotion pro = CU_TENSOR_MAP_L2_PROMOTION_L2_256B) {
    CUtensorMap m;
    cuuint32_t es[5] = {1, 1, 1, 1, 1};
    fn(&m, CU_TENSOR_MAP_DATA_TYPE_BFLOAT16, rank, (void*)base, dims, strides, box, es, CU_TENSOR_MAP_INTERLEAVE_NONE,
       swz, pro, CU_TENSOR_MAP_FLOAT_OOB_FILL_NONE);
    return m;
}

}

extern "C" void kernel_launch(void* const* d_in, const int* in_sizes, int n_in, void* d_out, int out_size) {
    (void)in_sizes; (void)n_in; (void)out_size;
    const __nv_bfloat16* x = (const __nv_bfloat16*)d_in[0];
    const __nv_bfloat16* wqkv = (const __nv_bfloat16*)d_in[1];
    const __nv_bfloat16* wo = (const __nv_bfloat16*)d_in[2];
    const __nv_bfloat16* wr = (const __nv_bfloat16*)d_in[4];
    const __nv_bfloat16* wg = (const __nv_bfloat16*)d_in[5];
    const __nv_bfloat16* wu = (const __nv_bfloat16*)d_in[6];
    const __nv_bfloat16* wd = (const __nv_bfloat16*)d_in[7];
    static EncodeFn fn = nullptr;
    static Scratch* scr = nullptr;
    if (!fn) {
        void* p = nullptr; cudaDriverEntryPointQueryResult q;
        cudaGetDriverEntryPoint("cuTensorMapEncodeTiled", &p, cudaEnableDefault, &q);
        fn = (EncodeFn)p;
        cudaFuncSetAttribute(fused_kernel, cudaFuncAttributeMaxDynamicSharedMemorySize, SMEM_LAUNCH);
        cudaGetSymbolAddress((void**)&scr, g_scr);
    }
    const cuuint64_t xd[4] = {2048, 16, 32, 2}, xs[4] = {4096, 131072, 65536, 128}, od[5] = {64, 16, 32, 2, 32};
    const cuuint32_t xb[4] = {64, 16, 4, 1}, ob[5] = {64, 16, 1, 1, 2 / OUT_PARTS};
    const cuuint64_t wdm[3] = {1024, 1024, 3}, wst[2] = {6144, 2048};
    const cuuint32_t wb[3] = {64, 64, 3};
    const cuuint64_t wod[3] = {64, 1024, 16}, wdd[3] = {64, 3584, 16}, wos[2] = {2048, 128};
    const cuuint32_t wob[3] = {64, 64, 2}, wdb[3] = {64, 64, 1};
    const CUtensorMapSwizzle s128 = CU_TENSOR_MAP_SWIZZLE_128B;
    CUtensorMap mx = make_map(fn, x, 4, xd, xs, xb, s128, (CUtensorMapL2promotion)P_X), mw = make_map(fn, wqkv, 3, wdm, wst, wb, s128, (CUtensorMapL2promotion)P_W);
    CUtensorMap mwo = make_map(fn, wo, 3, wod, wos, wob, s128, (CUtensorMapL2promotion)P_WO), mout = make_map(fn, d_out, 5, od, xs, ob, s128, (CUtensorMapL2promotion)P_OUT);
    const int swap_gu = wu < wg;
    const cuuint64_t gd[3] = {3584, 1024, 2}, gst[2] = {7168, (cuuint64_t)(swap_gu ? (const char*)wg - (const char*)wu : (const char*)wu - (const char*)wg)};
    const cuuint32_t gb[3] = {32, 64, 2};
    CUtensorMap mgu = make_map(fn, swap_gu ? wu : wg, 3, gd, gst, gb, CU_TENSOR_MAP_SWIZZLE_64B, (CUtensorMapL2promotion)P_GU);
    CUtensorMap mwd = make_map(fn, wd, 3, wdd, wos, wdb, s128, (CUtensorMapL2promotion)P_WD);
    const cuuint64_t md[2] = {64, 32768}, ms[1] = {128};
    const cuuint32_t mb[2] = {64, 64};
    CUtensorMap mo = make_map(fn, scr, 2, md, ms, mb, CU_TENSOR_MAP_SWIZZLE_NONE, (CUtensorMapL2promotion)P_O);
    const cuuint64_t rd[2] = {1024, 2048};
    const cuuint32_t rb[2] = {256, 16};
    CUtensorMap mr = make_map(fn, x, 2, rd, wos, rb, CU_TENSOR_MAP_SWIZZLE_NONE, (CUtensorMapL2promotion)P_R);
    cudaLaunchConfig_t cfg = {};
    cfg.gridDim = dim3(132); cfg.blockDim = dim3(512); cfg.dynamicSmemBytes = SMEM_LAUNCH; cfg.stream = cudaStreamPerThread;
    cudaLaunchAttribute at[1];
    at[0].id = cudaLaunchAttributeClusterDimension; at[0].val.clusterDim.x = 2; at[0].val.clusterDim.y = 1; at[0].val.clusterDim.z = 1;
    cfg.attrs = at; cfg.numAttrs = 1;
    cudaLaunchKernelEx(&cfg, fused_kernel, mx, mw, mwo, mout, mgu, mwd, mo, mr, x, wr, scr, swap_gu, Weights{(const char*)wqkv, (const char*)wo, (const char*)wg, (const char*)wu, (const char*)wd, (char*)d_out});
}
```

```cpp
#include <cuda_runtime.h>
#include <cuda.h>
#include <cuda_bf16.h>
#include <stdint.h>

namespace {

constexpr int BOX = 8192, W_BYTES = 3 * BOX;
constexpr int OFF_X1 = 6 * BOX, OFF_FR = 12 * BOX, OFF_E = 16 * BOX, OFF_W = 19 * BOX;
constexpr int OFF_WO = OFF_E;
constexpr int OFF_HIN = OFF_FR + 2048, OFF_GU = OFF_HIN + 2048, OFF_FS = OFF_GU + 1024;
constexpr int F_BYTES = 9216;
constexpr int CS_BYTES = 3136;
constexpr int OFF_CS = OFF_FS + 5 * F_BYTES;
constexpr int OFF_STAT = 28 * BOX;
constexpr int OFF_SEL = OFF_STAT + 2112, OFF_EP = OFF_SEL + 4;
constexpr int OFF_BAR = OFF_SEL + 16;
constexpr int B_WFULL = 0, B_XFULL = 3, B_ROW = 15, B_LATE = 19;
constexpr int B_AUX = 19, B_XT = 20, B_ZERO = 21, B_WOFULL = 22, B_OFULL = 28, B_FFULL = 40;
constexpr int B_WEMPTY = 45, B_F1DONE = 48, B_XEMPTY = 49, B_WOEMPTY = 55, B_OEMPTY = 61;
constexpr int B_G1DONE = 71, B_FEMPTY = 72, B_STAGED = 77, B_RDONE = 79, B_FREED = 80, NBAR = 83;
constexpr int SMEM_BYTES = OFF_BAR + NBAR * 8;
static_assert(OFF_FS + 3 * F_BYTES == OFF_E && OFF_CS + CS_BYTES <= OFF_W && SMEM_BYTES + 256 <= 232448 && OFF_BAR % 8 == 0, "smem");
#define POLL_NS 30
#define PF_RATE 10
#define PF_START 7
#define ZF_NS 100
#define FFN2_GATE (B_STAGED + 1)
#define PF_NW 6
#define EARLY_PK 17
#define ZF_GATE (B_ROW + 3)
#define HOLD 12
#define F2_DEPTH 0
#define OUT_PARTS 2
#define PF_D 8
#define NM 3
#define N7 9
#define NR 5
#define PF_DN 8
#define PF_DB 4096
#define PF_REV 0
#define RS_AT 5
#define Y_AT 2
#define P_X 0
#define P_W 0
#define P_WO 0
#define P_OUT 0
#define P_GU 2
#define P_WD 2
#define P_O 0
#define P_R 0
#define ROWS_AT 0x280
constexpr int NH = 56 - 7 * NM - N7;
static_assert(NH >= NR + 12 && NH <= 32 && NR < 6, "FFN2 split");
constexpr int BUDGET = 1 << 18;

struct Scratch {
    uint8_t o[2048 * 1024 * 2];
    uint4 ypart[8][16][128];
    uint32_t halo[128][512];
    uint32_t act[2][14336 + 4096];
    uint2 row[2048];
    uint4 cs[16][3][24];
    uint32_t oflag[16][32];
    uint32_t cnt[10][32];
    uint32_t sel[32], zflag[32], epoch[32];
};
__device__ __align__(1024) Scratch g_scr;
struct Weights { const char *wqkv, *wo, *wg, *wu, *wd; char* out; };

#define TS(i) do {} while (0)
#define TS_END() do {} while (0)
#define TSC(c, i) do {} while (0)
#define NRETRY() do {} while (0)
constexpr int SMEM_LAUNCH = SMEM_BYTES;
__device__ __forceinline__ uint32_t smem_u32(const void* p) { return (uint32_t)__cvta_generic_to_shared(p); }
__device__ __forceinline__ void mbar_init(uint32_t bar, uint32_t cnt) { asm volatile("mbarrier.init.shared::cta.b64 [%0], %1;" ::"r"(bar), "r"(cnt) : "memory"); }
__device__ __forceinline__ void mbar_expect_tx(uint32_t bar, uint32_t bytes) { asm volatile("mbarrier.arrive.expect_tx.shared::cta.b64 _, [%0], %1;" ::"r"(bar), "r"(bytes) : "memory"); }
__device__ __forceinline__ void mbar_arrive(uint32_t bar) { asm volatile("mbarrier.arrive.shared::cta.b64 _, [%0];" ::"r"(bar) : "memory"); }
__device__ __forceinline__ uint32_t mapa(uint32_t a, uint32_t cta) { uint32_t r; asm("mapa.shared::cluster.u32 %0, %1, %2;" : "=r"(r) : "r"(a), "r"(cta)); return r; }
__device__ __forceinline__ void mbar_arrive_at(uint32_t cbar) { asm volatile("mbarrier.arrive.shared::cluster.b64 _, [%0];" ::"r"(cbar) : "memory"); }
__device__ __forceinline__ void mbar_wait(uint32_t bar, uint32_t parity, int& budget) {
    asm volatile("{\n.reg .pred p;\nLAB_WAIT:\nmbarrier.try_wait.parity.shared::cta.b64 p, [%1], %2;\n"
                 "add.s32 %0, %0, -1;\nsetp.gt.and.s32 p, %0, 0, !p;\n@p bra LAB_WAIT;\n}" : "+r"(budget) : "r"(bar), "r"(parity) : "memory");
}
__device__ __forceinline__ void mbar_wait_hot(uint32_t bar, uint32_t parity, int& budget) {
    asm volatile("{\n.reg .pred p;\nmbarrier.try_wait.parity.shared::cta.b64 p, [%1], %2;\n@p bra LAB_DONE;\nLAB_WAIT:\nmbarrier.try_wait.parity.shared::cta.b64 p, [%1], %2;\n"
                 "add.s32 %0, %0, -1;\nsetp.gt.and.s32 p, %0, 0, !p;\n@p bra LAB_WAIT;\nLAB_DONE:\n}" : "+r"(budget) : "r"(bar), "r"(parity) : "memory");
}
__device__ __forceinline__ void tma_2d(uint32_t dst, const CUtensorMap* m, uint32_t bar, int c0, int c1) {
    asm volatile("cp.async.bulk.tensor.2d.shared::cluster.global.mbarrier::complete_tx::bytes [%0], [%1, {%3, %4}], [%2];" ::"r"(dst), "l"(m), "r"(bar), "r"(c0), "r"(c1) : "memory");
}
__device__ __forceinline__ void tma_2d_mc(uint32_t dst, const CUtensorMap* m, uint32_t bar, int c0, int c1) {
    asm volatile("cp.async.bulk.tensor.2d.shared::cluster.global.mbarrier::complete_tx::bytes.multicast::cluster [%0], [%1, {%3, %4}], [%2], %5;" ::"r"(dst), "l"(m), "r"(bar), "r"(c0), "r"(c1), "h"((uint16_t)3) : "memory");
}
__device__ __forceinline__ void tma_3d(uint32_t dst, const CUtensorMap* m, uint32_t bar, int c0, int c1, int c2) {
    asm volatile("cp.async.bulk.tensor.3d.shared::cluster.global.mbarrier::complete_tx::bytes [%0], [%1, {%3, %4, %5}], [%2];" ::"r"(dst), "l"(m), "r"(bar), "r"(c0), "r"(c1), "r"(c2) : "memory");
}
__device__ __forceinline__ void tma_4d(uint32_t dst, const CUtensorMap* m, uint32_t bar, int c0, int c1, int c2, int c3) {
    asm volatile("cp.async.bulk.tensor.4d.shared::cluster.global.mbarrier::complete_tx::bytes [%0], [%1, {%3, %4, %5, %6}], [%2];" ::"r"(dst), "l"(m), "r"(bar), "r"(c0), "r"(c1), "r"(c2), "r"(c3) : "memory");
}
__device__ __forceinline__ void tma_4d_mc(uint32_t dst, const CUtensorMap* m, uint32_t bar, int c0, int c1, int c2, int c3) {
    asm volatile("cp.async.bulk.tensor.4d.shared::cluster.global.mbarrier::complete_tx::bytes.multicast::cluster [%0], [%1, {%3, %4, %5, %6}], [%2], %7;" ::"r"(dst), "l"(m), "r"(bar), "r"(c0), "r"(c1), "r"(c2), "r"(c3), "h"((uint16_t)3) : "memory");
}
__device__ __forceinline__ void bulk_pf(const void* p, uint32_t bytes) { asm volatile("cp.async.bulk.prefetch.L2.global [%0], %1;" ::"l"(p), "r"(bytes) : "memory"); }
__device__ __forceinline__ void bulk_g2s(uint32_t dst, const void* src, uint32_t bytes, uint32_t bar) {
    asm volatile("cp.async.bulk.shared::cluster.global.mbarrier::complete_tx::bytes [%0], [%1], %2, [%3];" ::"r"(dst), "l"(src), "r"(bytes), "r"(bar) : "memory");
}
__device__ __forceinline__ void bulk_s2c(uint32_t cdst, uint32_t src, uint32_t bytes, uint32_t cbar) {
    asm volatile("cp.async.bulk.shared::cluster.shared::cta.mbarrier::complete_tx::bytes [%0], [%1], %2, [%3];" ::"r"(cdst), "r"(src), "r"(bytes), "r"(cbar) : "memory");
}
__device__ __forceinline__ void cluster_arrive() { asm volatile("barrier.cluster.arrive.relaxed.aligned;" ::: "memory"); }
__device__ __forceinline__ void cluster_wait() { asm volatile("barrier.cluster.wait.aligned;" ::: "memory"); }
__device__ __forceinline__ void fence_gpu() { asm volatile("fence.acq_rel.gpu;" ::: "memory"); }
__device__ __forceinline__ void fence_async_smem() { asm volatile("fence.proxy.async.shared::cta;" ::: "memory"); }
__device__ __forceinline__ void wg_fence() { asm volatile("wgmma.fence.sync.aligned;" ::: "memory"); }
__device__ __forceinline__ void wg_commit() { asm volatile("wgmma.commit_group.sync.aligned;" ::: "memory"); }
template <int N> __device__ __forceinline__ void wg_wait() { asm volatile("wgmma.wait_group.sync.aligned %0;" ::"n"(N) : "memory"); }
__device__ __forceinline__ uint64_t mkdesc(uint32_t lo, uint32_t hi) { return ((uint64_t)hi << 32) | lo; }
__host__ __device__ constexpr uint32_t dhi(uint32_t sbo, uint32_t mode) { return (sbo >> 4) | (mode << 30); }
__host__ __device__ constexpr uint32_t dlo(uint32_t off, uint32_t lbo) { return (off >> 4) + ((lbo >> 4) << 16); }
__device__ __forceinline__ bool elect_one() {
    uint32_t e;
    asm volatile("{\n.reg .pred p;\nelect.sync _|p, 0xffffffff;\nselp.u32 %0, 1, 0, p;\n}" : "=r"(e));
    return e;
}
template <int R> __device__ __forceinline__ void reg_inc() { asm volatile("setmaxnreg.inc.sync.aligned.u32 %0;" ::"n"(R)); }
template <int R> __device__ __forceinline__ void reg_dec() { asm volatile("setmaxnreg.dec.sync.aligned.u32 %0;" ::"n"(R)); }
__device__ __forceinline__ void bar_sync(int id, int n) { asm volatile("bar.sync %0, %1;" ::"r"(id), "r"(n) : "memory"); }
__device__ __forceinline__ void bar_arrive(int id, int n) { asm volatile("bar.arrive %0, %1;" ::"r"(id), "r"(n) : "memory"); }
__device__ __forceinline__ uint32_t pack_bf16(float lo, float hi) { uint32_t r; asm("cvt.rn.bf16x2.f32 %0, %1, %2;" : "=r"(r) : "f"(hi), "f"(lo)); return r; }
__device__ __forceinline__ uint32_t pack_here(float lo, float hi) { uint32_t r; asm volatile("cvt.rn.bf16x2.f32 %0, %1, %2;" : "=r"(r) : "f"(hi), "f"(lo)); return r; }
__device__ __forceinline__ float bf_lo(uint32_t u) { return __uint_as_float(u << 16); }
__device__ __forceinline__ float bf_hi(uint32_t u) { return __uint_as_float(u & 0xffff0000u); }
__device__ __forceinline__ float bf16r(float v) { return bf_lo(pack_bf16(v, 0.f)); }
__device__ __forceinline__ float rcp(float x) { float r; asm("rcp.approx.ftz.f32 %0, %1;" : "=f"(r) : "f"(x)); return r; }
__device__ __forceinline__ float ex2(float x) { float r; asm("ex2.approx.ftz.f32 %0, %1;" : "=f"(r) : "f"(x)); return r; }
__device__ __forceinline__ float sigmoidf(float v) { return rcp(1.f + ex2(v * -1.4426950408889634f)); }
__device__ __forceinline__ uint32_t movm(uint32_t a) { uint32_t d; asm volatile("movmatrix.sync.aligned.m8n8.trans.b16 %0, %1;" : "=r"(d) : "r"(a)); return d; }
__device__ __forceinline__ void mma16816(float (&c)[4], uint32_t a0, uint32_t a1, uint32_t a2, uint32_t a3, uint32_t b0, uint32_t b1) {
    asm volatile("mma.sync.aligned.m16n8k16.row.col.f32.bf16.bf16.f32 {%0,%1,%2,%3}, {%4,%5,%6,%7}, {%8,%9}, {%0,%1,%2,%3};"
                 : "+f"(c[0]), "+f"(c[1]), "+f"(c[2]), "+f"(c[3]) : "r"(a0), "r"(a1), "r"(a2), "r"(a3), "r"(b0), "r"(b1));
}
__device__ __forceinline__ void mma1688(float (&c)[4], uint32_t a0, uint32_t a1, uint32_t b0) {
    asm volatile("mma.sync.aligned.m16n8k8.row.col.f32.bf16.bf16.f32 {%0,%1,%2,%3}, {%4,%5}, {%6}, {%0,%1,%2,%3};"
                 : "+f"(c[0]), "+f"(c[1]), "+f"(c[2]), "+f"(c[3]) : "r"(a0), "r"(a1), "r"(b0));
}
__device__ __forceinline__ void stsm4(uint32_t a, uint32_t r0, uint32_t r1, uint32_t r2, uint32_t r3) {
    asm volatile("stmatrix.sync.aligned.m8n8.x4.shared.b16 [%0], {%1,%2,%3,%4};" ::"r"(a), "r"(r0), "r"(r1), "r"(r2), "r"(r3) : "memory");
}
__device__ __forceinline__ void ldsm4(uint32_t* r, uint32_t a) {
    asm volatile("ldmatrix.sync.aligned.m8n8.x4.shared.b16 {%0,%1,%2,%3}, [%4];" : "=r"(r[0]), "=r"(r[1]), "=r"(r[2]), "=r"(r[3]) : "r"(a) : "memory");
}
__device__ __forceinline__ void ldsm4t(uint32_t* r, uint32_t a) {
    asm volatile("ldmatrix.sync.aligned.m8n8.x4.trans.shared.b16 {%0,%1,%2,%3}, [%4];" : "=r"(r[0]), "=r"(r[1]), "=r"(r[2]), "=r"(r[3]) : "r"(a) : "memory");
}
__device__ __forceinline__ uint32_t ld_rlx(const void* p) { uint32_t v; asm volatile("ld.relaxed.gpu.global.u32 %0, [%1];" : "=r"(v) : "l"(p) : "memory"); return v; }
__device__ __forceinline__ uint32_t ld_acq(const void* p) { uint32_t v; asm volatile("ld.acquire.gpu.global.u32 %0, [%1];" : "=r"(v) : "l"(p) : "memory"); return v; }
__device__ __forceinline__ uint2 ld_rlx2(const void* p) { uint2 v; asm volatile("ld.relaxed.gpu.global.v2.u32 {%0,%1}, [%2];" : "=r"(v.x), "=r"(v.y) : "l"(p) : "memory"); return v; }
__device__ __forceinline__ uint4 ld_rlx4(const void* p) { uint4 v; asm volatile("ld.relaxed.gpu.global.v4.u32 {%0,%1,%2,%3}, [%4];" : "=r"(v.x), "=r"(v.y), "=r"(v.z), "=r"(v.w) : "l"(p) : "memory"); return v; }
__device__ __forceinline__ void st_rlx(void* p, uint32_t v) { asm volatile("st.relaxed.gpu.global.u32 [%0], %1;" ::"l"(p), "r"(v) : "memory"); }
__device__ __forceinline__ void st_rlx2(void* p, uint32_t a, uint32_t b) { asm volatile("st.relaxed.gpu.global.v2.u32 [%0], {%1,%2};" ::"l"(p), "r"(a), "r"(b) : "memory"); }
__device__ __forceinline__ void st_rlx4(void* p, uint32_t a, uint32_t b, uint32_t c, uint32_t d) { asm volatile("st.relaxed.gpu.global.v4.u32 [%0], {%1,%2,%3,%4};" ::"l"(p), "r"(a), "r"(b), "r"(c), "r"(d) : "memory"); }
__device__ __forceinline__ void red_add(uint32_t* p) { asm volatile("red.relaxed.gpu.global.add.u32 [%0], 1;" ::"l"(p) : "memory"); }
__device__ __forceinline__ uint4 ldg_nc(const void* p) { uint4 v; asm volatile("ld.global.nc.v4.u32 {%0,%1,%2,%3}, [%4];" : "=r"(v.x), "=r"(v.y), "=r"(v.z), "=r"(v.w) : "l"(p)); return v; }
__device__ __forceinline__ void sts4(uint32_t a, uint32_t x, uint32_t y, uint32_t z, uint32_t w) { asm volatile("st.shared.v4.u32 [%0], {%1,%2,%3,%4};" ::"r"(a), "r"(x), "r"(y), "r"(z), "r"(w) : "memory"); }
__device__ __forceinline__ void sts2(uint32_t a, uint32_t x, uint32_t y) { asm volatile("st.shared.v2.u32 [%0], {%1,%2};" ::"r"(a), "r"(x), "r"(y) : "memory"); }
__device__ __forceinline__ void sts1(uint32_t a, uint32_t v) { asm volatile("st.shared.u32 [%0], %1;" ::"r"(a), "r"(v) : "memory"); }
__device__ __forceinline__ uint4 lds4(uint32_t a) { uint4 v; asm volatile("ld.shared.v4.u32 {%0,%1,%2,%3}, [%4];" : "=r"(v.x), "=r"(v.y), "=r"(v.z), "=r"(v.w) : "r"(a) : "memory"); return v; }
__device__ __forceinline__ float4 lds4f(uint32_t a) { float4 v; asm volatile("ld.shared.v4.f32 {%0,%1,%2,%3}, [%4];" : "=f"(v.x), "=f"(v.y), "=f"(v.z), "=f"(v.w) : "r"(a) : "memory"); return v; }
__device__ __forceinline__ float2 lds2f(uint32_t a) { float2 v; asm volatile("ld.shared.v2.f32 {%0,%1}, [%2];" : "=f"(v.x), "=f"(v.y) : "r"(a) : "memory"); return v; }
__device__ __forceinline__ float lds1f(uint32_t a) { float v; asm volatile("ld.shared.f32 %0, [%1];" : "=f"(v) : "r"(a) : "memory"); return v; }
__device__ __forceinline__ uint32_t lds1(uint32_t a) { uint32_t v; asm volatile("ld.shared.u32 %0, [%1];" : "=r"(v) : "r"(a) : "memory"); return v; }
__device__ __forceinline__ uint32_t redux_max(uint32_t v) { uint32_t r; asm volatile("redux.sync.max.u32 %0, %1, 0xffffffff;" : "=r"(r) : "r"(v)); return r; }
__device__ __forceinline__ uint32_t poll_all(const uint32_t* p, uint32_t mask, uint32_t want, int& budget) {
    uint32_t v;
#pragma unroll 1
    while (v = ld_acq(p), !__all_sync(0xffffffffu, (v & mask) == want) && --budget > 0) __nanosleep(POLL_NS);
    return v;
}

template <int TA, int TB>
__device__ __forceinline__ void wgmma_n192(float (&d)[96], uint64_t da, uint64_t db, int keep) {
    asm volatile("{\n.reg .pred p;\nsetp.ne.b32 p, %98, 0;\n"
        "wgmma.mma_async.sync.aligned.m64n192k16.f32.bf16.bf16 "
        "{%0, %1, %2, %3, %4, %5, %6, %7, %8, %9, %10, %11, %12, %13, %14, %15, "
        "%16, %17, %18, %19, %20, %21, %22, %23, %24, %25, %26, %27, %28, %29, %30, %31, "
        "%32, %33, %34, %35, %36, %37, %38, %39, %40, %41, %42, %43, %44, %45, %46, %47, "
        "%48, %49, %50, %51, %52, %53, %54, %55, %56, %57, %58, %59, %60, %61, %62, %63, "
        "%64, %65, %66, %67, %68, %69, %70, %71, %72, %73, %74, %75, %76, %77, %78, %79, "
        "%80, %81, %82, %83, %84, %85, %86, %87, %88, %89, %90, %91, %92, %93, %94, %95}, "
        "%96, %97, p, 1, 1, %99, %100;\n}\n"
        : "+f"(d[0]), "+f"(d[1]), "+f"(d[2]), "+f"(d[3]), "+f"(d[4]), "+f"(d[5]), "+f"(d[6]), "+f"(d[7]),
          "+f"(d[8]), "+f"(d[9]), "+f"(d[10]), "+f"(d[11]), "+f"(d[12]), "+f"(d[13]), "+f"(d[14]), "+f"(d[15]),
          "+f"(d[16]), "+f"(d[17]), "+f"(d[18]), "+f"(d[19]), "+f"(d[20]), "+f"(d[21]), "+f"(d[22]), "+f"(d[23]),
          "+f"(d[24]), "+f"(d[25]), "+f"(d[26]), "+f"(d[27]), "+f"(d[28]), "+f"(d[29]), "+f"(d[30]), "+f"(d[31]),
          "+f"(d[32]), "+f"(d[33]), "+f"(d[34]), "+f"(d[35]), "+f"(d[36]), "+f"(d[37]), "+f"(d[38]), "+f"(d[39]),
          "+f"(d[40]), "+f"(d[41]), "+f"(d[42]), "+f"(d[43]), "+f"(d[44]), "+f"(d[45]), "+f"(d[46]), "+f"(d[47]),
          "+f"(d[48]), "+f"(d[49]), "+f"(d[50]), "+f"(d[51]), "+f"(d[52]), "+f"(d[53]), "+f"(d[54]), "+f"(d[55]),
          "+f"(d[56]), "+f"(d[57]), "+f"(d[58]), "+f"(d[59]), "+f"(d[60]), "+f"(d[61]), "+f"(d[62]), "+f"(d[63]),
          "+f"(d[64]), "+f"(d[65]), "+f"(d[66]), "+f"(d[67]), "+f"(d[68]), "+f"(d[69]), "+f"(d[70]), "+f"(d[71]),
          "+f"(d[72]), "+f"(d[73]), "+f"(d[74]), "+f"(d[75]), "+f"(d[76]), "+f"(d[77]), "+f"(d[78]), "+f"(d[79]),
          "+f"(d[80]), "+f"(d[81]), "+f"(d[82]), "+f"(d[83]), "+f"(d[84]), "+f"(d[85]), "+f"(d[86]), "+f"(d[87]),
          "+f"(d[88]), "+f"(d[89]), "+f"(d[90]), "+f"(d[91]), "+f"(d[92]), "+f"(d[93]), "+f"(d[94]), "+f"(d[95])
        : "l"(da), "l"(db), "r"(keep), "n"(TA), "n"(TB));
}
template <int TA, int TB>
__device__ __forceinline__ void wgmma_n128(float (&d)[64], uint64_t da, uint64_t db, int keep) {
    asm volatile("{\n.reg .pred p;\nsetp.ne.b32 p, %66, 0;\n"
        "wgmma.mma_async.sync.aligned.m64n128k16.f32.bf16.bf16 "
        "{%0, %1, %2, %3, %4, %5, %6, %7, %8, %9, %10, %11, %12, %13, %14, %15, "
        "%16, %17, %18, %19, %20, %21, %22, %23, %24, %25, %26, %27, %28, %29, %30, %31, "
        "%32, %33, %34, %35, %36, %37, %38, %39, %40, %41, %42, %43, %44, %45, %46, %47, "
        "%48, %49, %50, %51, %52, %53, %54, %55, %56, %57, %58, %59, %60, %61, %62, %63}, "
        "%64, %65, p, 1, 1, %67, %68;\n}\n"
        : "+f"(d[0]), "+f"(d[1]), "+f"(d[2]), "+f"(d[3]), "+f"(d[4]), "+f"(d[5]), "+f"(d[6]), "+f"(d[7]),
          "+f"(d[8]), "+f"(d[9]), "+f"(d[10]), "+f"(d[11]), "+f"(d[12]), "+f"(d[13]), "+f"(d[14]), "+f"(d[15]),
          "+f"(d[16]), "+f"(d[17]), "+f"(d[18]), "+f"(d[19]), "+f"(d[20]), "+f"(d[21]), "+f"(d[22]), "+f"(d[23]),
          "+f"(d[24]), "+f"(d[25]), "+f"(d[26]), "+f"(d[27]), "+f"(d[28]), "+f"(d[29]), "+f"(d[30]), "+f"(d[31]),
          "+f"(d[32]), "+f"(d[33]), "+f"(d[34]), "+f"(d[35]), "+f"(d[36]), "+f"(d[37]), "+f"(d[38]), "+f"(d[39]),
          "+f"(d[40]), "+f"(d[41]), "+f"(d[42]), "+f"(d[43]), "+f"(d[44]), "+f"(d[45]), "+f"(d[46]), "+f"(d[47]),
          "+f"(d[48]), "+f"(d[49]), "+f"(d[50]), "+f"(d[51]), "+f"(d[52]), "+f"(d[53]), "+f"(d[54]), "+f"(d[55]),
          "+f"(d[56]), "+f"(d[57]), "+f"(d[58]), "+f"(d[59]), "+f"(d[60]), "+f"(d[61]), "+f"(d[62]), "+f"(d[63])
        : "l"(da), "l"(db), "r"(keep), "n"(TA), "n"(TB));
}
template <int TA, int TB>
__device__ __forceinline__ void wgmma_n8(float (&d)[4], uint64_t da, uint64_t db, int keep) {
    asm volatile("{\n.reg .pred p;\nsetp.ne.b32 p, %6, 0;\n"
        "wgmma.mma_async.sync.aligned.m64n8k16.f32.bf16.bf16 "
        "{%0, %1, %2, %3}, "
        "%4, %5, p, 1, 1, %7, %8;\n}\n"
        : "+f"(d[0]), "+f"(d[1]), "+f"(d[2]), "+f"(d[3])
        : "l"(da), "l"(db), "r"(keep), "n"(TA), "n"(TB));
}
__device__ __forceinline__ void wgmma_rs_n192(float (&d)[96], uint32_t a0, uint32_t a1, uint32_t a2, uint32_t a3, uint64_t db) {
    asm volatile("{\n.reg .pred p;\nsetp.ne.b32 p, 1, 0;\n"
        "wgmma.mma_async.sync.aligned.m64n192k16.f32.bf16.bf16 "
        "{%0, %1, %2, %3, %4, %5, %6, %7, %8, %9, %10, %11, %12, %13, %14, %15, "
        "%16, %17, %18, %19, %20, %21, %22, %23, %24, %25, %26, %27, %28, %29, %30, %31, "
        "%32, %33, %34, %35, %36, %37, %38, %39, %40, %41, %42, %43, %44, %45, %46, %47, "
        "%48, %49, %50, %51, %52, %53, %54, %55, %56, %57, %58, %59, %60, %61, %62, %63, "
        "%64, %65, %66, %67, %68, %69, %70, %71, %72, %73, %74, %75, %76, %77, %78, %79, "
        "%80, %81, %82, %83, %84, %85, %86, %87, %88, %89, %90, %91, %92, %93, %94, %95}, "
        "{%96, %97, %98, %99}, %100, p, 1, 1, 1;\n}\n"
        : "+f"(d[0]), "+f"(d[1]), "+f"(d[2]), "+f"(d[3]), "+f"(d[4]), "+f"(d[5]), "+f"(d[6]), "+f"(d[7]),
          "+f"(d[8]), "+f"(d[9]), "+f"(d[10]), "+f"(d[11]), "+f"(d[12]), "+f"(d[13]), "+f"(d[14]), "+f"(d[15]),
          "+f"(d[16]), "+f"(d[17]), "+f"(d[18]), "+f"(d[19]), "+f"(d[20]), "+f"(d[21]), "+f"(d[22]), "+f"(d[23]),
          "+f"(d[24]), "+f"(d[25]), "+f"(d[26]), "+f"(d[27]), "+f"(d[28]), "+f"(d[29]), "+f"(d[30]), "+f"(d[31]),
          "+f"(d[32]), "+f"(d[33]), "+f"(d[34]), "+f"(d[35]), "+f"(d[36]), "+f"(d[37]), "+f"(d[38]), "+f"(d[39]),
          "+f"(d[40]), "+f"(d[41]), "+f"(d[42]), "+f"(d[43]), "+f"(d[44]), "+f"(d[45]), "+f"(d[46]), "+f"(d[47]),
          "+f"(d[48]), "+f"(d[49]), "+f"(d[50]), "+f"(d[51]), "+f"(d[52]), "+f"(d[53]), "+f"(d[54]), "+f"(d[55]),
          "+f"(d[56]), "+f"(d[57]), "+f"(d[58]), "+f"(d[59]), "+f"(d[60]), "+f"(d[61]), "+f"(d[62]), "+f"(d[63]),
          "+f"(d[64]), "+f"(d[65]), "+f"(d[66]), "+f"(d[67]), "+f"(d[68]), "+f"(d[69]), "+f"(d[70]), "+f"(d[71]),
          "+f"(d[72]), "+f"(d[73]), "+f"(d[74]), "+f"(d[75]), "+f"(d[76]), "+f"(d[77]), "+f"(d[78]), "+f"(d[79]),
          "+f"(d[80]), "+f"(d[81]), "+f"(d[82]), "+f"(d[83]), "+f"(d[84]), "+f"(d[85]), "+f"(d[86]), "+f"(d[87]),
          "+f"(d[88]), "+f"(d[89]), "+f"(d[90]), "+f"(d[91]), "+f"(d[92]), "+f"(d[93]), "+f"(d[94]), "+f"(d[95])
        : "r"(a0), "r"(a1), "r"(a2), "r"(a3), "l"(db));
}
__device__ __forceinline__ void wgmma_rs_n8(float (&d)[4], uint32_t a0, uint32_t a1, uint32_t a2, uint32_t a3, uint64_t db) {
    asm volatile("{\n.reg .pred p;\nsetp.ne.b32 p, 1, 0;\n"
        "wgmma.mma_async.sync.aligned.m64n8k16.f32.bf16.bf16 "
        "{%0, %1, %2, %3}, "
        "{%4, %5, %6, %7}, %8, p, 1, 1, 0;\n}\n"
        : "+f"(d[0]), "+f"(d[1]), "+f"(d[2]), "+f"(d[3])
        : "r"(a0), "r"(a1), "r"(a2), "r"(a3), "l"(db));
}

template <int HS>
__device__ __forceinline__ void attn_pair(const uint32_t* q, const uint32_t* k, const uint32_t* v, const uint32_t* kh, const uint32_t* vh,
                                          const float* fu, const float* fn, const float* rk, float bias0, float bias1, uint32_t mU, uint32_t zero, const float* ci, uint32_t* o) {
    float s0[2][4] = {}, s1[2][4] = {}, s2[2][4] = {};
#pragma unroll
    for (int n = 0; n < 4; n++) {
        const int hd = n & 1, a = 8 * hd + 2 * (n & 2);
        mma16816(s1[hd], q[a], q[a + 1], q[a + 2], q[a + 3], k[a], k[a + 2]);
        mma16816(s2[hd], q[a], q[a + 1], q[a + 2], q[a + 3], k[a + 1], k[a + 3]);
    }
#pragma unroll
    for (int n = 0; n < 4; n++) {
        const int hd = n & 1, a = 8 * hd + 2 * (n & 2);
        mma16816(s0[hd], q[a], q[a + 1], q[a + 2], q[a + 3], kh[HS * (a / 2)], kh[HS * (a / 2 + 1)]);
    }
    float e[2][4], m[2][2];
#pragma unroll
    for (int hd = 0; hd < 2; hd++) {
        e[hd][2] = fmaf(s1[hd][2], fu[2], s2[hd][2] * fn[2]); e[hd][3] = fmaf(s1[hd][3], fu[3], s2[hd][3] * fn[3]);
        e[hd][0] = fmaf(s0[hd][0], fu[0], fmaf(s1[hd][0], fn[0], bias0)); e[hd][1] = fmaf(s0[hd][1], fu[1], fmaf(s1[hd][1], fn[1], bias1));
        m[hd][1] = fmaxf(e[hd][2], e[hd][3]); m[hd][0] = fmaxf(e[hd][0], e[hd][1]);
    }
#pragma unroll
    for (int x = 1; x < 3; x++)
#pragma unroll
        for (int n = 0; n < 4; n++) m[n & 1][1 - (n >> 1)] = fmaxf(m[n & 1][1 - (n >> 1)], __shfl_xor_sync(0xffffffffu, m[n & 1][1 - (n >> 1)], x));
#pragma unroll
    for (int hd = 0; hd < 2; hd++) {
#pragma unroll
        for (int n = 0; n < 4; n++) e[hd][n] = ex2(e[hd][n] - m[hd][n >> 1]);
        float sum[4] = {};
        mma1688(sum, pack_bf16(e[hd][0], e[hd][1]), pack_bf16(e[hd][2], e[hd][3]), 0x3f803f80u);
        const float i0 = rcp(sum[0]), i1 = rcp(sum[2]);
        const uint32_t plo = pack_bf16(e[hd][0] * rk[0] * i0, e[hd][1] * rk[1] * i0), phi = pack_bf16(e[hd][2] * rk[2] * i1, e[hd][3] * rk[3] * i1);
        const uint32_t z0 = plo & zero, z1 = phi & zero;
        const uint32_t a0 = plo & ~mU, a1 = phi & mU, a3 = phi & ~mU, b0 = plo & mU;
#pragma unroll
        for (int jj = 0; jj < 4; jj++) {
            float c[4];
            asm volatile("mma.sync.aligned.m16n8k16.row.col.f32.bf16.bf16.f32 {%0,%1,%2,%3}, {%4,%5,%6,%7}, {%8,%9}, {%10,%11,%12,%13};"
                         : "=f"(c[0]), "=f"(c[1]), "=f"(c[2]), "=f"(c[3])
                         : "r"(a0), "r"(a1), "r"(z0), "r"(a3), "r"(v[8 * hd + 2 * jj]), "r"(v[8 * hd + 2 * jj + 1]), "f"(ci[0]), "f"(ci[1]), "f"(ci[2]), "f"(ci[3]));
            mma1688(c, b0, z1, vh[HS * (4 * hd + jj)]);
            o[8 * hd + 2 * jj] = pack_bf16(c[0], c[1]); o[8 * hd + 2 * jj + 1] = pack_bf16(c[2], c[3]);
        }
    }
}

__device__ __forceinline__ uint32_t norm_pair(uint32_t u, float m, float rinv) {
    const uint32_t d = pack_bf16(bf_lo(u) - m, bf_hi(u) - m);
    return max(pack_bf16(bf_lo(d) * rinv, bf_hi(d) * rinv), 1u);
}

__global__ void __cluster_dims__(2, 1, 1) __launch_bounds__(512, 1)
fused_kernel(const __grid_constant__ CUtensorMap mx, const __grid_constant__ CUtensorMap mw, const __grid_constant__ CUtensorMap mwo,
             const __grid_constant__ CUtensorMap mout, const __grid_constant__ CUtensorMap mgu, const __grid_constant__ CUtensorMap mwd,
             const __grid_constant__ CUtensorMap mo, const __grid_constant__ CUtensorMap mr,
             const __nv_bfloat16* __restrict__ x, const __nv_bfloat16* __restrict__ wr, Scratch* __restrict__ scr, int swap_gu, const Weights pf) {
    extern __shared__ __align__(1024) uint8_t smem[];
    const uint32_t sb = smem_u32(smem);
    const uint32_t bars = sb + OFF_BAR;
    const int hp = blockIdx.x & 1, cl = blockIdx.x >> 1;
    int pr = cl - 4;
    asm("{\n.reg .pred p;\nsetp.ge.s32 p, %1, 36;\nselp.s32 %0, %3, %0, p;\nsetp.lt.s32 p, %1, 4;\nselp.s32 %0, %2, %0, p;\n}" : "+r"(pr) : "r"(cl), "r"(39 + 8 * cl), "r"((cl * 293 - 2356) >> 8));
    if (threadIdx.x < 32 && elect_one()) {
        const uint32_t fx = bars + 8 * (B_XFULL + 1), fw = bars + 8 * (B_WFULL + 2);
        mbar_init(fx, 1); mbar_init(fw, 1);
        asm volatile("fence.mbarrier_init.release.cluster;" ::: "memory");
        if (cl < 64) {
            tma_4d(sb + 4 * BOX, &mx, fx, (pr >> 5) * 1024, 0, pr & 24, 1);
            tma_3d(sb + OFF_W + 2 * W_BYTES, &mw, fw, ((pr & 7) * 2 + hp) * 64, 0, 0);
            mbar_expect_tx(fx, BOX); mbar_expect_tx(fw, W_BYTES);
        }
    }
    const int tid = threadIdx.x, lane = tid & 31, warp = __shfl_sync(0xffffffffu, tid >> 5, 0);
    const uint32_t sd = (sb & 0x3FFFF) >> 4;
    const int b = pr * 2 + hp, mt = pr >> 3, p = pr & 7, nt = 2 * p + hp, rh = p & 1, cb = (p & 6) + hp;
    const int par = mt >> 2, j0 = (mt & 3) * 256;
    int budget = BUDGET;

    auto load_w = [&](int k, int s) {
        const uint32_t full = bars + 8 * (B_WFULL + s);
        mbar_expect_tx(full, W_BYTES);
        tma_3d(sb + OFF_W + s * W_BYTES, &mw, full, nt * 64, k * 64, 0);
    };
    auto load_x = [&](int n) {
        const int w = n & 1, j = n < 4 ? (n >> 1) + 4 : (n >> 1) - 2;
        const uint32_t full = bars + 8 * (B_XFULL + w * 6 + 5 - j);
        mbar_expect_tx(full, BOX);
        tma_4d(sb + w * OFF_X1 + j * BOX, &mx, full, par * 1024 + (n >> 2) * 64, 0, (j0 + w * 128) >> 5, (~n >> 1) & 1);
    };
    if (warp > 0 && warp < (b < 128 ? 9 : 16) && elect_one()) {
        mbar_init(bars + (warp == 1 ? 0 : 16 * warp + 8), 1); mbar_init(bars + (warp == 1 ? 8 : 16 * warp + 16), 1);
        if (warp == 1) mbar_init(bars + 24, 1);
        asm volatile("fence.mbarrier_init.release.cluster;" ::: "memory");
    }
    __syncthreads();

    if (b >= 128) {
        const int hc = b - 128, g = lane >> 2, t = lane & 3;
        const uint32_t ep = ld_rlx(&scr->epoch[0]) + 1;
        if (warp < 12) {
            const int n = warp / 3, part = warp - 3 * n;
            auto load = [&](int k) {
                const uint32_t full = bars + 8 * (2 * n + (k & 1));
                mbar_expect_tx(full, W_BYTES);
                tma_3d(sb + (2 * n + (k & 1)) * W_BYTES, &mw, full, (4 * hc + n) * 64, k * 64, 0);
            };
            if (part == 0 && elect_one()) { load(0); load(1); }
            __syncwarp();
            float c0[4] = {0.f, 0.f, 0.f, 0.f}, c1[4] = {0.f, 0.f, 0.f, 0.f};
            const uint32_t sel = g == 0 ? 0x3f80u : g == 1 ? 0x3f800000u : 0u;
            const uint32_t a = sb + 2 * n * W_BYTES + part * BOX + t * 256 + ((g ^ (2 * t)) << 4);
#pragma unroll 1
            for (int k = 0; k < 16; k++) {
                mbar_wait(bars + 8 * (2 * n + (k & 1)), (k >> 1) & 1, budget);
                uint4 v[8], u[8];
#pragma unroll
                for (int i = 0; i < 8; i++) { v[i] = lds4(a + (k & 1) * W_BYTES + i * 1024); u[i] = lds4(((a + 128) ^ 16) + (k & 1) * W_BYTES + i * 1024); }
                bar_sync(1 + n, 96);
                if (part == k % 3 && k < 14 && elect_one()) load(k + 2);
                __syncwarp();
#pragma unroll
                for (int i = 0; i < 8; i++) { mma16816(c0, v[i].x, v[i].y, u[i].x, u[i].y, sel, sel); mma16816(c1, v[i].z, v[i].w, u[i].z, u[i].w, sel, sel); }
            }
            if (t == 0) {
#pragma unroll
                for (int r = 0; r < 3; r++) {
                    const uint32_t q0 = (pack_bf16(c0[0], c0[1]) & ~1u) | (ep & 1), q1 = pack_bf16(c0[2], c0[3]), q2 = pack_bf16(c1[0], c1[1]), q3 = pack_bf16(c1[2], c1[3]);
                    st_rlx4(&scr->cs[4 * hc + n][r][part * 8 + g], q0, q1, q2, q3);
                    c0[0] -= bf_lo(q0); c0[1] -= bf_hi(q0); c0[2] -= bf_lo(q1); c0[3] -= bf_hi(q1);
                    c1[0] -= bf_lo(q2); c1[1] -= bf_hi(q2); c1[2] -= bf_lo(q3); c1[3] -= bf_hi(q3);
                }
            }
            TSC(tid == 0, 19);
        }
        {
            const int wg = warp >> 2, c2 = 4 * hc + wg, tw = tid & 127;
            const uint32_t ring = sb + wg * 6 * BOX, full = bars + 8 * (8 + wg * 6), ha = sb + 24 * BOX;
            const uint32_t* hsrc = scr->act[ep & 1] + (56 - NH) * 256;
            auto load = [&](int q, int s) { mbar_expect_tx(full + 8 * s, BOX); tma_3d(ring + s * BOX, &mwd, full + 8 * s, 0, (56 - NH + q) * 64, c2); };
            const uint32_t key = poll_all(&scr->sel[lane & 7], 31u, ep & 31, budget);
            __syncthreads();
            TSC(tid == 0, 12);
            if ((warp & 3) == 0 && elect_one()) {
#pragma unroll 1
                for (int q = 0; q < 6; q++) load(q, q);
            }
            __syncwarp();
            const int zr = (2047 - ((__shfl_sync(0xffffffffu, key, warp >> 1) >> 5) & 2047)) & ~30;
#pragma unroll
            for (int i = 0; i < 8; i++) st_rlx4(pf.out + (size_t)(zr + (warp & 1) * 16 + 2 * i) * 2048 + hc * 512 + lane * 16, 0, 0, 0, 0);
            __syncthreads();
            uint32_t wa[NR * 16];
#pragma unroll
            for (int q = 0; q < NR; q++) {
                mbar_wait(full + 8 * q, 0, budget);
#pragma unroll
                for (int j = 0; j < 4; j++) ldsm4t(wa + 16 * q + 4 * j, ring + q * BOX + j * 2048 + (lane >> 4) * 1024 + (lane & 7) * 128 + ((((warp & 3) * 2 + ((lane >> 3) & 1)) ^ (lane & 7)) << 4));
                bar_sync(1 + wg, 128);
                if ((warp & 3) == 0 && elect_one()) load(q + 6, q);
                __syncwarp();
            }
            if (tid == 64) { fence_gpu(); st_rlx(&scr->zflag[hc], ep); }
            if (warp == 1 && elect_one()) {
                int tries = BUDGET;
#pragma unroll 1
                while (ld_rlx(&scr->cnt[8][0]) != ep * (4 * NH) && --tries > 0) {}
                mbar_expect_tx(bars + 8 * 32, NH * 1024);
                bulk_g2s(ha, hsrc, NH * 1024, bars + 8 * 32);
                TS(17);
            }
            __syncwarp();
            mbar_wait(bars + 8 * 32, 0, budget);
#pragma unroll 1
            for (int i = tid; i < NH * 64; i += 512) {
                int tries = BUDGET;
                if (lds1(ha + i * 16) == 0) {
                    uint4 v;
#pragma unroll 1
                    do { v = ld_rlx4(hsrc + i * 4); } while (v.x == 0 && --tries > 0);
                    sts4(ha + i * 16, v.x, v.y, v.z, v.w);
                }
            }
            fence_async_smem();
            __syncthreads();
            TSC(tid == 0, 5);
            float acc[4] = {0.f, 0.f, 0.f, 0.f};
            int left = BUDGET;
            mbar_wait(full + 8 * NR, 0, left);
            const uint32_t da = sd + dlo(wg * 6 * BOX, BOX), db = sd + dlo(24 * BOX, 128), ahi = dhi(1024, 1) | (left >> 30), bhi = dhi(128, 0) | (left >> 30);
            uint4 v[8];
#pragma unroll
            for (int q = NR; q < NH; q++) {
                if (q > NR) mbar_wait(full + 8 * (q % 6), (q / 6) & 1, left);
                TSC(TIMING % 10 == 7 && tid == 0, 32 + q);
                wg_fence();
#pragma unroll
                for (int j = 0; j < 4; j++) wgmma_n8<1, 0>(acc, mkdesc(da + q % 6 * 512 + j * 128, ahi), mkdesc(db + q * 64 + j * 16, bhi), 1);
                wg_commit();
                if (q > NR && q + 5 < NH) {
                    wg_wait<1>();
                    if ((warp & 3) == (q & 3) && elect_one()) load(q + 5, (q - 1) % 6);
                    __syncwarp();
                }
                if (q == NR + RS_AT) {
                    wg_fence();
#pragma unroll
                    for (int j = 0; j < 4 * NR; j++) wgmma_rs_n8(acc, wa[4 * j], wa[4 * j + 1], wa[4 * j + 2], wa[4 * j + 3], mkdesc(db + j * 16, bhi));
                    wg_commit();
                }
                if (q == NH - Y_AT) {
#pragma unroll
                    for (int m = 0; m < 8; m++) v[m] = ld_rlx4(&scr->ypart[m][c2][tw]);
                }
            }
            wg_wait<0>();
            TSC(tid == 0, 18);
#pragma unroll 1
            for (int tries = BUDGET; tries > 0; tries--) {
                uint32_t bad = 0;
#pragma unroll
                for (int m = 0; m < 8; m++) bad |= v[m].x ^ ep;
                if (!(bad & 1)) break;
#pragma unroll
                for (int m = 0; m < 8; m++) if ((v[m].x ^ ep) & 1) v[m] = ld_rlx4(&scr->ypart[m][c2][tw]);
            }
            __syncwarp();
            const float sig = bf16r(sigmoidf(__uint_as_float(((int)key < 0 ? key & 0x7fffffffu : ~key) & 0xffff0000u)));
#pragma unroll
            for (int c = 0; c < 4; c++) {
#pragma unroll
                for (int m = 0; m < 8; m++) acc[c] += __uint_as_float((&v[m].x)[c]);
                acc[c] = bf16r(acc[c]) * __shfl_sync(0xffffffffu, sig, 2 * t + (c & 1));
            }
            char* dst = pf.out + (size_t)(2047 - ((__shfl_sync(0xffffffffu, key, g) >> 5) & 2047)) * 2048 + c2 * 128 + (warp & 3) * 32 + t * 4;
            asm volatile("red.relaxed.gpu.global.add.noftz.bf16x2 [%0], %1;" ::"l"(dst), "r"(movm(pack_bf16(acc[0], acc[1]))) : "memory");
            asm volatile("red.relaxed.gpu.global.add.noftz.bf16x2 [%0], %1;" ::"l"(dst + 16), "r"(movm(pack_bf16(acc[2], acc[3]))) : "memory");
            TSC(tid == 0, 20);
        }
        if (warp < 8) TS_END();
        return;
    }
    auto late_init = [&](int first, uint32_t cnt, int n) {
        if (elect_one()) {
#pragma unroll
            for (int i = 0; i < 13; i++) if (i < n) mbar_init(bars + 8 * (first + i), cnt);
            asm volatile("fence.mbarrier_init.release.cluster;" ::: "memory");
        }
        __syncwarp();
    };
    TSC(tid == 384, 3);

    const int c2 = b & 15, n2 = mt < 7 ? NM : N7;
    if (warp >= 12) {
        TSC(tid == 384, 11);
        reg_dec<24>();
        if (warp >= 14) late_init(B_G1DONE + 6 * (warp - 14), 4 * (warp - 13), 6);
        cluster_arrive();
        TSC(tid == 384, 14);
        if (warp == 12) {
            if (elect_one()) {
                TS(12);
                int c = 0;
#pragma unroll 1
                for (int n = 1; n < 12; n++) {
                    load_x(n);
                    #pragma unroll 1
                    for (; c < (n == 11 ? 4 : __popc(ROWS_AT & ((2 << n) - 1))); c++) { mbar_expect_tx(bars + 8 * (B_ROW + c), BOX); tma_2d(sb + OFF_FR + c * BOX, &mr, bars + 8 * (B_ROW + c), c * 256, b * 16); }
                    if (n == 3 || n == 7) load_w((n + 1) >> 2, n >> 2);
                }
            }
            __syncwarp();
            cluster_wait();
            if (elect_one()) {
                int s = 2; uint32_t ph = 0;
#pragma unroll 1
                for (int k = 3; k < 16; k++) {
                    mbar_wait(bars + 8 * (B_WEMPTY + s), ph, budget);
                    load_w(k, s);
                    if (++s == 3) s = 0;
                    if (s == 2) ph ^= 1;
                }
                s = 2;
#pragma unroll 1
                for (int i = 0; i < 16; i++) {
                    mbar_wait(bars + 8 * (i < 2 ? B_WEMPTY + i : i < 4 ? B_G1DONE : i < 6 ? B_F1DONE : B_WOEMPTY + s), i >= 12, budget);
                    if (i == 0) {
                        mbar_expect_tx(bars + 8 * B_XT, 4 * BOX);
#pragma unroll 1
                        for (int n = 0; n < 4; n++)
                            tma_4d(sb + (n >> 1) * OFF_X1 + (n & 1) * BOX, &mx, bars + 8 * B_XT, par * 1024 + cb * 128 + (n & 1) * 64, 0, (j0 + rh * 128) >> 5, 1 - (n >> 1));
                    }
                    const uint32_t full = bars + 8 * (B_WOFULL + s);
                    mbar_expect_tx(full, 2 * BOX);
                    tma_3d(sb + OFF_WO + s * 2 * BOX, &mwo, full, 0, ((2 * p + (i < 2 ? i ^ hp : i)) & 15) * 64, cb * 2);
                    TSC(TIMING % 10 == 4, 48 + i);
                    if (++s == 6) s = 0;
                }
            }
        } else {
            bar_sync(8, 224);
            const uint32_t ep = __shfl_sync(0xffffffffu, lds1(sb + OFF_EP), 0);
            if (warp == 13) {
                cluster_wait();
                if (elect_one()) {
                    int j = 4, q = 0, left = BUDGET; uint32_t ph = 0;
#pragma unroll 1
                    for (int n = 6; n < 32; n++) {
                        mbar_wait(bars + 8 * (B_XEMPTY + j), ph, left);
                        tma_4d_mc(sb + hp * OFF_X1 + j * BOX, &mx, bars + 8 * (B_XFULL + hp * 6 + 5 - j), par * 1024 + (n >> 1) * 64, 0, (j0 + hp * 128) >> 5, ~n & 1);
                        if (++j == 6) j = 0;
                        if (j == 4) ph ^= 1;
#pragma unroll 1
                        for (; q < (PF_RATE * (n - PF_START) >> 3) && q < 18 + PF_NW; q++) {
                            const int u = q - PF_NW;
                            if (u < 0) bulk_pf(pf.wqkv + (size_t)(1024 + 128 * u + b) * 6144, 6144);
                            else if (u < 16) bulk_pf((b < 64 ? pf.wg : pf.wu) + (size_t)(u * 64 + (b & 63)) * 7168, 7168);
                            else bulk_pf(pf.wo + (size_t)((u - 16) * 128 + b) * 8192, 8192);
                        }
                    }
                }
                __syncwarp();
                uint32_t* hs = &scr->halo[b - 16][lane * 4];
                uint4 v[4] = {};
                if (j0) {
#pragma unroll 1
                    do {
#pragma unroll
                        for (int c = 0; c < 4; c++) v[c] = ld_rlx4(hs + c * 128);
                    } while (__any_sync(0xffffffffu, min(min(v[0].x, v[1].x), min(v[2].x, v[3].x)) == 0) && --budget > 0);
#pragma unroll
                    for (int c = 0; c < 4; c++) st_rlx(hs + c * 128, 0);
                }
#pragma unroll
                for (int c = 0; c < 4; c++) stsm4(sb + OFF_HIN + c * 512 + lane * 16, v[c].x, v[c].y, v[c].z, v[c].w);
                bar_arrive(11, 64);
                const int src = ((mt * 2 + rh) * 2 + 1 - hp) * 1024;
                if (elect_one()) {
                    const uint32_t* fl = &scr->oflag[mt * 2 + 1 - hp][0];
                    const uint32_t inv = (ep & 1) - 1;
                    uint32_t ready = 0, ph = 0;
                    int s = 4;
#pragma unroll 1
                    for (int i = 2; i < 16; i++) {
                        const int kb = (2 * p + i) & 15;
#pragma unroll 1
                        while (!((ready >> kb) & 1) && --budget > 0) ready = ld_rlx(fl) ^ inv;
                        TSC(i == 2, 30);
                        mbar_wait(bars + 8 * (B_OEMPTY + s), ph, budget);
                        tma_2d_mc(sb + hp * OFF_X1 + s * BOX, &mo, bars + 8 * (B_OFULL + hp * 6 + s), 0, src + kb * 64);
                        TSC(TIMING % 10 == 4 && hp == 0, 32 + i);
                        if (++s == 6) s = 0;
                        if (s == 4) ph ^= 1;
                    }
                }
            } else if (warp == 14) {
                if (elect_one()) {
                    uint32_t s8 = 0, ph = 0;
                    int tries = BUDGET;
                    const uint32_t* act = scr->act[ep & 1];
                    auto counted = [&](int c, uint32_t n) {
#pragma unroll 1
                        while (ld_rlx(&scr->cnt[c][0]) != ep * n && --tries > 0) __nanosleep(POLL_NS);
                    };
                    auto weights = [&](const CUtensorMap* m, int c0, int c1, int c2_) {
                        mbar_wait(bars + 8 * B_FEMPTY + s8, ph, budget);
                        mbar_expect_tx(bars + 8 * B_FFULL + s8, F_BYTES);
                        tma_3d(sb + OFF_FS + s8 * (F_BYTES / 8), m, bars + 8 * B_FFULL + s8, c0, c1, c2_);
                    };
                    if (b < 112) {
                        counted(9, 32);
                        TS(26);
#pragma unroll 1
                        for (int q = 0; q < 16; q++) {
                            weights(&mgu, b * 32, q * 64, 0);
                            bulk_g2s(sb + OFF_FS + BOX + s8 * (F_BYTES / 8), act + 14336 + q * 256, 1024, bars + 8 * B_FFULL + s8);
                            TSC(TIMING % 10 == 5, 32 + q);
                            if (q >= PF_D && q < PF_D + PF_DN) bulk_pf(pf.wd + 7340032 - (size_t)((PF_REV ? q - PF_D + 1 : PF_DN + PF_D - q) * 112 - b) * PF_DB, PF_DB);
                            s8 += 8;
                            if (s8 == 40) { s8 = 0; ph ^= 1; }
                        }
                    }
#pragma unroll 1
                    for (int q = -3; q < n2; q++) {
                        if (q == 0) { counted(mt, 4 * n2); TS(29); }
                        if ((unsigned)q >= 3) weights(&mwd, 0, (mt * NM + (q < 0 ? q + 3 : q)) * 64, c2);
                        if (q >= 0) bulk_g2s(sb + OFF_FS + BOX + s8 * (F_BYTES / 8), act + (mt * NM + q) * 256, 1024, bars + 8 * B_FFULL + s8);
                        TSC(TIMING % 10 == 5, 51 + q);
                        s8 += 8;
                        if (s8 == 24) { s8 = 0; if ((unsigned)q >= 3) ph ^= 1; }
                    }
                }
            } else {
#pragma unroll 1
                for (int i = lane * 16; i < CS_BYTES; i += 512) sts4(sb + OFF_CS + i, 0, 0, 0, 0);
                mbar_wait(bars + 8 * ZF_GATE, 0, budget);
                uint8_t* oz = scr->o + ((size_t)mt * 64 + nt) * BOX + lane * 16;
#pragma unroll 1
                for (int i = 0; i < 16; i++, oz += 512) {
#pragma unroll
                    for (int n = 0; n < 4; n++) st_rlx4(oz + n * 16 * BOX, 0, 0, 0, 0);
                    __nanosleep(ZF_NS);
                }
                __syncwarp();
                fence_gpu();
                mbar_wait(bars + 8 * B_RDONE, 0, budget);
                int tries = BUDGET;
#pragma unroll 1
                for (int i = lane; i < 88; i += 32) {
                    const uint2* rp = &scr->row[2 * (j0 - 8 + i) + par];
                    uint2 v0, v1, v2;
#pragma unroll 1
                    do { v0 = ld_rlx2(rp + (j0 + i < 8 ? 16 : 0)); v1 = ld_rlx2(rp + 176); v2 = ld_rlx2(rp + 352); } while ((((v0.y ^ ep) | (v1.y ^ ep) | (v2.y ^ ep)) & 31) && --tries > 0);
                    sts2(sb + OFF_STAT + i * 8, (v0.x << 16) ^ 0x80000000u, __float_as_uint(rcp(bf_hi(v0.x))));
                    sts2(sb + OFF_STAT + i * 8 + 704, (v1.x << 16) ^ 0x80000000u, __float_as_uint(rcp(bf_hi(v1.x))));
                    sts2(sb + OFF_STAT + i * 8 + 1408, (v2.x << 16) ^ 0x80000000u, __float_as_uint(rcp(bf_hi(v2.x))));
                }
                __syncwarp();
                {
                    const int row = 2047 - ((poll_all(&scr->sel[lane & 7], 31u, ep & 31, budget) >> 5) & 2047), jj = (row >> 1) - j0 - rh * 128;
                    sts1(sb + OFF_SEL, __reduce_or_sync(0xffffffffu, (row & 1) == par && (unsigned)jj < 128 ? 1u << (jj >> 4) : 0u));
                }
                if (lane < 24) {
                    uint4 v[3];
#pragma unroll 1
                    while (v[0] = ld_rlx4(&scr->cs[nt][0][lane]), v[1] = ld_rlx4(&scr->cs[nt][1][lane]), v[2] = ld_rlx4(&scr->cs[nt][2][lane]),
                           (((v[0].x ^ ep) | (v[1].x ^ ep) | (v[2].x ^ ep)) & 1) && --tries > 0) __nanosleep(100);
#pragma unroll
                    for (int r = 0; r < 3; r++) sts4(sb + OFF_CS + 64 + lane * 128 + r * 16, v[r].x, v[r].y, v[r].z, v[r].w);
                }
                fence_async_smem();
                __syncwarp();
                if (elect_one()) {
                    mbar_arrive(bars + 8 * B_AUX);
                    TS(21);
                    mbar_expect_tx(bars + 8 * (B_OFULL + 3), BOX); mbar_expect_tx(bars + 8 * (B_OFULL + 9), BOX);
#pragma unroll 1
                    for (int v = 0; v < 2; v++) {
                        const uint32_t ring = sb + v * OFF_X1 + 2 * BOX, fb = bars + 8 * (B_OFULL + v * 6 + 2);
                        mbar_wait(bars + 8 * (B_STAGED + v), 0, budget);
                        asm volatile("red.relaxed.gpu.global.xor.b32 [%0], %1;" ::"l"(&scr->oflag[mt * 2 + 1 - v][0]), "r"(1u << nt) : "memory");
                        TS(13 + 2 * v);
                        mbar_arrive(fb);
                        mbar_wait(bars + 8 * B_G1DONE, 0, budget);
                        bulk_s2c(mapa(ring + BOX, hp ^ 1), ring, BOX, mapa(fb + 8, hp ^ 1));
                        if (v == 0) mbar_wait(bars + 8 * B_FREED, 0, budget);
#pragma unroll
                        for (int n = 0; n < 4; n++) {
                            mbar_expect_tx(bars + 8 * (B_OFULL + (n >> 1) * 6 + 4 + (n & 1)) - v * 32, BOX);
                            mbar_arrive_at(mapa(bars + 8 * B_OEMPTY, n >> 1) + (4 + (n & 1)) * 8 - v * 32);
                        }
                    }
                    if (lds1(sb + OFF_SEL)) {
#pragma unroll 1
                        while (ld_acq(&scr->zflag[p >> 1]) != ep && --tries > 0) {}
                        asm volatile("fence.proxy.async.global;" ::: "memory");
                    }
                    mbar_arrive(bars + 8 * B_ZERO);
                }
            }
        }
    } else if (warp >= 8) {
        TSC(tid == 256, 28);
        reg_dec<40>();
        TSC(tid == 256, 31);
        const int wq = warp - 8, ta = tid - 256;
        const uint32_t rbuf = sb + OFF_FR + wq * 2048;
        const uint4 wv = ldg_nc(wr + ta * 8);
        const uint32_t ep0 = ld_rlx(&scr->epoch[0]);
        late_init(B_LATE + 13 * wq, 1 + (wq >> 1), 13);
        cluster_arrive();
        if (ta == 0) sts1(sb + OFF_EP, ep0 + 1);
        sts4(sb + OFF_STAT + ta * 16, wv.x, wv.y, wv.z, wv.w);
        bar_sync(8, 224);
        const uint32_t ep = __shfl_sync(0xffffffffu, lds1(sb + OFF_EP), 0);
        {
            const int s = b * 16 + wq * 4 + (lane >> 3);
            if ((lane & 7) == 0) st_rlx2(&scr->row[s], 0, ep - 1);
            float sw = 0.f;
#pragma unroll 1
            for (int i = 0; i < 16; i++) { const uint32_t q = lds1(sb + OFF_STAT + i * 128 + lane * 4); sw += bf_lo(q) + bf_hi(q); }
#pragma unroll 1
            for (int o = 16; o > 0; o >>= 1) sw += __shfl_xor_sync(0xffffffffu, sw, o);
            float s1 = 0.f, s2 = 0.f, sr = 0.f;
            {
                float s1b = 0.f, s2b = 0.f, srb = 0.f;
                const uint32_t xb = rbuf + (lane >> 4) * 1024 + (lane & 15) * 16, wb = sb + OFF_STAT + (lane & 15) * 16;
#pragma unroll 1
                for (int i = 0; i < 8; i++) {
                    const uint4 w4 = lds4(wb + i * 256);
                    mbar_wait_hot(bars + 8 * (B_ROW + (i >> 1)), 0, budget);
                    TSC(ta == 0 && i == 0, 17);
                    const uint32_t o = (i >> 1) * BOX + (i & 1) * 256;
                    const uint4 u = lds4(xb + o), v = lds4(xb + o + 512);
#pragma unroll
                    for (int c = 0; c < 4; c++) {
                        const float w0 = bf_lo((&w4.x)[c]), w1 = bf_hi((&w4.x)[c]);
                        const float a0 = bf_lo((&u.x)[c]), a1 = bf_hi((&u.x)[c]), b0 = bf_lo((&v.x)[c]), b1 = bf_hi((&v.x)[c]);
                        s1 += a0; s2 = fmaf(a0, a0, s2); sr = fmaf(a0, w0, sr);
                        s1 += a1; s2 = fmaf(a1, a1, s2); sr = fmaf(a1, w1, sr);
                        s1b += b0; s2b = fmaf(b0, b0, s2b); srb = fmaf(b0, w0, srb);
                        s1b += b1; s2b = fmaf(b1, b1, s2b); srb = fmaf(b1, w1, srb);
                    }
                }
                const bool up = lane & 8;
                s1 = (up ? s1b : s1) + __shfl_xor_sync(0xffffffffu, up ? s1 : s1b, 8);
                s2 = (up ? s2b : s2) + __shfl_xor_sync(0xffffffffu, up ? s2 : s2b, 8);
                sr = (up ? srb : sr) + __shfl_xor_sync(0xffffffffu, up ? sr : srb, 8);
            }
#pragma unroll
            for (int o = 1; o < 8; o <<= 1) {
                s1 += __shfl_xor_sync(0xffffffffu, s1, o); s2 += __shfl_xor_sync(0xffffffffu, s2, o); sr += __shfl_xor_sync(0xffffffffu, sr, o);
            }
            const float mean = s1 * (1.f / 1024.f), mb = bf16r(mean);
            float var = fmaf(-mean, mean, s2 * (1.f / 1024.f));
            sr = fmaf(-mb, sw, sr);
            if (__builtin_expect(__any_sync(0xffffffffu, mean * mean > 256.f * var), 0)) {
                float a2 = 0.f, ar = 0.f;
#pragma unroll 1
                for (int i = 0; i < 64; i++) {
                    const uint32_t o = i * 32 + (lane & 7) * 4, q1 = lds1(rbuf + (lane >> 3) * 512 + (o >> 9) * BOX + (o & 511)), q2 = lds1(sb + OFF_STAT + o);
                    a2 = fmaf(bf_lo(q1) - mean, bf_lo(q1) - mean, fmaf(bf_hi(q1) - mean, bf_hi(q1) - mean, a2));
                    ar = fmaf(bf_lo(q1) - mb, bf_lo(q2), fmaf(bf_hi(q1) - mb, bf_hi(q2), ar));
                }
#pragma unroll 1
                for (int o = 1; o < 8; o <<= 1) { a2 += __shfl_xor_sync(0xffffffffu, a2, o); ar += __shfl_xor_sync(0xffffffffu, ar, o); }
                var = a2 * (1.f / 1024.f); sr = ar;
            }
            float den;
            asm("sqrt.approx.f32 %0, %1;" : "=f"(den) : "f"(bf16r(bf16r(var) + 1e-5f)));
            const uint32_t st = pack_bf16(mb, den);
            const uint32_t rb = pack_bf16(0.f, sr * rcp(bf_hi(st)) + 0.f);
            uint32_t ord = (int)rb < 0 ? ~rb & 0xffff0000u : rb | 0x80000000u;
            if ((rb & 0x7fffffffu) > 0x7f800000u) ord = 0;
            if ((lane & 7) == 0) st_rlx2(&scr->row[s], st, ord | ((2047 - s) << 5) | (ep & 31));
            __syncwarp();
            if (lane < 7) mbar_arrive(bars + 8 * (lane < 5 ? B_FEMPTY + lane : B_RDONE));
        }
        TSC(ta == 0, 18);
        if ((b >> 3) == 14) {
            const uint32_t gm = sb + OFF_E, cnt = gm + 64, res = gm + 80, list = gm + 128;
            uint32_t kv[16];
            int tries = BUDGET;
#pragma unroll 1
            do {
                uint32_t bad = 0;
#pragma unroll
                for (int n = 0; n < 16; n++) kv[n] = ld_rlx(&scr->row[n * 128 + ta].y);
#pragma unroll
                for (int n = 0; n < 16; n++) bad |= kv[n] ^ ep;
                if ((bad & 31) == 0) break;
            } while (--tries > 0);
            __syncwarp();
            TSC(ta == 0, 26);
            uint32_t m = 0;
#pragma unroll
            for (int n = 0; n < 16; n++) m = max(m, kv[n]);
            uint32_t gmax = m;
#pragma unroll
            for (int o = 1; o < 8; o <<= 1) gmax = max(gmax, __shfl_xor_sync(0xffffffffu, gmax, o));
            sts1(gm + (ta >> 3) * 4, gmax);
            sts1(cnt, 0);
            bar_sync(12, 128);
            const uint32_t c = lds1(gm + (lane & 15) * 4);
            int rank = 0;
#pragma unroll
            for (int i = 0; i < 2; i++) { const uint4 q = lds4(gm + (lane >> 4) * 32 + i * 16); rank += (q.x > c) + (q.y > c) + (q.z > c) + (q.w > c); }
            rank += __shfl_xor_sync(0xffffffffu, rank, 16);
            const uint32_t thr = redux_max(rank == 7 ? c : 0u);
#pragma unroll 1
            while (m >= thr) {
                uint32_t at, m2 = 0;
                asm volatile("atom.shared.add.u32 %0, [%1], 1;" : "=r"(at) : "r"(cnt) : "memory");
#pragma unroll
                for (int n = 0; n < 16; n++) m2 = max(m2, kv[n] < m ? kv[n] : 0u);
                sts1(list + at * 4, m);
                if (m2 == 0) break;
                m = m2;
            }
            bar_sync(12, 128);
            const int nc = lds1(cnt);
#pragma unroll 1
            for (int i = ta >> 3; i < ((nc + 3) & ~3); i += 16) {
                const uint32_t ki = lds1(list + i * 4);
                int r = 0;
#pragma unroll 1
                for (int n = lane & 7; n < nc; n += 8) r += lds1(list + n * 4) > ki;
                __syncwarp();
#pragma unroll
                for (int o = 1; o < 8; o <<= 1) r += __shfl_xor_sync(0xffffffffu, r, o);
                if (r == (b & 7) && i < nc) sts1(res, ki);
            }
            bar_sync(12, 128);
            const uint32_t k0 = lds1(res);
            const int r0 = 2047 - ((k0 >> 5) & 2047);
            TSC(ta == 0, 22);
            if (ta == 0) st_rlx(&scr->sel[b & 7], k0);
            const uint4 v0 = ldg_nc(x + (size_t)r0 * 1024 + ta * 8);
            const uint32_t s0 = ld_rlx(&scr->row[r0]);
            const float m0 = bf_lo(s0), i0 = rcp(bf_hi(s0));
            const int ao = 14336 + (ta >> 3) * 256 + (b & 7) * 32 + ((ta ^ b) & 7) * 4;
            st_rlx4(scr->act[ep & 1] + ao, norm_pair(v0.x, m0, i0), norm_pair(v0.y, m0, i0), norm_pair(v0.z, m0, i0), norm_pair(v0.w, m0, i0));
            __syncwarp();
            if (lane == 0) red_add(&scr->cnt[9][tries >> 30]);
            st_rlx4(scr->act[~ep & 1] + ao, 0, 0, 0, 0);
        }
        uint32_t s8 = 0, fph = 0;
        const uint32_t chk = __shfl_sync(0xffffffffu, sb + OFF_FS + BOX + lane * 32 + (lane & 28), lane);
        int left = BUDGET;
        if (b >= 112 && ta < 2) mbar_arrive(bars + 8 * B_F1DONE);
#pragma unroll 1
        for (int ph = b >= 112; ph < 2; ph++) {
            {
                float acc[4] = {0.f, 0.f, 0.f, 0.f};
                const uint32_t alo = sd + (ph ? dlo(OFF_FS, 8192) : dlo(OFF_FS, 4096)), ahi = ph ? dhi(1024, 1) : dhi(512, 2), astep = ph ? 128 : 64;
                const uint32_t bhi = ph ? dhi(128, 0) : dhi(1024, 1), bstep = ph ? 16 : 2, wrap = ph ? 24 : 40;
                uint32_t prev = 0;
                if (ph) mbar_wait(bars + 8 * FFN2_GATE, 0, left);
#pragma unroll 1
                for (int q = ph ? n2 : 16; q > 0; q--) {
                    const uint32_t da = alo + s8 * (F_BYTES >> 7), db = sd + dlo(OFF_FS + BOX, 128) + s8 * (F_BYTES >> 7);
                    mbar_wait_hot(bars + 8 * B_FFULL + s8, fph, left);
                    if (__builtin_expect(__any_sync(0xffffffffu, lds1(chk + s8 * (F_BYTES / 8)) == 0), 0)) {
                        int tries = BUDGET;
#pragma unroll 1
                        for (int n = lane * 4 + (left >> 30); n < 256; n += 128) {
                            uint4 v;
#pragma unroll 1
                            do { v = ld_rlx4(scr->act[ep & 1] + ((ph ? mt * NM + n2 : 72) - q) * 256 + n); } while (v.x == 0 && --tries > 0);
                            __syncwarp();
                            sts4(sb + OFF_FS + BOX + s8 * (F_BYTES / 8) + n * 4, v.x, v.y, v.z, v.w);
                        }
                        NRETRY();
                        fence_async_smem();
                        __syncwarp();
                    }
                    TSC(TIMING % 10 == 3 && ta == 0, 32 + (ph ? 16 + n2 : 16) - q);
                    wg_fence();
#pragma unroll
                    for (int j = 0; j < 4; j++) wgmma_n8<1, 0>(acc, mkdesc(da + j * astep, ahi), mkdesc(db + j * bstep, bhi), 1);
                    wg_commit();
                    wg_wait<1>();
                    if (ph) { wg_wait<0>(); if (lane == 0) prev = bars + 8 * B_FEMPTY + s8; }
                    if (prev) mbar_arrive(prev);
                    if (lane == 0) prev = bars + 8 * B_FEMPTY + s8;
                    s8 += 8;
                    if (s8 == wrap) { s8 = 0; fph ^= 1; }
                }
                wg_wait<0>();
                const int ln = lane + (left >> 30);
                if (ph == 0) {
                    if (prev) mbar_arrive(prev);
                    const bool second = (wq >= 2) != (swap_gu != 0);
                    const uint32_t xa = sb + OFF_GU + ((wq & 1) * 32 + ln) * 16;
                    if (second) sts4(xa, __float_as_uint(acc[0]), __float_as_uint(acc[1]), __float_as_uint(acc[2]), __float_as_uint(acc[3]));
                    bar_sync(12, 128);
                    if (second) { if (ln == 0) mbar_arrive(bars + 8 * B_F1DONE); }
                    else {
                        const float4 up = lds4f(xa);
                        float hv[4];
#pragma unroll
                        for (int c = 0; c < 4; c++) { const float ga = bf16r(acc[c]); hv[c] = bf16r(ga * sigmoidf(ga)) * bf16r((&up.x)[c]); }
                        const int ao = (b * 4 + (wq & 1) * 2) * 32 + ln;
                        st_rlx(scr->act[ep & 1] + ao, max(movm(pack_bf16(hv[0], hv[1])), 1u)); st_rlx(scr->act[ep & 1] + 32 + ao, max(movm(pack_bf16(hv[2], hv[3])), 1u));
                        __syncwarp();
                        if (ln == 0) red_add(&scr->cnt[b < 14 * NM ? b / (2 * NM) : b < 14 * NM + 2 * N7 ? 7 : 8][0]);
                        st_rlx(scr->act[~ep & 1] + ao, 0); st_rlx(scr->act[~ep & 1] + 32 + ao, 0);
                    }
                } else {
                    st_rlx4(&scr->ypart[mt][c2][wq * 32 + ln], (__float_as_uint(acc[0]) & ~1u) | (ep & 1), __float_as_uint(acc[1]), __float_as_uint(acc[2]), __float_as_uint(acc[3]));
                }
                TSC(ta == 0, 22 + ph);
            }
        }
        TSC(ta == 0, 24);
    } else {
        cluster_arrive();
        reg_inc<224>();
        const int w = warp >> 2, wi = warp & 3, g = lane >> 2, t = lane & 3;
        const bool elect = (tid & 127) == 0;
        const uint32_t mad = (lane & 15) * 128 + (((lane >> 4) ^ (lane & 7)) << 4);
        float acc[64];
        const uint32_t ring = sb + w * OFF_X1, ofull = bars + 8 * (B_OFULL + w * 6), oempty = mapa(bars + 8 * B_OEMPTY, w);
        const int r0 = rh * 128 + wi * 32 + (1 - w) * 16 + g;
        {
            float acc0[96], acc1[96];
            const uint32_t sta = sb + OFF_STAT + (8 + w * 128 + wi * 32) * 8;
            {
                const uint32_t xfull = bars + 8 * (B_XFULL + w * 6 + 5), xempty = mapa(bars + 8 * B_XEMPTY, w), dx0 = sd + dlo(w * OFF_X1, 16);
                uint32_t s8 = 16, ps8 = 0, ph = 0;
                TSC(tid == 0, 27);
                TSC(tid == 0, 25);
#pragma unroll 1
                for (int k = 0; k < 16; k++) {
                    const uint32_t dx = dx0 + s8 * (2 * BOX >> 7), dw = sd + dlo(OFF_W, BOX) + s8 * (W_BYTES >> 7);
                    mbar_wait(bars + 8 * B_WFULL + s8, ph, budget);
                    mbar_wait(xfull - 2 * s8, ph, budget);
                    TSC(elect && k == 0, 1 + 8 * w);
                    TSC(TIMING % 10 == 1 && tid == 0, 32 + k);
                    wg_wait<0>();
                    wg_fence();
#pragma unroll
                    for (int kk = 0; kk < 4; kk++) wgmma_n192<0, 1>(acc1, mkdesc(dx + kk * 2, dhi(1024, 1)), mkdesc(dw + kk * 128, dhi(1024, 1)), kk ? 1 : k);
                    wg_commit();
                    TSC(TIMING % 10 == 6 && elect, 32 + 16 * w + k);
                    if (elect && k > 0) {
                        mbar_arrive(bars + 8 * B_WEMPTY + ps8);
                        if (k <= 13) { mbar_expect_tx(xfull - 2 * ps8 - 8, BOX); mbar_arrive_at(xempty + 2 * ps8 + 8); }
                    }
                    if (k == 0) cluster_wait();
                    if (k == 15) {
                        mbar_wait(bars + 8 * B_AUX, 0, budget);
                        const uint32_t zero = budget >> 30, pm = t & 1 ? 0x4432 : 0x3232, ra = sta + ((t >> 1) * 16 + g) * 8;
                        const uint32_t a0 = __byte_perm(lds1(ra), 0, pm), a1 = __byte_perm(lds1(ra + 64), 0, pm), a2 = a0 & zero, a3 = a1 & zero;
                        wg_fence();
                        wgmma_rs_n192(acc1, a0, a1, a2, a3, mkdesc(sd + dlo(OFF_CS, 0), dhi(128, 0)));
                        wgmma_rs_n192(acc0, a0, a1, a2, a3, mkdesc(sd + dlo(OFF_CS + 64, 0), dhi(128, 0)));
                        wg_commit();
                    }
                    mbar_wait(xfull - 2 * s8 - 8, ph, budget);
                    wg_wait<0>();
                    wg_fence();
#pragma unroll
                    for (int kk = 0; kk < 4; kk++) wgmma_n192<0, 1>(acc0, mkdesc(dx + 512 + kk * 2, dhi(1024, 1)), mkdesc(dw + kk * 128, dhi(1024, 1)), kk ? 1 : k);
                    wg_commit();
                    if (elect && k <= 12) { mbar_expect_tx(xfull - 2 * s8, BOX); mbar_arrive_at(xempty + 2 * s8); }
                    ps8 = s8;
                    s8 = s8 == 16 ? 0 : s8 + 8;
                    if (s8 == 16) ph ^= 1;
                }
            }
            const uint32_t zero = budget >> 30;
            const bool u0 = 2 * t > g, u1 = 2 * t + 1 > g;
            uint32_t mU = (u0 ? 0xffffu : 0u) | (u1 ? 0xffff0000u : 0u);
            uint32_t ka0 = sta + (2 * t - (u0 ? 8 : 0)) * 8 + 4, ka1 = sta + (2 * t + 1 - (u1 ? 8 : 0)) * 8 + 4;
            float rk[2][4], fu[2][4], fn[2][4];
            auto factors = [&](int h) {
#pragma unroll
                for (int n = 0; n < 4; n += 2) {
                    const float rq = lds1f(sta + (16 * h + 4 * n + g) * 8 + 4) * (0.17677669529663687f * 1.4426950408889634f);
                    rk[h][n] = lds1f(ka0 + h * 128 + n * 32); rk[h][n + 1] = lds1f(ka1 + h * 128 + n * 32);
                    const float f0 = rq * rk[h][n], f1 = rq * rk[h][n + 1];
                    fu[h][n] = u0 ? f0 : 0.f; fn[h][n] = f0 - fu[h][n]; fu[h][n + 1] = u1 ? f1 : 0.f; fn[h][n + 1] = f1 - fu[h][n + 1];
                }
#pragma unroll
                for (int n = 0; n < 4; n++) asm volatile("" : "+f"(fu[h][n]), "+f"(fn[h][n]));
            };
            uint8_t* og = scr->o + ((size_t)(mt * 4 + w * 2) * 16 + nt) * BOX + wi * 256 + lane * 4;
            TSC(elect, 19 + w);
            uint32_t pk0[48], pk1[48], o[16] = {};
#pragma unroll
            for (int j = 0; j < 48; j++) if (j < 16 || (j & 1)) pk1[j] = pack_here(acc1[2 * j], acc1[2 * j + 1]);
            if (warp < 7) {
#pragma unroll
                for (int c = 0; c < 4; c++) stsm4(ring + 4 * BOX + wi * 2048 + c * 512 + lane * 16, pk1[17 + 8 * c], pk1[19 + 8 * c], pk1[21 + 8 * c], pk1[23 + 8 * c]);
                bar_arrive(1 + warp, 64);
            } else if (j0 != 768) {
#pragma unroll
                for (int c = 0; c < 4; c++) {
                    pk1[17 + 8 * c] = max(pk1[17 + 8 * c], 1u);
                    st_rlx4(&scr->halo[b][c * 128 + lane * 4], pk1[17 + 8 * c], pk1[19 + 8 * c], pk1[21 + 8 * c], pk1[23 + 8 * c]);
                }
            }
#pragma unroll
            for (int j = 16; j < 48; j += 2) pk1[j] = pack_here(acc1[2 * j], acc1[2 * j + 1]);
            factors(1);
            uint32_t od = sb + 2 * BOX + wi * 256 + (lane >> 4) * 1024 + (lane & 15) * 16, g1peer = mapa(bars + 8 * B_G1DONE, hp ^ 1);
            uint32_t ha = sb + (warp == 0 ? OFF_HIN : warp <= 4 ? 4 * BOX - 2048 : OFF_X1 + 4 * BOX - 5 * 2048) + warp * 2048 + lane * 16;
            const bool first = warp == 0 && j0 == 0;
            float bias0 = first && u0 ? -INFINITY : 0.f, bias1 = first && u1 ? -INFINITY : 0.f;
            asm volatile("" : "+l"(og), "+r"(mU), "+r"(od), "+r"(ha), "+f"(bias0), "+f"(bias1));
            mbar_wait(bars + 8 * B_XT, 0, budget);
            mbar_wait(bars + 8 * (B_WEMPTY + 1), 0, budget);
            wg_wait<0>();
            if (elect) { mbar_arrive(bars + 8 * B_G1DONE); mbar_arrive_at(g1peer); }
            TSC(elect, 2 + 8 * w);
            float ci[4];
#pragma unroll
            for (int n = 0; n < 4; n++) ci[n] = __uint_as_float((0x03800000u + n) | (budget >> 30));
            auto hand_over = [&](int v) {
                asm volatile("{\n.reg .pred p;\nsetp.ne.b32 p, %17, 0;\n"
                             "@p stmatrix.sync.aligned.m8n8.x4.shared.b16 [%16], {%0,%1,%2,%3};\n@p stmatrix.sync.aligned.m8n8.x4.shared.b16 [%16 + 2048], {%4,%5,%6,%7};\n"
                             "@p stmatrix.sync.aligned.m8n8.x4.shared.b16 [%16 + 4096], {%8,%9,%10,%11};\n@p stmatrix.sync.aligned.m8n8.x4.shared.b16 [%16 + 6144], {%12,%13,%14,%15};\n"
                             "fence.proxy.async.shared::cta;\n}"
                             ::"r"(o[0]), "r"(o[1]), "r"(o[2]), "r"(o[3]), "r"(o[4]), "r"(o[5]), "r"(o[6]), "r"(o[7]), "r"(o[8]), "r"(o[9]), "r"(o[10]), "r"(o[11]),
                               "r"(o[12]), "r"(o[13]), "r"(o[14]), "r"(o[15]), "r"(od + v * OFF_X1), "r"((int)(w == rh)) : "memory");
#pragma unroll
                for (int i = 0; i < 16; i++) asm volatile("st.global.u32 [%0], %1;" ::"l"(og + (1 - v) * 16 * BOX + (i >> 1) * 1024 + (i & 1) * 128), "r"(o[i]) : "memory");
                __syncwarp();
                if (lane == 0) mbar_arrive(bars + 8 * (B_STAGED + v));
            };
#pragma unroll
            for (int j = 32; j < 48; j++) pk1[j] = movm(pk1[j]);
#pragma unroll
            for (int j = EARLY_PK; j < 48; j++) if (j >= 32 || (j & 1) || EARLY_PK < 17) pk0[j] = pack_here(acc0[2 * j], acc0[2 * j + 1]);
#pragma unroll
            for (int j = 32; j < 48; j++) pk0[j] = movm(pk0[j]);
            attn_pair<2>(pk1, pk1 + 16, pk1 + 32, pk0 + 17, pk0 + 33, fu[1], fn[1], rk[1], 0.f, 0.f, mU, zero, ci, o);
            hand_over(0);
#pragma unroll
            for (int j = 0; j < 32; j++) if (j < EARLY_PK || (!(j & 1) && EARLY_PK == 17)) pk0[j] = pack_here(acc0[2 * j], acc0[2 * j + 1]);
            factors(0);
            bar_sync(warp ? warp : 11, 64);
            uint32_t hl[16];
            ldsm4(hl, ha); ldsm4(hl + 4, ha + 512); ldsm4t(hl + 8, ha + 1024); ldsm4t(hl + 12, ha + 1536);
            __syncwarp();
            if (lane == 0) mbar_arrive(bars + 8 * B_FREED);
            attn_pair<1>(pk0, pk0 + 16, pk0 + 32, hl, hl + 8, fu[0], fn[0], rk[0], bias0, bias1, mU, zero, ci, o);
            const float2 s0 = lds2f(sb + OFF_STAT + (8 + r0) * 8), s1 = lds2f(sb + OFF_STAT + (16 + r0) * 8);
            const float m0 = s0.x * s0.y, f0 = 1.f + s0.y, m1 = s1.x * s1.y, f1 = 1.f + s1.y;
            uint32_t xt[32];
#pragma unroll
            for (int j = 0; j < 8; j++) ldsm4(xt + 4 * j, ((ring + wi * 2048 + mad) ^ ((j & 3) * 32)) + (j >> 2) * BOX);
            hand_over(1);
#pragma unroll
            for (int j = 0; j < 32; j++) {
                acc[2 * j] = fmaf(bf_lo(xt[j]), j & 1 ? f1 : f0, j & 1 ? m1 : m0); acc[2 * j + 1] = fmaf(bf_hi(xt[j]), j & 1 ? f1 : f0, j & 1 ? m1 : m0);
            }
        }
        {
            const uint32_t da0 = sd + dlo(w * OFF_X1, 1024), db0 = sd + dlo(OFF_WO, BOX);
            const uint32_t chk = ring + wi * 256 + (lane >> 3) * 1032 + (lane & 7) * 32 + (lane & 4);
            uint32_t s8 = 16, ps8 = 0, ph = 0;
            mbar_wait(ofull + s8, 0, budget);
            mbar_wait(bars + 8 * B_WOFULL + s8, 0, budget);
            TSC(TIMING % 10 == 2 && elect, 32 + w * 16);
            const uint32_t ahi = dhi(128, 0) | (budget >> 30), bhi = dhi(1024, 1) | (budget >> 30);
            const int last = w ? HOLD : 15;
            uint32_t rel = elect ? 0x7fe : 0;
            uint32_t da = da0 + s8 * (BOX >> 7), db = db0 + s8 * (BOX >> 6);
#pragma unroll 1
            for (int i = 1;; i++) {
                wg_fence();
#pragma unroll
                for (int kk = 0; kk < 4; kk++) {
                    wgmma_n128<0, 1>(acc, mkdesc(da + kk * 128, ahi), mkdesc(db + kk * 128, bhi), 1);
                    if (kk & 1) wg_commit();
                }
                wg_wait<2>();
                if (rel & 1) { mbar_expect_tx(ofull + ps8, BOX); mbar_arrive_at(oempty + ps8); mbar_arrive(bars + 8 * B_WOEMPTY + ps8); }
                rel >>= 1;
                ps8 = s8;
                s8 = s8 == 40 ? 0 : s8 + 8;
                if (s8 == 16) ph ^= 1;
                da = da0 + s8 * (BOX >> 7); db = db0 + s8 * (BOX >> 6);
                uint32_t slow;
                asm volatile("{\n.reg .pred p, q, r;\n.reg .u32 u, v;\nmbarrier.try_wait.parity.shared::cta.b64 p, [%1], %3;\nmbarrier.try_wait.parity.shared::cta.b64 q, [%2], %3;\n"
                             "setp.ne.and.u32 r, %5, 1, p;\nmov.u32 u, 1;\nmov.u32 v, 1;\n@r ld.shared.u32 u, [%4];\n@r ld.shared.u32 v, [%4 + 4096];\n"
                             "and.pred p, p, q;\nmin.u32 u, u, v;\nsetp.eq.or.u32 p, u, 0, !p;\nvote.sync.any.pred p, p, 0xffffffff;\nselp.u32 %0, 1, 0, p;\n}"
                             : "=r"(slow) : "r"(ofull + s8), "r"(bars + 8 * B_WOFULL + s8), "r"(ph), "r"(chk + s8 * (BOX / 8)), "r"(i) : "memory");
                if (__builtin_expect(slow || i == last, 0)) {
                    uint32_t c8 = slow ? s8 : s8 + 8;
#pragma unroll 1
                    for (int n = slow ? i : i + 1; n < (i == last ? 16 : i + 1); n++, c8 += 8) {
                        const uint32_t cph = ph ^ (HOLD < 12 && c8 >= 16 && s8 < 16);
                        mbar_wait(ofull + c8, cph, budget);
                        mbar_wait(bars + 8 * B_WOFULL + c8, cph, budget);
                        if (__any_sync(0xffffffffu, min(lds1(chk + c8 * (BOX / 8)), lds1(chk + c8 * (BOX / 8) + 4096)) == 0)) {
                            const uint32_t at = wi * 256 + (lane >> 4) * 1024 + (lane & 15) * 16;
                            const uint8_t* src = scr->o + ((size_t)((mt * 2 + rh) * 2 + 1 - w) * 16 + ((2 * p + (n < 2 ? n ^ hp : n)) & 15)) * BOX + at;
#pragma unroll 1
                            for (int m = 0; m < 8192; m += 2048) {
                                uint4 v; int tries = 4096;
#pragma unroll 1
                                do { v = ld_rlx4(src + m); } while (v.x == 0 && --tries > 0);
                                sts4(ring + c8 * (BOX / 8) + at + m, v.x, v.y, v.z, v.w);
                            }
                            NRETRY();
                            fence_async_smem();
                            __syncwarp();
                        }
                    }
                    if (i == last) break;
                }
                TSC(TIMING % 10 == 2 && elect, 32 + w * 16 + i);
                wg_wait<1>();
            }
            if (w) bar_sync(9, 256);
#pragma unroll 1
            for (int i = last; i < 16; i++, da += 512, db += 1024) {
                wg_fence();
#pragma unroll
                for (int kk = 0; kk < 4; kk++) wgmma_n128<0, 1>(acc, mkdesc(da + kk * 128, ahi), mkdesc(db + kk * 128, bhi), 1);
                wg_commit();
            }
            if (!w) bar_arrive(9, 256);
            mbar_wait(bars + 8 * B_ZERO, 0, budget);
            const bool add = (__shfl_sync(0xffffffffu, lds1(sb + OFF_SEL), 0) >> (wi * 2 + 1 - w)) & 1;
            wg_wait<0>();
            TSC(elect, 7 + 9 * w);
            const uint32_t os0 = ring + wi * 4096;
#pragma unroll
            for (int hf = 0; hf < OUT_PARTS; hf++) {
#pragma unroll
                for (int j = hf * (8 / OUT_PARTS); j < (hf + 1) * (8 / OUT_PARTS); j++)
                    stsm4(((os0 + mad) ^ ((j & 3) * 32)) + (j >> 2) * 2048, pack_here(acc[8 * j], acc[8 * j + 1]), pack_here(acc[8 * j + 2], acc[8 * j + 3]),
                          pack_here(acc[8 * j + 4], acc[8 * j + 5]), pack_here(acc[8 * j + 6], acc[8 * j + 7]));
                fence_async_smem();
                __syncwarp();
                if (elect_one())
                    asm volatile("{\n.reg .pred p;\nsetp.ne.b32 p, %6, 0;\n@!p cp.async.bulk.tensor.5d.global.shared::cta.bulk_group [%0, {%2, %2, %3, %4, %5}], [%1];\n"
                                 "@p cp.reduce.async.bulk.tensor.5d.global.shared::cta.add.bulk_group [%0, {%2, %2, %3, %4, %5}], [%1];\n}"
                                 ::"l"(&mout), "r"(os0 + hf * 2048), "r"(0), "r"(((j0 + rh * 128) >> 5) + wi), "r"(1 - w), "r"(par * 16 + cb * 2 + hf), "r"((int)add) : "memory");
            }
            asm volatile("cp.async.bulk.commit_group;\ncp.async.bulk.wait_group.read 0;" ::: "memory");
            if (b == 0 && tid == 0) st_rlx(&scr->epoch[0], lds1(sb + OFF_EP));
            TSC(elect, 8 - 2 * w);
            TS_END();
        }
    }
}

typedef CUresult (*EncodeFn)(CUtensorMap*, CUtensorMapDataType, cuuint32_t, void*, const cuuint64_t*, const cuuint64_t*, const cuuint32_t*,
                             const cuuint32_t*, CUtensorMapInterleave, CUtensorMapSwizzle, CUtensorMapL2promotion, CUtensorMapFloatOOBfill);

CUtensorMap make_map(EncodeFn fn, const void* base, int rank, const cuuint64_t* dims, const cuuint64_t* strides, const cuuint32_t* box,
                     CUtensorMapSwizzle swz = CU_TENSOR_MAP_SWIZZLE_128B, CUtensorMapL2promotion pro = CU_TENSOR_MAP_L2_PROMOTION_L2_256B) {
    CUtensorMap m;
    cuuint32_t es[5] = {1, 1, 1, 1, 1};
    fn(&m, CU_TENSOR_MAP_DATA_TYPE_BFLOAT16, rank, (void*)base, dims, strides, box, es, CU_TENSOR_MAP_INTERLEAVE_NONE,
       swz, pro, CU_TENSOR_MAP_FLOAT_OOB_FILL_NONE);
    return m;
}

}

extern "C" void kernel_launch(void* const* d_in, const int* in_sizes, int n_in, void* d_out, int out_size) {
    (void)in_sizes; (void)n_in; (void)out_size;
    const __nv_bfloat16* x = (const __nv_bfloat16*)d_in[0];
    const __nv_bfloat16* wqkv = (const __nv_bfloat16*)d_in[1];
    const __nv_bfloat16* wo = (const __nv_bfloat16*)d_in[2];
    const __nv_bfloat16* wr = (const __nv_bfloat16*)d_in[4];
    const __nv_bfloat16* wg = (const __nv_bfloat16*)d_in[5];
    const __nv_bfloat16* wu = (const __nv_bfloat16*)d_in[6];
    const __nv_bfloat16* wd = (const __nv_bfloat16*)d_in[7];
    static EncodeFn fn = nullptr;
    static Scratch* scr = nullptr;
    if (!fn) {
        void* p = nullptr; cudaDriverEntryPointQueryResult q;
        cudaGetDriverEntryPoint("cuTensorMapEncodeTiled", &p, cudaEnableDefault, &q);
        fn = (EncodeFn)p;
        cudaFuncSetAttribute(fused_kernel, cudaFuncAttributeMaxDynamicSharedMemorySize, SMEM_LAUNCH);
        cudaGetSymbolAddress((void**)&scr, g_scr);
    }
    const cuuint64_t xd[4] = {2048, 16, 32, 2}, xs[4] = {4096, 131072, 65536, 128}, od[5] = {64, 16, 32, 2, 32};
    const cuuint32_t xb[4] = {64, 16, 4, 1}, ob[5] = {64, 16, 1, 1, 2 / OUT_PARTS};
    const cuuint64_t wdm[3] = {1024, 1024, 3}, wst[2] = {6144, 2048};
    const cuuint32_t wb[3] = {64, 64, 3};
    const cuuint64_t wod[3] = {64, 1024, 16}, wdd[3] = {64, 3584, 16}, wos[2] = {2048, 128};
    const cuuint32_t wob[3] = {64, 64, 2}, wdb[3] = {64, 64, 1};
    const CUtensorMapSwizzle s128 = CU_TENSOR_MAP_SWIZZLE_128B;
    CUtensorMap mx = make_map(fn, x, 4, xd, xs, xb, s128, (CUtensorMapL2promotion)P_X), mw = make_map(fn, wqkv, 3, wdm, wst, wb, s128, (CUtensorMapL2promotion)P_W);
    CUtensorMap mwo = make_map(fn, wo, 3, wod, wos, wob, s128, (CUtensorMapL2promotion)P_WO), mout = make_map(fn, d_out, 5, od, xs, ob, s128, (CUtensorMapL2promotion)P_OUT);
    const int swap_gu = wu < wg;
    const cuuint64_t gd[3] = {3584, 1024, 2}, gst[2] = {7168, (cuuint64_t)(swap_gu ? (const char*)wg - (const char*)wu : (const char*)wu - (const char*)wg)};
    const cuuint32_t gb[3] = {32, 64, 2};
    CUtensorMap mgu = make_map(fn, swap_gu ? wu : wg, 3, gd, gst, gb, CU_TENSOR_MAP_SWIZZLE_64B, (CUtensorMapL2promotion)P_GU);
    CUtensorMap mwd = make_map(fn, wd, 3, wdd, wos, wdb, s128, (CUtensorMapL2promotion)P_WD);
    const cuuint64_t md[2] = {64, 32768}, ms[1] = {128};
    const cuuint32_t mb[2] = {64, 64};
    CUtensorMap mo = make_map(fn, scr, 2, md, ms, mb, CU_TENSOR_MAP_SWIZZLE_NONE, (CUtensorMapL2promotion)P_O);
    const cuuint64_t rd[2] = {1024, 2048};
    const cuuint32_t rb[2] = {256, 16};
    CUtensorMap mr = make_map(fn, x, 2, rd, wos, rb, CU_TENSOR_MAP_SWIZZLE_NONE, (CUtensorMapL2promotion)P_R);
    cudaLaunchConfig_t cfg = {};
    cfg.gridDim = dim3(132); cfg.blockDim = dim3(512); cfg.dynamicSmemBytes = SMEM_LAUNCH; cfg.stream = cudaStreamPerThread;
    cudaLaunchKernelEx(&cfg, fused_kernel, mx, mw, mwo, mout, mgu, mwd, mo, mr, x, wr, scr, swap_gu, Weights{(const char*)wqkv, (const char*)wo, (const char*)wg, (const char*)wu, (const char*)wd, (char*)d_out});
}
```

```cpp
#include <cuda_runtime.h>
#include <cuda.h>
#include <cuda_bf16.h>
#include <stdint.h>

namespace {

constexpr int BOX = 8192, W_BYTES = 3 * BOX;
constexpr int OFF_X1 = 6 * BOX, OFF_FR = 12 * BOX, OFF_E = 16 * BOX, OFF_W = 19 * BOX;
constexpr int OFF_WO = OFF_E;
constexpr int OFF_HIN = OFF_FR + 2048, OFF_GU = OFF_HIN + 2048, OFF_FS = OFF_GU + 1024;
constexpr int F_BYTES = 9216;
constexpr int CS_BYTES = 3136;
constexpr int OFF_CS = OFF_FS + 5 * F_BYTES;
constexpr int OFF_STAT = 28 * BOX;
constexpr int OFF_SEL = OFF_STAT + 2112, OFF_EP = OFF_SEL + 4;
constexpr int OFF_BAR = OFF_SEL + 16;
constexpr int B_WFULL = 0, B_XFULL = 3, B_ROW = 15, B_LATE = 19;
constexpr int B_AUX = 19, B_XT = 20, B_ZERO = 21, B_WOFULL = 22, B_OFULL = 28, B_FFULL = 40;
constexpr int B_WEMPTY = 45, B_F1DONE = 48, B_XEMPTY = 49, B_WOEMPTY = 55, B_OEMPTY = 61;
constexpr int B_G1DONE = 71, B_FEMPTY = 72, B_STAGED = 77, B_RDONE = 79, B_FREED = 80, NBAR = 83;
constexpr int SMEM_BYTES = OFF_BAR + NBAR * 8;
static_assert(OFF_FS + 3 * F_BYTES == OFF_E && OFF_CS + CS_BYTES <= OFF_W && SMEM_BYTES + 256 <= 232448 && OFF_BAR % 8 == 0, "smem");
constexpr int PF_RATE = 10;
constexpr int PF_START = 7;
constexpr int HOLD = 12;
constexpr int NM = 3;
constexpr int N7 = 9;
constexpr int NR = 5;
constexpr int ROWS_AT = 0x280;
constexpr int NH = 56 - 7 * NM - N7;
static_assert(NH >= NR + 12 && NH <= 32 && NR < 6, "FFN2 split");
constexpr int BUDGET = 1 << 18;

struct Scratch {
    uint8_t o[2048 * 1024 * 2];
    uint4 ypart[8][16][128];
    uint32_t halo[128][512];
    uint32_t act[2][14336 + 4096];
    uint2 row[2048];
    uint4 cs[16][3][24];
    uint32_t oflag[16][32];
    uint32_t cnt[10][32];
    uint32_t sel[32], zflag[32], epoch[32];
};
__device__ __align__(1024) Scratch g_scr;
struct Weights { const char *wqkv, *wo, *wg, *wu, *wd; char* out; };

constexpr int SMEM_LAUNCH = SMEM_BYTES;
__device__ __forceinline__ uint32_t smem_u32(const void* p) { return (uint32_t)__cvta_generic_to_shared(p); }
__device__ __forceinline__ void mbar_init(uint32_t bar, uint32_t cnt) { asm volatile("mbarrier.init.shared::cta.b64 [%0], %1;" ::"r"(bar), "r"(cnt) : "memory"); }
__device__ __forceinline__ void mbar_expect_tx(uint32_t bar, uint32_t bytes) { asm volatile("mbarrier.arrive.expect_tx.shared::cta.b64 _, [%0], %1;" ::"r"(bar), "r"(bytes) : "memory"); }
__device__ __forceinline__ void mbar_arrive(uint32_t bar) { asm volatile("mbarrier.arrive.shared::cta.b64 _, [%0];" ::"r"(bar) : "memory"); }
__device__ __forceinline__ uint32_t mapa(uint32_t a, uint32_t cta) { uint32_t r; asm("mapa.shared::cluster.u32 %0, %1, %2;" : "=r"(r) : "r"(a), "r"(cta)); return r; }
__device__ __forceinline__ void mbar_arrive_at(uint32_t cbar) { asm volatile("mbarrier.arrive.shared::cluster.b64 _, [%0];" ::"r"(cbar) : "memory"); }
__device__ __forceinline__ void mbar_wait(uint32_t bar, uint32_t parity, int& budget) {
    asm volatile("{\n.reg .pred p;\nLAB_WAIT:\nmbarrier.try_wait.parity.shared::cta.b64 p, [%1], %2;\n"
                 "add.s32 %0, %0, -1;\nsetp.gt.and.s32 p, %0, 0, !p;\n@p bra LAB_WAIT;\n}" : "+r"(budget) : "r"(bar), "r"(parity) : "memory");
}
__device__ __forceinline__ void mbar_wait_hot(uint32_t bar, uint32_t parity, int& budget) {
    asm volatile("{\n.reg .pred p;\nmbarrier.try_wait.parity.shared::cta.b64 p, [%1], %2;\n@p bra LAB_DONE;\nLAB_WAIT:\nmbarrier.try_wait.parity.shared::cta.b64 p, [%1], %2;\n"
                 "add.s32 %0, %0, -1;\nsetp.gt.and.s32 p, %0, 0, !p;\n@p bra LAB_WAIT;\nLAB_DONE:\n}" : "+r"(budget) : "r"(bar), "r"(parity) : "memory");
}
__device__ __forceinline__ void tma_2d(uint32_t dst, const CUtensorMap* m, uint32_t bar, int c0, int c1) {
    asm volatile("cp.async.bulk.tensor.2d.shared::cluster.global.mbarrier::complete_tx::bytes [%0], [%1, {%3, %4}], [%2];" ::"r"(dst), "l"(m), "r"(bar), "r"(c0), "r"(c1) : "memory");
}
__device__ __forceinline__ void tma_2d_mc(uint32_t dst, const CUtensorMap* m, uint32_t bar, int c0, int c1) {
    asm volatile("cp.async.bulk.tensor.2d.shared::cluster.global.mbarrier::complete_tx::bytes.multicast::cluster [%0], [%1, {%3, %4}], [%2], %5;" ::"r"(dst), "l"(m), "r"(bar), "r"(c0), "r"(c1), "h"((uint16_t)3) : "memory");
}
__device__ __forceinline__ void tma_3d(uint32_t dst, const CUtensorMap* m, uint32_t bar, int c0, int c1, int c2) {
    asm volatile("cp.async.bulk.tensor.3d.shared::cluster.global.mbarrier::complete_tx::bytes [%0], [%1, {%3, %4, %5}], [%2];" ::"r"(dst), "l"(m), "r"(bar), "r"(c0), "r"(c1), "r"(c2) : "memory");
}
__device__ __forceinline__ void tma_4d(uint32_t dst, const CUtensorMap* m, uint32_t bar, int c0, int c1, int c2, int c3) {
    asm volatile("cp.async.bulk.tensor.4d.shared::cluster.global.mbarrier::complete_tx::bytes [%0], [%1, {%3, %4, %5, %6}], [%2];" ::"r"(dst), "l"(m), "r"(bar), "r"(c0), "r"(c1), "r"(c2), "r"(c3) : "memory");
}
__device__ __forceinline__ void tma_4d_mc(uint32_t dst, const CUtensorMap* m, uint32_t bar, int c0, int c1, int c2, int c3) {
    asm volatile("cp.async.bulk.tensor.4d.shared::cluster.global.mbarrier::complete_tx::bytes.multicast::cluster [%0], [%1, {%3, %4, %5, %6}], [%2], %7;" ::"r"(dst), "l"(m), "r"(bar), "r"(c0), "r"(c1), "r"(c2), "r"(c3), "h"((uint16_t)3) : "memory");
}
__device__ __forceinline__ void bulk_pf(const void* p, uint32_t bytes) { asm volatile("cp.async.bulk.prefetch.L2.global [%0], %1;" ::"l"(p), "r"(bytes) : "memory"); }
__device__ __forceinline__ void bulk_g2s(uint32_t dst, const void* src, uint32_t bytes, uint32_t bar) {
    asm volatile("cp.async.bulk.shared::cluster.global.mbarrier::complete_tx::bytes [%0], [%1], %2, [%3];" ::"r"(dst), "l"(src), "r"(bytes), "r"(bar) : "memory");
}
__device__ __forceinline__ void bulk_s2c(uint32_t cdst, uint32_t src, uint32_t bytes, uint32_t cbar) {
    asm volatile("cp.async.bulk.shared::cluster.shared::cta.mbarrier::complete_tx::bytes [%0], [%1], %2, [%3];" ::"r"(cdst), "r"(src), "r"(bytes), "r"(cbar) : "memory");
}
__device__ __forceinline__ void cluster_arrive() { asm volatile("barrier.cluster.arrive.relaxed.aligned;" ::: "memory"); }
__device__ __forceinline__ void cluster_wait() { asm volatile("barrier.cluster.wait.aligned;" ::: "memory"); }
__device__ __forceinline__ void fence_gpu() { asm volatile("fence.acq_rel.gpu;" ::: "memory"); }
__device__ __forceinline__ void fence_async_smem() { asm volatile("fence.proxy.async.shared::cta;" ::: "memory"); }
__device__ __forceinline__ void wg_fence() { asm volatile("wgmma.fence.sync.aligned;" ::: "memory"); }
__device__ __forceinline__ void wg_commit() { asm volatile("wgmma.commit_group.sync.aligned;" ::: "memory"); }
template <int N> __device__ __forceinline__ void wg_wait() { asm volatile("wgmma.wait_group.sync.aligned %0;" ::"n"(N) : "memory"); }
__device__ __forceinline__ uint64_t mkdesc(uint32_t lo, uint32_t hi) { return ((uint64_t)hi << 32) | lo; }
__host__ __device__ constexpr uint32_t dhi(uint32_t sbo, uint32_t mode) { return (sbo >> 4) | (mode << 30); }
__host__ __device__ constexpr uint32_t dlo(uint32_t off, uint32_t lbo) { return (off >> 4) + ((lbo >> 4) << 16); }
__device__ __forceinline__ bool elect_one() {
    uint32_t e;
    asm volatile("{\n.reg .pred p;\nelect.sync _|p, 0xffffffff;\nselp.u32 %0, 1, 0, p;\n}" : "=r"(e));
    return e;
}
template <int R> __device__ __forceinline__ void reg_inc() { asm volatile("setmaxnreg.inc.sync.aligned.u32 %0;" ::"n"(R)); }
template <int R> __device__ __forceinline__ void reg_dec() { asm volatile("setmaxnreg.dec.sync.aligned.u32 %0;" ::"n"(R)); }
__device__ __forceinline__ void bar_sync(int id, int n) { asm volatile("bar.sync %0, %1;" ::"r"(id), "r"(n) : "memory"); }
__device__ __forceinline__ void bar_arrive(int id, int n) { asm volatile("bar.arrive %0, %1;" ::"r"(id), "r"(n) : "memory"); }
__device__ __forceinline__ uint32_t pack_bf16(float lo, float hi) { uint32_t r; asm("cvt.rn.bf16x2.f32 %0, %1, %2;" : "=r"(r) : "f"(hi), "f"(lo)); return r; }
__device__ __forceinline__ uint32_t pack_here(float lo, float hi) { uint32_t r; asm volatile("cvt.rn.bf16x2.f32 %0, %1, %2;" : "=r"(r) : "f"(hi), "f"(lo)); return r; }
__device__ __forceinline__ float bf_lo(uint32_t u) { return __uint_as_float(u << 16); }
__device__ __forceinline__ float bf_hi(uint32_t u) { return __uint_as_float(u & 0xffff0000u); }
__device__ __forceinline__ float bf16r(float v) { return bf_lo(pack_bf16(v, 0.f)); }
__device__ __forceinline__ float rcp(float x) { float r; asm("rcp.approx.ftz.f32 %0, %1;" : "=f"(r) : "f"(x)); return r; }
__device__ __forceinline__ float ex2(float x) { float r; asm("ex2.approx.ftz.f32 %0, %1;" : "=f"(r) : "f"(x)); return r; }
__device__ __forceinline__ float sigmoidf(float v) { return rcp(1.f + ex2(v * -1.4426950408889634f)); }
__device__ __forceinline__ uint32_t movm(uint32_t a) { uint32_t d; asm volatile("movmatrix.sync.aligned.m8n8.trans.b16 %0, %1;" : "=r"(d) : "r"(a)); return d; }
__device__ __forceinline__ void mma16816(float (&c)[4], uint32_t a0, uint32_t a1, uint32_t a2, uint32_t a3, uint32_t b0, uint32_t b1) {
    asm volatile("mma.sync.aligned.m16n8k16.row.col.f32.bf16.bf16.f32 {%0,%1,%2,%3}, {%4,%5,%6,%7}, {%8,%9}, {%0,%1,%2,%3};"
                 : "+f"(c[0]), "+f"(c[1]), "+f"(c[2]), "+f"(c[3]) : "r"(a0), "r"(a1), "r"(a2), "r"(a3), "r"(b0), "r"(b1));
}
__device__ __forceinline__ void mma1688(float (&c)[4], uint32_t a0, uint32_t a1, uint32_t b0) {
    asm volatile("mma.sync.aligned.m16n8k8.row.col.f32.bf16.bf16.f32 {%0,%1,%2,%3}, {%4,%5}, {%6}, {%0,%1,%2,%3};"
                 : "+f"(c[0]), "+f"(c[1]), "+f"(c[2]), "+f"(c[3]) : "r"(a0), "r"(a1), "r"(b0));
}
__device__ __forceinline__ void stsm4(uint32_t a, uint32_t r0, uint32_t r1, uint32_t r2, uint32_t r3) {
    asm volatile("stmatrix.sync.aligned.m8n8.x4.shared.b16 [%0], {%1,%2,%3,%4};" ::"r"(a), "r"(r0), "r"(r1), "r"(r2), "r"(r3) : "memory");
}
__device__ __forceinline__ void ldsm4(uint32_t* r, uint32_t a) {
    asm volatile("ldmatrix.sync.aligned.m8n8.x4.shared.b16 {%0,%1,%2,%3}, [%4];" : "=r"(r[0]), "=r"(r[1]), "=r"(r[2]), "=r"(r[3]) : "r"(a) : "memory");
}
__device__ __forceinline__ void ldsm4t(uint32_t* r, uint32_t a) {
    asm volatile("ldmatrix.sync.aligned.m8n8.x4.trans.shared.b16 {%0,%1,%2,%3}, [%4];" : "=r"(r[0]), "=r"(r[1]), "=r"(r[2]), "=r"(r[3]) : "r"(a) : "memory");
}
__device__ __forceinline__ uint32_t ld_rlx(const void* p) { uint32_t v; asm volatile("ld.relaxed.gpu.global.u32 %0, [%1];" : "=r"(v) : "l"(p) : "memory"); return v; }
__device__ __forceinline__ uint32_t ld_acq(const void* p) { uint32_t v; asm volatile("ld.acquire.gpu.global.u32 %0, [%1];" : "=r"(v) : "l"(p) : "memory"); return v; }
__device__ __forceinline__ uint2 ld_rlx2(const void* p) { uint2 v; asm volatile("ld.relaxed.gpu.global.v2.u32 {%0,%1}, [%2];" : "=r"(v.x), "=r"(v.y) : "l"(p) : "memory"); return v; }
__device__ __forceinline__ uint4 ld_rlx4(const void* p) { uint4 v; asm volatile("ld.relaxed.gpu.global.v4.u32 {%0,%1,%2,%3}, [%4];" : "=r"(v.x), "=r"(v.y), "=r"(v.z), "=r"(v.w) : "l"(p) : "memory"); return v; }
__device__ __forceinline__ void st_rlx(void* p, uint32_t v) { asm volatile("st.relaxed.gpu.global.u32 [%0], %1;" ::"l"(p), "r"(v) : "memory"); }
__device__ __forceinline__ void st_rlx2(void* p, uint32_t a, uint32_t b) { asm volatile("st.relaxed.gpu.global.v2.u32 [%0], {%1,%2};" ::"l"(p), "r"(a), "r"(b) : "memory"); }
__device__ __forceinline__ void st_rlx4(void* p, uint32_t a, uint32_t b, uint32_t c, uint32_t d) { asm volatile("st.relaxed.gpu.global.v4.u32 [%0], {%1,%2,%3,%4};" ::"l"(p), "r"(a), "r"(b), "r"(c), "r"(d) : "memory"); }
__device__ __forceinline__ void red_add(uint32_t* p) { asm volatile("red.relaxed.gpu.global.add.u32 [%0], 1;" ::"l"(p) : "memory"); }
__device__ __forceinline__ uint4 ldg_nc(const void* p) { uint4 v; asm volatile("ld.global.nc.v4.u32 {%0,%1,%2,%3}, [%4];" : "=r"(v.x), "=r"(v.y), "=r"(v.z), "=r"(v.w) : "l"(p)); return v; }
__device__ __forceinline__ void sts4(uint32_t a, uint32_t x, uint32_t y, uint32_t z, uint32_t w) { asm volatile("st.shared.v4.u32 [%0], {%1,%2,%3,%4};" ::"r"(a), "r"(x), "r"(y), "r"(z), "r"(w) : "memory"); }
__device__ __forceinline__ void sts2(uint32_t a, uint32_t x, uint32_t y) { asm volatile("st.shared.v2.u32 [%0], {%1,%2};" ::"r"(a), "r"(x), "r"(y) : "memory"); }
__device__ __forceinline__ void sts1(uint32_t a, uint32_t v) { asm volatile("st.shared.u32 [%0], %1;" ::"r"(a), "r"(v) : "memory"); }
__device__ __forceinline__ uint4 lds4(uint32_t a) { uint4 v; asm volatile("ld.shared.v4.u32 {%0,%1,%2,%3}, [%4];" : "=r"(v.x), "=r"(v.y), "=r"(v.z), "=r"(v.w) : "r"(a) : "memory"); return v; }
__device__ __forceinline__ float4 lds4f(uint32_t a) { float4 v; asm volatile("ld.shared.v4.f32 {%0,%1,%2,%3}, [%4];" : "=f"(v.x), "=f"(v.y), "=f"(v.z), "=f"(v.w) : "r"(a) : "memory"); return v; }
__device__ __forceinline__ float2 lds2f(uint32_t a) { float2 v; asm volatile("ld.shared.v2.f32 {%0,%1}, [%2];" : "=f"(v.x), "=f"(v.y) : "r"(a) : "memory"); return v; }
__device__ __forceinline__ float lds1f(uint32_t a) { float v; asm volatile("ld.shared.f32 %0, [%1];" : "=f"(v) : "r"(a) : "memory"); return v; }
__device__ __forceinline__ uint32_t lds1(uint32_t a) { uint32_t v; asm volatile("ld.shared.u32 %0, [%1];" : "=r"(v) : "r"(a) : "memory"); return v; }
__device__ __forceinline__ uint32_t redux_max(uint32_t v) { uint32_t r; asm volatile("redux.sync.max.u32 %0, %1, 0xffffffff;" : "=r"(r) : "r"(v)); return r; }
__device__ __forceinline__ uint32_t poll_all(const uint32_t* p, uint32_t mask, uint32_t want, int& budget) {
    uint32_t v;
#pragma unroll 1
    while (v = ld_acq(p), !__all_sync(0xffffffffu, (v & mask) == want) && --budget > 0) __nanosleep(30);
    return v;
}

template <int TA, int TB>
__device__ __forceinline__ void wgmma_n192(float (&d)[96], uint64_t da, uint64_t db, int keep) {
    asm volatile("{\n.reg .pred p;\nsetp.ne.b32 p, %98, 0;\n"
        "wgmma.mma_async.sync.aligned.m64n192k16.f32.bf16.bf16 "
        "{%0, %1, %2, %3, %4, %5, %6, %7, %8, %9, %10, %11, %12, %13, %14, %15, "
        "%16, %17, %18, %19, %20, %21, %22, %23, %24, %25, %26, %27, %28, %29, %30, %31, "
        "%32, %33, %34, %35, %36, %37, %38, %39, %40, %41, %42, %43, %44, %45, %46, %47, "
        "%48, %49, %50, %51, %52, %53, %54, %55, %56, %57, %58, %59, %60, %61, %62, %63, "
        "%64, %65, %66, %67, %68, %69, %70, %71, %72, %73, %74, %75, %76, %77, %78, %79, "
        "%80, %81, %82, %83, %84, %85, %86, %87, %88, %89, %90, %91, %92, %93, %94, %95}, "
        "%96, %97, p, 1, 1, %99, %100;\n}\n"
        : "+f"(d[0]), "+f"(d[1]), "+f"(d[2]), "+f"(d[3]), "+f"(d[4]), "+f"(d[5]), "+f"(d[6]), "+f"(d[7]),
          "+f"(d[8]), "+f"(d[9]), "+f"(d[10]), "+f"(d[11]), "+f"(d[12]), "+f"(d[13]), "+f"(d[14]), "+f"(d[15]),
          "+f"(d[16]), "+f"(d[17]), "+f"(d[18]), "+f"(d[19]), "+f"(d[20]), "+f"(d[21]), "+f"(d[22]), "+f"(d[23]),
          "+f"(d[24]), "+f"(d[25]), "+f"(d[26]), "+f"(d[27]), "+f"(d[28]), "+f"(d[29]), "+f"(d[30]), "+f"(d[31]),
          "+f"(d[32]), "+f"(d[33]), "+f"(d[34]), "+f"(d[35]), "+f"(d[36]), "+f"(d[37]), "+f"(d[38]), "+f"(d[39]),
          "+f"(d[40]), "+f"(d[41]), "+f"(d[42]), "+f"(d[43]), "+f"(d[44]), "+f"(d[45]), "+f"(d[46]), "+f"(d[47]),
          "+f"(d[48]), "+f"(d[49]), "+f"(d[50]), "+f"(d[51]), "+f"(d[52]), "+f"(d[53]), "+f"(d[54]), "+f"(d[55]),
          "+f"(d[56]), "+f"(d[57]), "+f"(d[58]), "+f"(d[59]), "+f"(d[60]), "+f"(d[61]), "+f"(d[62]), "+f"(d[63]),
          "+f"(d[64]), "+f"(d[65]), "+f"(d[66]), "+f"(d[67]), "+f"(d[68]), "+f"(d[69]), "+f"(d[70]), "+f"(d[71]),
          "+f"(d[72]), "+f"(d[73]), "+f"(d[74]), "+f"(d[75]), "+f"(d[76]), "+f"(d[77]), "+f"(d[78]), "+f"(d[79]),
          "+f"(d[80]), "+f"(d[81]), "+f"(d[82]), "+f"(d[83]), "+f"(d[84]), "+f"(d[85]), "+f"(d[86]), "+f"(d[87]),
          "+f"(d[88]), "+f"(d[89]), "+f"(d[90]), "+f"(d[91]), "+f"(d[92]), "+f"(d[93]), "+f"(d[94]), "+f"(d[95])
        : "l"(da), "l"(db), "r"(keep), "n"(TA), "n"(TB));
}
template <int TA, int TB>
__device__ __forceinline__ void wgmma_n128(float (&d)[64], uint64_t da, uint64_t db, int keep) {
    asm volatile("{\n.reg .pred p;\nsetp.ne.b32 p, %66, 0;\n"
        "wgmma.mma_async.sync.aligned.m64n128k16.f32.bf16.bf16 "
        "{%0, %1, %2, %3, %4, %5, %6, %7, %8, %9, %10, %11, %12, %13, %14, %15, "
        "%16, %17, %18, %19, %20, %21, %22, %23, %24, %25, %26, %27, %28, %29, %30, %31, "
        "%32, %33, %34, %35, %36, %37, %38, %39, %40, %41, %42, %43, %44, %45, %46, %47, "
        "%48, %49, %50, %51, %52, %53, %54, %55, %56, %57, %58, %59, %60, %61, %62, %63}, "
        "%64, %65, p, 1, 1, %67, %68;\n}\n"
        : "+f"(d[0]), "+f"(d[1]), "+f"(d[2]), "+f"(d[3]), "+f"(d[4]), "+f"(d[5]), "+f"(d[6]), "+f"(d[7]),
          "+f"(d[8]), "+f"(d[9]), "+f"(d[10]), "+f"(d[11]), "+f"(d[12]), "+f"(d[13]), "+f"(d[14]), "+f"(d[15]),
          "+f"(d[16]), "+f"(d[17]), "+f"(d[18]), "+f"(d[19]), "+f"(d[20]), "+f"(d[21]), "+f"(d[22]), "+f"(d[23]),
          "+f"(d[24]), "+f"(d[25]), "+f"(d[26]), "+f"(d[27]), "+f"(d[28]), "+f"(d[29]), "+f"(d[30]), "+f"(d[31]),
          "+f"(d[32]), "+f"(d[33]), "+f"(d[34]), "+f"(d[35]), "+f"(d[36]), "+f"(d[37]), "+f"(d[38]), "+f"(d[39]),
          "+f"(d[40]), "+f"(d[41]), "+f"(d[42]), "+f"(d[43]), "+f"(d[44]), "+f"(d[45]), "+f"(d[46]), "+f"(d[47]),
          "+f"(d[48]), "+f"(d[49]), "+f"(d[50]), "+f"(d[51]), "+f"(d[52]), "+f"(d[53]), "+f"(d[54]), "+f"(d[55]),
          "+f"(d[56]), "+f"(d[57]), "+f"(d[58]), "+f"(d[59]), "+f"(d[60]), "+f"(d[61]), "+f"(d[62]), "+f"(d[63])
        : "l"(da), "l"(db), "r"(keep), "n"(TA), "n"(TB));
}
template <int TA, int TB>
__device__ __forceinline__ void wgmma_n8(float (&d)[4], uint64_t da, uint64_t db, int keep) {
    asm volatile("{\n.reg .pred p;\nsetp.ne.b32 p, %6, 0;\n"
        "wgmma.mma_async.sync.aligned.m64n8k16.f32.bf16.bf16 "
        "{%0, %1, %2, %3}, "
        "%4, %5, p, 1, 1, %7, %8;\n}\n"
        : "+f"(d[0]), "+f"(d[1]), "+f"(d[2]), "+f"(d[3])
        : "l"(da), "l"(db), "r"(keep), "n"(TA), "n"(TB));
}
__device__ __forceinline__ void wgmma_rs_n192(float (&d)[96], uint32_t a0, uint32_t a1, uint32_t a2, uint32_t a3, uint64_t db) {
    asm volatile("{\n.reg .pred p;\nsetp.ne.b32 p, 1, 0;\n"
        "wgmma.mma_async.sync.aligned.m64n192k16.f32.bf16.bf16 "
        "{%0, %1, %2, %3, %4, %5, %6, %7, %8, %9, %10, %11, %12, %13, %14, %15, "
        "%16, %17, %18, %19, %20, %21, %22, %23, %24, %25, %26, %27, %28, %29, %30, %31, "
        "%32, %33, %34, %35, %36, %37, %38, %39, %40, %41, %42, %43, %44, %45, %46, %47, "
        "%48, %49, %50, %51, %52, %53, %54, %55, %56, %57, %58, %59, %60, %61, %62, %63, "
        "%64, %65, %66, %67, %68, %69, %70, %71, %72, %73, %74, %75, %76, %77, %78, %79, "
        "%80, %81, %82, %83, %84, %85, %86, %87, %88, %89, %90, %91, %92, %93, %94, %95}, "
        "{%96, %97, %98, %99}, %100, p, 1, 1, 1;\n}\n"
        : "+f"(d[0]), "+f"(d[1]), "+f"(d[2]), "+f"(d[3]), "+f"(d[4]), "+f"(d[5]), "+f"(d[6]), "+f"(d[7]),
          "+f"(d[8]), "+f"(d[9]), "+f"(d[10]), "+f"(d[11]), "+f"(d[12]), "+f"(d[13]), "+f"(d[14]), "+f"(d[15]),
          "+f"(d[16]), "+f"(d[17]), "+f"(d[18]), "+f"(d[19]), "+f"(d[20]), "+f"(d[21]), "+f"(d[22]), "+f"(d[23]),
          "+f"(d[24]), "+f"(d[25]), "+f"(d[26]), "+f"(d[27]), "+f"(d[28]), "+f"(d[29]), "+f"(d[30]), "+f"(d[31]),
          "+f"(d[32]), "+f"(d[33]), "+f"(d[34]), "+f"(d[35]), "+f"(d[36]), "+f"(d[37]), "+f"(d[38]), "+f"(d[39]),
          "+f"(d[40]), "+f"(d[41]), "+f"(d[42]), "+f"(d[43]), "+f"(d[44]), "+f"(d[45]), "+f"(d[46]), "+f"(d[47]),
          "+f"(d[48]), "+f"(d[49]), "+f"(d[50]), "+f"(d[51]), "+f"(d[52]), "+f"(d[53]), "+f"(d[54]), "+f"(d[55]),
          "+f"(d[56]), "+f"(d[57]), "+f"(d[58]), "+f"(d[59]), "+f"(d[60]), "+f"(d[61]), "+f"(d[62]), "+f"(d[63]),
          "+f"(d[64]), "+f"(d[65]), "+f"(d[66]), "+f"(d[67]), "+f"(d[68]), "+f"(d[69]), "+f"(d[70]), "+f"(d[71]),
          "+f"(d[72]), "+f"(d[73]), "+f"(d[74]), "+f"(d[75]), "+f"(d[76]), "+f"(d[77]), "+f"(d[78]), "+f"(d[79]),
          "+f"(d[80]), "+f"(d[81]), "+f"(d[82]), "+f"(d[83]), "+f"(d[84]), "+f"(d[85]), "+f"(d[86]), "+f"(d[87]),
          "+f"(d[88]), "+f"(d[89]), "+f"(d[90]), "+f"(d[91]), "+f"(d[92]), "+f"(d[93]), "+f"(d[94]), "+f"(d[95])
        : "r"(a0), "r"(a1), "r"(a2), "r"(a3), "l"(db));
}
__device__ __forceinline__ void wgmma_rs_n8(float (&d)[4], uint32_t a0, uint32_t a1, uint32_t a2, uint32_t a3, uint64_t db) {
    asm volatile("{\n.reg .pred p;\nsetp.ne.b32 p, 1, 0;\n"
        "wgmma.mma_async.sync.aligned.m64n8k16.f32.bf16.bf16 "
        "{%0, %1, %2, %3}, "
        "{%4, %5, %6, %7}, %8, p, 1, 1, 0;\n}\n"
        : "+f"(d[0]), "+f"(d[1]), "+f"(d[2]), "+f"(d[3])
        : "r"(a0), "r"(a1), "r"(a2), "r"(a3), "l"(db));
}

template <int HS>
__device__ __forceinline__ void attn_pair(const uint32_t* q, const uint32_t* k, const uint32_t* v, const uint32_t* kh, const uint32_t* vh,
                                          const float* fu, const float* fn, const float* rk, float bias0, float bias1, uint32_t mU, uint32_t zero, const float* ci, uint32_t* o) {
    float s0[2][4] = {}, s1[2][4] = {}, s2[2][4] = {};
#pragma unroll
    for (int n = 0; n < 4; n++) {
        const int hd = n & 1, a = 8 * hd + 2 * (n & 2);
        mma16816(s1[hd], q[a], q[a + 1], q[a + 2], q[a + 3], k[a], k[a + 2]);
        mma16816(s2[hd], q[a], q[a + 1], q[a + 2], q[a + 3], k[a + 1], k[a + 3]);
    }
#pragma unroll
    for (int n = 0; n < 4; n++) {
        const int hd = n & 1, a = 8 * hd + 2 * (n & 2);
        mma16816(s0[hd], q[a], q[a + 1], q[a + 2], q[a + 3], kh[HS * (a / 2)], kh[HS * (a / 2 + 1)]);
    }
    float e[2][4], m[2][2];
#pragma unroll
    for (int hd = 0; hd < 2; hd++) {
        e[hd][2] = fmaf(s1[hd][2], fu[2], s2[hd][2] * fn[2]); e[hd][3] = fmaf(s1[hd][3], fu[3], s2[hd][3] * fn[3]);
        e[hd][0] = fmaf(s0[hd][0], fu[0], fmaf(s1[hd][0], fn[0], bias0)); e[hd][1] = fmaf(s0[hd][1], fu[1], fmaf(s1[hd][1], fn[1], bias1));
        m[hd][1] = fmaxf(e[hd][2], e[hd][3]); m[hd][0] = fmaxf(e[hd][0], e[hd][1]);
    }
#pragma unroll
    for (int x = 1; x < 3; x++)
#pragma unroll
        for (int n = 0; n < 4; n++) m[n & 1][1 - (n >> 1)] = fmaxf(m[n & 1][1 - (n >> 1)], __shfl_xor_sync(0xffffffffu, m[n & 1][1 - (n >> 1)], x));
#pragma unroll
    for (int hd = 0; hd < 2; hd++) {
#pragma unroll
        for (int n = 0; n < 4; n++) e[hd][n] = ex2(e[hd][n] - m[hd][n >> 1]);
        float sum[4] = {};
        mma1688(sum, pack_bf16(e[hd][0], e[hd][1]), pack_bf16(e[hd][2], e[hd][3]), 0x3f803f80u);
        const float i0 = rcp(sum[0]), i1 = rcp(sum[2]);
        const uint32_t plo = pack_bf16(e[hd][0] * rk[0] * i0, e[hd][1] * rk[1] * i0), phi = pack_bf16(e[hd][2] * rk[2] * i1, e[hd][3] * rk[3] * i1);
        const uint32_t z0 = plo & zero, z1 = phi & zero;
        const uint32_t a0 = plo & ~mU, a1 = phi & mU, a3 = phi & ~mU, b0 = plo & mU;
#pragma unroll
        for (int jj = 0; jj < 4; jj++) {
            float c[4];
            asm volatile("mma.sync.aligned.m16n8k16.row.col.f32.bf16.bf16.f32 {%0,%1,%2,%3}, {%4,%5,%6,%7}, {%8,%9}, {%10,%11,%12,%13};"
                         : "=f"(c[0]), "=f"(c[1]), "=f"(c[2]), "=f"(c[3])
                         : "r"(a0), "r"(a1), "r"(z0), "r"(a3), "r"(v[8 * hd + 2 * jj]), "r"(v[8 * hd + 2 * jj + 1]), "f"(ci[0]), "f"(ci[1]), "f"(ci[2]), "f"(ci[3]));
            mma1688(c, b0, z1, vh[HS * (4 * hd + jj)]);
            o[8 * hd + 2 * jj] = pack_bf16(c[0], c[1]); o[8 * hd + 2 * jj + 1] = pack_bf16(c[2], c[3]);
        }
    }
}

__device__ __forceinline__ uint32_t norm_pair(uint32_t u, float m, float rinv) {
    const uint32_t d = pack_bf16(bf_lo(u) - m, bf_hi(u) - m);
    return max(pack_bf16(bf_lo(d) * rinv, bf_hi(d) * rinv), 1u);
}

__global__ void __cluster_dims__(2, 1, 1) __launch_bounds__(512, 1)
fused_kernel(const __grid_constant__ CUtensorMap mx, const __grid_constant__ CUtensorMap mw, const __grid_constant__ CUtensorMap mwo,
             const __grid_constant__ CUtensorMap mout, const __grid_constant__ CUtensorMap mgu, const __grid_constant__ CUtensorMap mwd,
             const __grid_constant__ CUtensorMap mo, const __grid_constant__ CUtensorMap mr,
             const __nv_bfloat16* __restrict__ x, const __nv_bfloat16* __restrict__ wr, Scratch* __restrict__ scr, int swap_gu, const Weights pf) {
    extern __shared__ __align__(1024) uint8_t smem[];
    const uint32_t sb = smem_u32(smem);
    const uint32_t bars = sb + OFF_BAR;
    const int hp = blockIdx.x & 1, cl = blockIdx.x >> 1;
    int pr = cl - 4;
    asm("{\n.reg .pred p;\nsetp.ge.s32 p, %1, 36;\nselp.s32 %0, %3, %0, p;\nsetp.lt.s32 p, %1, 4;\nselp.s32 %0, %2, %0, p;\n}" : "+r"(pr) : "r"(cl), "r"(39 + 8 * cl), "r"((cl * 293 - 2356) >> 8));
    if (threadIdx.x < 32 && elect_one()) {
        const uint32_t fx = bars + 8 * (B_XFULL + 1), fw = bars + 8 * (B_WFULL + 2);
        mbar_init(fx, 1); mbar_init(fw, 1);
        asm volatile("fence.mbarrier_init.release.cluster;" ::: "memory");
        if (cl < 64) {
            tma_4d(sb + 4 * BOX, &mx, fx, (pr >> 5) * 1024, 0, pr & 24, 1);
            tma_3d(sb + OFF_W + 2 * W_BYTES, &mw, fw, ((pr & 7) * 2 + hp) * 64, 0, 0);
            mbar_expect_tx(fx, BOX); mbar_expect_tx(fw, W_BYTES);
        }
    }
    const int tid = threadIdx.x, lane = tid & 31, warp = __shfl_sync(0xffffffffu, tid >> 5, 0);
    const uint32_t sd = (sb & 0x3FFFF) >> 4;
    const int b = pr * 2 + hp, mt = pr >> 3, p = pr & 7, nt = 2 * p + hp, rh = p & 1, cb = (p & 6) + hp;
    const int par = mt >> 2, j0 = (mt & 3) * 256;
    int budget = BUDGET;

    auto load_w = [&](int k, int s) {
        const uint32_t full = bars + 8 * (B_WFULL + s);
        mbar_expect_tx(full, W_BYTES);
        tma_3d(sb + OFF_W + s * W_BYTES, &mw, full, nt * 64, k * 64, 0);
    };
    auto load_x = [&](int n) {
        const int w = n & 1, j = n < 4 ? (n >> 1) + 4 : (n >> 1) - 2;
        const uint32_t full = bars + 8 * (B_XFULL + w * 6 + 5 - j);
        mbar_expect_tx(full, BOX);
        tma_4d(sb + w * OFF_X1 + j * BOX, &mx, full, par * 1024 + (n >> 2) * 64, 0, (j0 + w * 128) >> 5, (~n >> 1) & 1);
    };
    if (warp > 0 && warp < (b < 128 ? 9 : 16) && elect_one()) {
        mbar_init(bars + (warp == 1 ? 0 : 16 * warp + 8), 1); mbar_init(bars + (warp == 1 ? 8 : 16 * warp + 16), 1);
        if (warp == 1) mbar_init(bars + 24, 1);
        asm volatile("fence.mbarrier_init.release.cluster;" ::: "memory");
    }
    __syncthreads();

    if (b >= 128) {
        const int hc = b - 128, g = lane >> 2, t = lane & 3;
        const uint32_t ep = ld_rlx(&scr->epoch[0]) + 1;
        if (warp < 12) {
            const int n = warp / 3, part = warp - 3 * n;
            auto load = [&](int k) {
                const uint32_t full = bars + 8 * (2 * n + (k & 1));
                mbar_expect_tx(full, W_BYTES);
                tma_3d(sb + (2 * n + (k & 1)) * W_BYTES, &mw, full, (4 * hc + n) * 64, k * 64, 0);
            };
            if (part == 0 && elect_one()) { load(0); load(1); }
            __syncwarp();
            float c0[4] = {0.f, 0.f, 0.f, 0.f}, c1[4] = {0.f, 0.f, 0.f, 0.f};
            const uint32_t sel = g == 0 ? 0x3f80u : g == 1 ? 0x3f800000u : 0u;
            const uint32_t a = sb + 2 * n * W_BYTES + part * BOX + t * 256 + ((g ^ (2 * t)) << 4);
#pragma unroll 1
            for (int k = 0; k < 16; k++) {
                mbar_wait(bars + 8 * (2 * n + (k & 1)), (k >> 1) & 1, budget);
                uint4 v[8], u[8];
#pragma unroll
                for (int i = 0; i < 8; i++) { v[i] = lds4(a + (k & 1) * W_BYTES + i * 1024); u[i] = lds4(((a + 128) ^ 16) + (k & 1) * W_BYTES + i * 1024); }
                bar_sync(1 + n, 96);
                if (part == k % 3 && k < 14 && elect_one()) load(k + 2);
                __syncwarp();
#pragma unroll
                for (int i = 0; i < 8; i++) { mma16816(c0, v[i].x, v[i].y, u[i].x, u[i].y, sel, sel); mma16816(c1, v[i].z, v[i].w, u[i].z, u[i].w, sel, sel); }
            }
            if (t == 0) {
#pragma unroll
                for (int r = 0; r < 3; r++) {
                    const uint32_t q0 = (pack_bf16(c0[0], c0[1]) & ~1u) | (ep & 1), q1 = pack_bf16(c0[2], c0[3]), q2 = pack_bf16(c1[0], c1[1]), q3 = pack_bf16(c1[2], c1[3]);
                    st_rlx4(&scr->cs[4 * hc + n][r][part * 8 + g], q0, q1, q2, q3);
                    c0[0] -= bf_lo(q0); c0[1] -= bf_hi(q0); c0[2] -= bf_lo(q1); c0[3] -= bf_hi(q1);
                    c1[0] -= bf_lo(q2); c1[1] -= bf_hi(q2); c1[2] -= bf_lo(q3); c1[3] -= bf_hi(q3);
                }
            }
        }
        {
            const int wg = warp >> 2, c2 = 4 * hc + wg, tw = tid & 127;
            const uint32_t ring = sb + wg * 6 * BOX, full = bars + 8 * (8 + wg * 6), ha = sb + 24 * BOX;
            const uint32_t* hsrc = scr->act[ep & 1] + (56 - NH) * 256;
            auto load = [&](int q, int s) { mbar_expect_tx(full + 8 * s, BOX); tma_3d(ring + s * BOX, &mwd, full + 8 * s, 0, (56 - NH + q) * 64, c2); };
            const uint32_t key = poll_all(&scr->sel[lane & 7], 31u, ep & 31, budget);
            __syncthreads();
            if ((warp & 3) == 0 && elect_one()) {
#pragma unroll 1
                for (int q = 0; q < 6; q++) load(q, q);
            }
            __syncwarp();
            const int zr = (2047 - ((__shfl_sync(0xffffffffu, key, warp >> 1) >> 5) & 2047)) & ~30;
#pragma unroll
            for (int i = 0; i < 8; i++) st_rlx4(pf.out + (size_t)(zr + (warp & 1) * 16 + 2 * i) * 2048 + hc * 512 + lane * 16, 0, 0, 0, 0);
            __syncthreads();
            uint32_t wa[NR * 16];
#pragma unroll
            for (int q = 0; q < NR; q++) {
                mbar_wait(full + 8 * q, 0, budget);
#pragma unroll
                for (int j = 0; j < 4; j++) ldsm4t(wa + 16 * q + 4 * j, ring + q * BOX + j * 2048 + (lane >> 4) * 1024 + (lane & 7) * 128 + ((((warp & 3) * 2 + ((lane >> 3) & 1)) ^ (lane & 7)) << 4));
                bar_sync(1 + wg, 128);
                if ((warp & 3) == 0 && elect_one()) load(q + 6, q);
                __syncwarp();
            }
            if (tid == 64) { fence_gpu(); st_rlx(&scr->zflag[hc], ep); }
            if (warp == 1 && elect_one()) {
                int tries = BUDGET;
#pragma unroll 1
                while (ld_rlx(&scr->cnt[8][0]) != ep * (4 * NH) && --tries > 0) {}
                mbar_expect_tx(bars + 8 * 32, NH * 1024);
                bulk_g2s(ha, hsrc, NH * 1024, bars + 8 * 32);
            }
            __syncwarp();
            mbar_wait(bars + 8 * 32, 0, budget);
#pragma unroll 1
            for (int i = tid; i < NH * 64; i += 512) {
                int tries = BUDGET;
                if (lds1(ha + i * 16) == 0) {
                    uint4 v;
#pragma unroll 1
                    do { v = ld_rlx4(hsrc + i * 4); } while (v.x == 0 && --tries > 0);
                    sts4(ha + i * 16, v.x, v.y, v.z, v.w);
                }
            }
            fence_async_smem();
            __syncthreads();
            float acc[4] = {0.f, 0.f, 0.f, 0.f};
            int left = BUDGET;
            mbar_wait(full + 8 * NR, 0, left);
            const uint32_t da = sd + dlo(wg * 6 * BOX, BOX), db = sd + dlo(24 * BOX, 128), ahi = dhi(1024, 1) | (left >> 30), bhi = dhi(128, 0) | (left >> 30);
            uint4 v[8];
#pragma unroll
            for (int q = NR; q < NH; q++) {
                if (q > NR) mbar_wait(full + 8 * (q % 6), (q / 6) & 1, left);
                wg_fence();
#pragma unroll
                for (int j = 0; j < 4; j++) wgmma_n8<1, 0>(acc, mkdesc(da + q % 6 * 512 + j * 128, ahi), mkdesc(db + q * 64 + j * 16, bhi), 1);
                wg_commit();
                if (q > NR && q + 5 < NH) {
                    wg_wait<1>();
                    if ((warp & 3) == (q & 3) && elect_one()) load(q + 5, (q - 1) % 6);
                    __syncwarp();
                }
                if (q == NR + 5) {
                    wg_fence();
#pragma unroll
                    for (int j = 0; j < 4 * NR; j++) wgmma_rs_n8(acc, wa[4 * j], wa[4 * j + 1], wa[4 * j + 2], wa[4 * j + 3], mkdesc(db + j * 16, bhi));
                    wg_commit();
                }
                if (q == NH - 2) {
#pragma unroll
                    for (int m = 0; m < 8; m++) v[m] = ld_rlx4(&scr->ypart[m][c2][tw]);
                }
            }
            wg_wait<0>();
#pragma unroll 1
            for (int tries = BUDGET; tries > 0; tries--) {
                uint32_t bad = 0;
#pragma unroll
                for (int m = 0; m < 8; m++) bad |= v[m].x ^ ep;
                if (!(bad & 1)) break;
#pragma unroll
                for (int m = 0; m < 8; m++) if ((v[m].x ^ ep) & 1) v[m] = ld_rlx4(&scr->ypart[m][c2][tw]);
            }
            __syncwarp();
            const float sig = bf16r(sigmoidf(__uint_as_float(((int)key < 0 ? key & 0x7fffffffu : ~key) & 0xffff0000u)));
#pragma unroll
            for (int c = 0; c < 4; c++) {
#pragma unroll
                for (int m = 0; m < 8; m++) acc[c] += __uint_as_float((&v[m].x)[c]);
                acc[c] = bf16r(acc[c]) * __shfl_sync(0xffffffffu, sig, 2 * t + (c & 1));
            }
            char* dst = pf.out + (size_t)(2047 - ((__shfl_sync(0xffffffffu, key, g) >> 5) & 2047)) * 2048 + c2 * 128 + (warp & 3) * 32 + t * 4;
            asm volatile("red.relaxed.gpu.global.add.noftz.bf16x2 [%0], %1;" ::"l"(dst), "r"(movm(pack_bf16(acc[0], acc[1]))) : "memory");
            asm volatile("red.relaxed.gpu.global.add.noftz.bf16x2 [%0], %1;" ::"l"(dst + 16), "r"(movm(pack_bf16(acc[2], acc[3]))) : "memory");
        }
        return;
    }
    auto late_init = [&](int first, uint32_t cnt, int n) {
        if (elect_one()) {
#pragma unroll
            for (int i = 0; i < 13; i++) if (i < n) mbar_init(bars + 8 * (first + i), cnt);
            asm volatile("fence.mbarrier_init.release.cluster;" ::: "memory");
        }
        __syncwarp();
    };

    const int c2 = b & 15, n2 = mt < 7 ? NM : N7;
    if (warp >= 12) {
        reg_dec<24>();
        if (warp >= 14) late_init(B_G1DONE + 6 * (warp - 14), 4 * (warp - 13), 6);
        cluster_arrive();
        if (warp == 12) {
            if (elect_one()) {
                int c = 0;
#pragma unroll 1
                for (int n = 1; n < 12; n++) {
                    load_x(n);
#pragma unroll 1
                    for (; c < (n == 11 ? 4 : __popc(ROWS_AT & ((2 << n) - 1))); c++) { mbar_expect_tx(bars + 8 * (B_ROW + c), BOX); tma_2d(sb + OFF_FR + c * BOX, &mr, bars + 8 * (B_ROW + c), c * 256, b * 16); }
                    if (n == 3 || n == 7) load_w((n + 1) >> 2, n >> 2);
                }
            }
            __syncwarp();
            cluster_wait();
            if (elect_one()) {
                int s = 2; uint32_t ph = 0;
#pragma unroll 1
                for (int k = 3; k < 16; k++) {
                    mbar_wait(bars + 8 * (B_WEMPTY + s), ph, budget);
                    load_w(k, s);
                    if (++s == 3) s = 0;
                    if (s == 2) ph ^= 1;
                }
                s = 2;
#pragma unroll 1
                for (int i = 0; i < 16; i++) {
                    mbar_wait(bars + 8 * (i < 2 ? B_WEMPTY + i : i < 4 ? B_G1DONE : i < 6 ? B_F1DONE : B_WOEMPTY + s), i >= 12, budget);
                    if (i == 0) {
                        mbar_expect_tx(bars + 8 * B_XT, 4 * BOX);
#pragma unroll 1
                        for (int n = 0; n < 4; n++)
                            tma_4d(sb + (n >> 1) * OFF_X1 + (n & 1) * BOX, &mx, bars + 8 * B_XT, par * 1024 + cb * 128 + (n & 1) * 64, 0, (j0 + rh * 128) >> 5, 1 - (n >> 1));
                    }
                    const uint32_t full = bars + 8 * (B_WOFULL + s);
                    mbar_expect_tx(full, 2 * BOX);
                    tma_3d(sb + OFF_WO + s * 2 * BOX, &mwo, full, 0, ((2 * p + (i < 2 ? i ^ hp : i)) & 15) * 64, cb * 2);
                    if (++s == 6) s = 0;
                }
            }
        } else {
            bar_sync(8, 224);
            const uint32_t ep = __shfl_sync(0xffffffffu, lds1(sb + OFF_EP), 0);
            if (warp == 13) {
                cluster_wait();
                if (elect_one()) {
                    int j = 4, q = 0, left = BUDGET; uint32_t ph = 0;
#pragma unroll 1
                    for (int n = 6; n < 32; n++) {
                        mbar_wait(bars + 8 * (B_XEMPTY + j), ph, left);
                        tma_4d_mc(sb + hp * OFF_X1 + j * BOX, &mx, bars + 8 * (B_XFULL + hp * 6 + 5 - j), par * 1024 + (n >> 1) * 64, 0, (j0 + hp * 128) >> 5, ~n & 1);
                        if (++j == 6) j = 0;
                        if (j == 4) ph ^= 1;
#pragma unroll 1
                        for (; q < (PF_RATE * (n - PF_START) >> 3) && q < 24; q++) {
                            const int u = q - 6;
                            if (u < 0) bulk_pf(pf.wqkv + (size_t)(1024 + 128 * u + b) * 6144, 6144);
                            else if (u < 16) bulk_pf((b < 64 ? pf.wg : pf.wu) + (size_t)(u * 64 + (b & 63)) * 7168, 7168);
                            else bulk_pf(pf.wo + (size_t)((u - 16) * 128 + b) * 8192, 8192);
                        }
                    }
                }
                __syncwarp();
                uint32_t* hs = &scr->halo[b - 16][lane * 4];
                uint4 v[4] = {};
                if (j0) {
#pragma unroll 1
                    do {
#pragma unroll
                        for (int c = 0; c < 4; c++) v[c] = ld_rlx4(hs + c * 128);
                    } while (__any_sync(0xffffffffu, min(min(v[0].x, v[1].x), min(v[2].x, v[3].x)) == 0) && --budget > 0);
#pragma unroll
                    for (int c = 0; c < 4; c++) st_rlx(hs + c * 128, 0);
                }
#pragma unroll
                for (int c = 0; c < 4; c++) stsm4(sb + OFF_HIN + c * 512 + lane * 16, v[c].x, v[c].y, v[c].z, v[c].w);
                bar_arrive(11, 64);
                const int src = ((mt * 2 + rh) * 2 + 1 - hp) * 1024;
                if (elect_one()) {
                    const uint32_t* fl = &scr->oflag[mt * 2 + 1 - hp][0];
                    const uint32_t inv = (ep & 1) - 1;
                    uint32_t ready = 0, ph = 0;
                    int s = 4;
#pragma unroll 1
                    for (int i = 2; i < 16; i++) {
                        const int kb = (2 * p + i) & 15;
#pragma unroll 1
                        while (!((ready >> kb) & 1) && --budget > 0) ready = ld_rlx(fl) ^ inv;
                        mbar_wait(bars + 8 * (B_OEMPTY + s), ph, budget);
                        tma_2d_mc(sb + hp * OFF_X1 + s * BOX, &mo, bars + 8 * (B_OFULL + hp * 6 + s), 0, src + kb * 64);
                        if (++s == 6) s = 0;
                        if (s == 4) ph ^= 1;
                    }
                }
            } else if (warp == 14) {
                if (elect_one()) {
                    uint32_t s8 = 0, ph = 0;
                    int tries = BUDGET;
                    const uint32_t* act = scr->act[ep & 1];
                    auto counted = [&](int c, uint32_t n) {
#pragma unroll 1
                        while (ld_rlx(&scr->cnt[c][0]) != ep * n && --tries > 0) __nanosleep(30);
                    };
                    auto weights = [&](const CUtensorMap* m, int c0, int c1, int c2_) {
                        mbar_wait(bars + 8 * B_FEMPTY + s8, ph, budget);
                        mbar_expect_tx(bars + 8 * B_FFULL + s8, F_BYTES);
                        tma_3d(sb + OFF_FS + s8 * (F_BYTES / 8), m, bars + 8 * B_FFULL + s8, c0, c1, c2_);
                    };
                    if (b < 112) {
                        counted(9, 32);
#pragma unroll 1
                        for (int q = 0; q < 16; q++) {
                            weights(&mgu, b * 32, q * 64, 0);
                            bulk_g2s(sb + OFF_FS + BOX + s8 * (F_BYTES / 8), act + 14336 + q * 256, 1024, bars + 8 * B_FFULL + s8);
                            if (q >= 8) bulk_pf(pf.wd + (size_t)(q * 112 + b) * 4096, 4096);
                            s8 += 8;
                            if (s8 == 40) { s8 = 0; ph ^= 1; }
                        }
                    }
#pragma unroll 1
                    for (int q = -3; q < n2; q++) {
                        if (q == 0) { counted(mt, 4 * n2); }
                        if ((unsigned)q >= 3) weights(&mwd, 0, (mt * NM + (q < 0 ? q + 3 : q)) * 64, c2);
                        if (q >= 0) bulk_g2s(sb + OFF_FS + BOX + s8 * (F_BYTES / 8), act + (mt * NM + q) * 256, 1024, bars + 8 * B_FFULL + s8);
                        s8 += 8;
                        if (s8 == 24) { s8 = 0; if ((unsigned)q >= 3) ph ^= 1; }
                    }
                }
            } else {
#pragma unroll 1
                for (int i = lane * 16; i < CS_BYTES; i += 512) sts4(sb + OFF_CS + i, 0, 0, 0, 0);
                mbar_wait(bars + 8 * (B_ROW + 3), 0, budget);
                uint8_t* oz = scr->o + ((size_t)mt * 64 + nt) * BOX + lane * 16;
#pragma unroll 1
                for (int i = 0; i < 16; i++, oz += 512) {
#pragma unroll
                    for (int n = 0; n < 4; n++) st_rlx4(oz + n * 16 * BOX, 0, 0, 0, 0);
                    __nanosleep(100);
                }
                __syncwarp();
                fence_gpu();
                mbar_wait(bars + 8 * B_RDONE, 0, budget);
                int tries = BUDGET;
#pragma unroll 1
                for (int i = lane; i < 88; i += 32) {
                    const uint2* rp = &scr->row[2 * (j0 - 8 + i) + par];
                    uint2 v0, v1, v2;
#pragma unroll 1
                    do { v0 = ld_rlx2(rp + (j0 + i < 8 ? 16 : 0)); v1 = ld_rlx2(rp + 176); v2 = ld_rlx2(rp + 352); } while ((((v0.y ^ ep) | (v1.y ^ ep) | (v2.y ^ ep)) & 31) && --tries > 0);
                    sts2(sb + OFF_STAT + i * 8, (v0.x << 16) ^ 0x80000000u, __float_as_uint(rcp(bf_hi(v0.x))));
                    sts2(sb + OFF_STAT + i * 8 + 704, (v1.x << 16) ^ 0x80000000u, __float_as_uint(rcp(bf_hi(v1.x))));
                    sts2(sb + OFF_STAT + i * 8 + 1408, (v2.x << 16) ^ 0x80000000u, __float_as_uint(rcp(bf_hi(v2.x))));
                }
                __syncwarp();
                {
                    const int row = 2047 - ((poll_all(&scr->sel[lane & 7], 31u, ep & 31, budget) >> 5) & 2047), jj = (row >> 1) - j0 - rh * 128;
                    sts1(sb + OFF_SEL, __reduce_or_sync(0xffffffffu, (row & 1) == par && (unsigned)jj < 128 ? 1u << (jj >> 4) : 0u));
                }
                if (lane < 24) {
                    uint4 v[3];
#pragma unroll 1
                    while (v[0] = ld_rlx4(&scr->cs[nt][0][lane]), v[1] = ld_rlx4(&scr->cs[nt][1][lane]), v[2] = ld_rlx4(&scr->cs[nt][2][lane]),
                           (((v[0].x ^ ep) | (v[1].x ^ ep) | (v[2].x ^ ep)) & 1) && --tries > 0) __nanosleep(100);
#pragma unroll
                    for (int r = 0; r < 3; r++) sts4(sb + OFF_CS + 64 + lane * 128 + r * 16, v[r].x, v[r].y, v[r].z, v[r].w);
                }
                fence_async_smem();
                __syncwarp();
                if (elect_one()) {
                    mbar_arrive(bars + 8 * B_AUX);
                    mbar_expect_tx(bars + 8 * (B_OFULL + 3), BOX); mbar_expect_tx(bars + 8 * (B_OFULL + 9), BOX);
#pragma unroll 1
                    for (int v = 0; v < 2; v++) {
                        const uint32_t ring = sb + v * OFF_X1 + 2 * BOX, fb = bars + 8 * (B_OFULL + v * 6 + 2);
                        mbar_wait(bars + 8 * (B_STAGED + v), 0, budget);
                        asm volatile("red.relaxed.gpu.global.xor.b32 [%0], %1;" ::"l"(&scr->oflag[mt * 2 + 1 - v][0]), "r"(1u << nt) : "memory");
                        mbar_arrive(fb);
                        mbar_wait(bars + 8 * B_G1DONE, 0, budget);
                        bulk_s2c(mapa(ring + BOX, hp ^ 1), ring, BOX, mapa(fb + 8, hp ^ 1));
                        if (v == 0) mbar_wait(bars + 8 * B_FREED, 0, budget);
#pragma unroll
                        for (int n = 0; n < 4; n++) {
                            mbar_expect_tx(bars + 8 * (B_OFULL + (n >> 1) * 6 + 4 + (n & 1)) - v * 32, BOX);
                            mbar_arrive_at(mapa(bars + 8 * B_OEMPTY, n >> 1) + (4 + (n & 1)) * 8 - v * 32);
                        }
                    }
                    if (lds1(sb + OFF_SEL)) {
#pragma unroll 1
                        while (ld_acq(&scr->zflag[p >> 1]) != ep && --tries > 0) {}
                        asm volatile("fence.proxy.async.global;" ::: "memory");
                    }
                    mbar_arrive(bars + 8 * B_ZERO);
                }
            }
        }
    } else if (warp >= 8) {
        reg_dec<40>();
        const int wq = warp - 8, ta = tid - 256;
        const uint32_t rbuf = sb + OFF_FR + wq * 2048;
        const uint4 wv = ldg_nc(wr + ta * 8);
        const uint32_t ep0 = ld_rlx(&scr->epoch[0]);
        late_init(B_LATE + 13 * wq, 1 + (wq >> 1), 13);
        cluster_arrive();
        if (ta == 0) sts1(sb + OFF_EP, ep0 + 1);
        sts4(sb + OFF_STAT + ta * 16, wv.x, wv.y, wv.z, wv.w);
        bar_sync(8, 224);
        const uint32_t ep = __shfl_sync(0xffffffffu, lds1(sb + OFF_EP), 0);
        {
            const int s = b * 16 + wq * 4 + (lane >> 3);
            if ((lane & 7) == 0) st_rlx2(&scr->row[s], 0, ep - 1);
            float sw = 0.f;
#pragma unroll 1
            for (int i = 0; i < 16; i++) { const uint32_t q = lds1(sb + OFF_STAT + i * 128 + lane * 4); sw += bf_lo(q) + bf_hi(q); }
#pragma unroll 1
            for (int o = 16; o > 0; o >>= 1) sw += __shfl_xor_sync(0xffffffffu, sw, o);
            float s1 = 0.f, s2 = 0.f, sr = 0.f;
            {
                float s1b = 0.f, s2b = 0.f, srb = 0.f;
                const uint32_t xb = rbuf + (lane >> 4) * 1024 + (lane & 15) * 16, wb = sb + OFF_STAT + (lane & 15) * 16;
#pragma unroll 1
                for (int i = 0; i < 8; i++) {
                    const uint4 w4 = lds4(wb + i * 256);
                    mbar_wait_hot(bars + 8 * (B_ROW + (i >> 1)), 0, budget);
                    const uint32_t o = (i >> 1) * BOX + (i & 1) * 256;
                    const uint4 u = lds4(xb + o), v = lds4(xb + o + 512);
#pragma unroll
                    for (int c = 0; c < 4; c++) {
                        const float w0 = bf_lo((&w4.x)[c]), w1 = bf_hi((&w4.x)[c]);
                        const float a0 = bf_lo((&u.x)[c]), a1 = bf_hi((&u.x)[c]), b0 = bf_lo((&v.x)[c]), b1 = bf_hi((&v.x)[c]);
                        s1 += a0; s2 = fmaf(a0, a0, s2); sr = fmaf(a0, w0, sr);
                        s1 += a1; s2 = fmaf(a1, a1, s2); sr = fmaf(a1, w1, sr);
                        s1b += b0; s2b = fmaf(b0, b0, s2b); srb = fmaf(b0, w0, srb);
                        s1b += b1; s2b = fmaf(b1, b1, s2b); srb = fmaf(b1, w1, srb);
                    }
                }
                const bool up = lane & 8;
                s1 = (up ? s1b : s1) + __shfl_xor_sync(0xffffffffu, up ? s1 : s1b, 8);
                s2 = (up ? s2b : s2) + __shfl_xor_sync(0xffffffffu, up ? s2 : s2b, 8);
                sr = (up ? srb : sr) + __shfl_xor_sync(0xffffffffu, up ? sr : srb, 8);
            }
#pragma unroll
            for (int o = 1; o < 8; o <<= 1) {
                s1 += __shfl_xor_sync(0xffffffffu, s1, o); s2 += __shfl_xor_sync(0xffffffffu, s2, o); sr += __shfl_xor_sync(0xffffffffu, sr, o);
            }
            const float mean = s1 * (1.f / 1024.f), mb = bf16r(mean);
            float var = fmaf(-mean, mean, s2 * (1.f / 1024.f));
            sr = fmaf(-mb, sw, sr);
            if (__builtin_expect(__any_sync(0xffffffffu, mean * mean > 256.f * var), 0)) {
                float a2 = 0.f, ar = 0.f;
#pragma unroll 1
                for (int i = 0; i < 64; i++) {
                    const uint32_t o = i * 32 + (lane & 7) * 4, q1 = lds1(rbuf + (lane >> 3) * 512 + (o >> 9) * BOX + (o & 511)), q2 = lds1(sb + OFF_STAT + o);
                    a2 = fmaf(bf_lo(q1) - mean, bf_lo(q1) - mean, fmaf(bf_hi(q1) - mean, bf_hi(q1) - mean, a2));
                    ar = fmaf(bf_lo(q1) - mb, bf_lo(q2), fmaf(bf_hi(q1) - mb, bf_hi(q2), ar));
                }
#pragma unroll 1
                for (int o = 1; o < 8; o <<= 1) { a2 += __shfl_xor_sync(0xffffffffu, a2, o); ar += __shfl_xor_sync(0xffffffffu, ar, o); }
                var = a2 * (1.f / 1024.f); sr = ar;
            }
            float den;
            asm("sqrt.approx.f32 %0, %1;" : "=f"(den) : "f"(bf16r(bf16r(var) + 1e-5f)));
            const uint32_t st = pack_bf16(mb, den);
            const uint32_t rb = pack_bf16(0.f, sr * rcp(bf_hi(st)) + 0.f);
            uint32_t ord = (int)rb < 0 ? ~rb & 0xffff0000u : rb | 0x80000000u;
            if ((rb & 0x7fffffffu) > 0x7f800000u) ord = 0;
            if ((lane & 7) == 0) st_rlx2(&scr->row[s], st, ord | ((2047 - s) << 5) | (ep & 31));
            __syncwarp();
            if (lane < 7) mbar_arrive(bars + 8 * (lane < 5 ? B_FEMPTY + lane : B_RDONE));
        }
        if ((b >> 3) == 14) {
            const uint32_t gm = sb + OFF_E, cnt = gm + 64, res = gm + 80, list = gm + 128;
            uint32_t kv[16];
            int tries = BUDGET;
#pragma unroll 1
            do {
                uint32_t bad = 0;
#pragma unroll
                for (int n = 0; n < 16; n++) kv[n] = ld_rlx(&scr->row[n * 128 + ta].y);
#pragma unroll
                for (int n = 0; n < 16; n++) bad |= kv[n] ^ ep;
                if ((bad & 31) == 0) break;
            } while (--tries > 0);
            __syncwarp();
            uint32_t m = 0;
#pragma unroll
            for (int n = 0; n < 16; n++) m = max(m, kv[n]);
            uint32_t gmax = m;
#pragma unroll
            for (int o = 1; o < 8; o <<= 1) gmax = max(gmax, __shfl_xor_sync(0xffffffffu, gmax, o));
            sts1(gm + (ta >> 3) * 4, gmax);
            sts1(cnt, 0);
            bar_sync(12, 128);
            const uint32_t c = lds1(gm + (lane & 15) * 4);
            int rank = 0;
#pragma unroll
            for (int i = 0; i < 2; i++) { const uint4 q = lds4(gm + (lane >> 4) * 32 + i * 16); rank += (q.x > c) + (q.y > c) + (q.z > c) + (q.w > c); }
            rank += __shfl_xor_sync(0xffffffffu, rank, 16);
            const uint32_t thr = redux_max(rank == 7 ? c : 0u);
#pragma unroll 1
            while (m >= thr) {
                uint32_t at, m2 = 0;
                asm volatile("atom.shared.add.u32 %0, [%1], 1;" : "=r"(at) : "r"(cnt) : "memory");
#pragma unroll
                for (int n = 0; n < 16; n++) m2 = max(m2, kv[n] < m ? kv[n] : 0u);
                sts1(list + at * 4, m);
                if (m2 == 0) break;
                m = m2;
            }
            bar_sync(12, 128);
            const int nc = lds1(cnt);
#pragma unroll 1
            for (int i = ta >> 3; i < ((nc + 3) & ~3); i += 16) {
                const uint32_t ki = lds1(list + i * 4);
                int r = 0;
#pragma unroll 1
                for (int n = lane & 7; n < nc; n += 8) r += lds1(list + n * 4) > ki;
                __syncwarp();
#pragma unroll
                for (int o = 1; o < 8; o <<= 1) r += __shfl_xor_sync(0xffffffffu, r, o);
                if (r == (b & 7) && i < nc) sts1(res, ki);
            }
            bar_sync(12, 128);
            const uint32_t k0 = lds1(res);
            const int r0 = 2047 - ((k0 >> 5) & 2047);
            if (ta == 0) st_rlx(&scr->sel[b & 7], k0);
            const uint4 v0 = ldg_nc(x + (size_t)r0 * 1024 + ta * 8);
            const uint32_t s0 = ld_rlx(&scr->row[r0]);
            const float m0 = bf_lo(s0), i0 = rcp(bf_hi(s0));
            const int ao = 14336 + (ta >> 3) * 256 + (b & 7) * 32 + ((ta ^ b) & 7) * 4;
            st_rlx4(scr->act[ep & 1] + ao, norm_pair(v0.x, m0, i0), norm_pair(v0.y, m0, i0), norm_pair(v0.z, m0, i0), norm_pair(v0.w, m0, i0));
            __syncwarp();
            if (lane == 0) red_add(&scr->cnt[9][tries >> 30]);
            st_rlx4(scr->act[~ep & 1] + ao, 0, 0, 0, 0);
        }
        uint32_t s8 = 0, fph = 0;
        const uint32_t chk = __shfl_sync(0xffffffffu, sb + OFF_FS + BOX + lane * 32 + (lane & 28), lane);
        int left = BUDGET;
        if (b >= 112 && ta < 2) mbar_arrive(bars + 8 * B_F1DONE);
#pragma unroll 1
        for (int ph = b >= 112; ph < 2; ph++) {
            {
                float acc[4] = {0.f, 0.f, 0.f, 0.f};
                const uint32_t alo = sd + (ph ? dlo(OFF_FS, 8192) : dlo(OFF_FS, 4096)), ahi = ph ? dhi(1024, 1) : dhi(512, 2), astep = ph ? 128 : 64;
                const uint32_t bhi = ph ? dhi(128, 0) : dhi(1024, 1), bstep = ph ? 16 : 2, wrap = ph ? 24 : 40;
                uint32_t prev = 0;
                if (ph) mbar_wait(bars + 8 * (B_STAGED + 1), 0, left);
#pragma unroll 1
                for (int q = ph ? n2 : 16; q > 0; q--) {
                    const uint32_t da = alo + s8 * (F_BYTES >> 7), db = sd + dlo(OFF_FS + BOX, 128) + s8 * (F_BYTES >> 7);
                    mbar_wait_hot(bars + 8 * B_FFULL + s8, fph, left);
                    if (__builtin_expect(__any_sync(0xffffffffu, lds1(chk + s8 * (F_BYTES / 8)) == 0), 0)) {
                        int tries = BUDGET;
#pragma unroll 1
                        for (int n = lane * 4 + (left >> 30); n < 256; n += 128) {
                            uint4 v;
#pragma unroll 1
                            do { v = ld_rlx4(scr->act[ep & 1] + ((ph ? mt * NM + n2 : 72) - q) * 256 + n); } while (v.x == 0 && --tries > 0);
                            __syncwarp();
                            sts4(sb + OFF_FS + BOX + s8 * (F_BYTES / 8) + n * 4, v.x, v.y, v.z, v.w);
                        }
                        fence_async_smem();
                        __syncwarp();
                    }
                    wg_fence();
#pragma unroll
                    for (int j = 0; j < 4; j++) wgmma_n8<1, 0>(acc, mkdesc(da + j * astep, ahi), mkdesc(db + j * bstep, bhi), 1);
                    wg_commit();
                    wg_wait<1>();
                    if (ph) { wg_wait<0>(); if (lane == 0) prev = bars + 8 * B_FEMPTY + s8; }
                    if (prev) mbar_arrive(prev);
                    if (lane == 0) prev = bars + 8 * B_FEMPTY + s8;
                    s8 += 8;
                    if (s8 == wrap) { s8 = 0; fph ^= 1; }
                }
                wg_wait<0>();
                const int ln = lane + (left >> 30);
                if (ph == 0) {
                    if (prev) mbar_arrive(prev);
                    const bool second = (wq >= 2) != (swap_gu != 0);
                    const uint32_t xa = sb + OFF_GU + ((wq & 1) * 32 + ln) * 16;
                    if (second) sts4(xa, __float_as_uint(acc[0]), __float_as_uint(acc[1]), __float_as_uint(acc[2]), __float_as_uint(acc[3]));
                    bar_sync(12, 128);
                    if (second) { if (ln == 0) mbar_arrive(bars + 8 * B_F1DONE); }
                    else {
                        const float4 up = lds4f(xa);
                        float hv[4];
#pragma unroll
                        for (int c = 0; c < 4; c++) { const float ga = bf16r(acc[c]); hv[c] = bf16r(ga * sigmoidf(ga)) * bf16r((&up.x)[c]); }
                        const int ao = (b * 4 + (wq & 1) * 2) * 32 + ln;
                        st_rlx(scr->act[ep & 1] + ao, max(movm(pack_bf16(hv[0], hv[1])), 1u)); st_rlx(scr->act[ep & 1] + 32 + ao, max(movm(pack_bf16(hv[2], hv[3])), 1u));
                        __syncwarp();
                        if (ln == 0) red_add(&scr->cnt[b < 14 * NM ? b / (2 * NM) : b < 14 * NM + 2 * N7 ? 7 : 8][0]);
                        st_rlx(scr->act[~ep & 1] + ao, 0); st_rlx(scr->act[~ep & 1] + 32 + ao, 0);
                    }
                } else {
                    st_rlx4(&scr->ypart[mt][c2][wq * 32 + ln], (__float_as_uint(acc[0]) & ~1u) | (ep & 1), __float_as_uint(acc[1]), __float_as_uint(acc[2]), __float_as_uint(acc[3]));
                }
            }
        }
    } else {
        cluster_arrive();
        reg_inc<224>();
        const int w = warp >> 2, wi = warp & 3, g = lane >> 2, t = lane & 3;
        const bool elect = (tid & 127) == 0;
        const uint32_t mad = (lane & 15) * 128 + (((lane >> 4) ^ (lane & 7)) << 4);
        float acc[64];
        const uint32_t ring = sb + w * OFF_X1, ofull = bars + 8 * (B_OFULL + w * 6), oempty = mapa(bars + 8 * B_OEMPTY, w);
        const int r0 = rh * 128 + wi * 32 + (1 - w) * 16 + g;
        {
            float acc0[96], acc1[96];
            const uint32_t sta = sb + OFF_STAT + (8 + w * 128 + wi * 32) * 8;
            {
                const uint32_t xfull = bars + 8 * (B_XFULL + w * 6 + 5), xempty = mapa(bars + 8 * B_XEMPTY, w), dx0 = sd + dlo(w * OFF_X1, 16);
                uint32_t s8 = 16, ps8 = 0, ph = 0;
#pragma unroll 1
                for (int k = 0; k < 16; k++) {
                    const uint32_t dx = dx0 + s8 * (2 * BOX >> 7), dw = sd + dlo(OFF_W, BOX) + s8 * (W_BYTES >> 7);
                    mbar_wait(bars + 8 * B_WFULL + s8, ph, budget);
                    mbar_wait(xfull - 2 * s8, ph, budget);
                    wg_wait<0>();
                    wg_fence();
#pragma unroll
                    for (int kk = 0; kk < 4; kk++) wgmma_n192<0, 1>(acc1, mkdesc(dx + kk * 2, dhi(1024, 1)), mkdesc(dw + kk * 128, dhi(1024, 1)), kk ? 1 : k);
                    wg_commit();
                    if (elect && k > 0) {
                        mbar_arrive(bars + 8 * B_WEMPTY + ps8);
                        if (k <= 13) { mbar_expect_tx(xfull - 2 * ps8 - 8, BOX); mbar_arrive_at(xempty + 2 * ps8 + 8); }
                    }
                    if (k == 0) cluster_wait();
                    if (k == 15) {
                        mbar_wait(bars + 8 * B_AUX, 0, budget);
                        const uint32_t zero = budget >> 30, pm = t & 1 ? 0x4432 : 0x3232, ra = sta + ((t >> 1) * 16 + g) * 8;
                        const uint32_t a0 = __byte_perm(lds1(ra), 0, pm), a1 = __byte_perm(lds1(ra + 64), 0, pm), a2 = a0 & zero, a3 = a1 & zero;
                        wg_fence();
                        wgmma_rs_n192(acc1, a0, a1, a2, a3, mkdesc(sd + dlo(OFF_CS, 0), dhi(128, 0)));
                        wgmma_rs_n192(acc0, a0, a1, a2, a3, mkdesc(sd + dlo(OFF_CS + 64, 0), dhi(128, 0)));
                        wg_commit();
                    }
                    mbar_wait(xfull - 2 * s8 - 8, ph, budget);
                    wg_wait<0>();
                    wg_fence();
#pragma unroll
                    for (int kk = 0; kk < 4; kk++) wgmma_n192<0, 1>(acc0, mkdesc(dx + 512 + kk * 2, dhi(1024, 1)), mkdesc(dw + kk * 128, dhi(1024, 1)), kk ? 1 : k);
                    wg_commit();
                    if (elect && k <= 12) { mbar_expect_tx(xfull - 2 * s8, BOX); mbar_arrive_at(xempty + 2 * s8); }
                    ps8 = s8;
                    s8 = s8 == 16 ? 0 : s8 + 8;
                    if (s8 == 16) ph ^= 1;
                }
            }
            const uint32_t zero = budget >> 30;
            const bool u0 = 2 * t > g, u1 = 2 * t + 1 > g;
            uint32_t mU = (u0 ? 0xffffu : 0u) | (u1 ? 0xffff0000u : 0u);
            uint32_t ka0 = sta + (2 * t - (u0 ? 8 : 0)) * 8 + 4, ka1 = sta + (2 * t + 1 - (u1 ? 8 : 0)) * 8 + 4;
            float rk[2][4], fu[2][4], fn[2][4];
            auto factors = [&](int h) {
#pragma unroll
                for (int n = 0; n < 4; n += 2) {
                    const float rq = lds1f(sta + (16 * h + 4 * n + g) * 8 + 4) * (0.17677669529663687f * 1.4426950408889634f);
                    rk[h][n] = lds1f(ka0 + h * 128 + n * 32); rk[h][n + 1] = lds1f(ka1 + h * 128 + n * 32);
                    const float f0 = rq * rk[h][n], f1 = rq * rk[h][n + 1];
                    fu[h][n] = u0 ? f0 : 0.f; fn[h][n] = f0 - fu[h][n]; fu[h][n + 1] = u1 ? f1 : 0.f; fn[h][n + 1] = f1 - fu[h][n + 1];
                }
#pragma unroll
                for (int n = 0; n < 4; n++) asm volatile("" : "+f"(fu[h][n]), "+f"(fn[h][n]));
            };
            uint8_t* og = scr->o + ((size_t)(mt * 4 + w * 2) * 16 + nt) * BOX + wi * 256 + lane * 4;
            uint32_t pk0[48], pk1[48], o[16] = {};
#pragma unroll
            for (int j = 0; j < 48; j++) if (j < 16 || (j & 1)) pk1[j] = pack_here(acc1[2 * j], acc1[2 * j + 1]);
            if (warp < 7) {
#pragma unroll
                for (int c = 0; c < 4; c++) stsm4(ring + 4 * BOX + wi * 2048 + c * 512 + lane * 16, pk1[17 + 8 * c], pk1[19 + 8 * c], pk1[21 + 8 * c], pk1[23 + 8 * c]);
                bar_arrive(1 + warp, 64);
            } else if (j0 != 768) {
#pragma unroll
                for (int c = 0; c < 4; c++) {
                    pk1[17 + 8 * c] = max(pk1[17 + 8 * c], 1u);
                    st_rlx4(&scr->halo[b][c * 128 + lane * 4], pk1[17 + 8 * c], pk1[19 + 8 * c], pk1[21 + 8 * c], pk1[23 + 8 * c]);
                }
            }
#pragma unroll
            for (int j = 16; j < 48; j += 2) pk1[j] = pack_here(acc1[2 * j], acc1[2 * j + 1]);
            factors(1);
            uint32_t od = sb + 2 * BOX + wi * 256 + (lane >> 4) * 1024 + (lane & 15) * 16, g1peer = mapa(bars + 8 * B_G1DONE, hp ^ 1);
            uint32_t ha = sb + (warp == 0 ? OFF_HIN : warp <= 4 ? 4 * BOX - 2048 : OFF_X1 + 4 * BOX - 5 * 2048) + warp * 2048 + lane * 16;
            const bool first = warp == 0 && j0 == 0;
            float bias0 = first && u0 ? -INFINITY : 0.f, bias1 = first && u1 ? -INFINITY : 0.f;
                        asm volatile("" : "+l"(og), "+r"(mU), "+r"(od), "+r"(ha), "+f"(bias0), "+f"(bias1));
            mbar_wait(bars + 8 * (B_WEMPTY + 1), 0, budget);
            wg_wait<0>();
            if (elect) { mbar_arrive(bars + 8 * B_G1DONE); mbar_arrive_at(g1peer); }
            float ci[4];
#pragma unroll
            for (int n = 0; n < 4; n++) ci[n] = __uint_as_float((0x03800000u + n) | (budget >> 30));
            auto hand_over = [&](int v) {
                asm volatile("{\n.reg .pred p;\nsetp.ne.b32 p, %17, 0;\n"
                             "@p stmatrix.sync.aligned.m8n8.x4.shared.b16 [%16], {%0,%1,%2,%3};\n@p stmatrix.sync.aligned.m8n8.x4.shared.b16 [%16 + 2048], {%4,%5,%6,%7};\n"
                             "@p stmatrix.sync.aligned.m8n8.x4.shared.b16 [%16 + 4096], {%8,%9,%10,%11};\n@p stmatrix.sync.aligned.m8n8.x4.shared.b16 [%16 + 6144], {%12,%13,%14,%15};\n"
                             "fence.proxy.async.shared::cta;\n}"
                             ::"r"(o[0]), "r"(o[1]), "r"(o[2]), "r"(o[3]), "r"(o[4]), "r"(o[5]), "r"(o[6]), "r"(o[7]), "r"(o[8]), "r"(o[9]), "r"(o[10]), "r"(o[11]),
                               "r"(o[12]), "r"(o[13]), "r"(o[14]), "r"(o[15]), "r"(od + v * OFF_X1), "r"((int)(w == rh)) : "memory");
#pragma unroll
                for (int i = 0; i < 16; i++) asm volatile("st.global.u32 [%0], %1;" ::"l"(og + (1 - v) * 16 * BOX + (i >> 1) * 1024 + (i & 1) * 128), "r"(o[i]) : "memory");
                __syncwarp();
                if (lane == 0) mbar_arrive(bars + 8 * (B_STAGED + v));
            };
            uint32_t xt[32];
#pragma unroll
            for (int j = 32; j < 48; j++) pk1[j] = movm(pk1[j]);
#pragma unroll
            for (int j = 0; j < 48; j++) if (j >= 32 || (j > 16 && (j & 1))) pk0[j] = pack_here(acc0[2 * j], acc0[2 * j + 1]);
#pragma unroll
            for (int j = 32; j < 48; j++) pk0[j] = movm(pk0[j]);
            mbar_wait(bars + 8 * B_XT, 0, budget);
            attn_pair<2>(pk1, pk1 + 16, pk1 + 32, pk0 + 17, pk0 + 33, fu[1], fn[1], rk[1], 0.f, 0.f, mU, zero, ci, o);
            hand_over(0);
#pragma unroll
            for (int j = 0; j < 32; j++) if (j < 16 || !(j & 1)) pk0[j] = pack_here(acc0[2 * j], acc0[2 * j + 1]);
            factors(0);
            bar_sync(warp ? warp : 11, 64);
            uint32_t hl[16];
            ldsm4(hl, ha); ldsm4(hl + 4, ha + 512); ldsm4t(hl + 8, ha + 1024); ldsm4t(hl + 12, ha + 1536);
            __syncwarp();
            if (lane == 0) mbar_arrive(bars + 8 * B_FREED);
            attn_pair<1>(pk0, pk0 + 16, pk0 + 32, hl, hl + 8, fu[0], fn[0], rk[0], bias0, bias1, mU, zero, ci, o);
            const float2 s0 = lds2f(sb + OFF_STAT + (8 + r0) * 8), s1 = lds2f(sb + OFF_STAT + (16 + r0) * 8);
#pragma unroll
            for (int j = 0; j < 8; j++) ldsm4(xt + 4 * j, ((ring + wi * 2048 + mad) ^ ((j & 3) * 32)) + (j >> 2) * BOX);
            const float m0 = s0.x * s0.y, f0 = 1.f + s0.y, m1 = s1.x * s1.y, f1 = 1.f + s1.y;
            hand_over(1);
#pragma unroll
            for (int j = 0; j < 32; j++) {
                acc[2 * j] = fmaf(bf_lo(xt[j]), j & 1 ? f1 : f0, j & 1 ? m1 : m0); acc[2 * j + 1] = fmaf(bf_hi(xt[j]), j & 1 ? f1 : f0, j & 1 ? m1 : m0);
            }
        }
        {
            const uint32_t da0 = sd + dlo(w * OFF_X1, 1024), db0 = sd + dlo(OFF_WO, BOX);
            const uint32_t chk = ring + wi * 256 + (lane >> 3) * 1032 + (lane & 7) * 32 + (lane & 4);
            uint32_t s8 = 16, ps8 = 0, ph = 0;
            mbar_wait(ofull + s8, 0, budget);
            mbar_wait(bars + 8 * B_WOFULL + s8, 0, budget);
            const uint32_t ahi = dhi(128, 0) | (budget >> 30), bhi = dhi(1024, 1) | (budget >> 30);
            const int last = w ? HOLD : 15;
            uint32_t rel = elect ? 0x7fe : 0;
            uint32_t da = da0 + s8 * (BOX >> 7), db = db0 + s8 * (BOX >> 6);
#pragma unroll 1
            for (int i = 1;; i++) {
                wg_fence();
#pragma unroll
                for (int kk = 0; kk < 4; kk++) {
                    wgmma_n128<0, 1>(acc, mkdesc(da + kk * 128, ahi), mkdesc(db + kk * 128, bhi), 1);
                    if (kk & 1) wg_commit();
                }
                wg_wait<2>();
                if (rel & 1) { mbar_expect_tx(ofull + ps8, BOX); mbar_arrive_at(oempty + ps8); mbar_arrive(bars + 8 * B_WOEMPTY + ps8); }
                rel >>= 1;
                ps8 = s8;
                s8 = s8 == 40 ? 0 : s8 + 8;
                if (s8 == 16) ph ^= 1;
                da = da0 + s8 * (BOX >> 7); db = db0 + s8 * (BOX >> 6);
                uint32_t slow;
                asm volatile("{\n.reg .pred p, q, r;\n.reg .u32 u, v;\nmbarrier.try_wait.parity.shared::cta.b64 p, [%1], %3;\nmbarrier.try_wait.parity.shared::cta.b64 q, [%2], %3;\n"
                             "setp.ne.and.u32 r, %5, 1, p;\nmov.u32 u, 1;\nmov.u32 v, 1;\n@r ld.shared.u32 u, [%4];\n@r ld.shared.u32 v, [%4 + 4096];\n"
                             "and.pred p, p, q;\nmin.u32 u, u, v;\nsetp.eq.or.u32 p, u, 0, !p;\nvote.sync.any.pred p, p, 0xffffffff;\nselp.u32 %0, 1, 0, p;\n}"
                             : "=r"(slow) : "r"(ofull + s8), "r"(bars + 8 * B_WOFULL + s8), "r"(ph), "r"(chk + s8 * (BOX / 8)), "r"(i) : "memory");
                if (__builtin_expect(slow || i == last, 0)) {
                    uint32_t c8 = slow ? s8 : s8 + 8;
#pragma unroll 1
                    for (int n = slow ? i : i + 1; n < (i == last ? 16 : i + 1); n++, c8 += 8) {
                        const uint32_t cph = ph ^ (HOLD < 12 && c8 >= 16 && s8 < 16);
                        mbar_wait(ofull + c8, cph, budget);
                        mbar_wait(bars + 8 * B_WOFULL + c8, cph, budget);
                        if (__any_sync(0xffffffffu, min(lds1(chk + c8 * (BOX / 8)), lds1(chk + c8 * (BOX / 8) + 4096)) == 0)) {
                            const uint32_t at = wi * 256 + (lane >> 4) * 1024 + (lane & 15) * 16;
                            const uint8_t* src = scr->o + ((size_t)((mt * 2 + rh) * 2 + 1 - w) * 16 + ((2 * p + (n < 2 ? n ^ hp : n)) & 15)) * BOX + at;
#pragma unroll 1
                            for (int m = 0; m < 8192; m += 2048) {
                                uint4 v; int tries = 4096;
#pragma unroll 1
                                do { v = ld_rlx4(src + m); } while (v.x == 0 && --tries > 0);
                                sts4(ring + c8 * (BOX / 8) + at + m, v.x, v.y, v.z, v.w);
                            }
                            fence_async_smem();
                            __syncwarp();
                        }
                    }
                    if (i == last) break;
                }
                wg_wait<1>();
            }
            if (w) bar_sync(9, 256);
#pragma unroll 1
            for (int i = last; i < 16; i++, da += 512, db += 1024) {
                wg_fence();
#pragma unroll
                for (int kk = 0; kk < 4; kk++) wgmma_n128<0, 1>(acc, mkdesc(da + kk * 128, ahi), mkdesc(db + kk * 128, bhi), 1);
                wg_commit();
            }
            if (!w) bar_arrive(9, 256);
            mbar_wait(bars + 8 * B_ZERO, 0, budget);
            const bool add = (__shfl_sync(0xffffffffu, lds1(sb + OFF_SEL), 0) >> (wi * 2 + 1 - w)) & 1;
            wg_wait<0>();
            const uint32_t os0 = ring + wi * 4096;
#pragma unroll
            for (int hf = 0; hf < 2; hf++) {
#pragma unroll
                for (int j = hf * 4; j < hf * 4 + 4; j++)
                    stsm4(((os0 + mad) ^ ((j & 3) * 32)) + (j >> 2) * 2048, pack_here(acc[8 * j], acc[8 * j + 1]), pack_here(acc[8 * j + 2], acc[8 * j + 3]),
                          pack_here(acc[8 * j + 4], acc[8 * j + 5]), pack_here(acc[8 * j + 6], acc[8 * j + 7]));
                fence_async_smem();
                __syncwarp();
                if (elect_one())
                    asm volatile("{\n.reg .pred p;\nsetp.ne.b32 p, %6, 0;\n@!p cp.async.bulk.tensor.5d.global.shared::cta.bulk_group [%0, {%2, %2, %3, %4, %5}], [%1];\n"
                                 "@p cp.reduce.async.bulk.tensor.5d.global.shared::cta.add.bulk_group [%0, {%2, %2, %3, %4, %5}], [%1];\n}"
                                 ::"l"(&mout), "r"(os0 + hf * 2048), "r"(0), "r"(((j0 + rh * 128) >> 5) + wi), "r"(1 - w), "r"(par * 16 + cb * 2 + hf), "r"((int)add) : "memory");
            }
            asm volatile("cp.async.bulk.commit_group;\ncp.async.bulk.wait_group.read 0;" ::: "memory");
            if (b == 0 && tid == 0) st_rlx(&scr->epoch[0], lds1(sb + OFF_EP));
        }
    }
}

struct Plain { __nv_bfloat16 xn[2048 * 1024], qkv[2048 * 3072], o[2048 * 1024], gu[2][8 * 3584], y[8 * 1024]; float r[2048]; int sel[8]; };
__device__ Plain g_plain;
__device__ __forceinline__ float tof(__nv_bfloat16 v) { return __bfloat162float(v); }
__device__ float block_sum(float v) {
    __shared__ float red[8];
    for (int o = 16; o > 0; o >>= 1) v += __shfl_xor_sync(0xffffffffu, v, o);
    __syncthreads();
    if ((threadIdx.x & 31) == 0) red[threadIdx.x >> 5] = v;
    __syncthreads();
    v = 0.f;
    for (int i = 0; i < 8; i++) v += red[i];
    return v;
}
__global__ void plain_ln(const __nv_bfloat16* x, const __nv_bfloat16* wr) {
    const int s = blockIdx.x;
    float v[4], a = 0.f;
    for (int i = 0; i < 4; i++) a += v[i] = tof(x[s * 1024 + i * 256 + threadIdx.x]);
    const float mean = block_sum(a) / 1024.f;
    a = 0.f;
    for (int i = 0; i < 4; i++) a += (v[i] - mean) * (v[i] - mean);
    const float den = bf16r(sqrtf(bf16r(bf16r(block_sum(a) / 1024.f) + 1e-5f)));
    a = 0.f;
    for (int i = 0; i < 4; i++) {
        const float n = bf16r(bf16r(v[i] - bf16r(mean)) / den);
        g_plain.xn[s * 1024 + i * 256 + threadIdx.x] = __float2bfloat16(n);
        a += n * tof(wr[i * 256 + threadIdx.x]);
    }
    a = block_sum(a);
    if (threadIdx.x == 0) g_plain.r[s] = bf16r(a);
}
__global__ void plain_topk() {
    const int s = blockIdx.x * 256 + threadIdx.x;
    int rank = 0;
    for (int i = 0; i < 2048; i++) rank += g_plain.r[i] > g_plain.r[s] || (g_plain.r[i] == g_plain.r[s] && i < s);
    if (rank < 8) g_plain.sel[rank] = s;
}
__global__ void plain_gemm(int what, const __nv_bfloat16* w, int K, int N, const __nv_bfloat16* x, __nv_bfloat16* out) {
    const int n = blockIdx.x * 256 + threadIdx.x, m0 = blockIdx.y * 8;
    float acc[8] = {};
    for (int k = 0; k < K; k++) {
        const float wv = tof(w[(size_t)k * N + n]);
        for (int i = 0; i < 8; i++) {
            float a;
            if (what == 3) { const float gt = tof(g_plain.gu[0][i * K + k]); a = bf16r(bf16r(gt / (1.f + expf(-gt))) * tof(g_plain.gu[1][i * K + k])); }
            else a = tof((what == 4 ? g_plain.o : g_plain.xn)[(what == 1 || what == 2 ? g_plain.sel[i] : m0 + i) * 1024 + k]);
            acc[i] = fmaf(a, wv, acc[i]);
        }
    }
    for (int i = 0; i < 8; i++) {
        if (what == 4) {
            const int at = (m0 + i) * 1024 + n;
            float u = 0.f;
            for (int j = 0; j < 8; j++) if (g_plain.sel[j] == m0 + i) u = bf16r(tof(g_plain.y[j * 1024 + n]) * bf16r(1.f / (1.f + expf(-g_plain.r[m0 + i]))));
            out[at] = __float2bfloat16(bf16r(tof(x[at]) + bf16r(acc[i])) + bf16r(tof(g_plain.xn[at]) + u));
        } else (what == 0 ? g_plain.qkv : what == 3 ? g_plain.y : g_plain.gu[what - 1])[(size_t)(m0 + i) * N + n] = __float2bfloat16(acc[i]);
    }
}
__global__ void plain_attn() {
    const int s = blockIdx.x, d = threadIdx.x;
    const float q = tof(g_plain.qkv[s * 3072 + d]);
    float l[8], mx = -INFINITY, sum = 0.f, o = 0.f;
    for (int w = 0; w < 8; w++) {
        float a = q * tof(g_plain.qkv[max(s - 2 * w, 0) * 3072 + 1024 + d]);
        for (int i = 16; i > 0; i >>= 1) a += __shfl_xor_sync(0xffffffffu, a, i);
        l[w] = s >= 2 * w ? bf16r(bf16r(a) * 0.17677669529663687f) : -1e9f;
        mx = fmaxf(mx, l[w]);
    }
    for (int w = 0; w < 8; w++) sum += l[w] = expf(l[w] - mx);
    for (int w = 0; w < 8; w++) o = fmaf(bf16r(l[w] / sum), tof(g_plain.qkv[max(s - 2 * w, 0) * 3072 + 2048 + d]), o);
    g_plain.o[s * 1024 + d] = __float2bfloat16(o);
}

typedef CUresult (*EncodeFn)(CUtensorMap*, CUtensorMapDataType, cuuint32_t, void*, const cuuint64_t*, const cuuint64_t*, const cuuint32_t*,
                             const cuuint32_t*, CUtensorMapInterleave, CUtensorMapSwizzle, CUtensorMapL2promotion, CUtensorMapFloatOOBfill);

CUtensorMap make_map(EncodeFn fn, const void* base, int rank, const cuuint64_t* dims, const cuuint64_t* strides, const cuuint32_t* box,
                     CUtensorMapSwizzle swz = CU_TENSOR_MAP_SWIZZLE_128B, CUtensorMapL2promotion pro = CU_TENSOR_MAP_L2_PROMOTION_NONE) {
    CUtensorMap m;
    cuuint32_t es[5] = {1, 1, 1, 1, 1};
    fn(&m, CU_TENSOR_MAP_DATA_TYPE_BFLOAT16, rank, (void*)base, dims, strides, box, es, CU_TENSOR_MAP_INTERLEAVE_NONE,
       swz, pro, CU_TENSOR_MAP_FLOAT_OOB_FILL_NONE);
    return m;
}

}

extern "C" void kernel_launch(void* const* d_in, const int* in_sizes, int n_in, void* d_out, int out_size) {
    (void)in_sizes; (void)n_in; (void)out_size;
    const __nv_bfloat16* x = (const __nv_bfloat16*)d_in[0];
    const __nv_bfloat16* wqkv = (const __nv_bfloat16*)d_in[1];
    const __nv_bfloat16* wo = (const __nv_bfloat16*)d_in[2];
    const __nv_bfloat16* wr = (const __nv_bfloat16*)d_in[4];
    const __nv_bfloat16* wg = (const __nv_bfloat16*)d_in[5];
    const __nv_bfloat16* wu = (const __nv_bfloat16*)d_in[6];
    const __nv_bfloat16* wd = (const __nv_bfloat16*)d_in[7];
    static EncodeFn fn = nullptr;
    static Scratch* scr = nullptr;
    static int clusters = 0;
    cudaLaunchConfig_t cfg = {};
    cfg.gridDim = dim3(132); cfg.blockDim = dim3(512); cfg.dynamicSmemBytes = SMEM_LAUNCH; cfg.stream = cudaStreamPerThread;
    if (!fn) {
        void* p = nullptr; cudaDriverEntryPointQueryResult q;
        cudaGetDriverEntryPoint("cuTensorMapEncodeTiled", &p, cudaEnableDefault, &q);
        fn = (EncodeFn)p;
        cudaFuncSetAttribute(fused_kernel, cudaFuncAttributeMaxDynamicSharedMemorySize, SMEM_LAUNCH);
        cudaGetSymbolAddress((void**)&scr, g_scr);
        cudaLaunchAttribute at;
        at.id = cudaLaunchAttributeClusterDimension; at.val.clusterDim.x = 2; at.val.clusterDim.y = 1; at.val.clusterDim.z = 1;
        cudaLaunchConfig_t qc = cfg;
        qc.attrs = &at; qc.numAttrs = 1;
        cudaOccupancyMaxActiveClusters(&clusters, fused_kernel, &qc);
    }
    if (clusters < 66) {
        __nv_bfloat16* out = (__nv_bfloat16*)d_out;
        plain_ln<<<2048, 256, 0, cfg.stream>>>(x, wr);
        plain_topk<<<8, 256, 0, cfg.stream>>>();
        plain_gemm<<<dim3(12, 256), 256, 0, cfg.stream>>>(0, wqkv, 1024, 3072, x, out);
        plain_attn<<<2048, 1024, 0, cfg.stream>>>();
        plain_gemm<<<14, 256, 0, cfg.stream>>>(1, wg, 1024, 3584, x, out);
        plain_gemm<<<14, 256, 0, cfg.stream>>>(2, wu, 1024, 3584, x, out);
        plain_gemm<<<4, 256, 0, cfg.stream>>>(3, wd, 3584, 1024, x, out);
        plain_gemm<<<dim3(4, 256), 256, 0, cfg.stream>>>(4, wo, 1024, 1024, x, out);
        return;
    }
    const cuuint64_t xd[4] = {2048, 16, 32, 2}, xs[4] = {4096, 131072, 65536, 128}, od[5] = {64, 16, 32, 2, 32};
    const cuuint32_t xb[4] = {64, 16, 4, 1}, ob[5] = {64, 16, 1, 1, 1};
    const cuuint64_t wdm[3] = {1024, 1024, 3}, wst[2] = {6144, 2048};
    const cuuint32_t wb[3] = {64, 64, 3};
    const cuuint64_t wod[3] = {64, 1024, 16}, wdd[3] = {64, 3584, 16}, wos[2] = {2048, 128};
    const cuuint32_t wob[3] = {64, 64, 2}, wdb[3] = {64, 64, 1};
    const CUtensorMapSwizzle s128 = CU_TENSOR_MAP_SWIZZLE_128B;
    CUtensorMap mx = make_map(fn, x, 4, xd, xs, xb, s128), mw = make_map(fn, wqkv, 3, wdm, wst, wb, s128);
    CUtensorMap mwo = make_map(fn, wo, 3, wod, wos, wob, s128), mout = make_map(fn, d_out, 5, od, xs, ob, s128);
    const int swap_gu = wu < wg;
    const cuuint64_t gd[3] = {3584, 1024, 2}, gst[2] = {7168, (cuuint64_t)(swap_gu ? (const char*)wg - (const char*)wu : (const char*)wu - (const char*)wg)};
    const cuuint32_t gb[3] = {32, 64, 2};
    CUtensorMap mgu = make_map(fn, swap_gu ? wu : wg, 3, gd, gst, gb, CU_TENSOR_MAP_SWIZZLE_64B, CU_TENSOR_MAP_L2_PROMOTION_L2_128B);
    CUtensorMap mwd = make_map(fn, wd, 3, wdd, wos, wdb, s128, CU_TENSOR_MAP_L2_PROMOTION_L2_128B);
    const cuuint64_t md[2] = {64, 32768}, ms[1] = {128};
    const cuuint32_t mb[2] = {64, 64};
    CUtensorMap mo = make_map(fn, scr, 2, md, ms, mb, CU_TENSOR_MAP_SWIZZLE_NONE);
    const cuuint64_t rd[2] = {1024, 2048};
    const cuuint32_t rb[2] = {256, 16};
    CUtensorMap mr = make_map(fn, x, 2, rd, wos, rb, CU_TENSOR_MAP_SWIZZLE_NONE);
    cudaLaunchKernelEx(&cfg, fused_kernel, mx, mw, mwo, mout, mgu, mwd, mo, mr, x, wr, scr, swap_gu, Weights{(const char*)wqkv, (const char*)wo, (const char*)wg, (const char*)wu, (const char*)wd, (char*)d_out});
}
```

```cpp
#include <cuda_runtime.h>
#include <cuda.h>
#include <cuda_bf16.h>
#include <stdint.h>

namespace {

constexpr int BOX = 8192, W_BYTES = 3 * BOX;
constexpr int OFF_X1 = 6 * BOX, OFF_FR = 12 * BOX, OFF_E = 16 * BOX, OFF_W = 19 * BOX;
constexpr int OFF_WO = OFF_E;
constexpr int OFF_HIN = OFF_FR + 2048, OFF_GU = OFF_HIN + 2048, OFF_FS = OFF_GU + 1024;
constexpr int F_BYTES = 9216;
constexpr int CS_BYTES = 3136;
constexpr int OFF_CS = OFF_FS + 5 * F_BYTES;
constexpr int OFF_STAT = 28 * BOX;
constexpr int OFF_SEL = OFF_STAT + 2112, OFF_EP = OFF_SEL + 4;
constexpr int OFF_BAR = OFF_SEL + 16;
constexpr int B_WFULL = 0, B_XFULL = 3, B_ROW = 15, B_LATE = 19;
constexpr int B_AUX = 19, B_XT = 20, B_ZERO = 21, B_WOFULL = 22, B_OFULL = 28, B_FFULL = 40;
constexpr int B_WEMPTY = 45, B_F1DONE = 48, B_XEMPTY = 49, B_WOEMPTY = 55, B_OEMPTY = 61;
constexpr int B_G1DONE = 71, B_FEMPTY = 72, B_STAGED = 77, B_RDONE = 79, B_FREED = 80, NBAR = 83;
constexpr int SMEM_BYTES = OFF_BAR + NBAR * 8;
static_assert(OFF_FS + 3 * F_BYTES == OFF_E && OFF_CS + CS_BYTES <= OFF_W && SMEM_BYTES + 256 <= 232448 && OFF_BAR % 8 == 0, "smem");
constexpr int PF_RATE = 10;
constexpr int PF_START = 7;
constexpr int HOLD = 12;
constexpr int NM = 3;
constexpr int N7 = 9;
constexpr int NR = 5;
constexpr int KEEP = 0x0bc;
constexpr int MOVM1 = 0;
constexpr int F0E = 0;
constexpr int ROWS_AT = 0x280;
constexpr int NH = 56 - 7 * NM - N7;
static_assert(NH >= NR + 12 && NH <= 32 && NR < 6, "FFN2 split");
constexpr int BUDGET = 1 << 18;

struct Scratch {
    uint8_t o[2048 * 1024 * 2];
    uint4 ypart[8][16][128];
    uint32_t halo[128][512];
    uint32_t act[2][14336 + 4096];
    uint2 row[2048];
    uint4 cs[16][3][24];
    uint32_t oflag[16][32];
    uint32_t cnt[10][32];
    uint32_t sel[32], zflag[32], epoch[32];
};
__device__ __align__(1024) Scratch g_scr;
struct Weights { const char *wqkv, *wo, *wg, *wu, *wd; char* out; };

constexpr int SMEM_LAUNCH = SMEM_BYTES;
__device__ __forceinline__ uint32_t smem_u32(const void* p) { return (uint32_t)__cvta_generic_to_shared(p); }
__device__ __forceinline__ void mbar_init(uint32_t bar, uint32_t cnt) { asm volatile("mbarrier.init.shared::cta.b64 [%0], %1;" ::"r"(bar), "r"(cnt) : "memory"); }
__device__ __forceinline__ void mbar_expect_tx(uint32_t bar, uint32_t bytes) { asm volatile("mbarrier.arrive.expect_tx.shared::cta.b64 _, [%0], %1;" ::"r"(bar), "r"(bytes) : "memory"); }
__device__ __forceinline__ void mbar_arrive(uint32_t bar) { asm volatile("mbarrier.arrive.shared::cta.b64 _, [%0];" ::"r"(bar) : "memory"); }
__device__ __forceinline__ uint32_t mapa(uint32_t a, uint32_t cta) { uint32_t r; asm("mapa.shared::cluster.u32 %0, %1, %2;" : "=r"(r) : "r"(a), "r"(cta)); return r; }
__device__ __forceinline__ void mbar_arrive_at(uint32_t cbar) { asm volatile("mbarrier.arrive.shared::cluster.b64 _, [%0];" ::"r"(cbar) : "memory"); }
__device__ __forceinline__ void mbar_wait(uint32_t bar, uint32_t parity, int& budget) {
    asm volatile("{\n.reg .pred p;\nLAB_WAIT:\nmbarrier.try_wait.parity.shared::cta.b64 p, [%1], %2;\n"
                 "add.s32 %0, %0, -1;\nsetp.gt.and.s32 p, %0, 0, !p;\n@p bra LAB_WAIT;\n}" : "+r"(budget) : "r"(bar), "r"(parity) : "memory");
}
__device__ __forceinline__ void mbar_wait_hot(uint32_t bar, uint32_t parity, int& budget) {
    asm volatile("{\n.reg .pred p;\nmbarrier.try_wait.parity.shared::cta.b64 p, [%1], %2;\n@p bra LAB_DONE;\nLAB_WAIT:\nmbarrier.try_wait.parity.shared::cta.b64 p, [%1], %2;\n"
                 "add.s32 %0, %0, -1;\nsetp.gt.and.s32 p, %0, 0, !p;\n@p bra LAB_WAIT;\nLAB_DONE:\n}" : "+r"(budget) : "r"(bar), "r"(parity) : "memory");
}
__device__ __forceinline__ void tma_2d(uint32_t dst, const CUtensorMap* m, uint32_t bar, int c0, int c1) {
    asm volatile("cp.async.bulk.tensor.2d.shared::cluster.global.mbarrier::complete_tx::bytes [%0], [%1, {%3, %4}], [%2];" ::"r"(dst), "l"(m), "r"(bar), "r"(c0), "r"(c1) : "memory");
}
__device__ __forceinline__ void tma_2d_mc(uint32_t dst, const CUtensorMap* m, uint32_t bar, int c0, int c1) {
    asm volatile("cp.async.bulk.tensor.2d.shared::cluster.global.mbarrier::complete_tx::bytes.multicast::cluster [%0], [%1, {%3, %4}], [%2], %5;" ::"r"(dst), "l"(m), "r"(bar), "r"(c0), "r"(c1), "h"((uint16_t)3) : "memory");
}
__device__ __forceinline__ void tma_3d(uint32_t dst, const CUtensorMap* m, uint32_t bar, int c0, int c1, int c2) {
    asm volatile("cp.async.bulk.tensor.3d.shared::cluster.global.mbarrier::complete_tx::bytes [%0], [%1, {%3, %4, %5}], [%2];" ::"r"(dst), "l"(m), "r"(bar), "r"(c0), "r"(c1), "r"(c2) : "memory");
}
__device__ __forceinline__ void tma_4d(uint32_t dst, const CUtensorMap* m, uint32_t bar, int c0, int c1, int c2, int c3) {
    asm volatile("cp.async.bulk.tensor.4d.shared::cluster.global.mbarrier::complete_tx::bytes [%0], [%1, {%3, %4, %5, %6}], [%2];" ::"r"(dst), "l"(m), "r"(bar), "r"(c0), "r"(c1), "r"(c2), "r"(c3) : "memory");
}
__device__ __forceinline__ void tma_4d_mc(uint32_t dst, const CUtensorMap* m, uint32_t bar, int c0, int c1, int c2, int c3) {
    asm volatile("cp.async.bulk.tensor.4d.shared::cluster.global.mbarrier::complete_tx::bytes.multicast::cluster [%0], [%1, {%3, %4, %5, %6}], [%2], %7;" ::"r"(dst), "l"(m), "r"(bar), "r"(c0), "r"(c1), "r"(c2), "r"(c3), "h"((uint16_t)3) : "memory");
}
__device__ __forceinline__ void bulk_pf(const void* p, uint32_t bytes) { asm volatile("cp.async.bulk.prefetch.L2.global [%0], %1;" ::"l"(p), "r"(bytes) : "memory"); }
__device__ __forceinline__ void bulk_g2s(uint32_t dst, const void* src, uint32_t bytes, uint32_t bar) {
    asm volatile("cp.async.bulk.shared::cluster.global.mbarrier::complete_tx::bytes [%0], [%1], %2, [%3];" ::"r"(dst), "l"(src), "r"(bytes), "r"(bar) : "memory");
}
__device__ __forceinline__ void bulk_s2c(uint32_t cdst, uint32_t src, uint32_t bytes, uint32_t cbar) {
    asm volatile("cp.async.bulk.shared::cluster.shared::cta.mbarrier::complete_tx::bytes [%0], [%1], %2, [%3];" ::"r"(cdst), "r"(src), "r"(bytes), "r"(cbar) : "memory");
}
__device__ __forceinline__ void cluster_arrive() { asm volatile("barrier.cluster.arrive.relaxed.aligned;" ::: "memory"); }
__device__ __forceinline__ void cluster_wait() { asm volatile("barrier.cluster.wait.aligned;" ::: "memory"); }
__device__ __forceinline__ void fence_gpu() { asm volatile("fence.acq_rel.gpu;" ::: "memory"); }
__device__ __forceinline__ void fence_async_smem() { asm volatile("fence.proxy.async.shared::cta;" ::: "memory"); }
__device__ __forceinline__ void wg_fence() { asm volatile("wgmma.fence.sync.aligned;" ::: "memory"); }
__device__ __forceinline__ void wg_commit() { asm volatile("wgmma.commit_group.sync.aligned;" ::: "memory"); }
template <int N> __device__ __forceinline__ void wg_wait() { asm volatile("wgmma.wait_group.sync.aligned %0;" ::"n"(N) : "memory"); }
__device__ __forceinline__ uint64_t mkdesc(uint32_t lo, uint32_t hi) { return ((uint64_t)hi << 32) | lo; }
__host__ __device__ constexpr uint32_t dhi(uint32_t sbo, uint32_t mode) { return (sbo >> 4) | (mode << 30); }
__host__ __device__ constexpr uint32_t dlo(uint32_t off, uint32_t lbo) { return (off >> 4) + ((lbo >> 4) << 16); }
__device__ __forceinline__ bool elect_one() {
    uint32_t e;
    asm volatile("{\n.reg .pred p;\nelect.sync _|p, 0xffffffff;\nselp.u32 %0, 1, 0, p;\n}" : "=r"(e));
    return e;
}
template <int R> __device__ __forceinline__ void reg_inc() { asm volatile("setmaxnreg.inc.sync.aligned.u32 %0;" ::"n"(R)); }
template <int R> __device__ __forceinline__ void reg_dec() { asm volatile("setmaxnreg.dec.sync.aligned.u32 %0;" ::"n"(R)); }
__device__ __forceinline__ void bar_sync(int id, int n) { asm volatile("bar.sync %0, %1;" ::"r"(id), "r"(n) : "memory"); }
__device__ __forceinline__ void bar_arrive(int id, int n) { asm volatile("bar.arrive %0, %1;" ::"r"(id), "r"(n) : "memory"); }
__device__ __forceinline__ uint32_t pack_bf16(float lo, float hi) { uint32_t r; asm("cvt.rn.bf16x2.f32 %0, %1, %2;" : "=r"(r) : "f"(hi), "f"(lo)); return r; }
__device__ __forceinline__ uint32_t pack_here(float lo, float hi) { uint32_t r; asm volatile("cvt.rn.bf16x2.f32 %0, %1, %2;" : "=r"(r) : "f"(hi), "f"(lo)); return r; }
__device__ __forceinline__ float bf_lo(uint32_t u) { return __uint_as_float(u << 16); }
__device__ __forceinline__ float bf_hi(uint32_t u) { return __uint_as_float(u & 0xffff0000u); }
__device__ __forceinline__ float bf16r(float v) { return bf_lo(pack_bf16(v, 0.f)); }
__device__ __forceinline__ float rcp(float x) { float r; asm("rcp.approx.ftz.f32 %0, %1;" : "=f"(r) : "f"(x)); return r; }
__device__ __forceinline__ float ex2(float x) { float r; asm("ex2.approx.ftz.f32 %0, %1;" : "=f"(r) : "f"(x)); return r; }
__device__ __forceinline__ float sigmoidf(float v) { return rcp(1.f + ex2(v * -1.4426950408889634f)); }
__device__ __forceinline__ uint32_t movm(uint32_t a) { uint32_t d; asm volatile("movmatrix.sync.aligned.m8n8.trans.b16 %0, %1;" : "=r"(d) : "r"(a)); return d; }
__device__ __forceinline__ void mma16816(float (&c)[4], uint32_t a0, uint32_t a1, uint32_t a2, uint32_t a3, uint32_t b0, uint32_t b1) {
    asm volatile("mma.sync.aligned.m16n8k16.row.col.f32.bf16.bf16.f32 {%0,%1,%2,%3}, {%4,%5,%6,%7}, {%8,%9}, {%0,%1,%2,%3};"
                 : "+f"(c[0]), "+f"(c[1]), "+f"(c[2]), "+f"(c[3]) : "r"(a0), "r"(a1), "r"(a2), "r"(a3), "r"(b0), "r"(b1));
}
__device__ __forceinline__ void mma1688(float (&c)[4], uint32_t a0, uint32_t a1, uint32_t b0) {
    asm volatile("mma.sync.aligned.m16n8k8.row.col.f32.bf16.bf16.f32 {%0,%1,%2,%3}, {%4,%5}, {%6}, {%0,%1,%2,%3};"
                 : "+f"(c[0]), "+f"(c[1]), "+f"(c[2]), "+f"(c[3]) : "r"(a0), "r"(a1), "r"(b0));
}
__device__ __forceinline__ void stsm4(uint32_t a, uint32_t r0, uint32_t r1, uint32_t r2, uint32_t r3) {
    asm volatile("stmatrix.sync.aligned.m8n8.x4.shared.b16 [%0], {%1,%2,%3,%4};" ::"r"(a), "r"(r0), "r"(r1), "r"(r2), "r"(r3) : "memory");
}
__device__ __forceinline__ void ldsm4(uint32_t* r, uint32_t a) {
    asm volatile("ldmatrix.sync.aligned.m8n8.x4.shared.b16 {%0,%1,%2,%3}, [%4];" : "=r"(r[0]), "=r"(r[1]), "=r"(r[2]), "=r"(r[3]) : "r"(a) : "memory");
}
__device__ __forceinline__ void ldsm4t(uint32_t* r, uint32_t a) {
    asm volatile("ldmatrix.sync.aligned.m8n8.x4.trans.shared.b16 {%0,%1,%2,%3}, [%4];" : "=r"(r[0]), "=r"(r[1]), "=r"(r[2]), "=r"(r[3]) : "r"(a) : "memory");
}
__device__ __forceinline__ uint32_t ld_rlx(const void* p) { uint32_t v; asm volatile("ld.relaxed.gpu.global.u32 %0, [%1];" : "=r"(v) : "l"(p) : "memory"); return v; }
__device__ __forceinline__ uint32_t ld_acq(const void* p) { uint32_t v; asm volatile("ld.acquire.gpu.global.u32 %0, [%1];" : "=r"(v) : "l"(p) : "memory"); return v; }
__device__ __forceinline__ uint2 ld_rlx2(const void* p) { uint2 v; asm volatile("ld.relaxed.gpu.global.v2.u32 {%0,%1}, [%2];" : "=r"(v.x), "=r"(v.y) : "l"(p) : "memory"); return v; }
__device__ __forceinline__ uint4 ld_rlx4(const void* p) { uint4 v; asm volatile("ld.relaxed.gpu.global.v4.u32 {%0,%1,%2,%3}, [%4];" : "=r"(v.x), "=r"(v.y), "=r"(v.z), "=r"(v.w) : "l"(p) : "memory"); return v; }
__device__ __forceinline__ void st_rlx(void* p, uint32_t v) { asm volatile("st.relaxed.gpu.global.u32 [%0], %1;" ::"l"(p), "r"(v) : "memory"); }
__device__ __forceinline__ void st_rlx2(void* p, uint32_t a, uint32_t b) { asm volatile("st.relaxed.gpu.global.v2.u32 [%0], {%1,%2};" ::"l"(p), "r"(a), "r"(b) : "memory"); }
__device__ __forceinline__ void st_rlx4(void* p, uint32_t a, uint32_t b, uint32_t c, uint32_t d) { asm volatile("st.relaxed.gpu.global.v4.u32 [%0], {%1,%2,%3,%4};" ::"l"(p), "r"(a), "r"(b), "r"(c), "r"(d) : "memory"); }
__device__ __forceinline__ void red_add(uint32_t* p) { asm volatile("red.relaxed.gpu.global.add.u32 [%0], 1;" ::"l"(p) : "memory"); }
__device__ __forceinline__ uint4 ldg_nc(const void* p) { uint4 v; asm volatile("ld.global.nc.v4.u32 {%0,%1,%2,%3}, [%4];" : "=r"(v.x), "=r"(v.y), "=r"(v.z), "=r"(v.w) : "l"(p)); return v; }
__device__ __forceinline__ void sts4(uint32_t a, uint32_t x, uint32_t y, uint32_t z, uint32_t w) { asm volatile("st.shared.v4.u32 [%0], {%1,%2,%3,%4};" ::"r"(a), "r"(x), "r"(y), "r"(z), "r"(w) : "memory"); }
__device__ __forceinline__ void sts2(uint32_t a, uint32_t x, uint32_t y) { asm volatile("st.shared.v2.u32 [%0], {%1,%2};" ::"r"(a), "r"(x), "r"(y) : "memory"); }
__device__ __forceinline__ void sts1(uint32_t a, uint32_t v) { asm volatile("st.shared.u32 [%0], %1;" ::"r"(a), "r"(v) : "memory"); }
__device__ __forceinline__ uint4 lds4(uint32_t a) { uint4 v; asm volatile("ld.shared.v4.u32 {%0,%1,%2,%3}, [%4];" : "=r"(v.x), "=r"(v.y), "=r"(v.z), "=r"(v.w) : "r"(a) : "memory"); return v; }
__device__ __forceinline__ float4 lds4f(uint32_t a) { float4 v; asm volatile("ld.shared.v4.f32 {%0,%1,%2,%3}, [%4];" : "=f"(v.x), "=f"(v.y), "=f"(v.z), "=f"(v.w) : "r"(a) : "memory"); return v; }
__device__ __forceinline__ float2 lds2f(uint32_t a) { float2 v; asm volatile("ld.shared.v2.f32 {%0,%1}, [%2];" : "=f"(v.x), "=f"(v.y) : "r"(a) : "memory"); return v; }
__device__ __forceinline__ float lds1f(uint32_t a) { float v; asm volatile("ld.shared.f32 %0, [%1];" : "=f"(v) : "r"(a) : "memory"); return v; }
__device__ __forceinline__ uint32_t lds1(uint32_t a) { uint32_t v; asm volatile("ld.shared.u32 %0, [%1];" : "=r"(v) : "r"(a) : "memory"); return v; }
__device__ __forceinline__ uint32_t redux_max(uint32_t v) { uint32_t r; asm volatile("redux.sync.max.u32 %0, %1, 0xffffffff;" : "=r"(r) : "r"(v)); return r; }
__device__ __forceinline__ uint32_t poll_all(const uint32_t* p, uint32_t mask, uint32_t want, int& budget) {
    uint32_t v;
#pragma unroll 1
    while (v = ld_acq(p), !__all_sync(0xffffffffu, (v & mask) == want) && --budget > 0) __nanosleep(30);
    return v;
}

template <int TA, int TB>
__device__ __forceinline__ void wgmma_n192(float (&d)[96], uint64_t da, uint64_t db, int keep) {
    asm volatile("{\n.reg .pred p;\nsetp.ne.b32 p, %98, 0;\n"
        "wgmma.mma_async.sync.aligned.m64n192k16.f32.bf16.bf16 "
        "{%0, %1, %2, %3, %4, %5, %6, %7, %8, %9, %10, %11, %12, %13, %14, %15, "
        "%16, %17, %18, %19, %20, %21, %22, %23, %24, %25, %26, %27, %28, %29, %30, %31, "
        "%32, %33, %34, %35, %36, %37, %38, %39, %40, %41, %42, %43, %44, %45, %46, %47, "
        "%48, %49, %50, %51, %52, %53, %54, %55, %56, %57, %58, %59, %60, %61, %62, %63, "
        "%64, %65, %66, %67, %68, %69, %70, %71, %72, %73, %74, %75, %76, %77, %78, %79, "
        "%80, %81, %82, %83, %84, %85, %86, %87, %88, %89, %90, %91, %92, %93, %94, %95}, "
        "%96, %97, p, 1, 1, %99, %100;\n}\n"
        : "+f"(d[0]), "+f"(d[1]), "+f"(d[2]), "+f"(d[3]), "+f"(d[4]), "+f"(d[5]), "+f"(d[6]), "+f"(d[7]),
          "+f"(d[8]), "+f"(d[9]), "+f"(d[10]), "+f"(d[11]), "+f"(d[12]), "+f"(d[13]), "+f"(d[14]), "+f"(d[15]),
          "+f"(d[16]), "+f"(d[17]), "+f"(d[18]), "+f"(d[19]), "+f"(d[20]), "+f"(d[21]), "+f"(d[22]), "+f"(d[23]),
          "+f"(d[24]), "+f"(d[25]), "+f"(d[26]), "+f"(d[27]), "+f"(d[28]), "+f"(d[29]), "+f"(d[30]), "+f"(d[31]),
          "+f"(d[32]), "+f"(d[33]), "+f"(d[34]), "+f"(d[35]), "+f"(d[36]), "+f"(d[37]), "+f"(d[38]), "+f"(d[39]),
          "+f"(d[40]), "+f"(d[41]), "+f"(d[42]), "+f"(d[43]), "+f"(d[44]), "+f"(d[45]), "+f"(d[46]), "+f"(d[47]),
          "+f"(d[48]), "+f"(d[49]), "+f"(d[50]), "+f"(d[51]), "+f"(d[52]), "+f"(d[53]), "+f"(d[54]), "+f"(d[55]),
          "+f"(d[56]), "+f"(d[57]), "+f"(d[58]), "+f"(d[59]), "+f"(d[60]), "+f"(d[61]), "+f"(d[62]), "+f"(d[63]),
          "+f"(d[64]), "+f"(d[65]), "+f"(d[66]), "+f"(d[67]), "+f"(d[68]), "+f"(d[69]), "+f"(d[70]), "+f"(d[71]),
          "+f"(d[72]), "+f"(d[73]), "+f"(d[74]), "+f"(d[75]), "+f"(d[76]), "+f"(d[77]), "+f"(d[78]), "+f"(d[79]),
          "+f"(d[80]), "+f"(d[81]), "+f"(d[82]), "+f"(d[83]), "+f"(d[84]), "+f"(d[85]), "+f"(d[86]), "+f"(d[87]),
          "+f"(d[88]), "+f"(d[89]), "+f"(d[90]), "+f"(d[91]), "+f"(d[92]), "+f"(d[93]), "+f"(d[94]), "+f"(d[95])
        : "l"(da), "l"(db), "r"(keep), "n"(TA), "n"(TB));
}
template <int TA, int TB>
__device__ __forceinline__ void wgmma_n128(float (&d)[64], uint64_t da, uint64_t db, int keep) {
    asm volatile("{\n.reg .pred p;\nsetp.ne.b32 p, %66, 0;\n"
        "wgmma.mma_async.sync.aligned.m64n128k16.f32.bf16.bf16 "
        "{%0, %1, %2, %3, %4, %5, %6, %7, %8, %9, %10, %11, %12, %13, %14, %15, "
        "%16, %17, %18, %19, %20, %21, %22, %23, %24, %25, %26, %27, %28, %29, %30, %31, "
        "%32, %33, %34, %35, %36, %37, %38, %39, %40, %41, %42, %43, %44, %45, %46, %47, "
        "%48, %49, %50, %51, %52, %53, %54, %55, %56, %57, %58, %59, %60, %61, %62, %63}, "
        "%64, %65, p, 1, 1, %67, %68;\n}\n"
        : "+f"(d[0]), "+f"(d[1]), "+f"(d[2]), "+f"(d[3]), "+f"(d[4]), "+f"(d[5]), "+f"(d[6]), "+f"(d[7]),
          "+f"(d[8]), "+f"(d[9]), "+f"(d[10]), "+f"(d[11]), "+f"(d[12]), "+f"(d[13]), "+f"(d[14]), "+f"(d[15]),
          "+f"(d[16]), "+f"(d[17]), "+f"(d[18]), "+f"(d[19]), "+f"(d[20]), "+f"(d[21]), "+f"(d[22]), "+f"(d[23]),
          "+f"(d[24]), "+f"(d[25]), "+f"(d[26]), "+f"(d[27]), "+f"(d[28]), "+f"(d[29]), "+f"(d[30]), "+f"(d[31]),
          "+f"(d[32]), "+f"(d[33]), "+f"(d[34]), "+f"(d[35]), "+f"(d[36]), "+f"(d[37]), "+f"(d[38]), "+f"(d[39]),
          "+f"(d[40]), "+f"(d[41]), "+f"(d[42]), "+f"(d[43]), "+f"(d[44]), "+f"(d[45]), "+f"(d[46]), "+f"(d[47]),
          "+f"(d[48]), "+f"(d[49]), "+f"(d[50]), "+f"(d[51]), "+f"(d[52]), "+f"(d[53]), "+f"(d[54]), "+f"(d[55]),
          "+f"(d[56]), "+f"(d[57]), "+f"(d[58]), "+f"(d[59]), "+f"(d[60]), "+f"(d[61]), "+f"(d[62]), "+f"(d[63])
        : "l"(da), "l"(db), "r"(keep), "n"(TA), "n"(TB));
}
template <int TA, int TB>
__device__ __forceinline__ void wgmma_n8(float (&d)[4], uint64_t da, uint64_t db, int keep) {
    asm volatile("{\n.reg .pred p;\nsetp.ne.b32 p, %6, 0;\n"
        "wgmma.mma_async.sync.aligned.m64n8k16.f32.bf16.bf16 "
        "{%0, %1, %2, %3}, "
        "%4, %5, p, 1, 1, %7, %8;\n}\n"
        : "+f"(d[0]), "+f"(d[1]), "+f"(d[2]), "+f"(d[3])
        : "l"(da), "l"(db), "r"(keep), "n"(TA), "n"(TB));
}
__device__ __forceinline__ void wgmma_rs_n192(float (&d)[96], uint32_t a0, uint32_t a1, uint32_t a2, uint32_t a3, uint64_t db) {
    asm volatile("{\n.reg .pred p;\nsetp.ne.b32 p, 1, 0;\n"
        "wgmma.mma_async.sync.aligned.m64n192k16.f32.bf16.bf16 "
        "{%0, %1, %2, %3, %4, %5, %6, %7, %8, %9, %10, %11, %12, %13, %14, %15, "
        "%16, %17, %18, %19, %20, %21, %22, %23, %24, %25, %26, %27, %28, %29, %30, %31, "
        "%32, %33, %34, %35, %36, %37, %38, %39, %40, %41, %42, %43, %44, %45, %46, %47, "
        "%48, %49, %50, %51, %52, %53, %54, %55, %56, %57, %58, %59, %60, %61, %62, %63, "
        "%64, %65, %66, %67, %68, %69, %70, %71, %72, %73, %74, %75, %76, %77, %78, %79, "
        "%80, %81, %82, %83, %84, %85, %86, %87, %88, %89, %90, %91, %92, %93, %94, %95}, "
        "{%96, %97, %98, %99}, %100, p, 1, 1, 1;\n}\n"
        : "+f"(d[0]), "+f"(d[1]), "+f"(d[2]), "+f"(d[3]), "+f"(d[4]), "+f"(d[5]), "+f"(d[6]), "+f"(d[7]),
          "+f"(d[8]), "+f"(d[9]), "+f"(d[10]), "+f"(d[11]), "+f"(d[12]), "+f"(d[13]), "+f"(d[14]), "+f"(d[15]),
          "+f"(d[16]), "+f"(d[17]), "+f"(d[18]), "+f"(d[19]), "+f"(d[20]), "+f"(d[21]), "+f"(d[22]), "+f"(d[23]),
          "+f"(d[24]), "+f"(d[25]), "+f"(d[26]), "+f"(d[27]), "+f"(d[28]), "+f"(d[29]), "+f"(d[30]), "+f"(d[31]),
          "+f"(d[32]), "+f"(d[33]), "+f"(d[34]), "+f"(d[35]), "+f"(d[36]), "+f"(d[37]), "+f"(d[38]), "+f"(d[39]),
          "+f"(d[40]), "+f"(d[41]), "+f"(d[42]), "+f"(d[43]), "+f"(d[44]), "+f"(d[45]), "+f"(d[46]), "+f"(d[47]),
          "+f"(d[48]), "+f"(d[49]), "+f"(d[50]), "+f"(d[51]), "+f"(d[52]), "+f"(d[53]), "+f"(d[54]), "+f"(d[55]),
          "+f"(d[56]), "+f"(d[57]), "+f"(d[58]), "+f"(d[59]), "+f"(d[60]), "+f"(d[61]), "+f"(d[62]), "+f"(d[63]),
          "+f"(d[64]), "+f"(d[65]), "+f"(d[66]), "+f"(d[67]), "+f"(d[68]), "+f"(d[69]), "+f"(d[70]), "+f"(d[71]),
          "+f"(d[72]), "+f"(d[73]), "+f"(d[74]), "+f"(d[75]), "+f"(d[76]), "+f"(d[77]), "+f"(d[78]), "+f"(d[79]),
          "+f"(d[80]), "+f"(d[81]), "+f"(d[82]), "+f"(d[83]), "+f"(d[84]), "+f"(d[85]), "+f"(d[86]), "+f"(d[87]),
          "+f"(d[88]), "+f"(d[89]), "+f"(d[90]), "+f"(d[91]), "+f"(d[92]), "+f"(d[93]), "+f"(d[94]), "+f"(d[95])
        : "r"(a0), "r"(a1), "r"(a2), "r"(a3), "l"(db));
}
__device__ __forceinline__ void wgmma_rs_n8(float (&d)[4], uint32_t a0, uint32_t a1, uint32_t a2, uint32_t a3, uint64_t db) {
    asm volatile("{\n.reg .pred p;\nsetp.ne.b32 p, 1, 0;\n"
        "wgmma.mma_async.sync.aligned.m64n8k16.f32.bf16.bf16 "
        "{%0, %1, %2, %3}, "
        "{%4, %5, %6, %7}, %8, p, 1, 1, 0;\n}\n"
        : "+f"(d[0]), "+f"(d[1]), "+f"(d[2]), "+f"(d[3])
        : "r"(a0), "r"(a1), "r"(a2), "r"(a3), "l"(db));
}

template <int HS>
__device__ __forceinline__ void attn_pair(const uint32_t* q, const uint32_t* k, const uint32_t* v, const uint32_t* kh, const uint32_t* vh,
                                          const float* fu, const float* fn, const float* rk, float bias0, float bias1, uint32_t mU, uint32_t zero, const float* ci, uint32_t* o) {
    float s0[2][4] = {}, s1[2][4] = {}, s2[2][4] = {};
#pragma unroll
    for (int n = 0; n < 4; n++) {
        const int hd = n & 1, a = 8 * hd + 2 * (n & 2);
        mma16816(s1[hd], q[a], q[a + 1], q[a + 2], q[a + 3], k[a], k[a + 2]);
        mma16816(s2[hd], q[a], q[a + 1], q[a + 2], q[a + 3], k[a + 1], k[a + 3]);
    }
#pragma unroll
    for (int n = 0; n < 4; n++) {
        const int hd = n & 1, a = 8 * hd + 2 * (n & 2);
        mma16816(s0[hd], q[a], q[a + 1], q[a + 2], q[a + 3], kh[HS * (a / 2)], kh[HS * (a / 2 + 1)]);
    }
    float e[2][4], m[2][2];
#pragma unroll
    for (int hd = 0; hd < 2; hd++) {
        e[hd][2] = fmaf(s1[hd][2], fu[2], s2[hd][2] * fn[2]); e[hd][3] = fmaf(s1[hd][3], fu[3], s2[hd][3] * fn[3]);
        e[hd][0] = fmaf(s0[hd][0], fu[0], fmaf(s1[hd][0], fn[0], bias0)); e[hd][1] = fmaf(s0[hd][1], fu[1], fmaf(s1[hd][1], fn[1], bias1));
        m[hd][1] = fmaxf(e[hd][2], e[hd][3]); m[hd][0] = fmaxf(e[hd][0], e[hd][1]);
    }
#pragma unroll
    for (int x = 1; x < 3; x++)
#pragma unroll
        for (int n = 0; n < 4; n++) m[n & 1][1 - (n >> 1)] = fmaxf(m[n & 1][1 - (n >> 1)], __shfl_xor_sync(0xffffffffu, m[n & 1][1 - (n >> 1)], x));
#pragma unroll
    for (int hd = 0; hd < 2; hd++) {
#pragma unroll
        for (int n = 0; n < 4; n++) e[hd][n] = ex2(e[hd][n] - m[hd][n >> 1]);
        float sum[4] = {};
        mma1688(sum, pack_bf16(e[hd][0], e[hd][1]), pack_bf16(e[hd][2], e[hd][3]), 0x3f803f80u);
        const float i0 = rcp(sum[0]), i1 = rcp(sum[2]);
        const uint32_t plo = pack_bf16(e[hd][0] * rk[0] * i0, e[hd][1] * rk[1] * i0), phi = pack_bf16(e[hd][2] * rk[2] * i1, e[hd][3] * rk[3] * i1);
        const uint32_t z0 = plo & zero, z1 = phi & zero;
        const uint32_t a0 = plo & ~mU, a1 = phi & mU, a3 = phi & ~mU, b0 = plo & mU;
#pragma unroll
        for (int jj = 0; jj < 4; jj++) {
            float c[4];
            asm volatile("mma.sync.aligned.m16n8k16.row.col.f32.bf16.bf16.f32 {%0,%1,%2,%3}, {%4,%5,%6,%7}, {%8,%9}, {%10,%11,%12,%13};"
                         : "=f"(c[0]), "=f"(c[1]), "=f"(c[2]), "=f"(c[3])
                         : "r"(a0), "r"(a1), "r"(z0), "r"(a3), "r"(v[8 * hd + 2 * jj]), "r"(v[8 * hd + 2 * jj + 1]), "f"(ci[0]), "f"(ci[1]), "f"(ci[2]), "f"(ci[3]));
            mma1688(c, b0, z1, vh[HS * (4 * hd + jj)]);
            o[8 * hd + 2 * jj] = pack_bf16(c[0], c[1]); o[8 * hd + 2 * jj + 1] = pack_bf16(c[2], c[3]);
        }
    }
}

__device__ __forceinline__ uint32_t norm_pair(uint32_t u, float m, float rinv) {
    const uint32_t d = pack_bf16(bf_lo(u) - m, bf_hi(u) - m);
    return max(pack_bf16(bf_lo(d) * rinv, bf_hi(d) * rinv), 1u);
}

__global__ void __cluster_dims__(2, 1, 1) __launch_bounds__(512, 1)
fused_kernel(const __grid_constant__ CUtensorMap mx, const __grid_constant__ CUtensorMap mw, const __grid_constant__ CUtensorMap mwo,
             const __grid_constant__ CUtensorMap mout, const __grid_constant__ CUtensorMap mgu, const __grid_constant__ CUtensorMap mwd,
             const __grid_constant__ CUtensorMap mo, const __grid_constant__ CUtensorMap mr,
             const __nv_bfloat16* __restrict__ x, const __nv_bfloat16* __restrict__ wr, Scratch* __restrict__ scr, int swap_gu, const Weights pf) {
    extern __shared__ __align__(1024) uint8_t smem[];
    const uint32_t sb = smem_u32(smem);
    const uint32_t bars = sb + OFF_BAR;
    const int hp = blockIdx.x & 1, cl = blockIdx.x >> 1;
    int pr = cl - 4;
    asm("{\n.reg .pred p;\nsetp.ge.s32 p, %1, 36;\nselp.s32 %0, %3, %0, p;\nsetp.lt.s32 p, %1, 4;\nselp.s32 %0, %2, %0, p;\n}" : "+r"(pr) : "r"(cl), "r"(39 + 8 * cl), "r"((cl * 293 - 2356) >> 8));
    if (threadIdx.x < 32 && elect_one()) {
        const uint32_t fx = bars + 8 * (B_XFULL + 1), fw = bars + 8 * (B_WFULL + 2);
        mbar_init(fx, 1); mbar_init(fw, 1);
        asm volatile("fence.mbarrier_init.release.cluster;" ::: "memory");
        if (cl < 64) {
            tma_4d(sb + 4 * BOX, &mx, fx, (pr >> 5) * 1024, 0, pr & 24, 1);
            tma_3d(sb + OFF_W + 2 * W_BYTES, &mw, fw, ((pr & 7) * 2 + hp) * 64, 0, 0);
            mbar_expect_tx(fx, BOX); mbar_expect_tx(fw, W_BYTES);
        }
    }
    const int tid = threadIdx.x, lane = tid & 31, warp = __shfl_sync(0xffffffffu, tid >> 5, 0);
    const uint32_t sd = (sb & 0x3FFFF) >> 4;
    const int b = pr * 2 + hp, mt = pr >> 3, p = pr & 7, nt = 2 * p + hp, rh = p & 1, cb = (p & 6) + hp;
    const int par = mt >> 2, j0 = (mt & 3) * 256;
    int budget = BUDGET;

    auto load_w = [&](int k, int s) {
        const uint32_t full = bars + 8 * (B_WFULL + s);
        mbar_expect_tx(full, W_BYTES);
        tma_3d(sb + OFF_W + s * W_BYTES, &mw, full, nt * 64, k * 64, 0);
    };
    auto load_x = [&](int n) {
        const int w = n & 1, j = n < 4 ? (n >> 1) + 4 : (n >> 1) - 2;
        const uint32_t full = bars + 8 * (B_XFULL + w * 6 + 5 - j);
        mbar_expect_tx(full, BOX);
        tma_4d(sb + w * OFF_X1 + j * BOX, &mx, full, par * 1024 + (n >> 2) * 64, 0, (j0 + w * 128) >> 5, (~n >> 1) & 1);
    };
    if (warp > 0 && warp < (b < 128 ? 9 : 16) && elect_one()) {
        mbar_init(bars + (warp == 1 ? 0 : 16 * warp + 8), 1); mbar_init(bars + (warp == 1 ? 8 : 16 * warp + 16), 1);
        if (warp == 1) mbar_init(bars + 24, 1);
        asm volatile("fence.mbarrier_init.release.cluster;" ::: "memory");
    }
    __syncthreads();

    if (b >= 128) {
        const int hc = b - 128, g = lane >> 2, t = lane & 3;
        const uint32_t ep = ld_rlx(&scr->epoch[0]) + 1;
        if (warp < 12) {
            const int n = warp / 3, part = warp - 3 * n;
            auto load = [&](int k) {
                const uint32_t full = bars + 8 * (2 * n + (k & 1));
                mbar_expect_tx(full, W_BYTES);
                tma_3d(sb + (2 * n + (k & 1)) * W_BYTES, &mw, full, (4 * hc + n) * 64, k * 64, 0);
            };
            if (part == 0 && elect_one()) { load(0); load(1); }
            __syncwarp();
            float c0[4] = {0.f, 0.f, 0.f, 0.f}, c1[4] = {0.f, 0.f, 0.f, 0.f};
            const uint32_t sel = g == 0 ? 0x3f80u : g == 1 ? 0x3f800000u : 0u;
            const uint32_t a = sb + 2 * n * W_BYTES + part * BOX + t * 256 + ((g ^ (2 * t)) << 4);
#pragma unroll 1
            for (int k = 0; k < 16; k++) {
                mbar_wait(bars + 8 * (2 * n + (k & 1)), (k >> 1) & 1, budget);
                uint4 v[8], u[8];
#pragma unroll
                for (int i = 0; i < 8; i++) { v[i] = lds4(a + (k & 1) * W_BYTES + i * 1024); u[i] = lds4(((a + 128) ^ 16) + (k & 1) * W_BYTES + i * 1024); }
                bar_sync(1 + n, 96);
                if (part == k % 3 && k < 14 && elect_one()) load(k + 2);
                __syncwarp();
#pragma unroll
                for (int i = 0; i < 8; i++) { mma16816(c0, v[i].x, v[i].y, u[i].x, u[i].y, sel, sel); mma16816(c1, v[i].z, v[i].w, u[i].z, u[i].w, sel, sel); }
            }
            if (t == 0) {
#pragma unroll
                for (int r = 0; r < 3; r++) {
                    const uint32_t q0 = (pack_bf16(c0[0], c0[1]) & ~1u) | (ep & 1), q1 = pack_bf16(c0[2], c0[3]), q2 = pack_bf16(c1[0], c1[1]), q3 = pack_bf16(c1[2], c1[3]);
                    st_rlx4(&scr->cs[4 * hc + n][r][part * 8 + g], q0, q1, q2, q3);
                    c0[0] -= bf_lo(q0); c0[1] -= bf_hi(q0); c0[2] -= bf_lo(q1); c0[3] -= bf_hi(q1);
                    c1[0] -= bf_lo(q2); c1[1] -= bf_hi(q2); c1[2] -= bf_lo(q3); c1[3] -= bf_hi(q3);
                }
            }
        }
        {
            const int wg = warp >> 2, c2 = 4 * hc + wg, tw = tid & 127;
            const uint32_t ring = sb + wg * 6 * BOX, full = bars + 8 * (8 + wg * 6), ha = sb + 24 * BOX;
            const uint32_t* hsrc = scr->act[ep & 1] + (56 - NH) * 256;
            auto load = [&](int q, int s) { mbar_expect_tx(full + 8 * s, BOX); tma_3d(ring + s * BOX, &mwd, full + 8 * s, 0, (56 - NH + q) * 64, c2); };
            const uint32_t key = poll_all(&scr->sel[lane & 7], 31u, ep & 31, budget);
            __syncthreads();
            if ((warp & 3) == 0 && elect_one()) {
#pragma unroll 1
                for (int q = 0; q < 6; q++) load(q, q);
            }
            __syncwarp();
            const int zr = (2047 - ((__shfl_sync(0xffffffffu, key, warp >> 1) >> 5) & 2047)) & ~30;
#pragma unroll
            for (int i = 0; i < 8; i++) st_rlx4(pf.out + (size_t)(zr + (warp & 1) * 16 + 2 * i) * 2048 + hc * 512 + lane * 16, 0, 0, 0, 0);
            __syncthreads();
            uint32_t wa[NR * 16];
#pragma unroll
            for (int q = 0; q < NR; q++) {
                mbar_wait(full + 8 * q, 0, budget);
#pragma unroll
                for (int j = 0; j < 4; j++) ldsm4t(wa + 16 * q + 4 * j, ring + q * BOX + j * 2048 + (lane >> 4) * 1024 + (lane & 7) * 128 + ((((warp & 3) * 2 + ((lane >> 3) & 1)) ^ (lane & 7)) << 4));
                bar_sync(1 + wg, 128);
                if ((warp & 3) == 0 && elect_one()) load(q + 6, q);
                __syncwarp();
            }
            if (tid == 64) { fence_gpu(); st_rlx(&scr->zflag[hc], ep); }
            if (warp == 1 && elect_one()) {
                int tries = BUDGET;
#pragma unroll 1
                while (ld_rlx(&scr->cnt[8][0]) != ep * (4 * NH) && --tries > 0) {}
                mbar_expect_tx(bars + 8 * 32, NH * 1024);
                bulk_g2s(ha, hsrc, NH * 1024, bars + 8 * 32);
            }
            __syncwarp();
            mbar_wait(bars + 8 * 32, 0, budget);
#pragma unroll 1
            for (int i = tid; i < NH * 64; i += 512) {
                int tries = BUDGET;
                if (lds1(ha + i * 16) == 0) {
                    uint4 v;
#pragma unroll 1
                    do { v = ld_rlx4(hsrc + i * 4); } while (v.x == 0 && --tries > 0);
                    sts4(ha + i * 16, v.x, v.y, v.z, v.w);
                }
            }
            fence_async_smem();
            __syncthreads();
            float acc[4] = {0.f, 0.f, 0.f, 0.f};
            int left = BUDGET;
            mbar_wait(full + 8 * NR, 0, left);
            const uint32_t da = sd + dlo(wg * 6 * BOX, BOX), db = sd + dlo(24 * BOX, 128), ahi = dhi(1024, 1) | (left >> 30), bhi = dhi(128, 0) | (left >> 30);
            uint4 v[8];
#pragma unroll
            for (int q = NR; q < NH; q++) {
                if (q > NR) mbar_wait(full + 8 * (q % 6), (q / 6) & 1, left);
                wg_fence();
#pragma unroll
                for (int j = 0; j < 4; j++) wgmma_n8<1, 0>(acc, mkdesc(da + q % 6 * 512 + j * 128, ahi), mkdesc(db + q * 64 + j * 16, bhi), 1);
                wg_commit();
                if (q > NR && q + 5 < NH) {
                    wg_wait<1>();
                    if ((warp & 3) == (q & 3) && elect_one()) load(q + 5, (q - 1) % 6);
                    __syncwarp();
                }
                if (q == NR + 5) {
                    wg_fence();
#pragma unroll
                    for (int j = 0; j < 4 * NR; j++) wgmma_rs_n8(acc, wa[4 * j], wa[4 * j + 1], wa[4 * j + 2], wa[4 * j + 3], mkdesc(db + j * 16, bhi));
                    wg_commit();
                }
                if (q == NH - 2) {
#pragma unroll
                    for (int m = 0; m < 8; m++) v[m] = ld_rlx4(&scr->ypart[m][c2][tw]);
                }
            }
            wg_wait<0>();
#pragma unroll 1
            for (int tries = BUDGET; tries > 0; tries--) {
                uint32_t bad = 0;
#pragma unroll
                for (int m = 0; m < 8; m++) bad |= v[m].x ^ ep;
                if (!(bad & 1)) break;
#pragma unroll
                for (int m = 0; m < 8; m++) if ((v[m].x ^ ep) & 1) v[m] = ld_rlx4(&scr->ypart[m][c2][tw]);
            }
            __syncwarp();
            const float sig = bf16r(sigmoidf(__uint_as_float(((int)key < 0 ? key & 0x7fffffffu : ~key) & 0xffff0000u)));
#pragma unroll
            for (int c = 0; c < 4; c++) {
#pragma unroll
                for (int m = 0; m < 8; m++) acc[c] += __uint_as_float((&v[m].x)[c]);
                acc[c] = bf16r(acc[c]) * __shfl_sync(0xffffffffu, sig, 2 * t + (c & 1));
            }
            char* dst = pf.out + (size_t)(2047 - ((__shfl_sync(0xffffffffu, key, g) >> 5) & 2047)) * 2048 + c2 * 128 + (warp & 3) * 32 + t * 4;
            asm volatile("red.relaxed.gpu.global.add.noftz.bf16x2 [%0], %1;" ::"l"(dst), "r"(movm(pack_bf16(acc[0], acc[1]))) : "memory");
            asm volatile("red.relaxed.gpu.global.add.noftz.bf16x2 [%0], %1;" ::"l"(dst + 16), "r"(movm(pack_bf16(acc[2], acc[3]))) : "memory");
        }
        return;
    }
    auto late_init = [&](int first, uint32_t cnt, int n) {
        if (elect_one()) {
#pragma unroll
            for (int i = 0; i < 13; i++) if (i < n) mbar_init(bars + 8 * (first + i), cnt);
            asm volatile("fence.mbarrier_init.release.cluster;" ::: "memory");
        }
        __syncwarp();
    };

    const int c2 = b & 15, n2 = mt < 7 ? NM : N7;
    if (warp >= 12) {
        reg_dec<24>();
        if (warp >= 14) late_init(B_G1DONE + 6 * (warp - 14), 4 * (warp - 13), 6);
        cluster_arrive();
        if (warp == 12) {
            if (elect_one()) {
                int c = 0;
#pragma unroll 1
                for (int n = 1; n < 12; n++) {
                    load_x(n);
#pragma unroll 1
                    for (; c < (n == 11 ? 4 : __popc(ROWS_AT & ((2 << n) - 1))); c++) { mbar_expect_tx(bars + 8 * (B_ROW + c), BOX); tma_2d(sb + OFF_FR + c * BOX, &mr, bars + 8 * (B_ROW + c), c * 256, b * 16); }
                    if (n == 3 || n == 7) load_w((n + 1) >> 2, n >> 2);
                }
            }
            __syncwarp();
            cluster_wait();
            if (elect_one()) {
                int s = 2; uint32_t ph = 0;
#pragma unroll 1
                for (int k = 3; k < 16; k++) {
                    mbar_wait(bars + 8 * (B_WEMPTY + s), ph, budget);
                    load_w(k, s);
                    if (++s == 3) s = 0;
                    if (s == 2) ph ^= 1;
                }
                s = 2;
#pragma unroll 1
                for (int i = 0; i < 16; i++) {
                    mbar_wait(bars + 8 * (i < 2 ? B_WEMPTY + i : i < 4 ? B_G1DONE : i < 6 ? B_F1DONE : B_WOEMPTY + s), i >= 12, budget);
                    if (i == 0) {
                        mbar_expect_tx(bars + 8 * B_XT, 4 * BOX);
#pragma unroll 1
                        for (int n = 0; n < 4; n++)
                            tma_4d(sb + (n >> 1) * OFF_X1 + (n & 1) * BOX, &mx, bars + 8 * B_XT, par * 1024 + cb * 128 + (n & 1) * 64, 0, (j0 + rh * 128) >> 5, 1 - (n >> 1));
                    }
                    const uint32_t full = bars + 8 * (B_WOFULL + s);
                    mbar_expect_tx(full, 2 * BOX);
                    tma_3d(sb + OFF_WO + s * 2 * BOX, &mwo, full, 0, ((2 * p + (i < 2 ? i ^ hp : i)) & 15) * 64, cb * 2);
                    if (++s == 6) s = 0;
                }
            }
        } else {
            bar_sync(8, 224);
            const uint32_t ep = __shfl_sync(0xffffffffu, lds1(sb + OFF_EP), 0);
            if (warp == 13) {
                cluster_wait();
                if (elect_one()) {
                    int j = 4, q = 0, left = BUDGET; uint32_t ph = 0;
#pragma unroll 1
                    for (int n = 6; n < 32; n++) {
                        mbar_wait(bars + 8 * (B_XEMPTY + j), ph, left);
                        tma_4d_mc(sb + hp * OFF_X1 + j * BOX, &mx, bars + 8 * (B_XFULL + hp * 6 + 5 - j), par * 1024 + (n >> 1) * 64, 0, (j0 + hp * 128) >> 5, ~n & 1);
                        if (++j == 6) j = 0;
                        if (j == 4) ph ^= 1;
#pragma unroll 1
                        for (; q < (PF_RATE * (n - PF_START) >> 3) && q < 24; q++) {
                            const int u = q - 6;
                            if (u < 0) bulk_pf(pf.wqkv + (size_t)(1024 + 128 * u + b) * 6144, 6144);
                            else if (u < 16) bulk_pf((b < 64 ? pf.wg : pf.wu) + (size_t)(u * 64 + (b & 63)) * 7168, 7168);
                            else bulk_pf(pf.wo + (size_t)((u - 16) * 128 + b) * 8192, 8192);
                        }
                    }
                }
                __syncwarp();
                uint32_t* hs = &scr->halo[b - 16][lane * 4];
                uint4 v[4] = {};
                if (j0) {
#pragma unroll 1
                    do {
#pragma unroll
                        for (int c = 0; c < 4; c++) v[c] = ld_rlx4(hs + c * 128);
                    } while (__any_sync(0xffffffffu, min(min(v[0].x, v[1].x), min(v[2].x, v[3].x)) == 0) && --budget > 0);
#pragma unroll
                    for (int c = 0; c < 4; c++) st_rlx(hs + c * 128, 0);
                }
#pragma unroll
                for (int c = 0; c < 4; c++) stsm4(sb + OFF_HIN + c * 512 + lane * 16, v[c].x, v[c].y, v[c].z, v[c].w);
                bar_arrive(11, 64);
                const int src = ((mt * 2 + rh) * 2 + 1 - hp) * 1024;
                if (elect_one()) {
                    const uint32_t* fl = &scr->oflag[mt * 2 + 1 - hp][0];
                    const uint32_t inv = (ep & 1) - 1;
                    uint32_t ready = 0, ph = 0;
                    int s = 4;
#pragma unroll 1
                    for (int i = 2; i < 16; i++) {
                        const int kb = (2 * p + i) & 15;
#pragma unroll 1
                        while (!((ready >> kb) & 1) && --budget > 0) ready = ld_rlx(fl) ^ inv;
                        mbar_wait(bars + 8 * (B_OEMPTY + s), ph, budget);
                        tma_2d_mc(sb + hp * OFF_X1 + s * BOX, &mo, bars + 8 * (B_OFULL + hp * 6 + s), 0, src + kb * 64);
                        if (++s == 6) s = 0;
                        if (s == 4) ph ^= 1;
                    }
                }
            } else if (warp == 14) {
                if (elect_one()) {
                    uint32_t s8 = 0, ph = 0;
                    int tries = BUDGET;
                    const uint32_t* act = scr->act[ep & 1];
                    auto counted = [&](int c, uint32_t n) {
#pragma unroll 1
                        while (ld_rlx(&scr->cnt[c][0]) != ep * n && --tries > 0) __nanosleep(30);
                    };
                    auto weights = [&](const CUtensorMap* m, int c0, int c1, int c2_) {
                        mbar_wait(bars + 8 * B_FEMPTY + s8, ph, budget);
                        mbar_expect_tx(bars + 8 * B_FFULL + s8, F_BYTES);
                        tma_3d(sb + OFF_FS + s8 * (F_BYTES / 8), m, bars + 8 * B_FFULL + s8, c0, c1, c2_);
                    };
                    if (b < 112) {
                        counted(9, 32);
#pragma unroll 1
                        for (int q = 0; q < 16; q++) {
                            weights(&mgu, b * 32, q * 64, 0);
                            bulk_g2s(sb + OFF_FS + BOX + s8 * (F_BYTES / 8), act + 14336 + q * 256, 1024, bars + 8 * B_FFULL + s8);
                            if (q >= 8) bulk_pf(pf.wd + (size_t)(q * 112 + b) * 4096, 4096);
                            s8 += 8;
                            if (s8 == 40) { s8 = 0; ph ^= 1; }
                        }
                    }
#pragma unroll 1
                    for (int q = -3; q < n2; q++) {
                        if (q == 0) { counted(mt, 4 * n2); }
                        if ((unsigned)q >= 3) weights(&mwd, 0, (mt * NM + (q < 0 ? q + 3 : q)) * 64, c2);
                        if (q >= 0) bulk_g2s(sb + OFF_FS + BOX + s8 * (F_BYTES / 8), act + (mt * NM + q) * 256, 1024, bars + 8 * B_FFULL + s8);
                        s8 += 8;
                        if (s8 == 24) { s8 = 0; if ((unsigned)q >= 3) ph ^= 1; }
                    }
                }
            } else {
#pragma unroll 1
                for (int i = lane * 16; i < CS_BYTES; i += 512) sts4(sb + OFF_CS + i, 0, 0, 0, 0);
                mbar_wait(bars + 8 * (B_ROW + 3), 0, budget);
                uint8_t* oz = scr->o + ((size_t)mt * 64 + nt) * BOX + lane * 16;
#pragma unroll 1
                for (int i = 0; i < 16; i++, oz += 512) {
#pragma unroll
                    for (int n = 0; n < 4; n++) st_rlx4(oz + n * 16 * BOX, 0, 0, 0, 0);
                    __nanosleep(100);
                }
                __syncwarp();
                fence_gpu();
                mbar_wait(bars + 8 * B_RDONE, 0, budget);
                int tries = BUDGET;
#pragma unroll 1
                for (int i = lane; i < 88; i += 32) {
                    const uint2* rp = &scr->row[2 * (j0 - 8 + i) + par];
                    uint2 v0, v1, v2;
#pragma unroll 1
                    do { v0 = ld_rlx2(rp + (j0 + i < 8 ? 16 : 0)); v1 = ld_rlx2(rp + 176); v2 = ld_rlx2(rp + 352); } while ((((v0.y ^ ep) | (v1.y ^ ep) | (v2.y ^ ep)) & 31) && --tries > 0);
                    sts2(sb + OFF_STAT + i * 8, (v0.x << 16) ^ 0x80000000u, __float_as_uint(rcp(bf_hi(v0.x))));
                    sts2(sb + OFF_STAT + i * 8 + 704, (v1.x << 16) ^ 0x80000000u, __float_as_uint(rcp(bf_hi(v1.x))));
                    sts2(sb + OFF_STAT + i * 8 + 1408, (v2.x << 16) ^ 0x80000000u, __float_as_uint(rcp(bf_hi(v2.x))));
                }
                __syncwarp();
                {
                    const int row = 2047 - ((poll_all(&scr->sel[lane & 7], 31u, ep & 31, budget) >> 5) & 2047), jj = (row >> 1) - j0 - rh * 128;
                    sts1(sb + OFF_SEL, __reduce_or_sync(0xffffffffu, (row & 1) == par && (unsigned)jj < 128 ? 1u << (jj >> 4) : 0u));
                }
                if (lane < 24) {
                    uint4 v[3];
#pragma unroll 1
                    while (v[0] = ld_rlx4(&scr->cs[nt][0][lane]), v[1] = ld_rlx4(&scr->cs[nt][1][lane]), v[2] = ld_rlx4(&scr->cs[nt][2][lane]),
                           (((v[0].x ^ ep) | (v[1].x ^ ep) | (v[2].x ^ ep)) & 1) && --tries > 0) __nanosleep(100);
#pragma unroll
                    for (int r = 0; r < 3; r++) sts4(sb + OFF_CS + 64 + lane * 128 + r * 16, v[r].x, v[r].y, v[r].z, v[r].w);
                }
                fence_async_smem();
                __syncwarp();
                if (elect_one()) {
                    mbar_arrive(bars + 8 * B_AUX);
                    mbar_expect_tx(bars + 8 * (B_OFULL + 3), BOX); mbar_expect_tx(bars + 8 * (B_OFULL + 9), BOX);
#pragma unroll 1
                    for (int v = 0; v < 2; v++) {
                        const uint32_t ring = sb + v * OFF_X1 + 2 * BOX, fb = bars + 8 * (B_OFULL + v * 6 + 2);
                        mbar_wait(bars + 8 * (B_STAGED + v), 0, budget);
                        asm volatile("red.relaxed.gpu.global.xor.b32 [%0], %1;" ::"l"(&scr->oflag[mt * 2 + 1 - v][0]), "r"(1u << nt) : "memory");
                        mbar_arrive(fb);
                        mbar_wait(bars + 8 * B_G1DONE, 0, budget);
                        bulk_s2c(mapa(ring + BOX, hp ^ 1), ring, BOX, mapa(fb + 8, hp ^ 1));
                        if (v == 0) mbar_wait(bars + 8 * B_FREED, 0, budget);
#pragma unroll
                        for (int n = 0; n < 4; n++) {
                            mbar_expect_tx(bars + 8 * (B_OFULL + (n >> 1) * 6 + 4 + (n & 1)) - v * 32, BOX);
                            mbar_arrive_at(mapa(bars + 8 * B_OEMPTY, n >> 1) + (4 + (n & 1)) * 8 - v * 32);
                        }
                    }
                    if (lds1(sb + OFF_SEL)) {
#pragma unroll 1
                        while (ld_acq(&scr->zflag[p >> 1]) != ep && --tries > 0) {}
                        asm volatile("fence.proxy.async.global;" ::: "memory");
                    }
                    mbar_arrive(bars + 8 * B_ZERO);
                }
            }
        }
    } else if (warp >= 8) {
        reg_dec<40>();
        const int wq = warp - 8, ta = tid - 256;
        const uint32_t rbuf = sb + OFF_FR + wq * 2048;
        const uint4 wv = ldg_nc(wr + ta * 8);
        const uint32_t ep0 = ld_rlx(&scr->epoch[0]);
        late_init(B_LATE + 13 * wq, 1 + (wq >> 1), 13);
        cluster_arrive();
        if (ta == 0) sts1(sb + OFF_EP, ep0 + 1);
        sts4(sb + OFF_STAT + ta * 16, wv.x, wv.y, wv.z, wv.w);
        bar_sync(8, 224);
        const uint32_t ep = __shfl_sync(0xffffffffu, lds1(sb + OFF_EP), 0);
        {
            const int s = b * 16 + wq * 4 + (lane >> 3);
            if ((lane & 7) == 0) st_rlx2(&scr->row[s], 0, ep - 1);
            float sw = 0.f;
#pragma unroll 1
            for (int i = 0; i < 16; i++) { const uint32_t q = lds1(sb + OFF_STAT + i * 128 + lane * 4); sw += bf_lo(q) + bf_hi(q); }
#pragma unroll 1
            for (int o = 16; o > 0; o >>= 1) sw += __shfl_xor_sync(0xffffffffu, sw, o);
            float s1 = 0.f, s2 = 0.f, sr = 0.f;
            {
                float s1b = 0.f, s2b = 0.f, srb = 0.f;
                const uint32_t xb = rbuf + (lane >> 4) * 1024 + (lane & 15) * 16, wb = sb + OFF_STAT + (lane & 15) * 16;
#pragma unroll 1
                for (int i = 0; i < 8; i++) {
                    const uint4 w4 = lds4(wb + i * 256);
                    mbar_wait_hot(bars + 8 * (B_ROW + (i >> 1)), 0, budget);
                    const uint32_t o = (i >> 1) * BOX + (i & 1) * 256;
                    const uint4 u = lds4(xb + o), v = lds4(xb + o + 512);
#pragma unroll
                    for (int c = 0; c < 4; c++) {
                        const float w0 = bf_lo((&w4.x)[c]), w1 = bf_hi((&w4.x)[c]);
                        const float a0 = bf_lo((&u.x)[c]), a1 = bf_hi((&u.x)[c]), b0 = bf_lo((&v.x)[c]), b1 = bf_hi((&v.x)[c]);
                        s1 += a0; s2 = fmaf(a0, a0, s2); sr = fmaf(a0, w0, sr);
                        s1 += a1; s2 = fmaf(a1, a1, s2); sr = fmaf(a1, w1, sr);
                        s1b += b0; s2b = fmaf(b0, b0, s2b); srb = fmaf(b0, w0, srb);
                        s1b += b1; s2b = fmaf(b1, b1, s2b); srb = fmaf(b1, w1, srb);
                    }
                }
                const bool up = lane & 8;
                s1 = (up ? s1b : s1) + __shfl_xor_sync(0xffffffffu, up ? s1 : s1b, 8);
                s2 = (up ? s2b : s2) + __shfl_xor_sync(0xffffffffu, up ? s2 : s2b, 8);
                sr = (up ? srb : sr) + __shfl_xor_sync(0xffffffffu, up ? sr : srb, 8);
            }
#pragma unroll
            for (int o = 1; o < 8; o <<= 1) {
                s1 += __shfl_xor_sync(0xffffffffu, s1, o); s2 += __shfl_xor_sync(0xffffffffu, s2, o); sr += __shfl_xor_sync(0xffffffffu, sr, o);
            }
            const float mean = s1 * (1.f / 1024.f), mb = bf16r(mean);
            float var = fmaf(-mean, mean, s2 * (1.f / 1024.f));
            sr = fmaf(-mb, sw, sr);
            if (__builtin_expect(__any_sync(0xffffffffu, mean * mean > 256.f * var), 0)) {
                float a2 = 0.f, ar = 0.f;
#pragma unroll 1
                for (int i = 0; i < 64; i++) {
                    const uint32_t o = i * 32 + (lane & 7) * 4, q1 = lds1(rbuf + (lane >> 3) * 512 + (o >> 9) * BOX + (o & 511)), q2 = lds1(sb + OFF_STAT + o);
                    a2 = fmaf(bf_lo(q1) - mean, bf_lo(q1) - mean, fmaf(bf_hi(q1) - mean, bf_hi(q1) - mean, a2));
                    ar = fmaf(bf_lo(q1) - mb, bf_lo(q2), fmaf(bf_hi(q1) - mb, bf_hi(q2), ar));
                }
#pragma unroll 1
                for (int o = 1; o < 8; o <<= 1) { a2 += __shfl_xor_sync(0xffffffffu, a2, o); ar += __shfl_xor_sync(0xffffffffu, ar, o); }
                var = a2 * (1.f / 1024.f); sr = ar;
            }
            float den;
            asm("sqrt.approx.f32 %0, %1;" : "=f"(den) : "f"(bf16r(bf16r(var) + 1e-5f)));
            const uint32_t st = pack_bf16(mb, den);
            const uint32_t rb = pack_bf16(0.f, sr * rcp(bf_hi(st)) + 0.f);
            uint32_t ord = (int)rb < 0 ? ~rb & 0xffff0000u : rb | 0x80000000u;
            if ((rb & 0x7fffffffu) > 0x7f800000u) ord = 0;
            if ((lane & 7) == 0) st_rlx2(&scr->row[s], st, ord | ((2047 - s) << 5) | (ep & 31));
            __syncwarp();
            if (lane < 7) mbar_arrive(bars + 8 * (lane < 5 ? B_FEMPTY + lane : B_RDONE));
        }
        if ((b >> 3) == 14) {
            const uint32_t gm = sb + OFF_E, cnt = gm + 64, res = gm + 80, list = gm + 128;
            uint32_t kv[16];
            int tries = BUDGET;
#pragma unroll 1
            do {
                uint32_t bad = 0;
#pragma unroll
                for (int n = 0; n < 16; n++) kv[n] = ld_rlx(&scr->row[n * 128 + ta].y);
#pragma unroll
                for (int n = 0; n < 16; n++) bad |= kv[n] ^ ep;
                if ((bad & 31) == 0) break;
            } while (--tries > 0);
            __syncwarp();
            uint32_t m = 0;
#pragma unroll
            for (int n = 0; n < 16; n++) m = max(m, kv[n]);
            uint32_t gmax = m;
#pragma unroll
            for (int o = 1; o < 8; o <<= 1) gmax = max(gmax, __shfl_xor_sync(0xffffffffu, gmax, o));
            sts1(gm + (ta >> 3) * 4, gmax);
            sts1(cnt, 0);
            bar_sync(12, 128);
            const uint32_t c = lds1(gm + (lane & 15) * 4);
            int rank = 0;
#pragma unroll
            for (int i = 0; i < 2; i++) { const uint4 q = lds4(gm + (lane >> 4) * 32 + i * 16); rank += (q.x > c) + (q.y > c) + (q.z > c) + (q.w > c); }
            rank += __shfl_xor_sync(0xffffffffu, rank, 16);
            const uint32_t thr = redux_max(rank == 7 ? c : 0u);
#pragma unroll 1
            while (m >= thr) {
                uint32_t at, m2 = 0;
                asm volatile("atom.shared.add.u32 %0, [%1], 1;" : "=r"(at) : "r"(cnt) : "memory");
#pragma unroll
                for (int n = 0; n < 16; n++) m2 = max(m2, kv[n] < m ? kv[n] : 0u);
                sts1(list + at * 4, m);
                if (m2 == 0) break;
                m = m2;
            }
            bar_sync(12, 128);
            const int nc = lds1(cnt);
#pragma unroll 1
            for (int i = ta >> 3; i < ((nc + 3) & ~3); i += 16) {
                const uint32_t ki = lds1(list + i * 4);
                int r = 0;
#pragma unroll 1
                for (int n = lane & 7; n < nc; n += 8) r += lds1(list + n * 4) > ki;
                __syncwarp();
#pragma unroll
                for (int o = 1; o < 8; o <<= 1) r += __shfl_xor_sync(0xffffffffu, r, o);
                if (r == (b & 7) && i < nc) sts1(res, ki);
            }
            bar_sync(12, 128);
            const uint32_t k0 = lds1(res);
            const int r0 = 2047 - ((k0 >> 5) & 2047);
            if (ta == 0) st_rlx(&scr->sel[b & 7], k0);
            const uint4 v0 = ldg_nc(x + (size_t)r0 * 1024 + ta * 8);
            const uint32_t s0 = ld_rlx(&scr->row[r0]);
            const float m0 = bf_lo(s0), i0 = rcp(bf_hi(s0));
            const int ao = 14336 + (ta >> 3) * 256 + (b & 7) * 32 + ((ta ^ b) & 7) * 4;
            st_rlx4(scr->act[ep & 1] + ao, norm_pair(v0.x, m0, i0), norm_pair(v0.y, m0, i0), norm_pair(v0.z, m0, i0), norm_pair(v0.w, m0, i0));
            __syncwarp();
            if (lane == 0) red_add(&scr->cnt[9][tries >> 30]);
            st_rlx4(scr->act[~ep & 1] + ao, 0, 0, 0, 0);
        }
        uint32_t s8 = 0, fph = 0;
        const uint32_t chk = __shfl_sync(0xffffffffu, sb + OFF_FS + BOX + lane * 32 + (lane & 28), lane);
        int left = BUDGET;
        if (b >= 112 && ta < 2) mbar_arrive(bars + 8 * B_F1DONE);
#pragma unroll 1
        for (int ph = b >= 112; ph < 2; ph++) {
            {
                float acc[4] = {0.f, 0.f, 0.f, 0.f};
                const uint32_t alo = sd + (ph ? dlo(OFF_FS, 8192) : dlo(OFF_FS, 4096)), ahi = ph ? dhi(1024, 1) : dhi(512, 2), astep = ph ? 128 : 64;
                const uint32_t bhi = ph ? dhi(128, 0) : dhi(1024, 1), bstep = ph ? 16 : 2, wrap = ph ? 24 : 40;
                uint32_t prev = 0;
                if (ph) mbar_wait(bars + 8 * (B_STAGED + 1), 0, left);
#pragma unroll 1
                for (int q = ph ? n2 : 16; q > 0; q--) {
                    const uint32_t da = alo + s8 * (F_BYTES >> 7), db = sd + dlo(OFF_FS + BOX, 128) + s8 * (F_BYTES >> 7);
                    mbar_wait_hot(bars + 8 * B_FFULL + s8, fph, left);
                    if (__builtin_expect(__any_sync(0xffffffffu, lds1(chk + s8 * (F_BYTES / 8)) == 0), 0)) {
                        int tries = BUDGET;
#pragma unroll 1
                        for (int n = lane * 4 + (left >> 30); n < 256; n += 128) {
                            uint4 v;
#pragma unroll 1
                            do { v = ld_rlx4(scr->act[ep & 1] + ((ph ? mt * NM + n2 : 72) - q) * 256 + n); } while (v.x == 0 && --tries > 0);
                            __syncwarp();
                            sts4(sb + OFF_FS + BOX + s8 * (F_BYTES / 8) + n * 4, v.x, v.y, v.z, v.w);
                        }
                        fence_async_smem();
                        __syncwarp();
                    }
                    wg_fence();
#pragma unroll
                    for (int j = 0; j < 4; j++) wgmma_n8<1, 0>(acc, mkdesc(da + j * astep, ahi), mkdesc(db + j * bstep, bhi), 1);
                    wg_commit();
                    wg_wait<1>();
                    if (ph) { wg_wait<0>(); if (lane == 0) prev = bars + 8 * B_FEMPTY + s8; }
                    if (prev) mbar_arrive(prev);
                    if (lane == 0) prev = bars + 8 * B_FEMPTY + s8;
                    s8 += 8;
                    if (s8 == wrap) { s8 = 0; fph ^= 1; }
                }
                wg_wait<0>();
                const int ln = lane + (left >> 30);
                if (ph == 0) {
                    if (prev) mbar_arrive(prev);
                    const bool second = (wq >= 2) != (swap_gu != 0);
                    const uint32_t xa = sb + OFF_GU + ((wq & 1) * 32 + ln) * 16;
                    if (second) sts4(xa, __float_as_uint(acc[0]), __float_as_uint(acc[1]), __float_as_uint(acc[2]), __float_as_uint(acc[3]));
                    bar_sync(12, 128);
                    if (second) { if (ln == 0) mbar_arrive(bars + 8 * B_F1DONE); }
                    else {
                        const float4 up = lds4f(xa);
                        float hv[4];
#pragma unroll
                        for (int c = 0; c < 4; c++) { const float ga = bf16r(acc[c]); hv[c] = bf16r(ga * sigmoidf(ga)) * bf16r((&up.x)[c]); }
                        const int ao = (b * 4 + (wq & 1) * 2) * 32 + ln;
                        st_rlx(scr->act[ep & 1] + ao, max(movm(pack_bf16(hv[0], hv[1])), 1u)); st_rlx(scr->act[ep & 1] + 32 + ao, max(movm(pack_bf16(hv[2], hv[3])), 1u));
                        __syncwarp();
                        if (ln == 0) red_add(&scr->cnt[b < 14 * NM ? b / (2 * NM) : b < 14 * NM + 2 * N7 ? 7 : 8][0]);
                        st_rlx(scr->act[~ep & 1] + ao, 0); st_rlx(scr->act[~ep & 1] + 32 + ao, 0);
                    }
                } else {
                    st_rlx4(&scr->ypart[mt][c2][wq * 32 + ln], (__float_as_uint(acc[0]) & ~1u) | (ep & 1), __float_as_uint(acc[1]), __float_as_uint(acc[2]), __float_as_uint(acc[3]));
                }
            }
        }
    } else {
        cluster_arrive();
        reg_inc<224>();
        const int w = warp >> 2, wi = warp & 3, g = lane >> 2, t = lane & 3;
        const bool elect = (tid & 127) == 0;
        float acc[64];
        const uint32_t ring = sb + w * OFF_X1, ofull = bars + 8 * (B_OFULL + w * 6), oempty = mapa(bars + 8 * B_OEMPTY, w);
        auto keep = [&](uint32_t v, int bit) { return KEEP >> bit & 1 ? __shfl_sync(0xffffffffu, v, lane) : v; };
        const uint32_t mad = keep(ring + wi * 2048 + (lane & 15) * 128 + (((lane >> 4) ^ (lane & 7)) << 4), 0);
        const uint32_t sr = keep(sb + OFF_STAT + (8 + rh * 128 + wi * 32 + (1 - w) * 16 + g) * 8, 1);
        {
            float acc0[96], acc1[96];
            const uint32_t sta = sb + OFF_STAT + (8 + w * 128 + wi * 32) * 8, sq = keep(sta + g * 8, 2);
            const uint32_t mU = keep((2 * t > g ? 0xffffu : 0u) | (2 * t + 1 > g ? 0xffff0000u : 0u), 3);
            const uint32_t ka0 = keep(sta + (2 * t - (2 * t > g ? 8 : 0)) * 8 + 4, 4), ka1 = keep(sta + (2 * t + 1 - (2 * t + 1 > g ? 8 : 0)) * 8 + 4, 4);
            const uint32_t oo = keep(((mt * 4 + w * 2) * 16 + nt) * BOX + wi * 256 + lane * 4, 5);
            const uint32_t od = keep(sb + 2 * BOX + wi * 256 + (lane >> 4) * 1024 + (lane & 15) * 16, 6);
            const uint32_t hd = keep(ring + 4 * BOX + wi * 2048 + lane * 16, 7);
            const uint32_t ha = keep(sb + (warp == 0 ? OFF_HIN : warp <= 4 ? 4 * BOX - 2048 : OFF_X1 + 4 * BOX - 5 * 2048) + warp * 2048 + lane * 16, 8);
            {
                const uint32_t xfull = bars + 8 * (B_XFULL + w * 6 + 5), xempty = mapa(bars + 8 * B_XEMPTY, w), dx0 = sd + dlo(w * OFF_X1, 16);
                uint32_t s8 = 16, ps8 = 0, ph = 0;
#pragma unroll 1
                for (int k = 0; k < 16; k++) {
                    const uint32_t dx = dx0 + s8 * (2 * BOX >> 7), dw = sd + dlo(OFF_W, BOX) + s8 * (W_BYTES >> 7);
                    mbar_wait(bars + 8 * B_WFULL + s8, ph, budget);
                    mbar_wait(xfull - 2 * s8, ph, budget);
                    wg_wait<0>();
                    wg_fence();
#pragma unroll
                    for (int kk = 0; kk < 4; kk++) wgmma_n192<0, 1>(acc1, mkdesc(dx + kk * 2, dhi(1024, 1)), mkdesc(dw + kk * 128, dhi(1024, 1)), kk ? 1 : k);
                    wg_commit();
                    if (elect && k > 0) {
                        mbar_arrive(bars + 8 * B_WEMPTY + ps8);
                        if (k <= 13) { mbar_expect_tx(xfull - 2 * ps8 - 8, BOX); mbar_arrive_at(xempty + 2 * ps8 + 8); }
                    }
                    if (k == 0) cluster_wait();
                    if (k == 15) {
                        mbar_wait(bars + 8 * B_AUX, 0, budget);
                        const uint32_t zero = budget >> 30, pm = t & 1 ? 0x4432 : 0x3232, ra = sq + (t >> 1) * 128;
                        const uint32_t a0 = __byte_perm(lds1(ra), 0, pm), a1 = __byte_perm(lds1(ra + 64), 0, pm), a2 = a0 & zero, a3 = a1 & zero;
                        wg_fence();
                        wgmma_rs_n192(acc1, a0, a1, a2, a3, mkdesc(sd + dlo(OFF_CS, 0), dhi(128, 0)));
                        wgmma_rs_n192(acc0, a0, a1, a2, a3, mkdesc(sd + dlo(OFF_CS + 64, 0), dhi(128, 0)));
                        wg_commit();
                    }
                    mbar_wait(xfull - 2 * s8 - 8, ph, budget);
                    wg_wait<0>();
                    wg_fence();
#pragma unroll
                    for (int kk = 0; kk < 4; kk++) wgmma_n192<0, 1>(acc0, mkdesc(dx + 512 + kk * 2, dhi(1024, 1)), mkdesc(dw + kk * 128, dhi(1024, 1)), kk ? 1 : k);
                    wg_commit();
                    if (elect && k <= 12) { mbar_expect_tx(xfull - 2 * s8, BOX); mbar_arrive_at(xempty + 2 * s8); }
                    ps8 = s8;
                    s8 = s8 == 16 ? 0 : s8 + 8;
                    if (s8 == 16) ph ^= 1;
                }
            }
            const uint32_t zero = budget >> 30;
            const bool u0 = mU & 1, u1 = (int)mU < 0;
            float rk[2][4], fu[2][4], fn[2][4];
            auto factors = [&](int h) {
#pragma unroll
                for (int n = 0; n < 4; n += 2) {
                    const float rq = lds1f(sq + (16 * h + 4 * n) * 8 + 4) * (0.17677669529663687f * 1.4426950408889634f);
                    rk[h][n] = lds1f(ka0 + h * 128 + n * 32); rk[h][n + 1] = lds1f(ka1 + h * 128 + n * 32);
                    const float f0 = rq * rk[h][n], f1 = rq * rk[h][n + 1];
                    fu[h][n] = u0 ? f0 : 0.f; fn[h][n] = f0 - fu[h][n]; fu[h][n + 1] = u1 ? f1 : 0.f; fn[h][n + 1] = f1 - fu[h][n + 1];
                }
#pragma unroll
                for (int n = 0; n < 4; n++) asm volatile("" : "+f"(fu[h][n]), "+f"(fn[h][n]));
            };
            uint8_t* og = scr->o + oo;
            uint32_t pk0[48], pk1[48], o[16] = {};
#pragma unroll
            for (int j = 0; j < 48; j++) if (j < 16 || (j & 1)) pk1[j] = pack_here(acc1[2 * j], acc1[2 * j + 1]);
            if (warp < 7) {
#pragma unroll
                for (int c = 0; c < 4; c++) stsm4(hd + c * 512, pk1[17 + 8 * c], pk1[19 + 8 * c], pk1[21 + 8 * c], pk1[23 + 8 * c]);
                bar_arrive(1 + warp, 64);
            } else if (j0 != 768) {
#pragma unroll
                for (int c = 0; c < 4; c++) {
                    pk1[17 + 8 * c] = max(pk1[17 + 8 * c], 1u);
                    st_rlx4(&scr->halo[b][c * 128 + lane * 4], pk1[17 + 8 * c], pk1[19 + 8 * c], pk1[21 + 8 * c], pk1[23 + 8 * c]);
                }
            }
#pragma unroll
            for (int j = 16; j < 48; j += 2) pk1[j] = pack_here(acc1[2 * j], acc1[2 * j + 1]);
            factors(1);
            const uint32_t g1peer = mapa(bars + 8 * B_G1DONE, hp ^ 1);
            asm volatile("" : "+l"(og));
#pragma unroll
            for (int j = 32; j < 32 + MOVM1; j++) pk1[j] = movm(pk1[j]);
            if (F0E) factors(0);
            mbar_wait(bars + 8 * (B_WEMPTY + 1), 0, budget);
            wg_wait<0>();
            if (elect) { mbar_arrive(bars + 8 * B_G1DONE); mbar_arrive_at(g1peer); }
            float ci[4];
#pragma unroll
            for (int n = 0; n < 4; n++) ci[n] = __uint_as_float((0x03800000u + n) | (budget >> 30));
            auto hand_over = [&](int v) {
                asm volatile("{\n.reg .pred p;\nsetp.ne.b32 p, %17, 0;\n"
                             "@p stmatrix.sync.aligned.m8n8.x4.shared.b16 [%16], {%0,%1,%2,%3};\n@p stmatrix.sync.aligned.m8n8.x4.shared.b16 [%16 + 2048], {%4,%5,%6,%7};\n"
                             "@p stmatrix.sync.aligned.m8n8.x4.shared.b16 [%16 + 4096], {%8,%9,%10,%11};\n@p stmatrix.sync.aligned.m8n8.x4.shared.b16 [%16 + 6144], {%12,%13,%14,%15};\n"
                             "fence.proxy.async.shared::cta;\n}"
                             ::"r"(o[0]), "r"(o[1]), "r"(o[2]), "r"(o[3]), "r"(o[4]), "r"(o[5]), "r"(o[6]), "r"(o[7]), "r"(o[8]), "r"(o[9]), "r"(o[10]), "r"(o[11]),
                               "r"(o[12]), "r"(o[13]), "r"(o[14]), "r"(o[15]), "r"(od + v * OFF_X1), "r"((int)(w == rh)) : "memory");
#pragma unroll
                for (int i = 0; i < 16; i++) asm volatile("st.global.u32 [%0], %1;" ::"l"(og + (1 - v) * 16 * BOX + (i >> 1) * 1024 + (i & 1) * 128), "r"(o[i]) : "memory");
                __syncwarp();
                if (lane == 0) mbar_arrive(bars + 8 * (B_STAGED + v));
            };
            uint32_t xt[32];
#pragma unroll
            for (int j = 32 + MOVM1; j < 48; j++) pk1[j] = movm(pk1[j]);
#pragma unroll
            for (int j = 0; j < 48; j++) if (j >= 32 || (j > 16 && (j & 1))) pk0[j] = pack_here(acc0[2 * j], acc0[2 * j + 1]);
#pragma unroll
            for (int j = 32; j < 48; j++) pk0[j] = movm(pk0[j]);
            mbar_wait(bars + 8 * B_XT, 0, budget);
            attn_pair<2>(pk1, pk1 + 16, pk1 + 32, pk0 + 17, pk0 + 33, fu[1], fn[1], rk[1], 0.f, 0.f, mU, zero, ci, o);
            hand_over(0);
#pragma unroll
            for (int j = 0; j < 32; j++) if (j < 16 || !(j & 1)) pk0[j] = pack_here(acc0[2 * j], acc0[2 * j + 1]);
            if (!F0E) factors(0);
            const bool first = warp == 0 && j0 == 0;
            const float bias0 = first && u0 ? -INFINITY : 0.f, bias1 = first && u1 ? -INFINITY : 0.f;
            bar_sync(warp ? warp : 11, 64);
            uint32_t hl[16];
            ldsm4(hl, ha); ldsm4(hl + 4, ha + 512); ldsm4t(hl + 8, ha + 1024); ldsm4t(hl + 12, ha + 1536);
            __syncwarp();
            if (lane == 0) mbar_arrive(bars + 8 * B_FREED);
            attn_pair<1>(pk0, pk0 + 16, pk0 + 32, hl, hl + 8, fu[0], fn[0], rk[0], bias0, bias1, mU, zero, ci, o);
            const float2 s0 = lds2f(sr), s1 = lds2f(sr + 64);
#pragma unroll
            for (int j = 0; j < 8; j++) ldsm4(xt + 4 * j, (mad ^ ((j & 3) * 32)) + (j >> 2) * BOX);
            const float m0 = s0.x * s0.y, f0 = 1.f + s0.y, m1 = s1.x * s1.y, f1 = 1.f + s1.y;
            hand_over(1);
#pragma unroll
            for (int j = 0; j < 32; j++) {
                acc[2 * j] = fmaf(bf_lo(xt[j]), j & 1 ? f1 : f0, j & 1 ? m1 : m0); acc[2 * j + 1] = fmaf(bf_hi(xt[j]), j & 1 ? f1 : f0, j & 1 ? m1 : m0);
            }
        }
        {
            const uint32_t da0 = sd + dlo(w * OFF_X1, 1024), db0 = sd + dlo(OFF_WO, BOX);
            const uint32_t chk = ring + wi * 256 + (lane >> 3) * 1032 + (lane & 7) * 32 + (lane & 4);
            uint32_t s8 = 16, ps8 = 0, ph = 0;
            mbar_wait(ofull + s8, 0, budget);
            mbar_wait(bars + 8 * B_WOFULL + s8, 0, budget);
            const uint32_t ahi = dhi(128, 0) | (budget >> 30), bhi = dhi(1024, 1) | (budget >> 30);
            const int last = w ? HOLD : 15;
            uint32_t rel = elect ? 0x7fe : 0;
            uint32_t da = da0 + s8 * (BOX >> 7), db = db0 + s8 * (BOX >> 6);
#pragma unroll 1
            for (int i = 1;; i++) {
                wg_fence();
#pragma unroll
                for (int kk = 0; kk < 4; kk++) {
                    wgmma_n128<0, 1>(acc, mkdesc(da + kk * 128, ahi), mkdesc(db + kk * 128, bhi), 1);
                    if (kk & 1) wg_commit();
                }
                wg_wait<2>();
                if (rel & 1) { mbar_expect_tx(ofull + ps8, BOX); mbar_arrive_at(oempty + ps8); mbar_arrive(bars + 8 * B_WOEMPTY + ps8); }
                rel >>= 1;
                ps8 = s8;
                s8 = s8 == 40 ? 0 : s8 + 8;
                if (s8 == 16) ph ^= 1;
                da = da0 + s8 * (BOX >> 7); db = db0 + s8 * (BOX >> 6);
                uint32_t slow;
                asm volatile("{\n.reg .pred p, q, r;\n.reg .u32 u, v;\nmbarrier.try_wait.parity.shared::cta.b64 p, [%1], %3;\nmbarrier.try_wait.parity.shared::cta.b64 q, [%2], %3;\n"
                             "setp.ne.and.u32 r, %5, 1, p;\nmov.u32 u, 1;\nmov.u32 v, 1;\n@r ld.shared.u32 u, [%4];\n@r ld.shared.u32 v, [%4 + 4096];\n"
                             "and.pred p, p, q;\nmin.u32 u, u, v;\nsetp.eq.or.u32 p, u, 0, !p;\nvote.sync.any.pred p, p, 0xffffffff;\nselp.u32 %0, 1, 0, p;\n}"
                             : "=r"(slow) : "r"(ofull + s8), "r"(bars + 8 * B_WOFULL + s8), "r"(ph), "r"(chk + s8 * (BOX / 8)), "r"(i) : "memory");
                if (__builtin_expect(slow || i == last, 0)) {
                    uint32_t c8 = slow ? s8 : s8 + 8;
#pragma unroll 1
                    for (int n = slow ? i : i + 1; n < (i == last ? 16 : i + 1); n++, c8 += 8) {
                        const uint32_t cph = ph ^ (HOLD < 12 && c8 >= 16 && s8 < 16);
                        mbar_wait(ofull + c8, cph, budget);
                        mbar_wait(bars + 8 * B_WOFULL + c8, cph, budget);
                        if (__any_sync(0xffffffffu, min(lds1(chk + c8 * (BOX / 8)), lds1(chk + c8 * (BOX / 8) + 4096)) == 0)) {
                            const uint32_t at = wi * 256 + (lane >> 4) * 1024 + (lane & 15) * 16;
                            const uint8_t* src = scr->o + ((size_t)((mt * 2 + rh) * 2 + 1 - w) * 16 + ((2 * p + (n < 2 ? n ^ hp : n)) & 15)) * BOX + at;
#pragma unroll 1
                            for (int m = 0; m < 8192; m += 2048) {
                                uint4 v; int tries = 4096;
#pragma unroll 1
                                do { v = ld_rlx4(src + m); } while (v.x == 0 && --tries > 0);
                                sts4(ring + c8 * (BOX / 8) + at + m, v.x, v.y, v.z, v.w);
                            }
                            fence_async_smem();
                            __syncwarp();
                        }
                    }
                    if (i == last) break;
                }
                wg_wait<1>();
            }
            if (w) bar_sync(9, 256);
#pragma unroll 1
            for (int i = last; i < 16; i++, da += 512, db += 1024) {
                wg_fence();
#pragma unroll
                for (int kk = 0; kk < 4; kk++) wgmma_n128<0, 1>(acc, mkdesc(da + kk * 128, ahi), mkdesc(db + kk * 128, bhi), 1);
                wg_commit();
            }
            if (!w) bar_arrive(9, 256);
            mbar_wait(bars + 8 * B_ZERO, 0, budget);
            const bool add = (__shfl_sync(0xffffffffu, lds1(sb + OFF_SEL), 0) >> (wi * 2 + 1 - w)) & 1;
            wg_wait<0>();
            const uint32_t os0 = ring + wi * 4096;
#pragma unroll
            for (int hf = 0; hf < 2; hf++) {
#pragma unroll
                for (int j = hf * 4; j < hf * 4 + 4; j++)
                    stsm4(((mad + wi * 2048) ^ ((j & 3) * 32)) + (j >> 2) * 2048, pack_here(acc[8 * j], acc[8 * j + 1]), pack_here(acc[8 * j + 2], acc[8 * j + 3]),
                          pack_here(acc[8 * j + 4], acc[8 * j + 5]), pack_here(acc[8 * j + 6], acc[8 * j + 7]));
                fence_async_smem();
                __syncwarp();
                if (elect_one())
                    asm volatile("{\n.reg .pred p;\nsetp.ne.b32 p, %6, 0;\n@!p cp.async.bulk.tensor.5d.global.shared::cta.bulk_group [%0, {%2, %2, %3, %4, %5}], [%1];\n"
                                 "@p cp.reduce.async.bulk.tensor.5d.global.shared::cta.add.bulk_group [%0, {%2, %2, %3, %4, %5}], [%1];\n}"
                                 ::"l"(&mout), "r"(os0 + hf * 2048), "r"(0), "r"(((j0 + rh * 128) >> 5) + wi), "r"(1 - w), "r"(par * 16 + cb * 2 + hf), "r"((int)add) : "memory");
            }
            asm volatile("cp.async.bulk.commit_group;\ncp.async.bulk.wait_group.read 0;" ::: "memory");
            if (b == 0 && tid == 0) st_rlx(&scr->epoch[0], lds1(sb + OFF_EP));
        }
    }
}

struct Plain { __nv_bfloat16 xn[2048 * 1024], qkv[2048 * 3072], o[2048 * 1024], gu[2][8 * 3584], y[8 * 1024]; float r[2048]; int sel[8]; };
__device__ Plain g_plain;
__device__ __forceinline__ float tof(__nv_bfloat16 v) { return __bfloat162float(v); }
__device__ float block_sum(float v) {
    __shared__ float red[8];
    for (int o = 16; o > 0; o >>= 1) v += __shfl_xor_sync(0xffffffffu, v, o);
    __syncthreads();
    if ((threadIdx.x & 31) == 0) red[threadIdx.x >> 5] = v;
    __syncthreads();
    v = 0.f;
    for (int i = 0; i < 8; i++) v += red[i];
    return v;
}
__global__ void plain_ln(const __nv_bfloat16* x, const __nv_bfloat16* wr) {
    const int s = blockIdx.x;
    float v[4], a = 0.f;
    for (int i = 0; i < 4; i++) a += v[i] = tof(x[s * 1024 + i * 256 + threadIdx.x]);
    const float mean = block_sum(a) / 1024.f;
    a = 0.f;
    for (int i = 0; i < 4; i++) a += (v[i] - mean) * (v[i] - mean);
    const float den = bf16r(sqrtf(bf16r(bf16r(block_sum(a) / 1024.f) + 1e-5f)));
    a = 0.f;
    for (int i = 0; i < 4; i++) {
        const float n = bf16r(bf16r(v[i] - bf16r(mean)) / den);
        g_plain.xn[s * 1024 + i * 256 + threadIdx.x] = __float2bfloat16(n);
        a += n * tof(wr[i * 256 + threadIdx.x]);
    }
    a = block_sum(a);
    if (threadIdx.x == 0) g_plain.r[s] = bf16r(a);
}
__global__ void plain_topk() {
    const int s = blockIdx.x * 256 + threadIdx.x;
    int rank = 0;
    for (int i = 0; i < 2048; i++) rank += g_plain.r[i] > g_plain.r[s] || (g_plain.r[i] == g_plain.r[s] && i < s);
    if (rank < 8) g_plain.sel[rank] = s;
}
__global__ void plain_gemm(int what, const __nv_bfloat16* w, int K, int N, const __nv_bfloat16* x, __nv_bfloat16* out) {
    const int n = blockIdx.x * 256 + threadIdx.x, m0 = blockIdx.y * 8;
    float acc[8] = {};
    for (int k = 0; k < K; k++) {
        const float wv = tof(w[(size_t)k * N + n]);
        for (int i = 0; i < 8; i++) {
            float a;
            if (what == 3) { const float gt = tof(g_plain.gu[0][i * K + k]); a = bf16r(bf16r(gt / (1.f + expf(-gt))) * tof(g_plain.gu[1][i * K + k])); }
            else a = tof((what == 4 ? g_plain.o : g_plain.xn)[(what == 1 || what == 2 ? g_plain.sel[i] : m0 + i) * 1024 + k]);
            acc[i] = fmaf(a, wv, acc[i]);
        }
    }
    for (int i = 0; i < 8; i++) {
        if (what == 4) {
            const int at = (m0 + i) * 1024 + n;
            float u = 0.f;
            for (int j = 0; j < 8; j++) if (g_plain.sel[j] == m0 + i) u = bf16r(tof(g_plain.y[j * 1024 + n]) * bf16r(1.f / (1.f + expf(-g_plain.r[m0 + i]))));
            out[at] = __float2bfloat16(bf16r(tof(x[at]) + bf16r(acc[i])) + bf16r(tof(g_plain.xn[at]) + u));
        } else (what == 0 ? g_plain.qkv : what == 3 ? g_plain.y : g_plain.gu[what - 1])[(size_t)(m0 + i) * N + n] = __float2bfloat16(acc[i]);
    }
}
__global__ void plain_attn() {
    const int s = blockIdx.x, d = threadIdx.x;
    const float q = tof(g_plain.qkv[s * 3072 + d]);
    float l[8], mx = -INFINITY, sum = 0.f, o = 0.f;
    for (int w = 0; w < 8; w++) {
        float a = q * tof(g_plain.qkv[max(s - 2 * w, 0) * 3072 + 1024 + d]);
        for (int i = 16; i > 0; i >>= 1) a += __shfl_xor_sync(0xffffffffu, a, i);
        l[w] = s >= 2 * w ? bf16r(bf16r(a) * 0.17677669529663687f) : -1e9f;
        mx = fmaxf(mx, l[w]);
    }
    for (int w = 0; w < 8; w++) sum += l[w] = expf(l[w] - mx);
    for (int w = 0; w < 8; w++) o = fmaf(bf16r(l[w] / sum), tof(g_plain.qkv[max(s - 2 * w, 0) * 3072 + 2048 + d]), o);
    g_plain.o[s * 1024 + d] = __float2bfloat16(o);
}

typedef CUresult (*EncodeFn)(CUtensorMap*, CUtensorMapDataType, cuuint32_t, void*, const cuuint64_t*, const cuuint64_t*, const cuuint32_t*,
                             const cuuint32_t*, CUtensorMapInterleave, CUtensorMapSwizzle, CUtensorMapL2promotion, CUtensorMapFloatOOBfill);

CUtensorMap make_map(EncodeFn fn, const void* base, int rank, const cuuint64_t* dims, const cuuint64_t* strides, const cuuint32_t* box,
                     CUtensorMapSwizzle swz = CU_TENSOR_MAP_SWIZZLE_128B, CUtensorMapL2promotion pro = CU_TENSOR_MAP_L2_PROMOTION_NONE) {
    CUtensorMap m;
    cuuint32_t es[5] = {1, 1, 1, 1, 1};
    fn(&m, CU_TENSOR_MAP_DATA_TYPE_BFLOAT16, rank, (void*)base, dims, strides, box, es, CU_TENSOR_MAP_INTERLEAVE_NONE,
       swz, pro, CU_TENSOR_MAP_FLOAT_OOB_FILL_NONE);
    return m;
}

}

extern "C" void kernel_launch(void* const* d_in, const int* in_sizes, int n_in, void* d_out, int out_size) {
    (void)in_sizes; (void)n_in; (void)out_size;
    const __nv_bfloat16* x = (const __nv_bfloat16*)d_in[0];
    const __nv_bfloat16* wqkv = (const __nv_bfloat16*)d_in[1];
    const __nv_bfloat16* wo = (const __nv_bfloat16*)d_in[2];
    const __nv_bfloat16* wr = (const __nv_bfloat16*)d_in[4];
    const __nv_bfloat16* wg = (const __nv_bfloat16*)d_in[5];
    const __nv_bfloat16* wu = (const __nv_bfloat16*)d_in[6];
    const __nv_bfloat16* wd = (const __nv_bfloat16*)d_in[7];
    static EncodeFn fn = nullptr;
    static Scratch* scr = nullptr;
    static int clusters = 0;
    cudaLaunchConfig_t cfg = {};
    cfg.gridDim = dim3(132); cfg.blockDim = dim3(512); cfg.dynamicSmemBytes = SMEM_LAUNCH; cfg.stream = cudaStreamPerThread;
    if (!fn) {
        void* p = nullptr; cudaDriverEntryPointQueryResult q;
        cudaGetDriverEntryPoint("cuTensorMapEncodeTiled", &p, cudaEnableDefault, &q);
        fn = (EncodeFn)p;
        cudaFuncSetAttribute(fused_kernel, cudaFuncAttributeMaxDynamicSharedMemorySize, SMEM_LAUNCH);
        cudaGetSymbolAddress((void**)&scr, g_scr);
        cudaLaunchAttribute at;
        at.id = cudaLaunchAttributeClusterDimension; at.val.clusterDim.x = 2; at.val.clusterDim.y = 1; at.val.clusterDim.z = 1;
        cudaLaunchConfig_t qc = cfg;
        qc.attrs = &at; qc.numAttrs = 1;
        cudaOccupancyMaxActiveClusters(&clusters, fused_kernel, &qc);
    }
    if (clusters < 66) {
        __nv_bfloat16* out = (__nv_bfloat16*)d_out;
        plain_ln<<<2048, 256, 0, cfg.stream>>>(x, wr);
        plain_topk<<<8, 256, 0, cfg.stream>>>();
        plain_gemm<<<dim3(12, 256), 256, 0, cfg.stream>>>(0, wqkv, 1024, 3072, x, out);
        plain_attn<<<2048, 1024, 0, cfg.stream>>>();
        plain_gemm<<<14, 256, 0, cfg.stream>>>(1, wg, 1024, 3584, x, out);
        plain_gemm<<<14, 256, 0, cfg.stream>>>(2, wu, 1024, 3584, x, out);
        plain_gemm<<<4, 256, 0, cfg.stream>>>(3, wd, 3584, 1024, x, out);
        plain_gemm<<<dim3(4, 256), 256, 0, cfg.stream>>>(4, wo, 1024, 1024, x, out);
        return;
    }
    const cuuint64_t xd[4] = {2048, 16, 32, 2}, xs[4] = {4096, 131072, 65536, 128}, od[5] = {64, 16, 32, 2, 32};
    const cuuint32_t xb[4] = {64, 16, 4, 1}, ob[5] = {64, 16, 1, 1, 1};
    const cuuint64_t wdm[3] = {1024, 1024, 3}, wst[2] = {6144, 2048};
    const cuuint32_t wb[3] = {64, 64, 3};
    const cuuint64_t wod[3] = {64, 1024, 16}, wdd[3] = {64, 3584, 16}, wos[2] = {2048, 128};
    const cuuint32_t wob[3] = {64, 64, 2}, wdb[3] = {64, 64, 1};
    const CUtensorMapSwizzle s128 = CU_TENSOR_MAP_SWIZZLE_128B;
    CUtensorMap mx = make_map(fn, x, 4, xd, xs, xb, s128), mw = make_map(fn, wqkv, 3, wdm, wst, wb, s128);
    CUtensorMap mwo = make_map(fn, wo, 3, wod, wos, wob, s128), mout = make_map(fn, d_out, 5, od, xs, ob, s128);
    const int swap_gu = wu < wg;
    const cuuint64_t gd[3] = {3584, 1024, 2}, gst[2] = {7168, (cuuint64_t)(swap_gu ? (const char*)wg - (const char*)wu : (const char*)wu - (const char*)wg)};
    const cuuint32_t gb[3] = {32, 64, 2};
    CUtensorMap mgu = make_map(fn, swap_gu ? wu : wg, 3, gd, gst, gb, CU_TENSOR_MAP_SWIZZLE_64B, CU_TENSOR_MAP_L2_PROMOTION_L2_128B);
    CUtensorMap mwd = make_map(fn, wd, 3, wdd, wos, wdb, s128, CU_TENSOR_MAP_L2_PROMOTION_L2_128B);
    const cuuint64_t md[2] = {64, 32768}, ms[1] = {128};
    const cuuint32_t mb[2] = {64, 64};
    CUtensorMap mo = make_map(fn, scr, 2, md, ms, mb, CU_TENSOR_MAP_SWIZZLE_NONE);
    const cuuint64_t rd[2] = {1024, 2048};
    const cuuint32_t rb[2] = {256, 16};
    CUtensorMap mr = make_map(fn, x, 2, rd, wos, rb, CU_TENSOR_MAP_SWIZZLE_NONE);
    cudaLaunchKernelEx(&cfg, fused_kernel, mx, mw, mwo, mout, mgu, mwd, mo, mr, x, wr, scr, swap_gu, Weights{(const char*)wqkv, (const char*)wo, (const char*)wg, (const char*)wu, (const char*)wd, (char*)d_out});
}
```
